```python
import torch

def _softmax(x, axis=-1):
    return torch.softmax(x, dim=axis)
def _gelu(x):
    return torch.nn.functional.gelu(x, approximate="tanh")
def _silu(x):
    return torch.nn.functional.silu(x)
def _sigmoid(x):
    return torch.sigmoid(x)
def _layernorm(x, axis=-1, eps=1e-5):
    m = x.mean(dim=axis, keepdim=True)
    v = x.var(dim=axis, keepdim=True, unbiased=False)
    return (x - m) / torch.sqrt(v + eps)
def _scatter_add(tgt, idx, src, axis=0):
    return tgt.clone().index_add_(axis, idx, src)
def _segment_sum(src, seg, n):
    out = torch.zeros((n,) + src.shape[1:], dtype=src.dtype)
    return out.index_add_(0, seg, src)
def _pad(x, pw):
    flat = tuple(v for pair in reversed(pw) for v in pair)
    return torch.nn.functional.pad(x, flat)

kernel_name = 'interleave_layers__sliding_local_dilated__glu_gated_bilinear__prompt'

def setup_inputs():

    _w = (lambda a: (lambda t: t.to(torch.bfloat16) if t.is_floating_point() else t)(torch.as_tensor(a)))
    def _A_setup():
        B, S, D = 1, 2048, 576
        return {
            "x": _w((lambda *s: torch.randn(*s, dtype=torch.bfloat16) * 0.05)(B, S, D)),
            "wqkv": _w((lambda *s: torch.randn(*s, dtype=torch.bfloat16) * 0.05)(D, 3 * D)),
            "wo": _w((lambda *s: torch.randn(*s, dtype=torch.bfloat16) * 0.05)(D, D)),
        }
    _A_in = _A_setup()

    def _B_setup():
        B, S, D, F = 1, 2048, 576, 4608
        return {
            "x": _w((lambda *s: torch.randn(*s, dtype=torch.bfloat16) * 0.05)(B, S, D)),
            "w_gate": _w((lambda *s: torch.randn(*s, dtype=torch.bfloat16) * 0.8)(D, F) * (D ** -0.5)),
            "w_up": _w((lambda *s: torch.randn(*s, dtype=torch.bfloat16) * 0.8)(D, F) * (D ** -0.5)),
            "w_down": _w((lambda *s: torch.randn(*s, dtype=torch.bfloat16) * 0.8)(F, D) * (F ** -0.5)),
        }
    _B_in = _B_setup()

    return {
        "A_x": _A_in["x"],
        "A_wqkv": _A_in["wqkv"],
        "A_wo": _A_in["wo"],
        "B_x": _B_in["x"],
        "B_w_gate": _B_in["w_gate"],
        "B_w_up": _B_in["w_up"],
        "B_w_down": _B_in["w_down"],
    }

def reference(A_x, A_wqkv, A_wo, B_x, B_w_gate, B_w_up, B_w_down):
    def _A_ref(x, wqkv, wo):
        B, S, D = x.shape
        H = 32; Dh = D // H
        W, dil = 8, 2
        qkv = (lambda x, *d: x.permute(*d))((x @ wqkv).reshape(B, S, 3, H, Dh), 2, 0, 3, 1, 4)
        q, k, v = qkv[0], qkv[1], qkv[2]
        scale = Dh ** -0.5
        pos = torch.arange(S)
        off = torch.arange(W) * dil
        idx = pos[:, None] - off[None, :]
        mask = idx >= 0
        idx_c = torch.where(mask, idx, 0).reshape(-1)
        kg = k[:, :, idx_c, :].reshape(B, H, S, W, Dh)
        vg = v[:, :, idx_c, :].reshape(B, H, S, W, Dh)
        logits = torch.einsum("bhsd,bhswd->bhsw", q, kg) * scale
        logits = torch.where(mask[None, None, :, :], logits, -1e9)
        attn = _softmax(logits, axis=-1)
        o = torch.einsum("bhsw,bhswd->bhsd", attn, vg)
        return (lambda x, *d: x.permute(*d))(o, 0, 2, 1, 3).reshape(B, S, D) @ wo

    def _B_ref(x, w_gate, w_up, w_down):
        g = torch.einsum("bsd,df->bsf", x, w_gate)
        u = torch.einsum("bsd,df->bsf", x, w_up)
        h = g * u
        return torch.einsum("bsf,fd->bsd", h, w_down)

    x = A_x
    x = x + _A_ref(_layernorm(x, axis=-1), A_wqkv, A_wo)
    x = x + _B_ref(_layernorm(x, axis=-1), B_w_gate, B_w_up, B_w_down)
    x = x + _A_ref(_layernorm(x, axis=-1), A_wqkv, A_wo)
    x = x + _B_ref(_layernorm(x, axis=-1), B_w_gate, B_w_up, B_w_down)
    return x
```

```cpp
#include <cuda_runtime.h>
#include <cuda_bf16.h>
#include <cuda.h>
#include <stdint.h>

namespace {

constexpr int D_ = 576;
constexpr int NCTA = 128;
#define NLAYERS 2
#define W_POLICY policy_evict_normal
#define OPEN 1
#define NSPILL 4
#define REGS_C 232
#define REGS_P 40
#define STR2(x) #x
#define STR(x) STR2(x)
constexpr uint32_t SM_X = 0;
constexpr uint32_t XSLOT = 18432;
constexpr uint32_t SM_SLAB = XSLOT;
constexpr uint32_t SLAB = 20736;
constexpr uint32_t SM_B = 147456;
constexpr uint32_t BSLOT = 16384;
constexpr uint32_t SM_KEEP = 229376;
constexpr uint32_t SM_BAR = SM_KEEP + 2048;
constexpr uint32_t BAR_FULLB = SM_BAR;
constexpr uint32_t BAR_FULLX = SM_BAR + 40;
constexpr uint32_t BAR_RREADY = SM_BAR + 104;
constexpr uint32_t BAR_CLR = SM_BAR + 120;
constexpr uint32_t BAR_EMPTYB = SM_BAR + 136;
constexpr uint32_t BAR_EMPTYX = SM_BAR + 176;
constexpr uint32_t BAR_REDDONE = SM_BAR + 240;
constexpr uint32_t BAR_DONE = SM_BAR + 256;
constexpr int NBAR = 34;
constexpr uint32_t SMEM_BYTES = SM_BAR + 1024;

struct Maps { CUtensorMap qm, qc, o, oc, g, u, g3, u3, d, out, outc; };

__device__ __align__(1024) uint4 g_act[3][32 * 36 * 128];
constexpr int INBOX = 1088;
__device__ __align__(1024) uint4 g_inbox[2][32 * 8 * INBOX];
__device__ __align__(1024) uint4 g_halo[32 * 8 * 192];
__device__ __align__(1024) uint2 g_sum[32 * 4 * 8 * 8];
__device__ __align__(1024) uint4 g_m2[32 * 4 * 8 * 8];
__device__ __align__(128) uint32_t g_flag[32 * 32];
#define PROF(i)

template<int N> __device__ __forceinline__ void wgmma_ss(float (&d)[N / 2], uint64_t da, uint64_t db, int sc);
template<> __device__ __forceinline__ void wgmma_ss<192>(float (&d)[96], uint64_t da, uint64_t db, int sc) {
  asm volatile("{\n.reg .pred p;\nsetp.ne.b32 p, %98, 0;\n"
    "wgmma.mma_async.sync.aligned.m64n192k16.f32.bf16.bf16 {%0,%1,%2,%3,%4,%5,%6,%7,%8,%9,%10,%11,%12,%13,%14,%15,%16,%17,%18,%19,%20,%21,%22,%23,%24,%25,%26,%27,%28,%29,%30,%31,%32,%33,%34,%35,%36,%37,%38,%39,%40,%41,%42,%43,%44,%45,%46,%47,%48,%49,%50,%51,%52,%53,%54,%55,%56,%57,%58,%59,%60,%61,%62,%63,%64,%65,%66,%67,%68,%69,%70,%71,%72,%73,%74,%75,%76,%77,%78,%79,%80,%81,%82,%83,%84,%85,%86,%87,%88,%89,%90,%91,%92,%93,%94,%95}, %96, %97, p, 1, 1, 0, 1;\n}\n"
    : "+f"(d[0]),"+f"(d[1]),"+f"(d[2]),"+f"(d[3]),"+f"(d[4]),"+f"(d[5]),"+f"(d[6]),"+f"(d[7]),"+f"(d[8]),"+f"(d[9]),"+f"(d[10]),"+f"(d[11]),"+f"(d[12]),"+f"(d[13]),"+f"(d[14]),"+f"(d[15]),"+f"(d[16]),"+f"(d[17]),"+f"(d[18]),"+f"(d[19]),"+f"(d[20]),"+f"(d[21]),"+f"(d[22]),"+f"(d[23]),"+f"(d[24]),"+f"(d[25]),"+f"(d[26]),"+f"(d[27]),"+f"(d[28]),"+f"(d[29]),"+f"(d[30]),"+f"(d[31]),"+f"(d[32]),"+f"(d[33]),"+f"(d[34]),"+f"(d[35]),"+f"(d[36]),"+f"(d[37]),"+f"(d[38]),"+f"(d[39]),"+f"(d[40]),"+f"(d[41]),"+f"(d[42]),"+f"(d[43]),"+f"(d[44]),"+f"(d[45]),"+f"(d[46]),"+f"(d[47]),"+f"(d[48]),"+f"(d[49]),"+f"(d[50]),"+f"(d[51]),"+f"(d[52]),"+f"(d[53]),"+f"(d[54]),"+f"(d[55]),"+f"(d[56]),"+f"(d[57]),"+f"(d[58]),"+f"(d[59]),"+f"(d[60]),"+f"(d[61]),"+f"(d[62]),"+f"(d[63]),"+f"(d[64]),"+f"(d[65]),"+f"(d[66]),"+f"(d[67]),"+f"(d[68]),"+f"(d[69]),"+f"(d[70]),"+f"(d[71]),"+f"(d[72]),"+f"(d[73]),"+f"(d[74]),"+f"(d[75]),"+f"(d[76]),"+f"(d[77]),"+f"(d[78]),"+f"(d[79]),"+f"(d[80]),"+f"(d[81]),"+f"(d[82]),"+f"(d[83]),"+f"(d[84]),"+f"(d[85]),"+f"(d[86]),"+f"(d[87]),"+f"(d[88]),"+f"(d[89]),"+f"(d[90]),"+f"(d[91]),"+f"(d[92]),"+f"(d[93]),"+f"(d[94]),"+f"(d[95]) : "l"(da), "l"(db), "r"(sc));
}
template<> __device__ __forceinline__ void wgmma_ss<256>(float (&d)[128], uint64_t da, uint64_t db, int sc) {
  asm volatile("{\n.reg .pred p;\nsetp.ne.b32 p, %130, 0;\n"
    "wgmma.mma_async.sync.aligned.m64n256k16.f32.bf16.bf16 {%0,%1,%2,%3,%4,%5,%6,%7,%8,%9,%10,%11,%12,%13,%14,%15,%16,%17,%18,%19,%20,%21,%22,%23,%24,%25,%26,%27,%28,%29,%30,%31,%32,%33,%34,%35,%36,%37,%38,%39,%40,%41,%42,%43,%44,%45,%46,%47,%48,%49,%50,%51,%52,%53,%54,%55,%56,%57,%58,%59,%60,%61,%62,%63,%64,%65,%66,%67,%68,%69,%70,%71,%72,%73,%74,%75,%76,%77,%78,%79,%80,%81,%82,%83,%84,%85,%86,%87,%88,%89,%90,%91,%92,%93,%94,%95,%96,%97,%98,%99,%100,%101,%102,%103,%104,%105,%106,%107,%108,%109,%110,%111,%112,%113,%114,%115,%116,%117,%118,%119,%120,%121,%122,%123,%124,%125,%126,%127}, %128, %129, p, 1, 1, 0, 1;\n}\n"
    : "+f"(d[0]),"+f"(d[1]),"+f"(d[2]),"+f"(d[3]),"+f"(d[4]),"+f"(d[5]),"+f"(d[6]),"+f"(d[7]),"+f"(d[8]),"+f"(d[9]),"+f"(d[10]),"+f"(d[11]),"+f"(d[12]),"+f"(d[13]),"+f"(d[14]),"+f"(d[15]),"+f"(d[16]),"+f"(d[17]),"+f"(d[18]),"+f"(d[19]),"+f"(d[20]),"+f"(d[21]),"+f"(d[22]),"+f"(d[23]),"+f"(d[24]),"+f"(d[25]),"+f"(d[26]),"+f"(d[27]),"+f"(d[28]),"+f"(d[29]),"+f"(d[30]),"+f"(d[31]),"+f"(d[32]),"+f"(d[33]),"+f"(d[34]),"+f"(d[35]),"+f"(d[36]),"+f"(d[37]),"+f"(d[38]),"+f"(d[39]),"+f"(d[40]),"+f"(d[41]),"+f"(d[42]),"+f"(d[43]),"+f"(d[44]),"+f"(d[45]),"+f"(d[46]),"+f"(d[47]),"+f"(d[48]),"+f"(d[49]),"+f"(d[50]),"+f"(d[51]),"+f"(d[52]),"+f"(d[53]),"+f"(d[54]),"+f"(d[55]),"+f"(d[56]),"+f"(d[57]),"+f"(d[58]),"+f"(d[59]),"+f"(d[60]),"+f"(d[61]),"+f"(d[62]),"+f"(d[63]),"+f"(d[64]),"+f"(d[65]),"+f"(d[66]),"+f"(d[67]),"+f"(d[68]),"+f"(d[69]),"+f"(d[70]),"+f"(d[71]),"+f"(d[72]),"+f"(d[73]),"+f"(d[74]),"+f"(d[75]),"+f"(d[76]),"+f"(d[77]),"+f"(d[78]),"+f"(d[79]),"+f"(d[80]),"+f"(d[81]),"+f"(d[82]),"+f"(d[83]),"+f"(d[84]),"+f"(d[85]),"+f"(d[86]),"+f"(d[87]),"+f"(d[88]),"+f"(d[89]),"+f"(d[90]),"+f"(d[91]),"+f"(d[92]),"+f"(d[93]),"+f"(d[94]),"+f"(d[95]),"+f"(d[96]),"+f"(d[97]),"+f"(d[98]),"+f"(d[99]),"+f"(d[100]),"+f"(d[101]),"+f"(d[102]),"+f"(d[103]),"+f"(d[104]),"+f"(d[105]),"+f"(d[106]),"+f"(d[107]),"+f"(d[108]),"+f"(d[109]),"+f"(d[110]),"+f"(d[111]),"+f"(d[112]),"+f"(d[113]),"+f"(d[114]),"+f"(d[115]),"+f"(d[116]),"+f"(d[117]),"+f"(d[118]),"+f"(d[119]),"+f"(d[120]),"+f"(d[121]),"+f"(d[122]),"+f"(d[123]),"+f"(d[124]),"+f"(d[125]),"+f"(d[126]),"+f"(d[127]) : "l"(da), "l"(db), "r"(sc));
}
template<int N> __device__ __forceinline__ void wgmma_rs(float (&d)[N / 2], uint32_t a0, uint32_t a1, uint32_t a2, uint32_t a3, uint64_t db, int sc);
template<> __device__ __forceinline__ void wgmma_rs<8>(float (&d)[4], uint32_t a0, uint32_t a1, uint32_t a2, uint32_t a3, uint64_t db, int sc) {
  asm volatile("{\n.reg .pred p;\nsetp.ne.b32 p, %9, 0;\n"
    "wgmma.mma_async.sync.aligned.m64n8k16.f32.bf16.bf16 {%0,%1,%2,%3}, {%4,%5,%6,%7}, %8, p, 1, 1, 1;\n}\n"
    : "+f"(d[0]),"+f"(d[1]),"+f"(d[2]),"+f"(d[3]) : "r"(a0), "r"(a1), "r"(a2), "r"(a3), "l"(db), "r"(sc));
}
template<> __device__ __forceinline__ void wgmma_rs<24>(float (&d)[12], uint32_t a0, uint32_t a1, uint32_t a2, uint32_t a3, uint64_t db, int sc) {
  asm volatile("{\n.reg .pred p;\nsetp.ne.b32 p, %17, 0;\n"
    "wgmma.mma_async.sync.aligned.m64n24k16.f32.bf16.bf16 {%0,%1,%2,%3,%4,%5,%6,%7,%8,%9,%10,%11}, {%12,%13,%14,%15}, %16, p, 1, 1, 1;\n}\n"
    : "+f"(d[0]),"+f"(d[1]),"+f"(d[2]),"+f"(d[3]),"+f"(d[4]),"+f"(d[5]),"+f"(d[6]),"+f"(d[7]),"+f"(d[8]),"+f"(d[9]),"+f"(d[10]),"+f"(d[11]) : "r"(a0), "r"(a1), "r"(a2), "r"(a3), "l"(db), "r"(sc));
}
template<> __device__ __forceinline__ void wgmma_rs<64>(float (&d)[32], uint32_t a0, uint32_t a1, uint32_t a2, uint32_t a3, uint64_t db, int sc) {
  asm volatile("{\n.reg .pred p;\nsetp.ne.b32 p, %37, 0;\n"
    "wgmma.mma_async.sync.aligned.m64n64k16.f32.bf16.bf16 {%0,%1,%2,%3,%4,%5,%6,%7,%8,%9,%10,%11,%12,%13,%14,%15,%16,%17,%18,%19,%20,%21,%22,%23,%24,%25,%26,%27,%28,%29,%30,%31}, {%32,%33,%34,%35}, %36, p, 1, 1, 1;\n}\n"
    : "+f"(d[0]),"+f"(d[1]),"+f"(d[2]),"+f"(d[3]),"+f"(d[4]),"+f"(d[5]),"+f"(d[6]),"+f"(d[7]),"+f"(d[8]),"+f"(d[9]),"+f"(d[10]),"+f"(d[11]),"+f"(d[12]),"+f"(d[13]),"+f"(d[14]),"+f"(d[15]),"+f"(d[16]),"+f"(d[17]),"+f"(d[18]),"+f"(d[19]),"+f"(d[20]),"+f"(d[21]),"+f"(d[22]),"+f"(d[23]),"+f"(d[24]),"+f"(d[25]),"+f"(d[26]),"+f"(d[27]),"+f"(d[28]),"+f"(d[29]),"+f"(d[30]),"+f"(d[31]) : "r"(a0), "r"(a1), "r"(a2), "r"(a3), "l"(db), "r"(sc));
}
template<> __device__ __forceinline__ void wgmma_rs<192>(float (&d)[96], uint32_t a0, uint32_t a1, uint32_t a2, uint32_t a3, uint64_t db, int sc) {
  asm volatile("{\n.reg .pred p;\nsetp.ne.b32 p, %101, 0;\n"
    "wgmma.mma_async.sync.aligned.m64n192k16.f32.bf16.bf16 {%0,%1,%2,%3,%4,%5,%6,%7,%8,%9,%10,%11,%12,%13,%14,%15,%16,%17,%18,%19,%20,%21,%22,%23,%24,%25,%26,%27,%28,%29,%30,%31,%32,%33,%34,%35,%36,%37,%38,%39,%40,%41,%42,%43,%44,%45,%46,%47,%48,%49,%50,%51,%52,%53,%54,%55,%56,%57,%58,%59,%60,%61,%62,%63,%64,%65,%66,%67,%68,%69,%70,%71,%72,%73,%74,%75,%76,%77,%78,%79,%80,%81,%82,%83,%84,%85,%86,%87,%88,%89,%90,%91,%92,%93,%94,%95}, {%96,%97,%98,%99}, %100, p, 1, 1, 1;\n}\n"
    : "+f"(d[0]),"+f"(d[1]),"+f"(d[2]),"+f"(d[3]),"+f"(d[4]),"+f"(d[5]),"+f"(d[6]),"+f"(d[7]),"+f"(d[8]),"+f"(d[9]),"+f"(d[10]),"+f"(d[11]),"+f"(d[12]),"+f"(d[13]),"+f"(d[14]),"+f"(d[15]),"+f"(d[16]),"+f"(d[17]),"+f"(d[18]),"+f"(d[19]),"+f"(d[20]),"+f"(d[21]),"+f"(d[22]),"+f"(d[23]),"+f"(d[24]),"+f"(d[25]),"+f"(d[26]),"+f"(d[27]),"+f"(d[28]),"+f"(d[29]),"+f"(d[30]),"+f"(d[31]),"+f"(d[32]),"+f"(d[33]),"+f"(d[34]),"+f"(d[35]),"+f"(d[36]),"+f"(d[37]),"+f"(d[38]),"+f"(d[39]),"+f"(d[40]),"+f"(d[41]),"+f"(d[42]),"+f"(d[43]),"+f"(d[44]),"+f"(d[45]),"+f"(d[46]),"+f"(d[47]),"+f"(d[48]),"+f"(d[49]),"+f"(d[50]),"+f"(d[51]),"+f"(d[52]),"+f"(d[53]),"+f"(d[54]),"+f"(d[55]),"+f"(d[56]),"+f"(d[57]),"+f"(d[58]),"+f"(d[59]),"+f"(d[60]),"+f"(d[61]),"+f"(d[62]),"+f"(d[63]),"+f"(d[64]),"+f"(d[65]),"+f"(d[66]),"+f"(d[67]),"+f"(d[68]),"+f"(d[69]),"+f"(d[70]),"+f"(d[71]),"+f"(d[72]),"+f"(d[73]),"+f"(d[74]),"+f"(d[75]),"+f"(d[76]),"+f"(d[77]),"+f"(d[78]),"+f"(d[79]),"+f"(d[80]),"+f"(d[81]),"+f"(d[82]),"+f"(d[83]),"+f"(d[84]),"+f"(d[85]),"+f"(d[86]),"+f"(d[87]),"+f"(d[88]),"+f"(d[89]),"+f"(d[90]),"+f"(d[91]),"+f"(d[92]),"+f"(d[93]),"+f"(d[94]),"+f"(d[95]) : "r"(a0), "r"(a1), "r"(a2), "r"(a3), "l"(db), "r"(sc));
}
template<> __device__ __forceinline__ void wgmma_rs<256>(float (&d)[128], uint32_t a0, uint32_t a1, uint32_t a2, uint32_t a3, uint64_t db, int sc) {
  asm volatile("{\n.reg .pred p;\nsetp.ne.b32 p, %133, 0;\n"
    "wgmma.mma_async.sync.aligned.m64n256k16.f32.bf16.bf16 {%0,%1,%2,%3,%4,%5,%6,%7,%8,%9,%10,%11,%12,%13,%14,%15,%16,%17,%18,%19,%20,%21,%22,%23,%24,%25,%26,%27,%28,%29,%30,%31,%32,%33,%34,%35,%36,%37,%38,%39,%40,%41,%42,%43,%44,%45,%46,%47,%48,%49,%50,%51,%52,%53,%54,%55,%56,%57,%58,%59,%60,%61,%62,%63,%64,%65,%66,%67,%68,%69,%70,%71,%72,%73,%74,%75,%76,%77,%78,%79,%80,%81,%82,%83,%84,%85,%86,%87,%88,%89,%90,%91,%92,%93,%94,%95,%96,%97,%98,%99,%100,%101,%102,%103,%104,%105,%106,%107,%108,%109,%110,%111,%112,%113,%114,%115,%116,%117,%118,%119,%120,%121,%122,%123,%124,%125,%126,%127}, {%128,%129,%130,%131}, %132, p, 1, 1, 1;\n}\n"
    : "+f"(d[0]),"+f"(d[1]),"+f"(d[2]),"+f"(d[3]),"+f"(d[4]),"+f"(d[5]),"+f"(d[6]),"+f"(d[7]),"+f"(d[8]),"+f"(d[9]),"+f"(d[10]),"+f"(d[11]),"+f"(d[12]),"+f"(d[13]),"+f"(d[14]),"+f"(d[15]),"+f"(d[16]),"+f"(d[17]),"+f"(d[18]),"+f"(d[19]),"+f"(d[20]),"+f"(d[21]),"+f"(d[22]),"+f"(d[23]),"+f"(d[24]),"+f"(d[25]),"+f"(d[26]),"+f"(d[27]),"+f"(d[28]),"+f"(d[29]),"+f"(d[30]),"+f"(d[31]),"+f"(d[32]),"+f"(d[33]),"+f"(d[34]),"+f"(d[35]),"+f"(d[36]),"+f"(d[37]),"+f"(d[38]),"+f"(d[39]),"+f"(d[40]),"+f"(d[41]),"+f"(d[42]),"+f"(d[43]),"+f"(d[44]),"+f"(d[45]),"+f"(d[46]),"+f"(d[47]),"+f"(d[48]),"+f"(d[49]),"+f"(d[50]),"+f"(d[51]),"+f"(d[52]),"+f"(d[53]),"+f"(d[54]),"+f"(d[55]),"+f"(d[56]),"+f"(d[57]),"+f"(d[58]),"+f"(d[59]),"+f"(d[60]),"+f"(d[61]),"+f"(d[62]),"+f"(d[63]),"+f"(d[64]),"+f"(d[65]),"+f"(d[66]),"+f"(d[67]),"+f"(d[68]),"+f"(d[69]),"+f"(d[70]),"+f"(d[71]),"+f"(d[72]),"+f"(d[73]),"+f"(d[74]),"+f"(d[75]),"+f"(d[76]),"+f"(d[77]),"+f"(d[78]),"+f"(d[79]),"+f"(d[80]),"+f"(d[81]),"+f"(d[82]),"+f"(d[83]),"+f"(d[84]),"+f"(d[85]),"+f"(d[86]),"+f"(d[87]),"+f"(d[88]),"+f"(d[89]),"+f"(d[90]),"+f"(d[91]),"+f"(d[92]),"+f"(d[93]),"+f"(d[94]),"+f"(d[95]),"+f"(d[96]),"+f"(d[97]),"+f"(d[98]),"+f"(d[99]),"+f"(d[100]),"+f"(d[101]),"+f"(d[102]),"+f"(d[103]),"+f"(d[104]),"+f"(d[105]),"+f"(d[106]),"+f"(d[107]),"+f"(d[108]),"+f"(d[109]),"+f"(d[110]),"+f"(d[111]),"+f"(d[112]),"+f"(d[113]),"+f"(d[114]),"+f"(d[115]),"+f"(d[116]),"+f"(d[117]),"+f"(d[118]),"+f"(d[119]),"+f"(d[120]),"+f"(d[121]),"+f"(d[122]),"+f"(d[123]),"+f"(d[124]),"+f"(d[125]),"+f"(d[126]),"+f"(d[127]) : "r"(a0), "r"(a1), "r"(a2), "r"(a3), "l"(db), "r"(sc));
}
template<int N> __device__ __forceinline__ void wgmma_rsz(float (&d)[N / 2], uint32_t a0, uint32_t a1, uint32_t a2, uint32_t a3, uint64_t db);
template<> __device__ __forceinline__ void wgmma_rsz<8>(float (&d)[4], uint32_t a0, uint32_t a1, uint32_t a2, uint32_t a3, uint64_t db) {
  asm volatile("{\n.reg .pred p;\nsetp.ne.b32 p, 0, 0;\n"
    "wgmma.mma_async.sync.aligned.m64n8k16.f32.bf16.bf16 {%0,%1,%2,%3}, {%4,%5,%6,%7}, %8, p, 1, 1, 1;\n}\n"
    : "=f"(d[0]),"=f"(d[1]),"=f"(d[2]),"=f"(d[3]) : "r"(a0), "r"(a1), "r"(a2), "r"(a3), "l"(db));
}
template<> __device__ __forceinline__ void wgmma_rsz<24>(float (&d)[12], uint32_t a0, uint32_t a1, uint32_t a2, uint32_t a3, uint64_t db) {
  asm volatile("{\n.reg .pred p;\nsetp.ne.b32 p, 0, 0;\n"
    "wgmma.mma_async.sync.aligned.m64n24k16.f32.bf16.bf16 {%0,%1,%2,%3,%4,%5,%6,%7,%8,%9,%10,%11}, {%12,%13,%14,%15}, %16, p, 1, 1, 1;\n}\n"
    : "=f"(d[0]),"=f"(d[1]),"=f"(d[2]),"=f"(d[3]),"=f"(d[4]),"=f"(d[5]),"=f"(d[6]),"=f"(d[7]),"=f"(d[8]),"=f"(d[9]),"=f"(d[10]),"=f"(d[11]) : "r"(a0), "r"(a1), "r"(a2), "r"(a3), "l"(db));
}
template<> __device__ __forceinline__ void wgmma_rsz<64>(float (&d)[32], uint32_t a0, uint32_t a1, uint32_t a2, uint32_t a3, uint64_t db) {
  asm volatile("{\n.reg .pred p;\nsetp.ne.b32 p, 0, 0;\n"
    "wgmma.mma_async.sync.aligned.m64n64k16.f32.bf16.bf16 {%0,%1,%2,%3,%4,%5,%6,%7,%8,%9,%10,%11,%12,%13,%14,%15,%16,%17,%18,%19,%20,%21,%22,%23,%24,%25,%26,%27,%28,%29,%30,%31}, {%32,%33,%34,%35}, %36, p, 1, 1, 1;\n}\n"
    : "=f"(d[0]),"=f"(d[1]),"=f"(d[2]),"=f"(d[3]),"=f"(d[4]),"=f"(d[5]),"=f"(d[6]),"=f"(d[7]),"=f"(d[8]),"=f"(d[9]),"=f"(d[10]),"=f"(d[11]),"=f"(d[12]),"=f"(d[13]),"=f"(d[14]),"=f"(d[15]),"=f"(d[16]),"=f"(d[17]),"=f"(d[18]),"=f"(d[19]),"=f"(d[20]),"=f"(d[21]),"=f"(d[22]),"=f"(d[23]),"=f"(d[24]),"=f"(d[25]),"=f"(d[26]),"=f"(d[27]),"=f"(d[28]),"=f"(d[29]),"=f"(d[30]),"=f"(d[31]) : "r"(a0), "r"(a1), "r"(a2), "r"(a3), "l"(db));
}
template<> __device__ __forceinline__ void wgmma_rsz<192>(float (&d)[96], uint32_t a0, uint32_t a1, uint32_t a2, uint32_t a3, uint64_t db) {
  asm volatile("{\n.reg .pred p;\nsetp.ne.b32 p, 0, 0;\n"
    "wgmma.mma_async.sync.aligned.m64n192k16.f32.bf16.bf16 {%0,%1,%2,%3,%4,%5,%6,%7,%8,%9,%10,%11,%12,%13,%14,%15,%16,%17,%18,%19,%20,%21,%22,%23,%24,%25,%26,%27,%28,%29,%30,%31,%32,%33,%34,%35,%36,%37,%38,%39,%40,%41,%42,%43,%44,%45,%46,%47,%48,%49,%50,%51,%52,%53,%54,%55,%56,%57,%58,%59,%60,%61,%62,%63,%64,%65,%66,%67,%68,%69,%70,%71,%72,%73,%74,%75,%76,%77,%78,%79,%80,%81,%82,%83,%84,%85,%86,%87,%88,%89,%90,%91,%92,%93,%94,%95}, {%96,%97,%98,%99}, %100, p, 1, 1, 1;\n}\n"
    : "=f"(d[0]),"=f"(d[1]),"=f"(d[2]),"=f"(d[3]),"=f"(d[4]),"=f"(d[5]),"=f"(d[6]),"=f"(d[7]),"=f"(d[8]),"=f"(d[9]),"=f"(d[10]),"=f"(d[11]),"=f"(d[12]),"=f"(d[13]),"=f"(d[14]),"=f"(d[15]),"=f"(d[16]),"=f"(d[17]),"=f"(d[18]),"=f"(d[19]),"=f"(d[20]),"=f"(d[21]),"=f"(d[22]),"=f"(d[23]),"=f"(d[24]),"=f"(d[25]),"=f"(d[26]),"=f"(d[27]),"=f"(d[28]),"=f"(d[29]),"=f"(d[30]),"=f"(d[31]),"=f"(d[32]),"=f"(d[33]),"=f"(d[34]),"=f"(d[35]),"=f"(d[36]),"=f"(d[37]),"=f"(d[38]),"=f"(d[39]),"=f"(d[40]),"=f"(d[41]),"=f"(d[42]),"=f"(d[43]),"=f"(d[44]),"=f"(d[45]),"=f"(d[46]),"=f"(d[47]),"=f"(d[48]),"=f"(d[49]),"=f"(d[50]),"=f"(d[51]),"=f"(d[52]),"=f"(d[53]),"=f"(d[54]),"=f"(d[55]),"=f"(d[56]),"=f"(d[57]),"=f"(d[58]),"=f"(d[59]),"=f"(d[60]),"=f"(d[61]),"=f"(d[62]),"=f"(d[63]),"=f"(d[64]),"=f"(d[65]),"=f"(d[66]),"=f"(d[67]),"=f"(d[68]),"=f"(d[69]),"=f"(d[70]),"=f"(d[71]),"=f"(d[72]),"=f"(d[73]),"=f"(d[74]),"=f"(d[75]),"=f"(d[76]),"=f"(d[77]),"=f"(d[78]),"=f"(d[79]),"=f"(d[80]),"=f"(d[81]),"=f"(d[82]),"=f"(d[83]),"=f"(d[84]),"=f"(d[85]),"=f"(d[86]),"=f"(d[87]),"=f"(d[88]),"=f"(d[89]),"=f"(d[90]),"=f"(d[91]),"=f"(d[92]),"=f"(d[93]),"=f"(d[94]),"=f"(d[95]) : "r"(a0), "r"(a1), "r"(a2), "r"(a3), "l"(db));
}
template<> __device__ __forceinline__ void wgmma_rsz<256>(float (&d)[128], uint32_t a0, uint32_t a1, uint32_t a2, uint32_t a3, uint64_t db) {
  asm volatile("{\n.reg .pred p;\nsetp.ne.b32 p, 0, 0;\n"
    "wgmma.mma_async.sync.aligned.m64n256k16.f32.bf16.bf16 {%0,%1,%2,%3,%4,%5,%6,%7,%8,%9,%10,%11,%12,%13,%14,%15,%16,%17,%18,%19,%20,%21,%22,%23,%24,%25,%26,%27,%28,%29,%30,%31,%32,%33,%34,%35,%36,%37,%38,%39,%40,%41,%42,%43,%44,%45,%46,%47,%48,%49,%50,%51,%52,%53,%54,%55,%56,%57,%58,%59,%60,%61,%62,%63,%64,%65,%66,%67,%68,%69,%70,%71,%72,%73,%74,%75,%76,%77,%78,%79,%80,%81,%82,%83,%84,%85,%86,%87,%88,%89,%90,%91,%92,%93,%94,%95,%96,%97,%98,%99,%100,%101,%102,%103,%104,%105,%106,%107,%108,%109,%110,%111,%112,%113,%114,%115,%116,%117,%118,%119,%120,%121,%122,%123,%124,%125,%126,%127}, {%128,%129,%130,%131}, %132, p, 1, 1, 1;\n}\n"
    : "=f"(d[0]),"=f"(d[1]),"=f"(d[2]),"=f"(d[3]),"=f"(d[4]),"=f"(d[5]),"=f"(d[6]),"=f"(d[7]),"=f"(d[8]),"=f"(d[9]),"=f"(d[10]),"=f"(d[11]),"=f"(d[12]),"=f"(d[13]),"=f"(d[14]),"=f"(d[15]),"=f"(d[16]),"=f"(d[17]),"=f"(d[18]),"=f"(d[19]),"=f"(d[20]),"=f"(d[21]),"=f"(d[22]),"=f"(d[23]),"=f"(d[24]),"=f"(d[25]),"=f"(d[26]),"=f"(d[27]),"=f"(d[28]),"=f"(d[29]),"=f"(d[30]),"=f"(d[31]),"=f"(d[32]),"=f"(d[33]),"=f"(d[34]),"=f"(d[35]),"=f"(d[36]),"=f"(d[37]),"=f"(d[38]),"=f"(d[39]),"=f"(d[40]),"=f"(d[41]),"=f"(d[42]),"=f"(d[43]),"=f"(d[44]),"=f"(d[45]),"=f"(d[46]),"=f"(d[47]),"=f"(d[48]),"=f"(d[49]),"=f"(d[50]),"=f"(d[51]),"=f"(d[52]),"=f"(d[53]),"=f"(d[54]),"=f"(d[55]),"=f"(d[56]),"=f"(d[57]),"=f"(d[58]),"=f"(d[59]),"=f"(d[60]),"=f"(d[61]),"=f"(d[62]),"=f"(d[63]),"=f"(d[64]),"=f"(d[65]),"=f"(d[66]),"=f"(d[67]),"=f"(d[68]),"=f"(d[69]),"=f"(d[70]),"=f"(d[71]),"=f"(d[72]),"=f"(d[73]),"=f"(d[74]),"=f"(d[75]),"=f"(d[76]),"=f"(d[77]),"=f"(d[78]),"=f"(d[79]),"=f"(d[80]),"=f"(d[81]),"=f"(d[82]),"=f"(d[83]),"=f"(d[84]),"=f"(d[85]),"=f"(d[86]),"=f"(d[87]),"=f"(d[88]),"=f"(d[89]),"=f"(d[90]),"=f"(d[91]),"=f"(d[92]),"=f"(d[93]),"=f"(d[94]),"=f"(d[95]),"=f"(d[96]),"=f"(d[97]),"=f"(d[98]),"=f"(d[99]),"=f"(d[100]),"=f"(d[101]),"=f"(d[102]),"=f"(d[103]),"=f"(d[104]),"=f"(d[105]),"=f"(d[106]),"=f"(d[107]),"=f"(d[108]),"=f"(d[109]),"=f"(d[110]),"=f"(d[111]),"=f"(d[112]),"=f"(d[113]),"=f"(d[114]),"=f"(d[115]),"=f"(d[116]),"=f"(d[117]),"=f"(d[118]),"=f"(d[119]),"=f"(d[120]),"=f"(d[121]),"=f"(d[122]),"=f"(d[123]),"=f"(d[124]),"=f"(d[125]),"=f"(d[126]),"=f"(d[127]) : "r"(a0), "r"(a1), "r"(a2), "r"(a3), "l"(db));
}
template<int N> __device__ __forceinline__ void wgmma_ra(float (&d)[N / 2], const uint4& a, uint64_t db, bool acc) {
  if (acc) wgmma_rs<N>(d, a.x, a.y, a.z, a.w, db, 1); else wgmma_rsz<N>(d, a.x, a.y, a.z, a.w, db);
}

__device__ __forceinline__ uint32_t smem_u32(const void* p) { return (uint32_t)__cvta_generic_to_shared(p); }
__device__ __forceinline__ void mbar_init(uint32_t bar, uint32_t cnt) { asm volatile("mbarrier.init.shared::cta.b64 [%0], %1;" ::"r"(bar), "r"(cnt)); }
__device__ __forceinline__ void mbar_expect_tx(uint32_t bar, uint32_t bytes) { asm volatile("mbarrier.arrive.expect_tx.shared::cta.b64 _, [%0], %1;" ::"r"(bar), "r"(bytes) : "memory"); }
__device__ __forceinline__ void mbar_arrive(uint32_t bar) { asm volatile("mbarrier.arrive.shared::cta.b64 _, [%0];" ::"r"(bar) : "memory"); }
__device__ __forceinline__ void mbar_arrive_remote(uint32_t rbar) { asm volatile("mbarrier.arrive.shared::cluster.b64 _, [%0];" ::"r"(rbar) : "memory"); }
__device__ __forceinline__ void mbar_wait(uint32_t bar, uint32_t parity) {
  asm volatile(
      "{\n.reg .pred p;\n.reg .u32 c;\nmov.u32 c, 0;\nLAB_WAIT:\nmbarrier.try_wait.parity.shared::cta.b64 p, [%0], %1;\n@p bra DONE;\n"
      "add.u32 c, c, 1;\nsetp.lt.u32 p, c, 1000000;\n@p bra LAB_WAIT;\ntrap;\nDONE:\n}\n" ::"r"(bar), "r"(parity) : "memory");
}
__device__ __forceinline__ void mbar_wait_c(uint32_t bar, uint32_t parity) {
  asm volatile("{\n.reg .pred p;\nLAB_WAIT:\nmbarrier.try_wait.parity.shared::cta.b64 p, [%0], %1;\n@!p bra LAB_WAIT;\n}\n" ::"r"(bar), "r"(parity) : "memory");
}
__device__ __forceinline__ void wtma2d(uint32_t dst, const CUtensorMap* m, int c0, int c1, uint32_t bar, uint64_t pol) {
  asm volatile("cp.async.bulk.tensor.2d.shared::cluster.global.mbarrier::complete_tx::bytes.multicast::cluster.L2::cache_hint [%0], [%1, {%3, %4}], [%2], %5, %6;"
               ::"r"(dst), "l"(m), "r"(bar), "r"(c0), "r"(c1), "h"((uint16_t)3), "l"(pol) : "memory");
}
__device__ __forceinline__ void wtma3d(uint32_t dst, const CUtensorMap* m, int c0, int c1, int c2, uint32_t bar, uint64_t pol) {
  asm volatile("cp.async.bulk.tensor.3d.shared::cluster.global.mbarrier::complete_tx::bytes.multicast::cluster.L2::cache_hint [%0], [%1, {%3, %4, %5}], [%2], %6, %7;"
               ::"r"(dst), "l"(m), "r"(bar), "r"(c0), "r"(c1), "r"(c2), "h"((uint16_t)3), "l"(pol) : "memory");
}
__device__ __forceinline__ void tma_store3d(const CUtensorMap* m, uint32_t src, int c0, int c1, int c2) {
  asm volatile("cp.async.bulk.tensor.3d.global.shared::cta.bulk_group [%0, {%2, %3, %4}], [%1];" ::"l"(m), "r"(src), "r"(c0), "r"(c1), "r"(c2) : "memory");
}
__device__ __forceinline__ void prefetch_l2(const void* p, uint32_t bytes) { asm volatile("cp.async.bulk.prefetch.L2.global [%0], %1;" ::"l"(p), "r"(bytes) : "memory"); }
__device__ __forceinline__ uint64_t policy_evict_first() { uint64_t p; asm volatile("createpolicy.fractional.L2::evict_first.b64 %0, 1.0;" : "=l"(p)); return p; }
__device__ __forceinline__ uint64_t policy_evict_normal() { uint64_t p; asm volatile("createpolicy.fractional.L2::evict_normal.b64 %0, 1.0;" : "=l"(p)); return p; }
__device__ __forceinline__ void bulk_commit() { asm volatile("cp.async.bulk.commit_group;" ::: "memory"); }
__device__ __forceinline__ void bulk_wait_all() { asm volatile("cp.async.bulk.wait_group 0;" ::: "memory"); }
__device__ __forceinline__ void fence_async_smem() { asm volatile("fence.proxy.async.shared::cta;" ::: "memory"); }
__device__ __forceinline__ bool elect_one() {
  uint32_t p;
  asm volatile("{\n.reg .pred P;\nelect.sync _|P, 0xffffffff;\nselp.u32 %0, 1, 0, P;\n}\n" : "=r"(p));
  return p;
}
__device__ __forceinline__ void wg_fence() { asm volatile("wgmma.fence.sync.aligned;" ::: "memory"); }
__device__ __forceinline__ void wg_commit() { asm volatile("wgmma.commit_group.sync.aligned;" ::: "memory"); }
template <int n> __device__ __forceinline__ void wg_wait() { asm volatile("wgmma.wait_group.sync.aligned %0;" ::"n"(n) : "memory"); }
__device__ __forceinline__ void wg_bar(int w) { asm volatile("bar.sync %0, 128;" ::"r"(w + 1) : "memory"); }
__device__ __forceinline__ void cluster_sync() { asm volatile("barrier.cluster.arrive.relaxed.aligned;\nbarrier.cluster.wait.aligned;" ::: "memory"); }
__device__ __forceinline__ constexpr uint64_t desc_hi(uint32_t lbo, uint32_t sbo, int sw) {
  return ((uint64_t)(lbo >> 4) << 16) | ((uint64_t)(sbo >> 4) << 32) | ((uint64_t)sw << 62);
}
__device__ __forceinline__ void fence_gpu() { asm volatile("fence.acq_rel.gpu;" ::: "memory"); }
__device__ __forceinline__ uint32_t ld_relaxed(const uint32_t* p) { uint32_t v; asm volatile("ld.relaxed.gpu.global.u32 %0, [%1];" : "=r"(v) : "l"(p) : "memory"); return v; }
__device__ __forceinline__ uint4 ld_relaxed4(const uint4* p) {
  uint4 v; asm volatile("ld.relaxed.gpu.global.v4.u32 {%0,%1,%2,%3}, [%4];" : "=r"(v.x), "=r"(v.y), "=r"(v.z), "=r"(v.w) : "l"(p) : "memory"); return v;
}
__device__ __forceinline__ uint2 ld_relaxed2(const uint2* p) {
  uint2 v; asm volatile("ld.relaxed.gpu.global.v2.u32 {%0,%1}, [%2];" : "=r"(v.x), "=r"(v.y) : "l"(p) : "memory"); return v;
}
__device__ __forceinline__ void st_relaxed(uint32_t* p, uint32_t a) { asm volatile("st.relaxed.gpu.global.u32 [%0], %1;" ::"l"(p), "r"(a) : "memory"); }
__device__ __forceinline__ void st_relaxed4(uint4* p, uint32_t a, uint32_t b, uint32_t c, uint32_t d) {
  asm volatile("st.relaxed.gpu.global.v4.u32 [%0], {%1,%2,%3,%4};" ::"l"(p), "r"(a), "r"(b), "r"(c), "r"(d) : "memory");
}
__device__ __forceinline__ void st_relaxed2(uint2* p, uint32_t a, uint32_t b) {
  asm volatile("st.relaxed.gpu.global.v2.u32 [%0], {%1,%2};" ::"l"(p), "r"(a), "r"(b) : "memory");
}
__device__ __forceinline__ void red4(uint4* p, uint32_t a, uint32_t b, uint32_t c, uint32_t d) {
  asm volatile("red.relaxed.gpu.global.add.noftz.v4.bf16x2 [%0], {%1,%2,%3,%4};" ::"l"(p), "r"(a), "r"(b), "r"(c), "r"(d) : "memory");
}
__device__ __forceinline__ void red2(uint2* p, uint32_t a, uint32_t b) {
  asm volatile("red.relaxed.gpu.global.add.noftz.v2.bf16x2 [%0], {%1,%2};" ::"l"(p), "r"(a), "r"(b) : "memory");
}
constexpr int SPIN_MAX = 1 << 21;
__device__ __forceinline__ uint32_t pack_bf16(float lo, float hi) { uint32_t r; asm("cvt.rn.bf16x2.f32 %0, %1, %2;" : "=r"(r) : "f"(hi), "f"(lo)); return r; }
__device__ __forceinline__ float bf_lo(uint32_t v) { return __uint_as_float(v << 16); }
__device__ __forceinline__ float bf_hi(uint32_t v) { return __uint_as_float(v & 0xffff0000u); }
__device__ __forceinline__ float2 lds64(uint32_t a) { float2 v; asm volatile("ld.shared.v2.f32 {%0,%1}, [%2];" : "=f"(v.x), "=f"(v.y) : "r"(a)); return v; }
__device__ __forceinline__ void sts64f(uint32_t a, float x, float y) { asm volatile("st.shared.v2.f32 [%0], {%1,%2};" ::"r"(a), "f"(x), "f"(y) : "memory"); }
__device__ __forceinline__ void sts128(uint32_t a, uint32_t x, uint32_t y, uint32_t z, uint32_t u) { asm volatile("st.shared.v4.b32 [%0], {%1,%2,%3,%4};" ::"r"(a), "r"(x), "r"(y), "r"(z), "r"(u) : "memory"); }
__device__ __forceinline__ uint4 lds128(uint32_t a) { uint4 v; asm volatile("ld.shared.v4.u32 {%0,%1,%2,%3}, [%4];" : "=r"(v.x), "=r"(v.y), "=r"(v.z), "=r"(v.w) : "r"(a) : "memory"); return v; }
__device__ __forceinline__ uint32_t hadd2(uint32_t a, uint32_t b) { uint32_t r; asm("add.rn.bf16x2 %0, %1, %2;" : "=r"(r) : "r"(a), "r"(b)); return r; }
__device__ __forceinline__ void stsm4(uint32_t a, uint32_t r0, uint32_t r1, uint32_t r2, uint32_t r3) {
  asm volatile("stmatrix.sync.aligned.m8n8.x4.shared.b16 [%0], {%1,%2,%3,%4};" ::"r"(a), "r"(r0), "r"(r1), "r"(r2), "r"(r3) : "memory");
}
__device__ __forceinline__ void stsm2(uint32_t a, uint32_t r0, uint32_t r1) {
  asm volatile("stmatrix.sync.aligned.m8n8.x2.shared.b16 [%0], {%1,%2};" ::"r"(a), "r"(r0), "r"(r1) : "memory");
}
__device__ __forceinline__ void ldsm4(uint32_t (&r)[4], uint32_t a) {
  asm volatile("ldmatrix.sync.aligned.m8n8.x4.shared.b16 {%0,%1,%2,%3}, [%4];" : "=r"(r[0]), "=r"(r[1]), "=r"(r[2]), "=r"(r[3]) : "r"(a) : "memory");
}
__device__ __forceinline__ void ldsm4t(uint32_t (&r)[4], uint32_t a) {
  asm volatile("ldmatrix.sync.aligned.m8n8.x4.trans.shared.b16 {%0,%1,%2,%3}, [%4];" : "=r"(r[0]), "=r"(r[1]), "=r"(r[2]), "=r"(r[3]) : "r"(a) : "memory");
}
__device__ __forceinline__ void mma16816z(float (&d)[4], uint32_t a0, uint32_t a1, uint32_t a2, uint32_t a3, uint32_t b0, uint32_t b1) {
  asm("mma.sync.aligned.m16n8k16.row.col.f32.bf16.bf16.f32 {%0,%1,%2,%3}, {%4,%5,%6,%7}, {%8,%9}, {%10,%10,%10,%10};"
      : "=f"(d[0]), "=f"(d[1]), "=f"(d[2]), "=f"(d[3]) : "r"(a0), "r"(a1), "r"(a2), "r"(a3), "r"(b0), "r"(b1), "f"(0.f));
}
__device__ __forceinline__ void mma1688(float (&d)[4], uint32_t a0, uint32_t a1, uint32_t b0) {
  asm("mma.sync.aligned.m16n8k8.row.col.f32.bf16.bf16.f32 {%0,%1,%2,%3}, {%4,%5}, {%6}, {%0,%1,%2,%3};"
      : "+f"(d[0]), "+f"(d[1]), "+f"(d[2]), "+f"(d[3]) : "r"(a0), "r"(a1), "r"(b0));
}
__device__ __forceinline__ float quad_sum(float v) { v += __shfl_xor_sync(0xffffffffu, v, 1); v += __shfl_xor_sync(0xffffffffu, v, 2); return v; }
__device__ __forceinline__ float quad_max(float v) { v = fmaxf(v, __shfl_xor_sync(0xffffffffu, v, 1)); v = fmaxf(v, __shfl_xor_sync(0xffffffffu, v, 2)); return v; }
__device__ __forceinline__ float rcp(float x) { float r; asm("rcp.approx.ftz.f32 %0, %1;" : "=f"(r) : "f"(x)); return r; }
__device__ __forceinline__ float ex2(float x) { float r; asm("ex2.approx.ftz.f32 %0, %1;" : "=f"(r) : "f"(x)); return r; }
__device__ __forceinline__ uint32_t tagged(uint32_t v, uint32_t tag) { return (v & ~1u) | tag; }

__device__ __forceinline__ int group_k0(int g) { return g < 16 ? 64 * (g & 7) + 4 * (g & 8) : 32 * g; }

struct Cons {
  uint32_t sb;
  uint32_t rem;
  uint32_t sB, mB;
  bool elect;
  __device__ __forceinline__ void release2(uint32_t bar) const { if (elect) { mbar_arrive(sb + bar); mbar_arrive_remote(rem + bar); } }
  __device__ __forceinline__ uint32_t nextB(uint32_t& prev) {
    mbar_wait_c(sb + BAR_FULLB + sB, mB);
    const uint32_t a = (((sb & 0x3FFFF) + SM_B) >> 4) + sB * (BSLOT / 128);
    prev = sB == 0 ? 32 : sB - 8;
    sB += 8;
    if (sB == 40) { sB = 0; mB ^= 1; }
    return a;
  }
  __device__ __forceinline__ void releaseLastB() const { release2(BAR_EMPTYB + (sB == 0 ? 32 : sB - 8)); }
};

__device__ __forceinline__ void publish_x(const float (&v)[36], uint32_t (&p)[18], uint4* box, int si, int j, int t, uint32_t tag, uint32_t stag) {
  float s0 = v[0] + v[1], s1 = v[2] + v[3];
#pragma unroll
  for (int c = 1; c < 9; c++) { s0 += v[4 * c] + v[4 * c + 1]; s1 += v[4 * c + 2] + v[4 * c + 3]; }
  s0 = quad_sum(s0); s1 = quad_sum(s1);
  const uint32_t s0t = (__float_as_uint(s0) & ~3u) | stag;
  if ((t & 3) == 0) st_relaxed2(g_sum + si, s0t, __float_as_uint(s1));
#pragma unroll
  for (int i = 0; i < 18; i++) p[i] = pack_bf16(v[2 * i], v[2 * i + 1]);
  uint4* d = box + 2 * j * 128 + t;
#pragma unroll
  for (int i = 0; i < 4; i++) st_relaxed4(d + ((i & 1) + 8 * (i & 2)) * 128, tagged(p[4 * i], tag), p[4 * i + 1], p[4 * i + 2], p[4 * i + 3]);
  st_relaxed2((uint2*)(box + (32 + (j >> 1)) * 128 + t) + (j & 1), tagged(p[16], tag), p[17]);
  const float m0 = s0 * (1.f / 72), m1 = s1 * (1.f / 72);
  float d0 = 0.f, d1 = 0.f;
#pragma unroll
  for (int c = 0; c < 9; c++) {
    float a = v[4 * c] - m0, b = v[4 * c + 1] - m0; d0 = fmaf(a, a, fmaf(b, b, d0));
    a = v[4 * c + 2] - m1; b = v[4 * c + 3] - m1; d1 = fmaf(a, a, fmaf(b, b, d1));
  }
  d0 = quad_sum(d0); d1 = quad_sum(d1);
  if ((t & 3) == 0) st_relaxed4(g_m2 + si, s0t, __float_as_uint(s1), __float_as_uint(d0), __float_as_uint(d1));
}

template <class Pre, class Mma>
__device__ __forceinline__ float2 gather_gemm(Cons& c, const uint4* src, int sq, uint32_t tag, uint32_t stag, Pre&& pre, Mma&& mma) {
  uint2 sa, sc;
  do { sa = ld_relaxed2(g_sum + sq); sc = ld_relaxed2(g_sum + sq + 8); } while (__any_sync(0xffffffffu, ((sa.x ^ stag) | (sc.x ^ stag)) & 3));
  uint4 x[6][2];
#pragma unroll
  for (int g = 0; g < 6; g++) { x[g][0] = ld_relaxed4(src + 2 * g * 128); x[g][1] = ld_relaxed4(src + (2 * g + 1) * 128); }
  const float m0 = quad_sum(__uint_as_float(sa.x) + __uint_as_float(sc.x)) * (-1.f / 576), m1 = quad_sum(__uint_as_float(sa.y) + __uint_as_float(sc.y)) * (-1.f / 576);
  const uint32_t nm0 = pack_bf16(m0, m0), nm1 = pack_bf16(m1, m1);
  pre();
  uint4 u0, u1;
#pragma unroll
  for (int g = 0; g < 18; g++) {
    uint4 &a = x[g % 6][0], &b = x[g % 6][1];
    while (__any_sync(0xffffffffu, ((a.x ^ tag) | (b.x ^ tag) | (g < 16 ? 0u : (a.z ^ tag) | (b.z ^ tag))) & 1)) {
      a = ld_relaxed4(src + 2 * g * 128); b = ld_relaxed4(src + (2 * g + 1) * 128);
    }
    a.x = hadd2(a.x, nm0); a.y = hadd2(a.y, nm1); a.z = hadd2(a.z, nm0); a.w = hadd2(a.w, nm1);
    b.x = hadd2(b.x, nm0); b.y = hadd2(b.y, nm1); b.z = hadd2(b.z, nm0); b.w = hadd2(b.w, nm1);
    uint32_t prev;
    const uint32_t bb = c.nextB(prev);
    mma(g, bb, a, b);
    wg_wait<1>();
    if (g > 0) c.release2(BAR_EMPTYB + prev);
    if (g > 0 && g < 13) { x[(g - 1) % 6][0] = ld_relaxed4(src + 2 * (g + 5) * 128); x[(g - 1) % 6][1] = ld_relaxed4(src + (2 * g + 11) * 128); }
    if (g == 13) { u0 = ld_relaxed4(g_m2 + sq); u1 = ld_relaxed4(g_m2 + sq + 8); }
  }
  while (__any_sync(0xffffffffu, ((u0.x ^ stag) | (u1.x ^ stag)) & 3)) { u0 = ld_relaxed4(g_m2 + sq); u1 = ld_relaxed4(g_m2 + sq + 8); }
  float e0 = fmaf(__uint_as_float(u0.x), 1.f / 72, m0), e1 = fmaf(__uint_as_float(u1.x), 1.f / 72, m0);
  const float v0 = quad_sum(fmaf(72.f, fmaf(e0, e0, e1 * e1), __uint_as_float(u0.z) + __uint_as_float(u1.z)));
  e0 = fmaf(__uint_as_float(u0.y), 1.f / 72, m1); e1 = fmaf(__uint_as_float(u1.y), 1.f / 72, m1);
  const float v1 = quad_sum(fmaf(72.f, fmaf(e0, e0, e1 * e1), __uint_as_float(u0.w) + __uint_as_float(u1.w)));
  const float2 r = make_float2(rsqrtf(fmaf(v0, 1.f / 576, 1e-5f)), rsqrtf(fmaf(v1, 1.f / 576, 1e-5f)));
  wg_wait<0>();
  c.releaseLastB();
  return r;
}

template <int NB, int OFF>
__device__ __forceinline__ void glu(const float (&a)[128], uint32_t (&h)[144]) {
#pragma unroll
  for (int b = 0; b < 2 * NB; b++) h[OFF + b] = pack_bf16(a[2 * b] * a[4 * NB + 2 * b], a[2 * b + 1] * a[4 * NB + 2 * b + 1]);
}

__global__ void __cluster_dims__(2, 1, 1) __launch_bounds__(384, 1)
fused_kernel(const __grid_constant__ Maps maps, const __nv_bfloat16* __restrict__ x_in, const char* __restrict__ wqkv,
             const char* __restrict__ wo, const char* __restrict__ wg, const char* __restrict__ wu, const char* __restrict__ wd) {
  extern __shared__ __align__(1024) uint8_t smem_raw[];
  const uint32_t sb = smem_u32(smem_raw);
  const int warp = __shfl_sync(0xffffffffu, threadIdx.x >> 5, 0);
  const int lane = threadIdx.x & 31;
  const int rank = blockIdx.x & 1;
#define CTA_J(b) (((b) >> 1) & 7)
#define CTA_RB(b) ((((b) >> 4) << 1) | ((b) & 1))
  const int j = CTA_J(blockIdx.x), rb = CTA_RB(blockIdx.x);

  uint32_t xin[18];
  if (warp < 8) {
    const __nv_bfloat16* xr = x_in + (size_t)(128 * rb + 2 * (16 * (warp & 3) + (lane >> 2)) + (warp >> 2)) * D_ + 2 * (lane & 3);
#pragma unroll
    for (int cc = 0; cc < 9; cc++) {
      const int col = cc < 8 ? 64 * j + 8 * cc : 512 + 8 * j;
      xin[2 * cc] = __ldg((const uint32_t*)(xr + col)); xin[2 * cc + 1] = __ldg((const uint32_t*)(xr + 16 * D_ + col));
    }
  } else if (warp == 8) {
    if (lane < 11) asm volatile("prefetch.tensormap [%0];" ::"l"(&maps.qm + lane) : "memory");
  } else if (warp == 9) {
    if (lane < 4) prefetch_l2(wqkv + blockIdx.x * 15552 + lane * 3888, 3888);
  } else if (threadIdx.x < 320 + NBAR) {
    const uint32_t o = SM_BAR + 8 * (threadIdx.x - 320);
    mbar_init(sb + o, o >= BAR_EMPTYB ? 4 : 1);
    asm volatile("fence.mbarrier_init.release.cluster;" ::: "memory");
    if (sb & 1023) asm volatile("trap;");
  }
  __syncthreads();
  cluster_sync();

  if (warp >= 8) {
    asm volatile("setmaxnreg.dec.sync.aligned.u32 " STR(REGS_P) ";");
    if (warp == 8) {
      const uint64_t pol = W_POLICY();
      uint32_t s = 0, ph = 1;
      auto slot = [&](uint32_t bytes, auto&& issue) {
        const uint32_t bar = sb + BAR_FULLB + 8 * s;
        mbar_wait(sb + BAR_EMPTYB + 8 * s, ph);
        if (elect_one()) {
          mbar_expect_tx(bar, bytes);
          issue(sb + SM_B + s * BSLOT, bar);
        }
        if (++s == 5) { s = 0; ph ^= 1; }
      };
#pragma unroll 1
      for (int layer = 0; layer < NLAYERS; layer++) {
#pragma unroll 1
        for (int g = 0; g < 18; g++)
          slot(2 * 6912, [&](uint32_t dst, uint32_t bar) {
            const int k = group_k0(g) + 16 * rank;
            wtma3d(dst + rank * 8192, &maps.qm, 72 * j, k, 0, bar, pol);
            wtma3d(dst + rank * 8192 + 6144, &maps.qc, 72 * j + 64, k, 0, bar, pol);
          });
#pragma unroll 1
        for (int t = 0; t < 5; t++) {
          const CUtensorMap* m = &maps.g + (t < 3 ? rank : 2 + rank);
          const int c2 = t < 3 ? 9 * j + 2 * t : 18 * j + 3 + 3 * t;
          const uint32_t half = t < 3 ? 8192 : 6144;
#pragma unroll 1
          for (int g = 0; g < 18; g++)
            slot(2 * half, [&](uint32_t dst, uint32_t bar) { wtma3d(dst + rank * half, m, 0, group_k0(g), c2, bar, pol); });
        }
      }
    } else if (warp == 9) {
      const uint64_t pol = W_POLICY();
      uint32_t mE = 0xff;
      auto acquire = [&](uint32_t s) { mbar_wait(sb + BAR_EMPTYX + 8 * s, (mE >> s) & 1); mE ^= 1u << s; };
      auto slot = [&](uint32_t s, const CUtensorMap* m, int col, int row) {
        acquire(s);
        if (elect_one()) {
          mbar_expect_tx(sb + BAR_FULLX + 8 * s, XSLOT);
          wtma2d(sb + SM_X + s * XSLOT + rank * 9216, m, col, row + 72 * rank, sb + BAR_FULLX + 8 * s, pol);
        }
      };
#pragma unroll 1
      for (int layer = 0; layer < NLAYERS; layer++) {
        if (layer == 0) mbar_wait(sb + BAR_FULLB + 32, 0);
#pragma unroll 1
        for (int i = 0; i < 4; i++) slot(4 + i, &maps.o, 64 * j, 144 * i);
        acquire(0);
        if (elect_one()) {
          mbar_expect_tx(sb + BAR_FULLX, 9216);
          wtma2d(sb + SM_X + rank * 4608, &maps.oc, 512 + 8 * j, 288 * rank, sb + BAR_FULLX, pol);
          wtma2d(sb + SM_X + rank * 4608 + 2304, &maps.oc, 512 + 8 * j, 288 * rank + 144, sb + BAR_FULLX, pol);
        }
#pragma unroll 1
        for (int i = 1; i < 4; i++) acquire(i);
#pragma unroll 1
        for (int u = 0; u < 36; u++) slot(u & 7, &maps.d, u < 4 ? 512 : 64 * ((j + (u >> 2)) & 7), 576 * j + 144 * (u & 3));
      }
    } else {
      const int w = warp - 10, grp = 2 * rb + w;
      mbar_wait(sb + BAR_FULLB + 32, 0);
#pragma unroll 1
      for (int layer = 0; layer < NLAYERS; layer++) {
        uint4* ib = g_inbox[layer] + (grp * 8 + j) * INBOX + lane;
#pragma unroll 1
        for (int i = 0; i < INBOX; i += 32) {
          st_relaxed4(ib + i, 0, 0, 0, 0);
          if (layer == 0 && i < 3 * 32 && lane < 12) prefetch_l2((w ? wu : wg) + (size_t)(36 * rb + 12 * (i >> 5) + lane) * 9216 + 1152 * j, 1152);
          if (layer == NLAYERS - 1 && i == 0 && lane < 6) prefetch_l2(wd + (size_t)(576 * j + 36 * rb + 18 * w + 3 * lane) * 1152, 3456);
          __nanosleep(64);
        }
        if (layer == 0) {
          fence_gpu();
          __syncwarp();
          if (lane == 0) mbar_arrive(sb + BAR_CLR + 8 * w);
        }
      }
#pragma unroll 1
      for (int layer = 0; layer < NLAYERS; layer++) {
        mbar_wait(sb + BAR_REDDONE + 8 * w, layer);
        fence_gpu();
        __syncwarp();
        if (lane == 0) st_relaxed(g_flag + grp * 32 + j, layer ^ 1);
        for (int it = 0; it < SPIN_MAX; it++)
          if (__all_sync(0xffffffffu, ld_relaxed(g_flag + grp * 32 + (lane & 7)) == (layer ^ 1))) break;
        fence_gpu();
        if (lane == 0) mbar_arrive(sb + BAR_RREADY + 8 * w);
      }
      mbar_wait(sb + BAR_DONE + 8 * w, 0);
    }
    __syncwarp();
    cluster_sync();
  } else {
    asm volatile("setmaxnreg.inc.sync.aligned.u32 " STR(REGS_C) ";");
#define THREAD_IDS()                                                                   \
    int tid_ = threadIdx.x, bid_ = blockIdx.x;                                          \
    asm volatile("" : "+r"(tid_), "+r"(bid_));                                          \
    const int w = warp >> 2, wp = warp & 3;                                             \
    const int lane = tid_ & 31, t = tid_ & 127, g = lane >> 2, q = lane & 3;           \
    const int j = CTA_J(bid_), rb = CTA_RB(bid_), grp = 2 * rb + w;                    \
    const int st0 = (grp * 4 + wp) * 64 + g;             \
    const uint32_t dsb = (sb & 0x3FFFF) >> 4;                                          \
    (void)t; (void)g; (void)q; (void)grp; (void)j; (void)st0; (void)dsb
    Cons c;
    c.sb = sb; c.sB = 0; c.mB = 0; c.elect = (threadIdx.x & 127) == 0;
    asm volatile("mapa.shared::cluster.u32 %0, %1, %2;" : "=r"(c.rem) : "r"(sb), "r"(rank ^ 1));
    uint32_t mX = 0;
    PROF(0);
    if (OPEN) {
      THREAD_IDS();
      if (q == 0) { st_relaxed2(g_sum + st0 + 8 * j, 0, 0); st_relaxed4(g_m2 + st0 + 8 * j, 0, 0, 0, 0); }
      if (wp == 3) {
#pragma unroll
        for (int i = 0; i < 6; i++) st_relaxed4(g_halo + (grp * 8 + j) * 192 + lane + i * 32, 0, 0, 0, 0);
      }
    }
    float v[36];
#pragma unroll
    for (int i = 0; i < 18; i++) { v[2 * i] = bf_lo(xin[i]); v[2 * i + 1] = bf_hi(xin[i]); }
#pragma unroll 1
    for (int layer = 0;; layer++) {
      const uint32_t tag = layer ^ 1;
      const int pb = 1 + layer * 30;
      uint32_t res[18];
      {
        THREAD_IDS();
        PROF(pb + 0);
        publish_x(v, res, g_act[0] + grp * 4608, st0 + 8 * j, j, t, tag, 2 * layer + 1);
        PROF(pb + 1);
        float a1[96], a2[12];
        const float2 rs = gather_gemm(c, g_act[0] + grp * 4608 + t, st0 + 16 * q, tag, 2 * layer + 1, [&] { PROF(pb + 2); },
          [&](int gi, uint32_t bb, const uint4& f0, const uint4& f1) {
            if (gi == 0) PROF(pb + 3);
            wg_fence();
            wgmma_ra<192>(a1, f0, desc_hi(2048, 1024, 1) + bb, gi > 0);
            wgmma_ra<24>(a2, f0, desc_hi(128, 256, 0) + (bb + 384), gi > 0);
            wgmma_ra<192>(a1, f1, desc_hi(2048, 1024, 1) + (bb + 512), true);
            wgmma_ra<24>(a2, f1, desc_hi(128, 256, 0) + (bb + 896), true);
            wg_commit();
          });
        PROF(pb + 4);
        const uint32_t slab = sb + SM_SLAB + w * SLAB;
        {
          uint32_t kv[36];
#pragma unroll
          for (int cc = 0; cc < 18; cc++) {
            const float* a = cc == 8 ? a2 + 4 : cc == 17 ? a2 + 8 : cc < 8 ? a1 + 32 + 4 * cc : a1 + 28 + 4 * cc;
            kv[18 + cc] = pack_bf16(a[2] * rs.y, a[3] * rs.y);
          }
          if (wp == 3) {
            uint4* hp = g_halo + (grp * 8 + j) * 192 + lane;
#pragma unroll
            for (int i = 0; i < 6; i++) st_relaxed4(hp + i * 32, kv[18 + 3 * i], kv[19 + 3 * i], kv[20 + 3 * i], tag);
          }
#pragma unroll
          for (int cc = 0; cc < 18; cc++) {
            const float* a = cc == 8 ? a2 + 4 : cc == 17 ? a2 + 8 : cc < 8 ? a1 + 32 + 4 * cc : a1 + 28 + 4 * cc;
            kv[cc] = pack_bf16(a[0] * rs.x, a[1] * rs.x);
          }
          const uint32_t sd = slab + (lane >> 4) * 1152 + (8 + 16 * wp + (lane & 15)) * 16;
#pragma unroll
          for (int i = 0; i < 9; i++) stsm4(sd + i * 2304, kv[2 * i], kv[18 + 2 * i], kv[2 * i + 1], kv[19 + 2 * i]);
        }
        uint32_t Q[18];
#pragma unroll
        for (int cc = 0; cc < 8; cc++) { Q[2 * cc] = pack_bf16(a1[4 * cc], a1[4 * cc + 1]); Q[2 * cc + 1] = pack_bf16(a1[4 * cc + 2], a1[4 * cc + 3]); }
        Q[16] = pack_bf16(a2[0], a2[1]); Q[17] = pack_bf16(a2[2], a2[3]);
        wg_bar(w);
        if (wp == 0) {
          uint32_t kv[18];
#pragma unroll
          for (int i = 0; i < 18; i++) kv[i] = 0;
          if (rb > 0) {
            const uint4* hp = g_halo + ((grp - 2) * 8 + j) * 192 + lane;
            uint32_t bad;
            do {
              bad = 0;
#pragma unroll
              for (int i = 0; i < 6; i++) {
                const uint4 u = ld_relaxed4(hp + i * 32);
                kv[3 * i] = u.x; kv[3 * i + 1] = u.y; kv[3 * i + 2] = u.z; bad |= u.w ^ tag;
              }
            } while (__any_sync(0xffffffffu, bad));
          }
          const uint32_t sd = slab + (lane >> 3) * 1152 + (lane & 7) * 16;
#pragma unroll
          for (int i = 0; i < 4; i++) stsm4(sd + i * 4608, kv[4 * i], kv[4 * i + 1], kv[4 * i + 2], kv[4 * i + 3]);
          stsm2(sd + 4 * 4608, kv[16], kv[17]);
          __syncwarp();
        }
        PROF(pb + 5);
        const uint32_t kvb = slab + (16 * wp + lane) * 16;
        const bool lo0 = 2 * q > g, lo1 = 2 * q + 1 > g;
        const uint32_t M = (lo0 ? 0xffffu : 0u) | (lo1 ? 0xffff0000u : 0u);
        const bool first = (rb == 0 && wp == 0);
        const float sl0 = rs.x * (0.23570226039551584f * 1.4426950408889634f), sl1 = rs.y * (0.23570226039551584f * 1.4426950408889634f);
        uint4* ob = g_act[1] + grp * 4608 + t;
        uint32_t k0[4], v0[4];
        ldsm4(k0, kvb);
        ldsm4t(v0, kvb + 9 * 1152);
        uint32_t car0 = 0, car1 = 0;
#pragma unroll
        for (int h = 0; h < 4; h++) {
          uint32_t k1[4], k2[4], v1[4], v2[4];
          ldsm4(k1, kvb + (2 * h + 1) * 1152);
          ldsm4(k2, kvb + (2 * h + 2) * 1152);
          ldsm4t(v1, kvb + (10 + 2 * h) * 1152);
          ldsm4t(v2, kvb + (11 + 2 * h) * 1152);
          const uint32_t qa0 = q >= h ? Q[4 * h] : 0, qa1 = q >= h ? Q[4 * h + 1] : 0;
          const uint32_t qc0 = q <= h ? Q[4 * h + 4] : 0, qc1 = q <= h ? Q[4 * h + 5] : 0;
          float s[3][4];
#pragma unroll
          for (int kb = 0; kb < 3; kb++) {
            mma16816z(s[kb], qa0, qa1, Q[4 * h + 2], Q[4 * h + 3], k0[kb], k1[kb]);
            mma1688(s[kb], qc0, qc1, k2[kb]);
          }
          if (first) s[0][0] = s[0][1] = -INFINITY;
          const float l00 = lo0 ? s[0][0] : s[1][0], l01 = lo1 ? s[0][1] : s[1][1];
          const float l10 = lo0 ? s[1][2] : s[2][2], l11 = lo1 ? s[1][3] : s[2][3];
          const float mx0 = quad_max(fmaxf(l00, l01)) * sl0, mx1 = quad_max(fmaxf(l10, l11)) * sl1;
          const float p00 = ex2(fmaf(l00, sl0, -mx0)), p01 = ex2(fmaf(l01, sl0, -mx0));
          const float p10 = ex2(fmaf(l10, sl1, -mx1)), p11 = ex2(fmaf(l11, sl1, -mx1));
          const float i0 = rcp(quad_sum(p00 + p01)), i1 = rcp(quad_sum(p10 + p11));
          const uint32_t P0 = pack_bf16(p00 * i0, p01 * i0), P1 = pack_bf16(p10 * i1, p11 * i1);
          float oa[4], oc[4], od[4];
          mma16816z(oa, P0 & M, 0u, P0 & ~M, P1 & M, v0[0], v0[1]);
          mma16816z(oc, P0 & M, 0u, P0 & ~M, P1 & M, v1[0], v1[1]);
          mma16816z(od, P0 & M, 0u, P0 & ~M, P1 & M, v2[0], v2[1]);
          mma1688(oa, 0u, P1 & ~M, v0[2]);
          mma1688(oc, 0u, P1 & ~M, v1[2]);
          mma1688(od, 0u, P1 & ~M, v2[2]);
          const uint32_t o0 = q < h ? car0 : pack_bf16(oa[0], oa[1]), o1 = q < h ? car1 : pack_bf16(oa[2], oa[3]);
          st_relaxed4(ob + (8 * h + j) * 128, tagged(o0, tag), o1, pack_bf16(oc[0], oc[1]), pack_bf16(oc[2], oc[3]));
          car0 = pack_bf16(od[0], od[1]); car1 = pack_bf16(od[2], od[3]);
#pragma unroll
          for (int i = 0; i < 4; i++) { k0[i] = k2[i]; v0[i] = v2[i]; }
        }
        st_relaxed2((uint2*)(ob + (32 + (j >> 1)) * 128) + (j & 1), tagged(car0, tag), car1);
        PROF(pb + 6);
      }
      uint32_t lsb;
      {
        THREAD_IDS();
        const uint4* src = g_act[1] + grp * 4608 + t;
        uint4 x[36];
#pragma unroll
        for (int i = 0; i < 16; i++) x[i] = ld_relaxed4(src + i * 128);
        float a[32], a8[4];
#pragma unroll
        for (int i = 0; i < 5; i++) mbar_wait_c(sb + BAR_FULLX + 8 * ((4 + i) & 7), (mX >> ((4 + i) & 7)) & 1);
        mX ^= 0xf1;
#pragma unroll
        for (int b = 0; b < 9; b++) {
          while (true) {
            uint32_t bad = 0;
#pragma unroll
            for (int i = 4 * b; i < 4 * b + 4; i++) bad |= (x[i].x ^ tag) | (b < 8 ? 0u : x[i].z ^ tag);
            if (!__any_sync(0xffffffffu, bad & 1)) break;
#pragma unroll
            for (int i = 4 * b; i < 4 * b + 4; i++) x[i] = ld_relaxed4(src + i * 128);
          }
          if (b == 0) {
            PROF(pb + 7);
#pragma unroll
            for (int i = 16; i < 36; i++) x[i] = ld_relaxed4(src + i * 128);
          }
          wg_fence();
#pragma unroll
          for (int i = 4 * b; i < 4 * b + 4; i++) {
            const int r0 = i < 32 ? 72 * (i & 7) + 16 * (i >> 3) : 144 * (i - 32) + 64, rs = i < 32 ? 8 : 72;
            wgmma_ra<64>(a, x[i], desc_hi(0, rs * 128, 1) + (dsb + ((SM_X + 4 * XSLOT) >> 4) + r0 * 8), i > 0);
            wgmma_ra<8>(a8, x[i], desc_hi(rs * 16, 0, 0) + (dsb + (SM_X >> 4) + r0), i > 0);
          }
          wg_commit();
        }
        if (layer == 0) mbar_wait_c(sb + BAR_CLR + 8 * w, 0);
        wg_wait<0>();
        PROF(pb + 8);
#pragma unroll
        for (int i = 0; i < 18; i++) {
          v[2 * i] = bf_lo(res[i]) + (i < 16 ? a[2 * i] : a8[2 * i - 32]);
          v[2 * i + 1] = bf_hi(res[i]) + (i < 16 ? a[2 * i + 1] : a8[2 * i - 31]);
        }
        publish_x(v, res, g_act[2] + grp * 4608, st0 + 8 * j, j, t, tag, (2 * layer + 2) & 3);
        lsb = 0;
#pragma unroll
        for (int i = 0; i < 5; i++) lsb |= ((res[4 * i] ^ tag) & 1) << i;
        PROF(pb + 9);
      }
      uint32_t h[144];
      {
        THREAD_IDS();
        float a[128];
        const uint32_t xd = sb + SM_X + w * 2048 + (lane >> 4) * 1024 + (16 * wp + (lane & 15)) * 16;
        const float2 rs = gather_gemm(c, g_act[2] + grp * 4608 + t, st0 + 16 * q, tag, (2 * layer + 2) & 3,
          [&] { PROF(pb + 10); asm volatile("bar.sync 3, 256;" ::: "memory"); },
          [&](int gi, uint32_t bb, const uint4& f0, const uint4& f1) {
            if (gi == 0) PROF(pb + 11);
            wg_fence();
            wgmma_ra<256>(a, f0, desc_hi(4096, 1024, 1) + bb, gi > 0);
            wgmma_ra<256>(a, f1, desc_hi(4096, 1024, 1) + (bb + 128), true);
            wg_commit();
            stsm4(xd + gi * 8192, f0.x, f0.y, f0.z, f0.w);
            stsm4(xd + gi * 8192 + 4096, f1.x, f1.y, f1.z, f1.w);
            if (gi == 17) { fence_async_smem(); wg_bar(w); }
          });
        sts64f(sb + SM_KEEP + tid_ * 8, rs.x * rs.x, rs.y * rs.y);
        PROF(pb + 12);
        glu<16, 0>(a, h);
        const uint64_t da0 = desc_hi(1024, 128, 0) + (dsb + ((SM_X + w * 2048) >> 4));
        auto tile = [&](auto wide, auto last) {
#pragma unroll 1
          for (int gi = 0; gi < 18; gi++) {
            uint32_t prev;
            const uint32_t bb = c.nextB(prev);
            const uint64_t da = da0 + gi * 512;
            wg_fence();
            if (wide()) {
              wgmma_ss<256>(a, da, desc_hi(4096, 1024, 1) + bb, gi);
              wgmma_ss<256>(a, da + 256, desc_hi(4096, 1024, 1) + (bb + 128), 1);
            } else {
              wgmma_ss<192>(*(float(*)[96])a, da, desc_hi(2048, 512, 2) + bb, gi);
              wgmma_ss<192>(*(float(*)[96])a, da + 256, desc_hi(2048, 512, 2) + (bb + 64), 1);
            }
            wg_commit();
            wg_wait<1>();
            if (gi > 0 && !(last() && gi > 13)) c.release2(BAR_EMPTYB + prev);
            if (last() && gi == 12 && t < 4) { mbar_arrive(sb + BAR_EMPTYX + 8 * t); mbar_arrive_remote(c.rem + BAR_EMPTYX + 8 * t); }
          }
          wg_wait<0>();
          if (!last()) c.releaseLastB();
          if (last() && t < 4) { mbar_arrive(sb + BAR_EMPTYX + 32 + 8 * t); mbar_arrive_remote(c.rem + BAR_EMPTYX + 32 + 8 * t); }
        };
        auto yes = [] { return true; };
        auto no = [] { return false; };
        tile(yes, no); PROF(pb + 13); glu<16, 32>(a, h);
        tile(yes, no); PROF(pb + 14); glu<16, 64>(a, h);
        tile(no, no); PROF(pb + 15); glu<12, 96>(a, h);
        const uint32_t hole = sb + SM_B + 12288 + tid_ * 16;
#pragma unroll
        for (int i = 0; i < NSPILL; i++) sts128(hole + i * BSLOT, h[96 + 4 * i], h[97 + 4 * i], h[98 + 4 * i], h[99 + 4 * i]);
        tile(no, yes); PROF(pb + 16); glu<12, 120>(a, h);
#pragma unroll
        for (int i = 0; i < NSPILL; i++) { const uint4 u = lds128(hole + i * BSLOT); h[96 + 4 * i] = u.x; h[97 + 4 * i] = u.y; h[98 + 4 * i] = u.z; h[99 + 4 * i] = u.w; }
      }
      {
        THREAD_IDS();
        float d[32];
        uint32_t pk[16];
#pragma unroll
        for (int i = 0; i < 16; i++) pk[i] = 0;
        uint4* const ib = g_inbox[layer] + grp * 8 * INBOX;
        auto pass = [&](uint32_t s0, auto&& hook) {
          const uint64_t db = desc_hi(0, 1024, 1) + (dsb + (SM_X >> 4) + s0 * (XSLOT >> 4));
#pragma unroll
          for (int i = 0; i < 4; i++) {
            mbar_wait_c(sb + BAR_FULLX + 8 * (s0 + i), (mX >> (s0 + i)) & 1);
            wg_fence();
#pragma unroll
            for (int k = 9 * i; k < 9 * i + 9; k++) wgmma_ra<64>(d, make_uint4(h[4 * k], h[4 * k + 1], h[4 * k + 2], h[4 * k + 3]), db + k * 128, k > 0);
            wg_commit();
            hook(i);
            if (i > 0) { wg_wait<1>(); c.release2(BAR_EMPTYX + 8 * (s0 + i - 1)); }
          }
          mX ^= 15u << s0;
        };
        PROF(pb + 17);
#pragma unroll 1
        for (int p = 0; p < 8; p++) {
          const uint32_t s0 = 4 * (p & 1);
          pass(s0, [&](int i) {
            if (i == 0) {
              if (p > 1) {
                uint4* dst = ib + ((j + p - 1) & 7) * INBOX + t;
#pragma unroll
                for (int k = 0; k < 4; k++) red4(dst + k * 128, pk[4 * k], pk[4 * k + 1], pk[4 * k + 2], pk[4 * k + 3]);
                if (p == 7) { __syncwarp(); if (lane == 0) mbar_arrive(sb + BAR_REDDONE + 8 * w); }
              } else if (p == 1) {
                if (t < 5) { mbar_arrive(sb + BAR_EMPTYB + 8 * t); mbar_arrive_remote(c.rem + BAR_EMPTYB + 8 * t); }
#pragma unroll
                for (int k = 0; k < 8; k++) red2((uint2*)(ib + k * INBOX + 1024) + t, pk[2 * k], pk[2 * k + 1]);
              }
            }
          });
          wg_wait<0>();
          c.release2(BAR_EMPTYX + 8 * (s0 + 3));
#pragma unroll
          for (int i = 0; i < 16; i++) pk[i] = pack_bf16(d[2 * i], d[2 * i + 1]);
        }
        PROF(pb + 18);
        uint4 R[4], P[4], X[4];
        uint2 R9, X9;
        const uint4* in = ib + j * INBOX + t;
        pass(0, [&](int i) {
          if (i == 0) {
            uint4* dst = ib + ((j + 7) & 7) * INBOX + 512 + t;
#pragma unroll
            for (int k = 0; k < 4; k++) st_relaxed4(dst + k * 128, max(pk[4 * k], 1u), pk[4 * k + 1], pk[4 * k + 2], pk[4 * k + 3]);
          } else if (i == 2) {
            const uint4* box = g_act[2] + grp * 4608 + t;
#pragma unroll
            for (int k = 0; k < 4; k++) X[k] = ld_relaxed4(box + (2 * j + (k & 1) + 8 * (k & 2)) * 128);
            X9 = ld_relaxed2((const uint2*)(box + (32 + (j >> 1)) * 128) + (j & 1));
            mbar_wait_c(sb + BAR_RREADY + 8 * w, layer);
#pragma unroll
            for (int k = 0; k < 4; k++) R[k] = ld_relaxed4(in + k * 128);
            R9 = ld_relaxed2((const uint2*)(in - t + 1024) + t);
          } else if (i == 3) {
#pragma unroll
            for (int k = 0; k < 4; k++) P[k] = ld_relaxed4(in + 512 + k * 128);
          }
        });
        PROF(pb + 19);
        const float2 r2 = lds64(sb + SM_KEEP + tid_ * 8);
#pragma unroll
        for (int k = 0; k < 4; k++) X[k].x ^= (lsb >> k) & 1;
        X9.x ^= lsb >> 4;
        v[32] = fmaf(bf_lo(R9.x), r2.x, bf_lo(X9.x)); v[33] = fmaf(bf_hi(R9.x), r2.x, bf_hi(X9.x));
        v[34] = fmaf(bf_lo(R9.y), r2.y, bf_lo(X9.y)); v[35] = fmaf(bf_hi(R9.y), r2.y, bf_hi(X9.y));
        while (__any_sync(0xffffffffu, P[0].x == 0 || P[1].x == 0 || P[2].x == 0 || P[3].x == 0)) {
#pragma unroll
          for (int k = 0; k < 4; k++) P[k] = ld_relaxed4(in + 512 + k * 128);
        }
        auto comb = [&](int i, uint32_t r, uint32_t p, uint32_t x) {
          const float s = i & 1 ? r2.y : r2.x;
          v[2 * i] = fmaf(bf_lo(r) + bf_lo(p), s, bf_lo(x)); v[2 * i + 1] = fmaf(bf_hi(r) + bf_hi(p), s, bf_hi(x));
        };
#pragma unroll
        for (int k = 0; k < 4; k++) {
          comb(4 * k, R[k].x, P[k].x, X[k].x); comb(4 * k + 1, R[k].y, P[k].y, X[k].y);
          comb(4 * k + 2, R[k].z, P[k].z, X[k].z); comb(4 * k + 3, R[k].w, P[k].w, X[k].w);
        }
        PROF(pb + 20);
        wg_wait<0>();
        c.release2(BAR_EMPTYX + 24);
        PROF(pb + 21);
#pragma unroll
        for (int i = 0; i < 32; i++) v[i] = fmaf(d[i], i & 2 ? r2.y : r2.x, v[i]);
      }
      if (layer == NLAYERS - 1) break;
    }
    {
      THREAD_IDS();
      const uint32_t stg = sb + SM_B + warp * 4096;
      const uint32_t sd = stg + (lane & 15) * 128;
#pragma unroll
      for (int i = 0; i < 4; i++)
        stsm4(sd + (((2 * i + (lane >> 4)) ^ (lane & 7)) << 4), pack_bf16(v[8 * i], v[8 * i + 1]), pack_bf16(v[8 * i + 2], v[8 * i + 3]),
              pack_bf16(v[8 * i + 4], v[8 * i + 5]), pack_bf16(v[8 * i + 6], v[8 * i + 7]));
      stsm2(stg + 2048 + (lane & 15) * 16, pack_bf16(v[32], v[33]), pack_bf16(v[34], v[35]));
      fence_async_smem();
      __syncwarp();
      if (lane == 0) {
        tma_store3d(&maps.out, stg, 64 * j, w, 64 * rb + 16 * wp);
        tma_store3d(&maps.outc, stg + 2048, 512 + 8 * j, w, 64 * rb + 16 * wp);
        bulk_commit();
        bulk_wait_all();
        mbar_arrive(sb + BAR_DONE + 8 * w);
      }
      PROF(61);
    }
    __syncwarp();
    cluster_sync();
  }
}

typedef CUresult (*EncFn)(CUtensorMap*, CUtensorMapDataType, cuuint32_t, void*, const cuuint64_t*, const cuuint64_t*, const cuuint32_t*,
                          const cuuint32_t*, CUtensorMapInterleave, CUtensorMapSwizzle, CUtensorMapL2promotion, CUtensorMapFloatOOBfill);

void make_map(EncFn enc, CUtensorMap* m, const void* p, int rank, uint64_t d0, uint64_t d1, uint64_t d2, uint64_t s1, uint64_t s2, uint32_t b0,
              uint32_t b1, uint32_t b2, CUtensorMapSwizzle sw) {
  cuuint64_t gd[3] = {d0, d1, d2};
  cuuint64_t gs[2] = {s1, s2};
  cuuint32_t bd[3] = {b0, b1, b2};
  cuuint32_t es[3] = {1, 1, 1};
  enc(m, CU_TENSOR_MAP_DATA_TYPE_BFLOAT16, rank, const_cast<void*>(p), gd, gs, bd, es, CU_TENSOR_MAP_INTERLEAVE_NONE, sw,
      CU_TENSOR_MAP_L2_PROMOTION_L2_128B, CU_TENSOR_MAP_FLOAT_OOB_FILL_NONE);
}

}

extern "C" void kernel_launch(void* const* d_in, const int* in_sizes, int n_in, void* d_out, int out_size) {
  const __nv_bfloat16* x = (const __nv_bfloat16*)d_in[0];
  const char *wqkv = (const char*)d_in[1], *wo = (const char*)d_in[2], *wg = (const char*)d_in[4], *wu = (const char*)d_in[5], *wd = (const char*)d_in[6];
  static EncFn enc = nullptr;
  if (!enc) {
    cudaDriverEntryPointQueryResult qr;
    cudaGetDriverEntryPoint("cuTensorMapEncodeTiled", (void**)&enc, cudaEnableDefault, &qr);
    cudaFuncSetAttribute(fused_kernel, cudaFuncAttributeMaxDynamicSharedMemorySize, SMEM_BYTES);
  }
  const CUtensorMapSwizzle S0 = CU_TENSOR_MAP_SWIZZLE_NONE, S64 = CU_TENSOR_MAP_SWIZZLE_64B, S128 = CU_TENSOR_MAP_SWIZZLE_128B;
  Maps m;
  make_map(enc, &m.qm, wqkv, 3, 576, 576, 3, 3456, 1152, 64, 16, 3, S128);
  make_map(enc, &m.qc, wqkv, 3, 576, 576, 3, 3456, 1152, 8, 16, 3, S0);
  make_map(enc, &m.o, wo, 2, 576, 576, 1, 1152, 0, 64, 72, 1, S128);
  make_map(enc, &m.oc, wo, 2, 576, 576, 1, 1152, 0, 8, 144, 1, S0);
  make_map(enc, &m.g, wg, 3, 64, 576, 72, 9216, 128, 64, 32, 2, S128);
  make_map(enc, &m.u, wu, 3, 64, 576, 72, 9216, 128, 64, 32, 2, S128);
  make_map(enc, &m.g3, wg, 3, 32, 576, 144, 9216, 64, 32, 32, 3, S64);
  make_map(enc, &m.u3, wu, 3, 32, 576, 144, 9216, 64, 32, 32, 3, S64);
  make_map(enc, &m.d, wd, 2, 576, 4608, 1, 1152, 0, 64, 72, 1, S128);
  make_map(enc, &m.out, d_out, 3, 576, 2, 1024, 1152, 2304, 64, 1, 16, S128);
  make_map(enc, &m.outc, d_out, 3, 576, 2, 1024, 1152, 2304, 8, 1, 16, S0);
  fused_kernel<<<NCTA, 384, SMEM_BYTES>>>(m, x, wqkv, wo, wg, wu, wd);
}
```

```cpp
#include <cuda_runtime.h>
#include <cuda_bf16.h>
#include <cuda.h>
#include <stdint.h>
#include <stddef.h>

namespace {

constexpr int D_ = 576;
constexpr int NCTA = 128;
#define NLAYERS 2
#define W_POLICY policy_evict_first
#define A_POLICY policy_evict_normal
#define OPEN 1
#define PFMODE 3
#define NFIRST 3
#define WWIN 2
#define SPEC 1
#define LEAD 0
#define ATTBAR 0
#define QD 2
#define QG 5
#define XDELAY 0
#define WOH 1
#define PFSLEEP 700
#define GPCMAP 1
#define NSPILL 4
#define REGS_C 232
#define REGS_P 40
#define STR2(x) #x
#define STR(x) STR2(x)
constexpr uint32_t SM_X = 0;
constexpr uint32_t XSLOT = 18432;
constexpr uint32_t SM_WOC = SM_X + 3 * XSLOT + 9216;
constexpr uint32_t SM_B = 147456;
constexpr uint32_t BSLOT = 16384;
constexpr uint32_t SM_KEEP = 229376;
constexpr uint32_t SM_BAR = SM_KEEP + 2048;
constexpr uint32_t BAR_FULLB = SM_BAR;
constexpr uint32_t BAR_FULLX = SM_BAR + 40;
constexpr uint32_t BAR_RREADY = SM_BAR + 104;
constexpr uint32_t BAR_CLR = SM_BAR + 120;
constexpr uint32_t BAR_EMPTYB = SM_BAR + 144;
constexpr uint32_t BAR_EMPTYX = SM_BAR + 184;
constexpr uint32_t BAR_REDDONE = SM_BAR + 248;
constexpr uint32_t BAR_DONE = SM_BAR + 264;
constexpr uint32_t SM_PROG = SM_BAR + 288;
constexpr uint32_t SMEM_BYTES = SM_BAR + 1024;

struct Maps { CUtensorMap qm[2], qc[2], o, oc, g, u, g3, u3, d, out, outc; };

constexpr int INBOX = 1088;
struct Group {
  uint2 sum[4 * 8 * 8];
  uint4 m2[4 * 8 * 8];
  uint32_t flag[512];
  uint4 halo[8 * 160];
  uint4 act[3][36 * 128];
  uint4 inbox[2][8 * INBOX];
};
__device__ __align__(1024) Group g_ws[32];
#define PROF(i)
#define PROFX(i)

template<int N> __device__ __forceinline__ void wgmma_ss(float (&d)[N / 2], uint64_t da, uint64_t db, int sc);
template<> __device__ __forceinline__ void wgmma_ss<192>(float (&d)[96], uint64_t da, uint64_t db, int sc) {
  asm volatile("{\n.reg .pred p;\nsetp.ne.b32 p, %98, 0;\n"
    "wgmma.mma_async.sync.aligned.m64n192k16.f32.bf16.bf16 {%0,%1,%2,%3,%4,%5,%6,%7,%8,%9,%10,%11,%12,%13,%14,%15,%16,%17,%18,%19,%20,%21,%22,%23,%24,%25,%26,%27,%28,%29,%30,%31,%32,%33,%34,%35,%36,%37,%38,%39,%40,%41,%42,%43,%44,%45,%46,%47,%48,%49,%50,%51,%52,%53,%54,%55,%56,%57,%58,%59,%60,%61,%62,%63,%64,%65,%66,%67,%68,%69,%70,%71,%72,%73,%74,%75,%76,%77,%78,%79,%80,%81,%82,%83,%84,%85,%86,%87,%88,%89,%90,%91,%92,%93,%94,%95}, %96, %97, p, 1, 1, 0, 1;\n}\n"
    : "+f"(d[0]),"+f"(d[1]),"+f"(d[2]),"+f"(d[3]),"+f"(d[4]),"+f"(d[5]),"+f"(d[6]),"+f"(d[7]),"+f"(d[8]),"+f"(d[9]),"+f"(d[10]),"+f"(d[11]),"+f"(d[12]),"+f"(d[13]),"+f"(d[14]),"+f"(d[15]),"+f"(d[16]),"+f"(d[17]),"+f"(d[18]),"+f"(d[19]),"+f"(d[20]),"+f"(d[21]),"+f"(d[22]),"+f"(d[23]),"+f"(d[24]),"+f"(d[25]),"+f"(d[26]),"+f"(d[27]),"+f"(d[28]),"+f"(d[29]),"+f"(d[30]),"+f"(d[31]),"+f"(d[32]),"+f"(d[33]),"+f"(d[34]),"+f"(d[35]),"+f"(d[36]),"+f"(d[37]),"+f"(d[38]),"+f"(d[39]),"+f"(d[40]),"+f"(d[41]),"+f"(d[42]),"+f"(d[43]),"+f"(d[44]),"+f"(d[45]),"+f"(d[46]),"+f"(d[47]),"+f"(d[48]),"+f"(d[49]),"+f"(d[50]),"+f"(d[51]),"+f"(d[52]),"+f"(d[53]),"+f"(d[54]),"+f"(d[55]),"+f"(d[56]),"+f"(d[57]),"+f"(d[58]),"+f"(d[59]),"+f"(d[60]),"+f"(d[61]),"+f"(d[62]),"+f"(d[63]),"+f"(d[64]),"+f"(d[65]),"+f"(d[66]),"+f"(d[67]),"+f"(d[68]),"+f"(d[69]),"+f"(d[70]),"+f"(d[71]),"+f"(d[72]),"+f"(d[73]),"+f"(d[74]),"+f"(d[75]),"+f"(d[76]),"+f"(d[77]),"+f"(d[78]),"+f"(d[79]),"+f"(d[80]),"+f"(d[81]),"+f"(d[82]),"+f"(d[83]),"+f"(d[84]),"+f"(d[85]),"+f"(d[86]),"+f"(d[87]),"+f"(d[88]),"+f"(d[89]),"+f"(d[90]),"+f"(d[91]),"+f"(d[92]),"+f"(d[93]),"+f"(d[94]),"+f"(d[95]) : "l"(da), "l"(db), "r"(sc));
}
template<> __device__ __forceinline__ void wgmma_ss<256>(float (&d)[128], uint64_t da, uint64_t db, int sc) {
  asm volatile("{\n.reg .pred p;\nsetp.ne.b32 p, %130, 0;\n"
    "wgmma.mma_async.sync.aligned.m64n256k16.f32.bf16.bf16 {%0,%1,%2,%3,%4,%5,%6,%7,%8,%9,%10,%11,%12,%13,%14,%15,%16,%17,%18,%19,%20,%21,%22,%23,%24,%25,%26,%27,%28,%29,%30,%31,%32,%33,%34,%35,%36,%37,%38,%39,%40,%41,%42,%43,%44,%45,%46,%47,%48,%49,%50,%51,%52,%53,%54,%55,%56,%57,%58,%59,%60,%61,%62,%63,%64,%65,%66,%67,%68,%69,%70,%71,%72,%73,%74,%75,%76,%77,%78,%79,%80,%81,%82,%83,%84,%85,%86,%87,%88,%89,%90,%91,%92,%93,%94,%95,%96,%97,%98,%99,%100,%101,%102,%103,%104,%105,%106,%107,%108,%109,%110,%111,%112,%113,%114,%115,%116,%117,%118,%119,%120,%121,%122,%123,%124,%125,%126,%127}, %128, %129, p, 1, 1, 0, 1;\n}\n"
    : "+f"(d[0]),"+f"(d[1]),"+f"(d[2]),"+f"(d[3]),"+f"(d[4]),"+f"(d[5]),"+f"(d[6]),"+f"(d[7]),"+f"(d[8]),"+f"(d[9]),"+f"(d[10]),"+f"(d[11]),"+f"(d[12]),"+f"(d[13]),"+f"(d[14]),"+f"(d[15]),"+f"(d[16]),"+f"(d[17]),"+f"(d[18]),"+f"(d[19]),"+f"(d[20]),"+f"(d[21]),"+f"(d[22]),"+f"(d[23]),"+f"(d[24]),"+f"(d[25]),"+f"(d[26]),"+f"(d[27]),"+f"(d[28]),"+f"(d[29]),"+f"(d[30]),"+f"(d[31]),"+f"(d[32]),"+f"(d[33]),"+f"(d[34]),"+f"(d[35]),"+f"(d[36]),"+f"(d[37]),"+f"(d[38]),"+f"(d[39]),"+f"(d[40]),"+f"(d[41]),"+f"(d[42]),"+f"(d[43]),"+f"(d[44]),"+f"(d[45]),"+f"(d[46]),"+f"(d[47]),"+f"(d[48]),"+f"(d[49]),"+f"(d[50]),"+f"(d[51]),"+f"(d[52]),"+f"(d[53]),"+f"(d[54]),"+f"(d[55]),"+f"(d[56]),"+f"(d[57]),"+f"(d[58]),"+f"(d[59]),"+f"(d[60]),"+f"(d[61]),"+f"(d[62]),"+f"(d[63]),"+f"(d[64]),"+f"(d[65]),"+f"(d[66]),"+f"(d[67]),"+f"(d[68]),"+f"(d[69]),"+f"(d[70]),"+f"(d[71]),"+f"(d[72]),"+f"(d[73]),"+f"(d[74]),"+f"(d[75]),"+f"(d[76]),"+f"(d[77]),"+f"(d[78]),"+f"(d[79]),"+f"(d[80]),"+f"(d[81]),"+f"(d[82]),"+f"(d[83]),"+f"(d[84]),"+f"(d[85]),"+f"(d[86]),"+f"(d[87]),"+f"(d[88]),"+f"(d[89]),"+f"(d[90]),"+f"(d[91]),"+f"(d[92]),"+f"(d[93]),"+f"(d[94]),"+f"(d[95]),"+f"(d[96]),"+f"(d[97]),"+f"(d[98]),"+f"(d[99]),"+f"(d[100]),"+f"(d[101]),"+f"(d[102]),"+f"(d[103]),"+f"(d[104]),"+f"(d[105]),"+f"(d[106]),"+f"(d[107]),"+f"(d[108]),"+f"(d[109]),"+f"(d[110]),"+f"(d[111]),"+f"(d[112]),"+f"(d[113]),"+f"(d[114]),"+f"(d[115]),"+f"(d[116]),"+f"(d[117]),"+f"(d[118]),"+f"(d[119]),"+f"(d[120]),"+f"(d[121]),"+f"(d[122]),"+f"(d[123]),"+f"(d[124]),"+f"(d[125]),"+f"(d[126]),"+f"(d[127]) : "l"(da), "l"(db), "r"(sc));
}
template<int N> __device__ __forceinline__ void wgmma_rs(float (&d)[N / 2], uint32_t a0, uint32_t a1, uint32_t a2, uint32_t a3, uint64_t db, int sc);
template<> __device__ __forceinline__ void wgmma_rs<8>(float (&d)[4], uint32_t a0, uint32_t a1, uint32_t a2, uint32_t a3, uint64_t db, int sc) {
  asm volatile("{\n.reg .pred p;\nsetp.ne.b32 p, %9, 0;\n"
    "wgmma.mma_async.sync.aligned.m64n8k16.f32.bf16.bf16 {%0,%1,%2,%3}, {%4,%5,%6,%7}, %8, p, 1, 1, 1;\n}\n"
    : "+f"(d[0]),"+f"(d[1]),"+f"(d[2]),"+f"(d[3]) : "r"(a0), "r"(a1), "r"(a2), "r"(a3), "l"(db), "r"(sc));
}
template<> __device__ __forceinline__ void wgmma_rs<24>(float (&d)[12], uint32_t a0, uint32_t a1, uint32_t a2, uint32_t a3, uint64_t db, int sc) {
  asm volatile("{\n.reg .pred p;\nsetp.ne.b32 p, %17, 0;\n"
    "wgmma.mma_async.sync.aligned.m64n24k16.f32.bf16.bf16 {%0,%1,%2,%3,%4,%5,%6,%7,%8,%9,%10,%11}, {%12,%13,%14,%15}, %16, p, 1, 1, 1;\n}\n"
    : "+f"(d[0]),"+f"(d[1]),"+f"(d[2]),"+f"(d[3]),"+f"(d[4]),"+f"(d[5]),"+f"(d[6]),"+f"(d[7]),"+f"(d[8]),"+f"(d[9]),"+f"(d[10]),"+f"(d[11]) : "r"(a0), "r"(a1), "r"(a2), "r"(a3), "l"(db), "r"(sc));
}
template<> __device__ __forceinline__ void wgmma_rs<64>(float (&d)[32], uint32_t a0, uint32_t a1, uint32_t a2, uint32_t a3, uint64_t db, int sc) {
  asm volatile("{\n.reg .pred p;\nsetp.ne.b32 p, %37, 0;\n"
    "wgmma.mma_async.sync.aligned.m64n64k16.f32.bf16.bf16 {%0,%1,%2,%3,%4,%5,%6,%7,%8,%9,%10,%11,%12,%13,%14,%15,%16,%17,%18,%19,%20,%21,%22,%23,%24,%25,%26,%27,%28,%29,%30,%31}, {%32,%33,%34,%35}, %36, p, 1, 1, 1;\n}\n"
    : "+f"(d[0]),"+f"(d[1]),"+f"(d[2]),"+f"(d[3]),"+f"(d[4]),"+f"(d[5]),"+f"(d[6]),"+f"(d[7]),"+f"(d[8]),"+f"(d[9]),"+f"(d[10]),"+f"(d[11]),"+f"(d[12]),"+f"(d[13]),"+f"(d[14]),"+f"(d[15]),"+f"(d[16]),"+f"(d[17]),"+f"(d[18]),"+f"(d[19]),"+f"(d[20]),"+f"(d[21]),"+f"(d[22]),"+f"(d[23]),"+f"(d[24]),"+f"(d[25]),"+f"(d[26]),"+f"(d[27]),"+f"(d[28]),"+f"(d[29]),"+f"(d[30]),"+f"(d[31]) : "r"(a0), "r"(a1), "r"(a2), "r"(a3), "l"(db), "r"(sc));
}
template<> __device__ __forceinline__ void wgmma_rs<192>(float (&d)[96], uint32_t a0, uint32_t a1, uint32_t a2, uint32_t a3, uint64_t db, int sc) {
  asm volatile("{\n.reg .pred p;\nsetp.ne.b32 p, %101, 0;\n"
    "wgmma.mma_async.sync.aligned.m64n192k16.f32.bf16.bf16 {%0,%1,%2,%3,%4,%5,%6,%7,%8,%9,%10,%11,%12,%13,%14,%15,%16,%17,%18,%19,%20,%21,%22,%23,%24,%25,%26,%27,%28,%29,%30,%31,%32,%33,%34,%35,%36,%37,%38,%39,%40,%41,%42,%43,%44,%45,%46,%47,%48,%49,%50,%51,%52,%53,%54,%55,%56,%57,%58,%59,%60,%61,%62,%63,%64,%65,%66,%67,%68,%69,%70,%71,%72,%73,%74,%75,%76,%77,%78,%79,%80,%81,%82,%83,%84,%85,%86,%87,%88,%89,%90,%91,%92,%93,%94,%95}, {%96,%97,%98,%99}, %100, p, 1, 1, 1;\n}\n"
    : "+f"(d[0]),"+f"(d[1]),"+f"(d[2]),"+f"(d[3]),"+f"(d[4]),"+f"(d[5]),"+f"(d[6]),"+f"(d[7]),"+f"(d[8]),"+f"(d[9]),"+f"(d[10]),"+f"(d[11]),"+f"(d[12]),"+f"(d[13]),"+f"(d[14]),"+f"(d[15]),"+f"(d[16]),"+f"(d[17]),"+f"(d[18]),"+f"(d[19]),"+f"(d[20]),"+f"(d[21]),"+f"(d[22]),"+f"(d[23]),"+f"(d[24]),"+f"(d[25]),"+f"(d[26]),"+f"(d[27]),"+f"(d[28]),"+f"(d[29]),"+f"(d[30]),"+f"(d[31]),"+f"(d[32]),"+f"(d[33]),"+f"(d[34]),"+f"(d[35]),"+f"(d[36]),"+f"(d[37]),"+f"(d[38]),"+f"(d[39]),"+f"(d[40]),"+f"(d[41]),"+f"(d[42]),"+f"(d[43]),"+f"(d[44]),"+f"(d[45]),"+f"(d[46]),"+f"(d[47]),"+f"(d[48]),"+f"(d[49]),"+f"(d[50]),"+f"(d[51]),"+f"(d[52]),"+f"(d[53]),"+f"(d[54]),"+f"(d[55]),"+f"(d[56]),"+f"(d[57]),"+f"(d[58]),"+f"(d[59]),"+f"(d[60]),"+f"(d[61]),"+f"(d[62]),"+f"(d[63]),"+f"(d[64]),"+f"(d[65]),"+f"(d[66]),"+f"(d[67]),"+f"(d[68]),"+f"(d[69]),"+f"(d[70]),"+f"(d[71]),"+f"(d[72]),"+f"(d[73]),"+f"(d[74]),"+f"(d[75]),"+f"(d[76]),"+f"(d[77]),"+f"(d[78]),"+f"(d[79]),"+f"(d[80]),"+f"(d[81]),"+f"(d[82]),"+f"(d[83]),"+f"(d[84]),"+f"(d[85]),"+f"(d[86]),"+f"(d[87]),"+f"(d[88]),"+f"(d[89]),"+f"(d[90]),"+f"(d[91]),"+f"(d[92]),"+f"(d[93]),"+f"(d[94]),"+f"(d[95]) : "r"(a0), "r"(a1), "r"(a2), "r"(a3), "l"(db), "r"(sc));
}
template<> __device__ __forceinline__ void wgmma_rs<256>(float (&d)[128], uint32_t a0, uint32_t a1, uint32_t a2, uint32_t a3, uint64_t db, int sc) {
  asm volatile("{\n.reg .pred p;\nsetp.ne.b32 p, %133, 0;\n"
    "wgmma.mma_async.sync.aligned.m64n256k16.f32.bf16.bf16 {%0,%1,%2,%3,%4,%5,%6,%7,%8,%9,%10,%11,%12,%13,%14,%15,%16,%17,%18,%19,%20,%21,%22,%23,%24,%25,%26,%27,%28,%29,%30,%31,%32,%33,%34,%35,%36,%37,%38,%39,%40,%41,%42,%43,%44,%45,%46,%47,%48,%49,%50,%51,%52,%53,%54,%55,%56,%57,%58,%59,%60,%61,%62,%63,%64,%65,%66,%67,%68,%69,%70,%71,%72,%73,%74,%75,%76,%77,%78,%79,%80,%81,%82,%83,%84,%85,%86,%87,%88,%89,%90,%91,%92,%93,%94,%95,%96,%97,%98,%99,%100,%101,%102,%103,%104,%105,%106,%107,%108,%109,%110,%111,%112,%113,%114,%115,%116,%117,%118,%119,%120,%121,%122,%123,%124,%125,%126,%127}, {%128,%129,%130,%131}, %132, p, 1, 1, 1;\n}\n"
    : "+f"(d[0]),"+f"(d[1]),"+f"(d[2]),"+f"(d[3]),"+f"(d[4]),"+f"(d[5]),"+f"(d[6]),"+f"(d[7]),"+f"(d[8]),"+f"(d[9]),"+f"(d[10]),"+f"(d[11]),"+f"(d[12]),"+f"(d[13]),"+f"(d[14]),"+f"(d[15]),"+f"(d[16]),"+f"(d[17]),"+f"(d[18]),"+f"(d[19]),"+f"(d[20]),"+f"(d[21]),"+f"(d[22]),"+f"(d[23]),"+f"(d[24]),"+f"(d[25]),"+f"(d[26]),"+f"(d[27]),"+f"(d[28]),"+f"(d[29]),"+f"(d[30]),"+f"(d[31]),"+f"(d[32]),"+f"(d[33]),"+f"(d[34]),"+f"(d[35]),"+f"(d[36]),"+f"(d[37]),"+f"(d[38]),"+f"(d[39]),"+f"(d[40]),"+f"(d[41]),"+f"(d[42]),"+f"(d[43]),"+f"(d[44]),"+f"(d[45]),"+f"(d[46]),"+f"(d[47]),"+f"(d[48]),"+f"(d[49]),"+f"(d[50]),"+f"(d[51]),"+f"(d[52]),"+f"(d[53]),"+f"(d[54]),"+f"(d[55]),"+f"(d[56]),"+f"(d[57]),"+f"(d[58]),"+f"(d[59]),"+f"(d[60]),"+f"(d[61]),"+f"(d[62]),"+f"(d[63]),"+f"(d[64]),"+f"(d[65]),"+f"(d[66]),"+f"(d[67]),"+f"(d[68]),"+f"(d[69]),"+f"(d[70]),"+f"(d[71]),"+f"(d[72]),"+f"(d[73]),"+f"(d[74]),"+f"(d[75]),"+f"(d[76]),"+f"(d[77]),"+f"(d[78]),"+f"(d[79]),"+f"(d[80]),"+f"(d[81]),"+f"(d[82]),"+f"(d[83]),"+f"(d[84]),"+f"(d[85]),"+f"(d[86]),"+f"(d[87]),"+f"(d[88]),"+f"(d[89]),"+f"(d[90]),"+f"(d[91]),"+f"(d[92]),"+f"(d[93]),"+f"(d[94]),"+f"(d[95]),"+f"(d[96]),"+f"(d[97]),"+f"(d[98]),"+f"(d[99]),"+f"(d[100]),"+f"(d[101]),"+f"(d[102]),"+f"(d[103]),"+f"(d[104]),"+f"(d[105]),"+f"(d[106]),"+f"(d[107]),"+f"(d[108]),"+f"(d[109]),"+f"(d[110]),"+f"(d[111]),"+f"(d[112]),"+f"(d[113]),"+f"(d[114]),"+f"(d[115]),"+f"(d[116]),"+f"(d[117]),"+f"(d[118]),"+f"(d[119]),"+f"(d[120]),"+f"(d[121]),"+f"(d[122]),"+f"(d[123]),"+f"(d[124]),"+f"(d[125]),"+f"(d[126]),"+f"(d[127]) : "r"(a0), "r"(a1), "r"(a2), "r"(a3), "l"(db), "r"(sc));
}
template<int N> __device__ __forceinline__ void wgmma_rsz(float (&d)[N / 2], uint32_t a0, uint32_t a1, uint32_t a2, uint32_t a3, uint64_t db);
template<> __device__ __forceinline__ void wgmma_rsz<8>(float (&d)[4], uint32_t a0, uint32_t a1, uint32_t a2, uint32_t a3, uint64_t db) {
  asm volatile("{\n.reg .pred p;\nsetp.ne.b32 p, 0, 0;\n"
    "wgmma.mma_async.sync.aligned.m64n8k16.f32.bf16.bf16 {%0,%1,%2,%3}, {%4,%5,%6,%7}, %8, p, 1, 1, 1;\n}\n"
    : "=f"(d[0]),"=f"(d[1]),"=f"(d[2]),"=f"(d[3]) : "r"(a0), "r"(a1), "r"(a2), "r"(a3), "l"(db));
}
template<> __device__ __forceinline__ void wgmma_rsz<24>(float (&d)[12], uint32_t a0, uint32_t a1, uint32_t a2, uint32_t a3, uint64_t db) {
  asm volatile("{\n.reg .pred p;\nsetp.ne.b32 p, 0, 0;\n"
    "wgmma.mma_async.sync.aligned.m64n24k16.f32.bf16.bf16 {%0,%1,%2,%3,%4,%5,%6,%7,%8,%9,%10,%11}, {%12,%13,%14,%15}, %16, p, 1, 1, 1;\n}\n"
    : "=f"(d[0]),"=f"(d[1]),"=f"(d[2]),"=f"(d[3]),"=f"(d[4]),"=f"(d[5]),"=f"(d[6]),"=f"(d[7]),"=f"(d[8]),"=f"(d[9]),"=f"(d[10]),"=f"(d[11]) : "r"(a0), "r"(a1), "r"(a2), "r"(a3), "l"(db));
}
template<> __device__ __forceinline__ void wgmma_rsz<64>(float (&d)[32], uint32_t a0, uint32_t a1, uint32_t a2, uint32_t a3, uint64_t db) {
  asm volatile("{\n.reg .pred p;\nsetp.ne.b32 p, 0, 0;\n"
    "wgmma.mma_async.sync.aligned.m64n64k16.f32.bf16.bf16 {%0,%1,%2,%3,%4,%5,%6,%7,%8,%9,%10,%11,%12,%13,%14,%15,%16,%17,%18,%19,%20,%21,%22,%23,%24,%25,%26,%27,%28,%29,%30,%31}, {%32,%33,%34,%35}, %36, p, 1, 1, 1;\n}\n"
    : "=f"(d[0]),"=f"(d[1]),"=f"(d[2]),"=f"(d[3]),"=f"(d[4]),"=f"(d[5]),"=f"(d[6]),"=f"(d[7]),"=f"(d[8]),"=f"(d[9]),"=f"(d[10]),"=f"(d[11]),"=f"(d[12]),"=f"(d[13]),"=f"(d[14]),"=f"(d[15]),"=f"(d[16]),"=f"(d[17]),"=f"(d[18]),"=f"(d[19]),"=f"(d[20]),"=f"(d[21]),"=f"(d[22]),"=f"(d[23]),"=f"(d[24]),"=f"(d[25]),"=f"(d[26]),"=f"(d[27]),"=f"(d[28]),"=f"(d[29]),"=f"(d[30]),"=f"(d[31]) : "r"(a0), "r"(a1), "r"(a2), "r"(a3), "l"(db));
}
template<> __device__ __forceinline__ void wgmma_rsz<192>(float (&d)[96], uint32_t a0, uint32_t a1, uint32_t a2, uint32_t a3, uint64_t db) {
  asm volatile("{\n.reg .pred p;\nsetp.ne.b32 p, 0, 0;\n"
    "wgmma.mma_async.sync.aligned.m64n192k16.f32.bf16.bf16 {%0,%1,%2,%3,%4,%5,%6,%7,%8,%9,%10,%11,%12,%13,%14,%15,%16,%17,%18,%19,%20,%21,%22,%23,%24,%25,%26,%27,%28,%29,%30,%31,%32,%33,%34,%35,%36,%37,%38,%39,%40,%41,%42,%43,%44,%45,%46,%47,%48,%49,%50,%51,%52,%53,%54,%55,%56,%57,%58,%59,%60,%61,%62,%63,%64,%65,%66,%67,%68,%69,%70,%71,%72,%73,%74,%75,%76,%77,%78,%79,%80,%81,%82,%83,%84,%85,%86,%87,%88,%89,%90,%91,%92,%93,%94,%95}, {%96,%97,%98,%99}, %100, p, 1, 1, 1;\n}\n"
    : "=f"(d[0]),"=f"(d[1]),"=f"(d[2]),"=f"(d[3]),"=f"(d[4]),"=f"(d[5]),"=f"(d[6]),"=f"(d[7]),"=f"(d[8]),"=f"(d[9]),"=f"(d[10]),"=f"(d[11]),"=f"(d[12]),"=f"(d[13]),"=f"(d[14]),"=f"(d[15]),"=f"(d[16]),"=f"(d[17]),"=f"(d[18]),"=f"(d[19]),"=f"(d[20]),"=f"(d[21]),"=f"(d[22]),"=f"(d[23]),"=f"(d[24]),"=f"(d[25]),"=f"(d[26]),"=f"(d[27]),"=f"(d[28]),"=f"(d[29]),"=f"(d[30]),"=f"(d[31]),"=f"(d[32]),"=f"(d[33]),"=f"(d[34]),"=f"(d[35]),"=f"(d[36]),"=f"(d[37]),"=f"(d[38]),"=f"(d[39]),"=f"(d[40]),"=f"(d[41]),"=f"(d[42]),"=f"(d[43]),"=f"(d[44]),"=f"(d[45]),"=f"(d[46]),"=f"(d[47]),"=f"(d[48]),"=f"(d[49]),"=f"(d[50]),"=f"(d[51]),"=f"(d[52]),"=f"(d[53]),"=f"(d[54]),"=f"(d[55]),"=f"(d[56]),"=f"(d[57]),"=f"(d[58]),"=f"(d[59]),"=f"(d[60]),"=f"(d[61]),"=f"(d[62]),"=f"(d[63]),"=f"(d[64]),"=f"(d[65]),"=f"(d[66]),"=f"(d[67]),"=f"(d[68]),"=f"(d[69]),"=f"(d[70]),"=f"(d[71]),"=f"(d[72]),"=f"(d[73]),"=f"(d[74]),"=f"(d[75]),"=f"(d[76]),"=f"(d[77]),"=f"(d[78]),"=f"(d[79]),"=f"(d[80]),"=f"(d[81]),"=f"(d[82]),"=f"(d[83]),"=f"(d[84]),"=f"(d[85]),"=f"(d[86]),"=f"(d[87]),"=f"(d[88]),"=f"(d[89]),"=f"(d[90]),"=f"(d[91]),"=f"(d[92]),"=f"(d[93]),"=f"(d[94]),"=f"(d[95]) : "r"(a0), "r"(a1), "r"(a2), "r"(a3), "l"(db));
}
template<> __device__ __forceinline__ void wgmma_rsz<256>(float (&d)[128], uint32_t a0, uint32_t a1, uint32_t a2, uint32_t a3, uint64_t db) {
  asm volatile("{\n.reg .pred p;\nsetp.ne.b32 p, 0, 0;\n"
    "wgmma.mma_async.sync.aligned.m64n256k16.f32.bf16.bf16 {%0,%1,%2,%3,%4,%5,%6,%7,%8,%9,%10,%11,%12,%13,%14,%15,%16,%17,%18,%19,%20,%21,%22,%23,%24,%25,%26,%27,%28,%29,%30,%31,%32,%33,%34,%35,%36,%37,%38,%39,%40,%41,%42,%43,%44,%45,%46,%47,%48,%49,%50,%51,%52,%53,%54,%55,%56,%57,%58,%59,%60,%61,%62,%63,%64,%65,%66,%67,%68,%69,%70,%71,%72,%73,%74,%75,%76,%77,%78,%79,%80,%81,%82,%83,%84,%85,%86,%87,%88,%89,%90,%91,%92,%93,%94,%95,%96,%97,%98,%99,%100,%101,%102,%103,%104,%105,%106,%107,%108,%109,%110,%111,%112,%113,%114,%115,%116,%117,%118,%119,%120,%121,%122,%123,%124,%125,%126,%127}, {%128,%129,%130,%131}, %132, p, 1, 1, 1;\n}\n"
    : "=f"(d[0]),"=f"(d[1]),"=f"(d[2]),"=f"(d[3]),"=f"(d[4]),"=f"(d[5]),"=f"(d[6]),"=f"(d[7]),"=f"(d[8]),"=f"(d[9]),"=f"(d[10]),"=f"(d[11]),"=f"(d[12]),"=f"(d[13]),"=f"(d[14]),"=f"(d[15]),"=f"(d[16]),"=f"(d[17]),"=f"(d[18]),"=f"(d[19]),"=f"(d[20]),"=f"(d[21]),"=f"(d[22]),"=f"(d[23]),"=f"(d[24]),"=f"(d[25]),"=f"(d[26]),"=f"(d[27]),"=f"(d[28]),"=f"(d[29]),"=f"(d[30]),"=f"(d[31]),"=f"(d[32]),"=f"(d[33]),"=f"(d[34]),"=f"(d[35]),"=f"(d[36]),"=f"(d[37]),"=f"(d[38]),"=f"(d[39]),"=f"(d[40]),"=f"(d[41]),"=f"(d[42]),"=f"(d[43]),"=f"(d[44]),"=f"(d[45]),"=f"(d[46]),"=f"(d[47]),"=f"(d[48]),"=f"(d[49]),"=f"(d[50]),"=f"(d[51]),"=f"(d[52]),"=f"(d[53]),"=f"(d[54]),"=f"(d[55]),"=f"(d[56]),"=f"(d[57]),"=f"(d[58]),"=f"(d[59]),"=f"(d[60]),"=f"(d[61]),"=f"(d[62]),"=f"(d[63]),"=f"(d[64]),"=f"(d[65]),"=f"(d[66]),"=f"(d[67]),"=f"(d[68]),"=f"(d[69]),"=f"(d[70]),"=f"(d[71]),"=f"(d[72]),"=f"(d[73]),"=f"(d[74]),"=f"(d[75]),"=f"(d[76]),"=f"(d[77]),"=f"(d[78]),"=f"(d[79]),"=f"(d[80]),"=f"(d[81]),"=f"(d[82]),"=f"(d[83]),"=f"(d[84]),"=f"(d[85]),"=f"(d[86]),"=f"(d[87]),"=f"(d[88]),"=f"(d[89]),"=f"(d[90]),"=f"(d[91]),"=f"(d[92]),"=f"(d[93]),"=f"(d[94]),"=f"(d[95]),"=f"(d[96]),"=f"(d[97]),"=f"(d[98]),"=f"(d[99]),"=f"(d[100]),"=f"(d[101]),"=f"(d[102]),"=f"(d[103]),"=f"(d[104]),"=f"(d[105]),"=f"(d[106]),"=f"(d[107]),"=f"(d[108]),"=f"(d[109]),"=f"(d[110]),"=f"(d[111]),"=f"(d[112]),"=f"(d[113]),"=f"(d[114]),"=f"(d[115]),"=f"(d[116]),"=f"(d[117]),"=f"(d[118]),"=f"(d[119]),"=f"(d[120]),"=f"(d[121]),"=f"(d[122]),"=f"(d[123]),"=f"(d[124]),"=f"(d[125]),"=f"(d[126]),"=f"(d[127]) : "r"(a0), "r"(a1), "r"(a2), "r"(a3), "l"(db));
}
template<int N> __device__ __forceinline__ void wgmma_ra(float (&d)[N / 2], const uint4& a, uint64_t db, bool acc) {
  if (acc) wgmma_rs<N>(d, a.x, a.y, a.z, a.w, db, 1); else wgmma_rsz<N>(d, a.x, a.y, a.z, a.w, db);
}

__device__ __forceinline__ uint32_t smem_u32(const void* p) { return (uint32_t)__cvta_generic_to_shared(p); }
__device__ __forceinline__ void mbar_init(uint32_t bar, uint32_t cnt) { asm volatile("mbarrier.init.shared::cta.b64 [%0], %1;" ::"r"(bar), "r"(cnt)); }
__device__ __forceinline__ void mbar_expect_tx(uint32_t bar, uint32_t bytes) { asm volatile("mbarrier.arrive.expect_tx.shared::cta.b64 _, [%0], %1;" ::"r"(bar), "r"(bytes) : "memory"); }
__device__ __forceinline__ void mbar_arrive(uint32_t bar) { asm volatile("mbarrier.arrive.shared::cta.b64 _, [%0];" ::"r"(bar) : "memory"); }
__device__ __forceinline__ void mbar_arrive_remote(uint32_t rbar) { asm volatile("mbarrier.arrive.shared::cluster.b64 _, [%0];" ::"r"(rbar) : "memory"); }
__device__ __forceinline__ void mbar_wait(uint32_t bar, uint32_t parity) {
  asm volatile(
      "{\n.reg .pred p;\n.reg .u32 c;\nmov.u32 c, 0;\nLAB_WAIT:\nmbarrier.try_wait.parity.shared::cta.b64 p, [%0], %1;\n@p bra DONE;\n"
      "add.u32 c, c, 1;\nsetp.lt.u32 p, c, 1000000;\n@p bra LAB_WAIT;\ntrap;\nDONE:\n}\n" ::"r"(bar), "r"(parity) : "memory");
}
__device__ __forceinline__ void mbar_wait_c(uint32_t bar, uint32_t parity) {
  asm volatile("{\n.reg .pred p;\nLAB_WAIT:\nmbarrier.try_wait.parity.shared::cta.b64 p, [%0], %1;\n@!p bra LAB_WAIT;\n}\n" ::"r"(bar), "r"(parity) : "memory");
}
__device__ __forceinline__ void wtma2d(uint32_t dst, const CUtensorMap* m, int c0, int c1, uint32_t bar, uint64_t pol) {
  asm volatile("cp.async.bulk.tensor.2d.shared::cluster.global.mbarrier::complete_tx::bytes.multicast::cluster.L2::cache_hint [%0], [%1, {%3, %4}], [%2], %5, %6;"
               ::"r"(dst), "l"(m), "r"(bar), "r"(c0), "r"(c1), "h"((uint16_t)3), "l"(pol) : "memory");
}
__device__ __forceinline__ void wtma3d(uint32_t dst, const CUtensorMap* m, int c0, int c1, int c2, uint32_t bar, uint64_t pol) {
  asm volatile("cp.async.bulk.tensor.3d.shared::cluster.global.mbarrier::complete_tx::bytes.multicast::cluster.L2::cache_hint [%0], [%1, {%3, %4, %5}], [%2], %6, %7;"
               ::"r"(dst), "l"(m), "r"(bar), "r"(c0), "r"(c1), "r"(c2), "h"((uint16_t)3), "l"(pol) : "memory");
}
__device__ __forceinline__ void wtma5d(uint32_t dst, const CUtensorMap* m, int c0, int c3, uint32_t bar, uint64_t pol) {
  asm volatile("cp.async.bulk.tensor.5d.shared::cluster.global.mbarrier::complete_tx::bytes.multicast::cluster.L2::cache_hint [%0], [%1, {%3, %5, %5, %4, %5}], [%2], %6, %7;"
               ::"r"(dst), "l"(m), "r"(bar), "r"(c0), "r"(c3), "r"(0), "h"((uint16_t)3), "l"(pol) : "memory");
}
__device__ __forceinline__ void tma_store3d(const CUtensorMap* m, uint32_t src, int c0, int c1, int c2) {
  asm volatile("cp.async.bulk.tensor.3d.global.shared::cta.bulk_group [%0, {%2, %3, %4}], [%1];" ::"l"(m), "r"(src), "r"(c0), "r"(c1), "r"(c2) : "memory");
}
__device__ __forceinline__ void prefetch_l2(const void* p, uint32_t bytes) { asm volatile("cp.async.bulk.prefetch.L2.global [%0], %1;" ::"l"(p), "r"(bytes) : "memory"); }
__device__ __forceinline__ uint64_t policy_evict_first() { uint64_t p; asm volatile("createpolicy.fractional.L2::evict_first.b64 %0, 1.0;" : "=l"(p)); return p; }
__device__ __forceinline__ uint64_t policy_evict_normal() { uint64_t p; asm volatile("createpolicy.fractional.L2::evict_normal.b64 %0, 1.0;" : "=l"(p)); return p; }
__device__ __forceinline__ void bulk_commit() { asm volatile("cp.async.bulk.commit_group;" ::: "memory"); }
__device__ __forceinline__ void bulk_wait_all() { asm volatile("cp.async.bulk.wait_group 0;" ::: "memory"); }
__device__ __forceinline__ void fence_async_smem() { asm volatile("fence.proxy.async.shared::cta;" ::: "memory"); }
__device__ __forceinline__ bool elect_one() {
  uint32_t p;
  asm volatile("{\n.reg .pred P;\nelect.sync _|P, 0xffffffff;\nselp.u32 %0, 1, 0, P;\n}\n" : "=r"(p));
  return p;
}
__device__ __forceinline__ void wg_fence() { asm volatile("wgmma.fence.sync.aligned;" ::: "memory"); }
__device__ __forceinline__ void wg_commit() { asm volatile("wgmma.commit_group.sync.aligned;" ::: "memory"); }
template <int n> __device__ __forceinline__ void wg_wait() { asm volatile("wgmma.wait_group.sync.aligned %0;" ::"n"(n) : "memory"); }
__device__ __forceinline__ void wg_bar(int w) { asm volatile("bar.sync %0, 128;" ::"r"(w + 1) : "memory"); }
__device__ __forceinline__ void cluster_sync() { asm volatile("barrier.cluster.arrive.relaxed.aligned;\nbarrier.cluster.wait.aligned;" ::: "memory"); }
__device__ __forceinline__ constexpr uint64_t desc_hi(uint32_t lbo, uint32_t sbo, int sw) {
  return ((uint64_t)(lbo >> 4) << 16) | ((uint64_t)(sbo >> 4) << 32) | ((uint64_t)sw << 62);
}
__device__ __forceinline__ void fence_gpu() { asm volatile("fence.acq_rel.gpu;" ::: "memory"); }
__device__ __forceinline__ uint32_t ld_relaxed(const uint32_t* p) { uint32_t v; asm volatile("ld.relaxed.gpu.global.u32 %0, [%1];" : "=r"(v) : "l"(p) : "memory"); return v; }
__device__ __forceinline__ uint4 ld_relaxed4(const uint4* p) {
  uint4 v; asm volatile("ld.relaxed.gpu.global.v4.u32 {%0,%1,%2,%3}, [%4];" : "=r"(v.x), "=r"(v.y), "=r"(v.z), "=r"(v.w) : "l"(p) : "memory"); return v;
}
__device__ __forceinline__ uint2 ld_relaxed2(const uint2* p) {
  uint2 v; asm volatile("ld.relaxed.gpu.global.v2.u32 {%0,%1}, [%2];" : "=r"(v.x), "=r"(v.y) : "l"(p) : "memory"); return v;
}
__device__ __forceinline__ uint4 ldg128(const void* p) {
  uint4 v; asm volatile("ld.global.nc.v4.u32 {%0,%1,%2,%3}, [%4];" : "=r"(v.x), "=r"(v.y), "=r"(v.z), "=r"(v.w) : "l"(p)); return v;
}
__device__ __forceinline__ uint32_t ldg32(const void* p) { uint32_t v; asm volatile("ld.global.nc.u32 %0, [%1];" : "=r"(v) : "l"(p)); return v; }
__device__ __forceinline__ void st_relaxed(uint32_t* p, uint32_t a) { asm volatile("st.relaxed.gpu.global.u32 [%0], %1;" ::"l"(p), "r"(a) : "memory"); }
__device__ __forceinline__ void st_relaxed4(uint4* p, uint32_t a, uint32_t b, uint32_t c, uint32_t d) {
  asm volatile("st.relaxed.gpu.global.v4.u32 [%0], {%1,%2,%3,%4};" ::"l"(p), "r"(a), "r"(b), "r"(c), "r"(d) : "memory");
}
__device__ __forceinline__ void st_relaxed2(uint2* p, uint32_t a, uint32_t b) {
  asm volatile("st.relaxed.gpu.global.v2.u32 [%0], {%1,%2};" ::"l"(p), "r"(a), "r"(b) : "memory");
}
__device__ __forceinline__ void red4(uint4* p, uint32_t a, uint32_t b, uint32_t c, uint32_t d) {
  asm volatile("red.relaxed.gpu.global.add.noftz.v4.bf16x2 [%0], {%1,%2,%3,%4};" ::"l"(p), "r"(a), "r"(b), "r"(c), "r"(d) : "memory");
}
__device__ __forceinline__ void red2(uint2* p, uint32_t a, uint32_t b) {
  asm volatile("red.relaxed.gpu.global.add.noftz.v2.bf16x2 [%0], {%1,%2};" ::"l"(p), "r"(a), "r"(b) : "memory");
}
constexpr int SPIN_MAX = 1 << 21;
__device__ __forceinline__ uint32_t pack_bf16(float lo, float hi) { uint32_t r; asm("cvt.rn.bf16x2.f32 %0, %1, %2;" : "=r"(r) : "f"(hi), "f"(lo)); return r; }
__device__ __forceinline__ float bf_lo(uint32_t v) { return __uint_as_float(v << 16); }
__device__ __forceinline__ float bf_hi(uint32_t v) { return __uint_as_float(v & 0xffff0000u); }
__device__ __forceinline__ float2 lds64(uint32_t a) { float2 v; asm volatile("ld.shared.v2.f32 {%0,%1}, [%2];" : "=f"(v.x), "=f"(v.y) : "r"(a)); return v; }
__device__ __forceinline__ void sts64f(uint32_t a, float x, float y) { asm volatile("st.shared.v2.f32 [%0], {%1,%2};" ::"r"(a), "f"(x), "f"(y) : "memory"); }
__device__ __forceinline__ void sts32(uint32_t a, uint32_t x) { asm volatile("st.volatile.shared.b32 [%0], %1;" ::"r"(a), "r"(x) : "memory"); }
__device__ __forceinline__ void gate(uint32_t a, int need) {
  for (int it = 0; it < SPIN_MAX; it++) {
    int v; asm volatile("ld.volatile.shared.b32 %0, [%1];" : "=r"(v) : "r"(a) : "memory");
    if (v >= need) break;
    __nanosleep(32);
  }
}
__device__ __forceinline__ void sts128(uint32_t a, uint32_t x, uint32_t y, uint32_t z, uint32_t u) { asm volatile("st.shared.v4.b32 [%0], {%1,%2,%3,%4};" ::"r"(a), "r"(x), "r"(y), "r"(z), "r"(u) : "memory"); }
__device__ __forceinline__ uint4 lds128(uint32_t a) { uint4 v; asm volatile("ld.shared.v4.u32 {%0,%1,%2,%3}, [%4];" : "=r"(v.x), "=r"(v.y), "=r"(v.z), "=r"(v.w) : "r"(a) : "memory"); return v; }
__device__ __forceinline__ uint32_t hadd2(uint32_t a, uint32_t b) { uint32_t r; asm("add.rn.bf16x2 %0, %1, %2;" : "=r"(r) : "r"(a), "r"(b)); return r; }
__device__ __forceinline__ void stsm4(uint32_t a, uint32_t r0, uint32_t r1, uint32_t r2, uint32_t r3) {
  asm volatile("stmatrix.sync.aligned.m8n8.x4.shared.b16 [%0], {%1,%2,%3,%4};" ::"r"(a), "r"(r0), "r"(r1), "r"(r2), "r"(r3) : "memory");
}
__device__ __forceinline__ void stsm2(uint32_t a, uint32_t r0, uint32_t r1) {
  asm volatile("stmatrix.sync.aligned.m8n8.x2.shared.b16 [%0], {%1,%2};" ::"r"(a), "r"(r0), "r"(r1) : "memory");
}
__device__ __forceinline__ uint32_t movm(uint32_t a) { uint32_t r; asm("movmatrix.sync.aligned.m8n8.trans.b16 %0, %1;" : "=r"(r) : "r"(a)); return r; }
__device__ __forceinline__ void mma16816z(float (&d)[4], uint32_t a0, uint32_t a1, uint32_t a2, uint32_t a3, uint32_t b0, uint32_t b1) {
  asm("mma.sync.aligned.m16n8k16.row.col.f32.bf16.bf16.f32 {%0,%1,%2,%3}, {%4,%5,%6,%7}, {%8,%9}, {%10,%10,%10,%10};"
      : "=f"(d[0]), "=f"(d[1]), "=f"(d[2]), "=f"(d[3]) : "r"(a0), "r"(a1), "r"(a2), "r"(a3), "r"(b0), "r"(b1), "f"(0.f));
}
__device__ __forceinline__ void mma1688(float (&d)[4], uint32_t a0, uint32_t a1, uint32_t b0) {
  asm("mma.sync.aligned.m16n8k8.row.col.f32.bf16.bf16.f32 {%0,%1,%2,%3}, {%4,%5}, {%6}, {%0,%1,%2,%3};"
      : "+f"(d[0]), "+f"(d[1]), "+f"(d[2]), "+f"(d[3]) : "r"(a0), "r"(a1), "r"(b0));
}
__device__ __forceinline__ float quad_sum(float v) { v += __shfl_xor_sync(0xffffffffu, v, 1); v += __shfl_xor_sync(0xffffffffu, v, 2); return v; }
__device__ __forceinline__ float quad_max(float v) { v = fmaxf(v, __shfl_xor_sync(0xffffffffu, v, 1)); v = fmaxf(v, __shfl_xor_sync(0xffffffffu, v, 2)); return v; }
__device__ __forceinline__ float rcp(float x) { float r; asm("rcp.approx.ftz.f32 %0, %1;" : "=f"(r) : "f"(x)); return r; }
__device__ __forceinline__ float rsq(float x) { float r; asm("rsqrt.approx.ftz.f32 %0, %1;" : "=f"(r) : "f"(x)); return r; }
__device__ __forceinline__ float ex2(float x) { float r; asm("ex2.approx.ftz.f32 %0, %1;" : "=f"(r) : "f"(x)); return r; }
__device__ __forceinline__ uint32_t tagged(uint32_t v, uint32_t tag) { return (v & ~1u) | tag; }

__device__ __forceinline__ int group_k0(int g) { return g < 16 ? 64 * (g & 7) + 4 * (g & 8) : 32 * g; }
__device__ __forceinline__ constexpr uint32_t qkv_xslot(int g) { return (0x5140762u >> (4 * (g - 5))) & 15; }

struct Cons {
  uint32_t sb;
  uint32_t rem;
  uint32_t sB, mB;
  uint32_t mX;
  bool elect;
  __device__ __forceinline__ void release2(uint32_t bar) const { if (elect) { mbar_arrive(sb + bar); mbar_arrive_remote(rem + bar); } }
  __device__ __forceinline__ uint32_t nextB(uint32_t& prev) {
    mbar_wait_c(sb + BAR_FULLB + sB, mB);
    const uint32_t a = (((sb & 0x3FFFF) + SM_B) >> 4) + sB * (BSLOT / 128);
    prev = sB == 0 ? 32 : sB - 8;
    sB += 8;
    if (sB == 40) { sB = 0; mB ^= 1; }
    return a;
  }
  __device__ __forceinline__ void progress(uint32_t v) const { if (elect) sts32(sb + SM_PROG + (threadIdx.x >> 5), v); }
  __device__ __forceinline__ void releaseLastB() const { release2(BAR_EMPTYB + (sB == 0 ? 32 : sB - 8)); }
};

template <bool QKV, class Pre, class Mma>
__device__ __forceinline__ float2 ln_gemm(Cons& c, Group* G, const float (&v)[36], uint32_t (&p)[18], bool direct, const char* xrow, int st0, int j, int t,
                                          uint32_t tag, uint32_t stag, Pre&& pre, Mma&& mma) {
  constexpr int NBUF = 5;
  const uint32_t pbase = direct ? 0 : 32;
  uint4* const box = G->act[QKV ? 0 : 2];
  uint4 x[NBUF][2];
  auto load_box = [&](int g) { x[g % NBUF][0] = ld_relaxed4(box + t + 2 * g * 128); x[g % NBUF][1] = ld_relaxed4(box + t + (2 * g + 1) * 128); };
  auto load_in = [&](int g) {
    const uint4* a = (const uint4*)(xrow + 28 * (t & 3)) + 8 * (g >> 1) + (g & 1);
    x[g % NBUF][0] = ldg128(a); x[g % NBUF][1] = ldg128(a + 1152);
  };
  auto load = [&](int g) { if (direct) load_in(g); else load_box(g); };
#pragma unroll
  for (int i = 0; i < 18; i++) p[i] = pack_bf16(v[2 * i], v[2 * i + 1]);
  uint4* const d = box + 2 * j * 128 + t;
  if (!direct) {
#pragma unroll
    for (int i = 0; i < 2; i++) st_relaxed4(d + i * 128, tagged(p[i], tag), p[i + 2], p[i + 4], p[i + 6]);
  }
  float s0 = v[0] + v[1], s1 = v[2] + v[3];
#pragma unroll
  for (int i = 1; i < 9; i++) { s0 += v[4 * i] + v[4 * i + 1]; s1 += v[4 * i + 2] + v[4 * i + 3]; }
  s0 = quad_sum(s0); s1 = quad_sum(s1);
  const uint32_t s0t = (__float_as_uint(s0) & ~3u) | stag;
  if ((t & 3) == 0) st_relaxed2(G->sum + st0 + 8 * j, s0t, __float_as_uint(s1));
  const int sq = st0 + 16 * (t & 3);
  uint2 sa, sc;
  auto poll = [&] { sa = ld_relaxed2(G->sum + sq); sc = ld_relaxed2(G->sum + sq + 8); };
  if (SPEC) {
#pragma unroll
    for (int g = 0; g < NFIRST; g++) load(g);
    poll();
  }
  float d0 = 0.f, d1 = 0.f;
  {
    const float m0 = s0 * (1.f / 72), m1 = s1 * (1.f / 72);
#pragma unroll
    for (int i = 0; i < 9; i++) {
      float a = v[4 * i] - m0, b = v[4 * i + 1] - m0; d0 = fmaf(a, a, fmaf(b, b, d0));
      a = v[4 * i + 2] - m1; b = v[4 * i + 3] - m1; d1 = fmaf(a, a, fmaf(b, b, d1));
    }
    d0 = quad_sum(d0); d1 = quad_sum(d1);
  }
  pre(0);
  if (!SPEC) poll();
  while (__any_sync(0xffffffffu, ((sa.x ^ stag) | (sc.x ^ stag)) & 3)) poll();
  const uint32_t vmask = direct ? 0 : 1;
#pragma unroll
  for (int g = 0; g < NFIRST; g++) {
    if (!SPEC) load(g);
    else if (__any_sync(0xffffffffu, ((x[g][0].x ^ tag) | (x[g][1].x ^ tag)) & vmask)) load_box(g);
  }
  c.progress(QKV ? pbase + 1 : 53 - 32 * tag);
  if (!direct) {
#pragma unroll
    for (int i = 0; i < 2; i++) st_relaxed4(d + (16 + i) * 128, tagged(p[8 + i], tag), p[10 + i], p[12 + i], p[14 + i]);
    st_relaxed2((uint2*)(box + (32 + (j >> 1)) * 128 + t) + (j & 1), tagged(p[16], tag), p[17]);
  }
  if ((t & 3) == 0) st_relaxed4(G->m2 + st0 + 8 * j, s0t, __float_as_uint(s1), __float_as_uint(d0), __float_as_uint(d1));
#pragma unroll
  for (int g = NFIRST; g < NBUF; g++) load(g);
  const float m0 = quad_sum(__uint_as_float(sa.x) + __uint_as_float(sc.x)) * (-1.f / 576), m1 = quad_sum(__uint_as_float(sa.y) + __uint_as_float(sc.y)) * (-1.f / 576);
  const uint32_t nm0 = pack_bf16(m0, m0), nm1 = pack_bf16(m1, m1);
  pre(1);
  uint4 u0, u1;
#pragma unroll
  for (int g = 0; g < 18; g++) {
    uint4 &a = x[g % NBUF][0], &b = x[g % NBUF][1];
    while (__any_sync(0xffffffffu, ((a.x ^ tag) | (b.x ^ tag) | (g < 16 ? 0u : (a.z ^ tag) | (b.z ^ tag))) & vmask)) load_box(g);
    const bool rows = g < 16 || direct;
    const uint4 f0 = make_uint4(hadd2(a.x, nm0), hadd2(rows ? b.x : a.y, nm1), hadd2(rows ? a.y : a.z, nm0), hadd2(rows ? b.y : a.w, nm1));
    const uint4 f1 = make_uint4(hadd2(rows ? a.z : b.x, nm0), hadd2(rows ? b.z : b.y, nm1), hadd2(rows ? a.w : b.z, nm0), hadd2(b.w, nm1));
    if (g + NBUF < 18) load(g + NBUF);
    if (g == 13) { u0 = ld_relaxed4(G->m2 + sq); u1 = ld_relaxed4(G->m2 + sq + 8); }
    if (g == 14 && direct) {
#pragma unroll
      for (int i = 0; i < 18; i++) p[i] = ldg32(xrow + (i < 16 ? 128 * j + 16 * (i >> 1) : 1024 + 16 * j) + (i & 1) * 16 * 1152);
    }
    const bool inx = QKV && g >= 5 && g < 12;
    uint32_t prev = c.sB == 0 ? 32 : c.sB - 8, bb;
    if (inx) {
      mbar_wait_c(c.sb + BAR_FULLX + 8 * qkv_xslot(g), (c.mX >> qkv_xslot(g)) & 1);
      bb = ((c.sb & 0x3FFFF) + SM_X + qkv_xslot(g) * XSLOT) >> 4;
    } else {
      bb = c.nextB(prev);
    }
    mma(g, bb, f0, f1);
    wg_wait<1>();
    if (g > 0 && !(QKV && g > 5 && g <= 12)) c.release2(BAR_EMPTYB + prev);
    if (QKV && g > 0 && g < 15) c.progress(pbase + 1 + g);
    if (QKV && g == 13 && t < 4) { mbar_arrive(c.sb + BAR_EMPTYX + 32 + 8 * t); mbar_arrive_remote(c.rem + BAR_EMPTYX + 32 + 8 * t); }
  }
  if (QKV) c.mX ^= 0xf7;
  while (__any_sync(0xffffffffu, ((u0.x ^ stag) | (u1.x ^ stag)) & 3)) { u0 = ld_relaxed4(G->m2 + sq); u1 = ld_relaxed4(G->m2 + sq + 8); }
  float e0 = fmaf(__uint_as_float(u0.x), 1.f / 72, m0), e1 = fmaf(__uint_as_float(u1.x), 1.f / 72, m0);
  const float v0 = quad_sum(fmaf(72.f, fmaf(e0, e0, e1 * e1), __uint_as_float(u0.z) + __uint_as_float(u1.z)));
  e0 = fmaf(__uint_as_float(u0.y), 1.f / 72, m1); e1 = fmaf(__uint_as_float(u1.y), 1.f / 72, m1);
  const float v1 = quad_sum(fmaf(72.f, fmaf(e0, e0, e1 * e1), __uint_as_float(u0.w) + __uint_as_float(u1.w)));
  float2 r = make_float2(rsq(fmaf(v0, 1.f / 576, 1e-5f)), rsq(fmaf(v1, 1.f / 576, 1e-5f)));
  asm volatile("" : "+f"(r.x), "+f"(r.y));
  wg_wait<0>();
  c.releaseLastB();
  return r;
}

template <int NB, int OFF>
__device__ __forceinline__ void glu(const float (&a)[128], uint32_t (&h)[144]) {
#pragma unroll
  for (int b = 0; b < 2 * NB; b++) h[OFF + b] = pack_bf16(a[2 * b] * a[4 * NB + 2 * b], a[2 * b + 1] * a[4 * NB + 2 * b + 1]);
}

__global__ void __cluster_dims__(2, 1, 1) __launch_bounds__(384, 1)
fused_kernel(const __nv_bfloat16* __restrict__ x_in, Group* ws, const char* __restrict__ wqkv,
             const char* __restrict__ wg, const char* __restrict__ wu, const char* __restrict__ wd, const __grid_constant__ Maps maps,
             const char* __restrict__ wo) {
  extern __shared__ __align__(1024) uint8_t smem_raw[];
  const uint32_t sb = smem_u32(smem_raw);
  const int warp = __shfl_sync(0xffffffffu, threadIdx.x >> 5, 0);
  const int lane = threadIdx.x & 31;
  const int rank = blockIdx.x & 1;
  int lb = blockIdx.x;
  if (GPCMAP) {
    const int cl = blockIdx.x >> 1, u = cl - 36;
    lb = (cl < 4 ? cl : cl < 36 ? 8 * ((cl - 4) & 7) + ((cl - 4) >> 3) + (((cl - 4) & 7) ? 0 : 4) : 8 * (1 + u % 7) + 4 + u / 7) * 2 + rank;
  }
#define CTA_J(b) (((b) >> 1) & 7)
#define CTA_RB(b) ((((b) >> 4) << 1) | ((b) & 1))
  const int j = CTA_J(lb), rb = CTA_RB(lb);

  PROF(23);
  const uint64_t pola = A_POLICY();
  auto qkv_group = [&](int layer, int g, uint32_t dst, uint32_t bar) {
    const int m = (layer ? group_k0(g) >> 3 : 32 * (g >> 1) + 4 * (g & 1)) + 2 * rank;
    wtma5d(dst + rank * 8192, maps.qm + layer, 72 * j, m, bar, pola);
    wtma5d(dst + rank * 8192 + 6144, maps.qc + layer, 72 * j + 64, m, bar, pola);
  };
  if (warp >= 8 && elect_one()) {
    if (warp >= 10) asm volatile("prefetch.tensormap [%0];" ::"l"(maps.qm + 2 * (warp - 10)) : "memory");
#pragma unroll
    for (int i = 0; i < 9; i++) mbar_init(sb + SM_BAR + 72 * (warp - 8) + 8 * i, warp < 10 ? 1 : 4);
    sts32(sb + SM_PROG + 4 * (warp - 8), 0);
    asm volatile("fence.mbarrier_init.release.cluster;" ::: "memory");
  }
  __syncwarp();
  if (warp == 8) PROFX(53);
  asm volatile("barrier.cluster.arrive.relaxed.aligned;" ::: "memory");
  uint4 xin[4];
  uint32_t xin9[2];
  if (warp >= 8) {
    asm volatile("barrier.cluster.wait.aligned;" ::: "memory");
    if (warp == 8) PROFX(56);
    if (warp < 8 + QD && elect_one()) {
      mbar_expect_tx(sb + BAR_FULLB + 8 * (warp - 8), 2 * 6912);
      qkv_group(0, warp - 8, sb + SM_B + (warp - 8) * BSLOT, sb + BAR_FULLB + 8 * (warp - 8));
    }
    if (warp == 11 && elect_one()) prefetch_l2(wqkv + blockIdx.x * 15552, 15552);
    __syncwarp();
    if (warp == 9) PROFX(54);
  } else {
    if (OPEN) {
      Group* G = ws + 2 * rb + (warp >> 2);
      const int o = (warp & 3) * 64 + 8 * j + (lane >> 2);
      if ((lane & 3) == 0) { st_relaxed2(G->sum + o, 0, 0); st_relaxed4(G->m2 + o, 0, 0, 0, 0); }
      if ((warp & 3) == 3) {
#pragma unroll
        for (int i = 0; i < 5; i++) st_relaxed4(G->halo + j * 160 + lane + i * 32, 0, 0, 0, 0);
      }
    }
    const char* xr = (const char*)x_in + (128 * rb + 2 * (16 * (warp & 3) + (lane >> 2)) + (warp >> 2)) * 1152;
#pragma unroll
    for (int i = 0; i < 4; i++) xin[i] = ldg128(xr + 128 * j + 32 * (lane & 3) + 16 * (i >> 1) + (i & 1) * 16 * 1152);
#pragma unroll
    for (int i = 0; i < 2; i++) xin9[i] = ldg32(xr + 1024 + 16 * j + 4 * (lane & 3) + i * 16 * 1152);
  }
  PROF(24);

  if (warp >= 8) {
    asm volatile("setmaxnreg.dec.sync.aligned.u32 " STR(REGS_P) ";");
    if (warp == 8) PROFX(55);
    const uint64_t pol = W_POLICY();
    auto qkv_gate = [&](int layer, int g) {
      if (layer == 0) {
        const int e = g - QD;
        mbar_wait(sb + (e < 5 ? BAR_FULLB + 8 * e : e < 12 ? BAR_FULLX + 8 * qkv_xslot(e) : BAR_FULLB + 8 * (e - 12)), e >= 12);
      }
      gate(sb + SM_PROG, layer ? (g < 8 ? 0 : 33 + ((g - 8) * 23 >> 4)) : g - QG);
    };
    if (warp == 8) {
      uint32_t s = QD, ph = 1;
      auto slot = [&](uint32_t bytes, auto&& issue) {
        const uint32_t bar = sb + BAR_FULLB + 8 * s;
        mbar_wait(sb + BAR_EMPTYB + 8 * s, ph);
        if (elect_one()) {
          mbar_expect_tx(bar, bytes);
          issue(sb + SM_B + s * BSLOT, bar);
        }
        if (++s == 5) { s = 0; ph ^= 1; }
      };
#pragma unroll 1
      for (int layer = 0; layer < NLAYERS; layer++) {
#pragma unroll 1
        for (int g = layer ? 0 : QD; g < 18; g += g == 4 ? 8 : 1) {
          qkv_gate(layer, g);
          slot(2 * 6912, [&](uint32_t dst, uint32_t bar) { qkv_group(layer, g, dst, bar); });
        }
        gate(sb + SM_PROG, 32 * layer + 20);
        gate(sb + SM_PROG + 4, 32 * layer + 20);
#pragma unroll 1
        for (int t = 0; t < 5; t++) {
          const CUtensorMap* m = &maps.g + (t < 3 ? rank : 2 + rank);
          const int c2 = t < 3 ? 9 * j + 2 * t : 18 * j + 3 + 3 * t;
          const uint32_t half = t < 3 ? 8192 : 6144;
#pragma unroll 1
          for (int g = 0; g < 18; g++)
            slot(2 * half, [&](uint32_t dst, uint32_t bar) { wtma3d(dst + rank * half, m, 0, group_k0(g), c2, bar, pol); });
        }
      }
    } else if (warp == 9) {
      uint32_t mE = 0xff;
      auto acquire = [&](uint32_t s) { mbar_wait(sb + BAR_EMPTYX + 8 * s, (mE >> s) & 1); mE ^= 1u << s; };
      auto slot = [&](uint32_t s, const CUtensorMap* m, int col, int row, uint64_t pol) {
        acquire(s);
        if (elect_one()) {
          mbar_expect_tx(sb + BAR_FULLX + 8 * s, XSLOT);
          wtma2d(sb + SM_X + s * XSLOT + rank * 9216, m, col, row + 72 * rank, sb + BAR_FULLX + 8 * s, pol);
        }
      };
#pragma unroll 1
      for (int layer = 0; layer < NLAYERS; layer++) {
#pragma unroll 1
        for (int g = 5; g < 12; g++) {
          const uint32_t s = qkv_xslot(g);
          qkv_gate(layer, g);
          acquire(s);
          if (elect_one()) {
            mbar_expect_tx(sb + BAR_FULLX + 8 * s, 2 * 6912);
            qkv_group(layer, g, sb + SM_X + s * XSLOT, sb + BAR_FULLX + 8 * s);
          }
        }
        acquire(3);
        if (elect_one()) {
          mbar_expect_tx(sb + BAR_FULLX + 24, 9216);
          wtma2d(sb + SM_WOC + rank * 4608, &maps.oc, 512 + 8 * j, 288 * rank, sb + BAR_FULLX + 24, pola);
          wtma2d(sb + SM_WOC + rank * 4608 + 2304, &maps.oc, 512 + 8 * j, 288 * rank + 144, sb + BAR_FULLX + 24, pola);
        }
#pragma unroll 1
        for (int i = 0; i < 4; i++) slot(4 + i, &maps.o, 64 * j, 144 * i, pola);
#pragma unroll 1
        for (int u = 0; u < 36; u++) slot(4 * (u & 1) + ((u >> 1) & 3), &maps.d, u < 4 ? 512 : 64 * ((j + (u >> 2)) & 7), 576 * j + 144 * (u & 3), pol);
      }
    } else {
      const int w = warp - 10, grp = 2 * rb + w;
      gate(sb + SM_PROG, 3);
      if (w == 0) PROFX(58);
      auto prefetch_gu = [&](int l0, int n) {
#pragma unroll 1
        for (int i = lane; i < 36 * n; i += 32) {
          asm volatile("prefetch.global.L2 [%0];" ::"l"((w ? wu : wg) + (size_t)(36 * rb + i / n) * 9216 + 1152 * j + 128 * (l0 + i % n)));
          __nanosleep(PFSLEEP);
        }
      };
      auto clear = [&](uint4* p, int n) {
#pragma unroll 1
        for (int i = lane; i < n; i += 64) { st_relaxed4(p + i, 0, 0, 0, 0); st_relaxed4(p + i + 32, 0, 0, 0, 0); __nanosleep(32); }
      };
      auto exchange = [&](uint32_t v, uint32_t bar) {
        fence_gpu();
        __syncwarp();
        if (lane == 0) st_relaxed(ws[grp].flag + j, v);
        for (int it = 0; it < SPIN_MAX; it++) {
          const uint32_t f = ld_relaxed(ws[grp].flag + (lane & 7));
          if (__all_sync(0xffffffffu, v ? f >= v : f == 0)) break;
        }
        if (lane == 0) mbar_arrive(sb + bar + 8 * w);
      };
      if (lane == 0) prefetch_l2(wo + (2 * blockIdx.x + w) * 2592, 2592);
#pragma unroll 1
      for (int layer = 0; layer < NLAYERS; layer++) {
        gate(sb + SM_PROG, 32 * layer + 3);
        prefetch_gu(0, 2);
        gate(sb + SM_PROG, 32 * layer + 21);
        prefetch_gu(2, 2);
        if (layer == 0) {
          clear(ws[grp].act[0] + 576 * j, 576);
          clear(ws[grp].inbox[0] + 2 * j * INBOX, 2 * INBOX);
          exchange(1, BAR_CLR);
          if (w == 0) PROFX(59);
        }
        prefetch_gu(4, 2);
        prefetch_gu(6, 3);
#pragma unroll 1
        for (int i = lane; i < 162; i += 32) {
          asm volatile("prefetch.global.L2 [%0];" ::"l"(wd + (size_t)(576 * j + 36 * rb + 18 * w) * 1152 + 128 * i));
          __nanosleep(PFSLEEP);
        }
        if (w == 0 && layer == 0) PROFX(60);
        mbar_wait(sb + BAR_REDDONE + 8 * w, layer);
        if (w == 0) PROFX(64 + 53 + 4 * layer);
        exchange(2 - 2 * layer, BAR_RREADY);
        if (w == 0) PROFX(64 + 56 + 4 * layer);
      }
      mbar_wait(sb + BAR_DONE + 8 * w, 0);
    }
    __syncwarp();
    cluster_sync();
  } else {
    asm volatile("setmaxnreg.inc.sync.aligned.u32 " STR(REGS_C) ";");
#define THREAD_IDS()                                                                   \
    int tid_ = threadIdx.x, bid_ = lb;                                                  \
    asm volatile("" : "+r"(tid_), "+r"(bid_));                                          \
    const int w = warp >> 2, wp = warp & 3;                                             \
    const int lane = tid_ & 31, t = tid_ & 127, g = lane >> 2, q = lane & 3;           \
    const int j = CTA_J(bid_), rb = CTA_RB(bid_), grp = 2 * rb + w;                    \
    const int st0 = wp * 64 + g;                         \
    Group* const G = ws + grp;                                                         \
    const uint32_t dsb = (sb & 0x3FFFF) >> 4;                                          \
    (void)t; (void)g; (void)q; (void)grp; (void)j; (void)st0; (void)dsb; (void)G
    Cons c;
    c.sb = sb; c.sB = 0; c.mB = 0; c.mX = 0; c.elect = (threadIdx.x & 127) == 0;
    asm volatile("mapa.shared::cluster.u32 %0, %1, %2;" : "=r"(c.rem) : "r"(sb), "r"(rank ^ 1));
    PROF(0);
    float v[36];
#pragma unroll
    for (int i = 0; i < 4; i++) {
      const int o = 16 * (i >> 1) + 2 * (i & 1);
      v[o] = bf_lo(xin[i].x); v[o + 1] = bf_hi(xin[i].x); v[o + 4] = bf_lo(xin[i].y); v[o + 5] = bf_hi(xin[i].y);
      v[o + 8] = bf_lo(xin[i].z); v[o + 9] = bf_hi(xin[i].z); v[o + 12] = bf_lo(xin[i].w); v[o + 13] = bf_hi(xin[i].w);
    }
    v[32] = bf_lo(xin9[0]); v[33] = bf_hi(xin9[0]); v[34] = bf_lo(xin9[1]); v[35] = bf_hi(xin9[1]);
#pragma unroll 1
    for (int layer = 0;; layer++) {
      const uint32_t tag = layer ^ 1;
      const int pb = 1 + layer * 30;
      uint32_t res[18];
      uint4 x[36];
      {
        THREAD_IDS();
        PROF(pb + 0);
        float a1[96], a2[12];
        const float2 rs = ln_gemm<true>(c, G, v, res, layer == 0, (const char*)x_in + (128 * rb + 2 * (16 * wp + g) + w) * 1152 + 4 * q, st0, j, t, 1, 2 * layer + 1,
          [&](int i) { if (!XDELAY && i == 0 && layer == 0) asm volatile("barrier.cluster.wait.aligned;" ::: "memory"); PROF(pb + 1 + i); },
          [&](int gi, uint32_t bb, const uint4& f0, const uint4& f1) {
            if (gi == 0) PROF(pb + 3);
            wg_fence();
            wgmma_ra<192>(a1, f0, desc_hi(2048, 1024, 1) + bb, gi > 0);
            wgmma_ra<24>(a2, f0, desc_hi(128, 256, 0) + (bb + 384), gi > 0);
            wgmma_ra<192>(a1, f1, desc_hi(2048, 1024, 1) + (bb + 512), true);
            wgmma_ra<24>(a2, f1, desc_hi(128, 256, 0) + (bb + 896), true);
            wg_commit();
          });
        PROF(pb + 4);
        uint32_t kv[3][18];
        auto cvt = [&](int b, float r) {
#pragma unroll
          for (int cc = 0; cc < 18; cc++) {
            const float* a = (cc == 8 ? a2 + 4 : cc == 17 ? a2 + 8 : cc < 8 ? a1 + 32 + 4 * cc : a1 + 28 + 4 * cc) + 2 * (b - 1);
            const uint32_t u = pack_bf16(a[0] * r, a[1] * r);
            kv[b][cc] = cc < 9 ? u : movm(u);
          }
        };
        cvt(2, rs.y);
        const uint32_t msg = sb + SM_X + (w ? 3 * XSLOT + wp * 2304 : wp * XSLOT + 15360) + lane * 16;
        if (wp == 3) {
          uint4* hp = G->halo + j * 160 + lane;
#pragma unroll
          for (int i = 0; i < 4; i++) st_relaxed4(hp + i * 32, tagged(kv[2][4 * i], tag), kv[2][4 * i + 1], kv[2][4 * i + 2], kv[2][4 * i + 3]);
          st_relaxed2((uint2*)(hp + 128), tagged(kv[2][16], tag), kv[2][17]);
        } else {
#pragma unroll
          for (int i = 0; i < 4; i++) sts128(msg + i * 512, kv[2][4 * i], kv[2][4 * i + 1], kv[2][4 * i + 2], kv[2][4 * i + 3]);
          sts64f(msg + 2048 - lane * 8, __uint_as_float(kv[2][16]), __uint_as_float(kv[2][17]));
        }
        cvt(1, rs.x);
        uint32_t Q[4][6];
#pragma unroll
        for (int h = 0; h < 4; h++)
#pragma unroll
          for (int i = 0; i < 6; i++) {
            const float* a = 4 * h + i < 16 ? a1 + 8 * h + 2 * i : a2 + 8 * h + 2 * i - 32;
            const uint32_t u = pack_bf16(a[0], a[1]);
            Q[h][i] = i < 2 ? (q >= h ? u : 0) : i < 4 ? u : (q <= h ? u : 0);
          }
        const bool lo0 = 2 * q > g, lo1 = 2 * q + 1 > g;
        const uint32_t M = (lo0 ? 0xffffu : 0u) | (lo1 ? 0xffff0000u : 0u);
        auto scores = [&](int h, int b, float (&s)[4]) {
          mma16816z(s, Q[h][0], Q[h][1], Q[h][2], Q[h][3], kv[b][2 * h], kv[b][2 * h + 1]);
          mma1688(s, Q[h][4], Q[h][5], kv[b][2 * h + 2]);
        };
        auto softmax = [&](float (&l)[4][2], float r, uint32_t (&P)[4]) {
          const float sl = r * (0.23570226039551584f * 1.4426950408889634f);
          float m[4];
#pragma unroll
          for (int h = 0; h < 4; h++) { m[h] = fmaxf(l[h][0], l[h][1]); m[h] = fmaxf(m[h], __shfl_xor_sync(0xffffffffu, m[h], 1)); }
#pragma unroll
          for (int h = 0; h < 4; h++) m[h] = fmaxf(m[h], __shfl_xor_sync(0xffffffffu, m[h], 2)) * sl;
#pragma unroll
          for (int h = 0; h < 4; h++) {
            l[h][0] = ex2(fmaf(l[h][0], sl, -m[h])); l[h][1] = ex2(fmaf(l[h][1], sl, -m[h]));
            m[h] = l[h][0] + l[h][1]; m[h] += __shfl_xor_sync(0xffffffffu, m[h], 1);
          }
#pragma unroll
          for (int h = 0; h < 4; h++) { m[h] = rcp(m[h] + __shfl_xor_sync(0xffffffffu, m[h], 2)); P[h] = pack_bf16(l[h][0] * m[h], l[h][1] * m[h]); }
        };
        if (ATTBAR) {
          if (w) asm volatile("bar.arrive 4, 256;" ::: "memory"); else asm volatile("bar.sync 4, 256;" ::: "memory");
        }
        const bool remote = wp == 0 && rb > 0;
        const uint4* hp = (G - 2)->halo + j * 160 + lane;
        auto halo = [&] {
#pragma unroll
          for (int i = 0; i < 4; i++) { const uint4 u = ld_relaxed4(hp + i * 32); kv[0][4 * i] = u.x; kv[0][4 * i + 1] = u.y; kv[0][4 * i + 2] = u.z; kv[0][4 * i + 3] = u.w; }
          const uint2 u = ld_relaxed2((const uint2*)(hp + 128));
          kv[0][16] = u.x; kv[0][17] = u.y;
        };
#pragma unroll
        for (int i = 0; i < 18; i++) kv[0][i] = 0;
        if (remote) halo();
        float l0[4][2], l1[4][2];
#pragma unroll
        for (int h = 0; h < 4; h++) {
          float s1[4], s2[4];
          scores(h, 1, s1); scores(h, 2, s2);
          l0[h][0] = s1[0]; l0[h][1] = s1[1];
          l1[h][0] = lo0 ? s1[2] : s2[2]; l1[h][1] = lo1 ? s1[3] : s2[3];
        }
        uint32_t P0[4], P1[4];
        softmax(l1, rs.y, P1);
        if (remote) {
          while (__any_sync(0xffffffffu, ((kv[0][0] ^ tag) | (kv[0][4] ^ tag) | (kv[0][8] ^ tag) | (kv[0][12] ^ tag) | (kv[0][16] ^ tag)) & 1)) halo();
        }
        c.progress(32 * layer + 20);
        wg_bar(w);
        if (wp > 0) {
          const uint32_t from = msg - (w ? 2304 : XSLOT);
#pragma unroll
          for (int i = 0; i < 4; i++) { const uint4 u = lds128(from + i * 512); kv[0][4 * i] = u.x; kv[0][4 * i + 1] = u.y; kv[0][4 * i + 2] = u.z; kv[0][4 * i + 3] = u.w; }
          const float2 u = lds64(from + 2048 - lane * 8);
          kv[0][16] = __float_as_uint(u.x); kv[0][17] = __float_as_uint(u.y);
        }
        PROF(pb + 5);
        const bool first = (rb == 0 && wp == 0);
#pragma unroll
        for (int h = 0; h < 4; h++) {
          float s0[4];
          scores(h, 0, s0);
          if (first) s0[0] = s0[1] = -INFINITY;
          l0[h][0] = lo0 ? s0[0] : l0[h][0]; l0[h][1] = lo1 ? s0[1] : l0[h][1];
        }
        softmax(l0, rs.x, P0);
        uint4* ob = G->act[1] + t;
        uint32_t car0 = 0, car1 = 0;
#pragma unroll
        for (int h = 0; h < 4; h++) {
          float o[3][4];
#pragma unroll
          for (int i = 0; i < 3; i++) {
            mma16816z(o[i], P0[h] & ~M, P1[h] & M, 0u, P1[h] & ~M, kv[1][9 + 2 * h + i], kv[2][9 + 2 * h + i]);
            mma1688(o[i], P0[h] & M, 0u, kv[0][9 + 2 * h + i]);
          }
          const uint32_t o0 = q < h ? car0 : pack_bf16(o[0][0], o[0][1]), o1 = q < h ? car1 : pack_bf16(o[0][2], o[0][3]);
          st_relaxed4(ob + (8 * h + j) * 128, tagged(o0, tag), o1, pack_bf16(o[1][0], o[1][1]), pack_bf16(o[1][2], o[1][3]));
          car0 = pack_bf16(o[2][0], o[2][1]); car1 = pack_bf16(o[2][2], o[2][3]);
          if (h == WOH) {
#pragma unroll
            for (int i = 0; i < 4 * WWIN; i++) x[i] = ld_relaxed4(ob + i * 128);
          }
        }
        st_relaxed2((uint2*)(ob + (32 + (j >> 1)) * 128) + (j & 1), tagged(car0, tag), car1);
        PROF(pb + 6);
      }
      {
        THREAD_IDS();
        const uint4* src = G->act[1] + t;
        float a[32], a8[4];
#pragma unroll
        for (int i = 3; i < 8; i++) mbar_wait_c(sb + BAR_FULLX + 8 * i, (c.mX >> i) & 1);
        c.mX ^= 0xf8;
#pragma unroll
        for (int b = 0; b < 9; b++) {
          while (true) {
            uint32_t bad = 0;
#pragma unroll
            for (int i = 4 * b; i < 4 * b + 4; i++) bad |= (x[i].x ^ tag) | (b < 8 ? 0u : x[i].z ^ tag);
            if (!__any_sync(0xffffffffu, bad & 1)) break;
#pragma unroll
            for (int i = 4 * b; i < 4 * b + 4; i++) x[i] = ld_relaxed4(src + i * 128);
          }
          if (b == 0) PROF(pb + 7);
          if (b + WWIN < 9) {
#pragma unroll
            for (int i = 4 * (b + WWIN); i < 4 * (b + WWIN) + 4; i++) x[i] = ld_relaxed4(src + i * 128);
          }
          wg_fence();
#pragma unroll
          for (int i = 4 * b; i < 4 * b + 4; i++) {
            const int r0 = i < 32 ? 72 * (i & 7) + 16 * (i >> 3) : 144 * (i - 32) + 64, rs = i < 32 ? 8 : 72;
            wgmma_ra<64>(a, x[i], desc_hi(0, rs * 128, 1) + (dsb + ((SM_X + 4 * XSLOT) >> 4) + r0 * 8), i > 0);
            wgmma_ra<8>(a8, x[i], desc_hi(rs * 16, 0, 0) + (dsb + (SM_WOC >> 4) + r0), i > 0);
          }
          wg_commit();
        }
        wg_wait<0>();
        if (w == 0) asm volatile("bar.arrive 3, 256;" ::: "memory");
        PROF(pb + 8);
#pragma unroll
        for (int i = 0; i < 18; i++) {
          v[2 * i] = bf_lo(res[i]) + (i < 16 ? a[2 * i] : a8[2 * i - 32]);
          v[2 * i + 1] = bf_hi(res[i]) + (i < 16 ? a[2 * i + 1] : a8[2 * i - 31]);
        }
      }
      uint32_t lsb;
      uint32_t h[144];
      {
        THREAD_IDS();
        float a[128];
        const uint32_t xd = sb + SM_X + w * 4 * XSLOT + (lane >> 4) * 1024 + (16 * wp + (lane & 15)) * 16;
        const float2 rs = ln_gemm<false>(c, G, v, res, false, nullptr, st0, j, t, tag, (2 * layer + 2) & 3,
          [&](int i) {
            if (i == 0) {
              lsb = ((res[0] & 1) | (res[1] & 1) << 1 | (res[8] & 1) << 2 | (res[9] & 1) << 3 | (res[16] & 1) << 4) ^ (tag * 31);
              if (w == 1) asm volatile("bar.sync 3, 256;" ::: "memory");
            }
            PROF(pb + 9 + i);
          },
          [&](int gi, uint32_t bb, const uint4& f0, const uint4& f1) {
            if (gi == 0) PROF(pb + 11);
            wg_fence();
            wgmma_ra<256>(a, f0, desc_hi(4096, 1024, 1) + bb, gi > 0);
            wgmma_ra<256>(a, f1, desc_hi(4096, 1024, 1) + (bb + 128), true);
            wg_commit();
            stsm4(xd + gi * 4096, f0.x, f0.y, f0.z, f0.w);
            stsm4(xd + gi * 4096 + 2048, f1.x, f1.y, f1.z, f1.w);
            if (gi == 17) { fence_async_smem(); wg_bar(w); }
          });
        sts64f(sb + SM_KEEP + tid_ * 8, rs.x * rs.x, rs.y * rs.y);
        PROF(pb + 12);
        glu<16, 0>(a, h);
        const uint64_t da0 = desc_hi(1024, 128, 0) + (dsb + ((SM_X + w * 4 * XSLOT) >> 4));
        auto tile = [&](auto wide, auto last) {
          const uint32_t xe = BAR_EMPTYX + 8 * (t & 1) + 16 * (t & 2);
#pragma unroll 1
          for (int gi = 0; gi < 18; gi++) {
            uint32_t prev;
            const uint32_t bb = c.nextB(prev);
            const uint64_t da = da0 + gi * 256;
            wg_fence();
            if (wide()) {
              wgmma_ss<256>(a, da, desc_hi(4096, 1024, 1) + bb, gi);
              wgmma_ss<256>(a, da + 128, desc_hi(4096, 1024, 1) + (bb + 128), 1);
            } else {
              wgmma_ss<192>(*(float(*)[96])a, da, desc_hi(2048, 512, 2) + bb, gi);
              wgmma_ss<192>(*(float(*)[96])a, da + 128, desc_hi(2048, 512, 2) + (bb + 64), 1);
            }
            wg_commit();
            wg_wait<1>();
            if (gi > 0 && !(last() && gi > 13)) c.release2(BAR_EMPTYB + prev);
            if (last() && gi == 12 && t < 4) { mbar_arrive(sb + xe); mbar_arrive_remote(c.rem + xe); }
          }
          wg_wait<0>();
          if (!last()) c.releaseLastB();
          if (last() && t < 4) { mbar_arrive(sb + xe + 16); mbar_arrive_remote(c.rem + xe + 16); }
        };
        auto yes = [] { return true; };
        auto no = [] { return false; };
        tile(yes, no); PROF(pb + 13); glu<16, 32>(a, h);
        tile(yes, no); PROF(pb + 14); glu<16, 64>(a, h);
        tile(no, no); PROF(pb + 15); glu<12, 96>(a, h);
        const uint32_t hole = sb + SM_B + 12288 + tid_ * 16;
#pragma unroll
        for (int i = 0; i < NSPILL; i++) sts128(hole + i * BSLOT, h[96 + 4 * i], h[97 + 4 * i], h[98 + 4 * i], h[99 + 4 * i]);
        tile(no, yes); PROF(pb + 16); glu<12, 120>(a, h);
#pragma unroll
        for (int i = 0; i < NSPILL; i++) { const uint4 u = lds128(hole + i * BSLOT); h[96 + 4 * i] = u.x; h[97 + 4 * i] = u.y; h[98 + 4 * i] = u.z; h[99 + 4 * i] = u.w; }
      }
      {
        THREAD_IDS();
        float d[32];
        uint32_t pk[16];
#pragma unroll
        for (int i = 0; i < 16; i++) pk[i] = 0;
        uint4* const ib = G->inbox[layer];
        auto pass = [&](uint32_t s0, auto&& hook) {
          const uint64_t db = desc_hi(0, 1024, 1) + (dsb + (SM_X >> 4) + s0 * (XSLOT >> 4));
#pragma unroll
          for (int i = 0; i < 4; i++) {
            const int si = 4 * (i & 1) + (i >> 1);
            mbar_wait_c(sb + BAR_FULLX + 8 * (s0 + si), (c.mX >> (s0 + si)) & 1);
            wg_fence();
#pragma unroll
            for (int k = 0; k < 9; k++) {
              const uint32_t* hk = h + 36 * i + 4 * k;
              wgmma_ra<64>(d, make_uint4(hk[0], hk[1], hk[2], hk[3]), db + (si * (XSLOT >> 4) + k * 128), i + k > 0);
            }
            wg_commit();
            hook(i);
            if (i > 0) { wg_wait<1>(); c.release2(BAR_EMPTYX + 8 * (s0 + 4 * ((i - 1) & 1) + ((i - 1) >> 1))); }
          }
          c.mX ^= 0x33u << s0;
        };
        if (LEAD && w == 1) asm volatile("bar.sync 5, 256;" ::: "memory");
        PROF(pb + 17);
#pragma unroll 1
        for (int p = 0; p < 8; p++) {
          const uint32_t s0 = 2 * (p & 1);
          pass(s0, [&](int i) {
            if (LEAD && i == (LEAD & 3) && p == (LEAD >> 2) && w == 0) asm volatile("bar.arrive 5, 256;" ::: "memory");
            if (i == 0) {
              if (p > 1) {
                uint4* dst = ib + ((j + p - 1) & 7) * INBOX + t;
#pragma unroll
                for (int k = 0; k < 4; k++) red4(dst + k * 128, pk[4 * k], pk[4 * k + 1], pk[4 * k + 2], pk[4 * k + 3]);
                if (p == 7) { __syncwarp(); if (lane == 0) mbar_arrive(sb + BAR_REDDONE + 8 * w); }
              } else if (p == 1) {
                mbar_wait_c(sb + BAR_CLR + 8 * w, 0);
                if (t < 5) { mbar_arrive(sb + BAR_EMPTYB + 8 * t); mbar_arrive_remote(c.rem + BAR_EMPTYB + 8 * t); }
#pragma unroll
                for (int k = 0; k < 8; k++) red2((uint2*)(ib + k * INBOX + 1024) + t, pk[2 * k], pk[2 * k + 1]);
              }
            }
          });
          wg_wait<0>();
          c.release2(BAR_EMPTYX + 8 * (s0 + 5));
#pragma unroll
          for (int i = 0; i < 16; i++) pk[i] = pack_bf16(d[2 * i], d[2 * i + 1]);
        }
        PROF(pb + 18);
        uint4 R[4], P[4], X[4];
        uint2 R9, X9;
        const uint4* in = ib + j * INBOX + t;
        pass(0, [&](int i) {
          if (i == 0) {
            uint4* dst = ib + ((j + 7) & 7) * INBOX + 512 + t;
#pragma unroll
            for (int k = 0; k < 4; k++) st_relaxed4(dst + k * 128, max(pk[4 * k], 1u), pk[4 * k + 1], pk[4 * k + 2], pk[4 * k + 3]);
            const uint4* box = G->act[2] + t;
#pragma unroll
            for (int k = 0; k < 4; k++) X[k] = ld_relaxed4(box + (2 * j + (k & 1) + 8 * (k & 2)) * 128);
            X9 = ld_relaxed2((const uint2*)(box + (32 + (j >> 1)) * 128) + (j & 1));
          } else if (i == 2) {
            mbar_wait_c(sb + BAR_RREADY + 8 * w, layer);
#pragma unroll
            for (int k = 0; k < 4; k++) R[k] = ld_relaxed4(in + k * 128);
            R9 = ld_relaxed2((const uint2*)(in - t + 1024) + t);
          } else if (i == 3) {
#pragma unroll
            for (int k = 0; k < 4; k++) P[k] = ld_relaxed4(in + 512 + k * 128);
          }
        });
        PROF(pb + 19);
        const float2 r2 = lds64(sb + SM_KEEP + tid_ * 8);
#pragma unroll
        for (int k = 0; k < 4; k++) X[k].x ^= (lsb >> k) & 1;
        X9.x ^= lsb >> 4;
        v[32] = fmaf(bf_lo(R9.x), r2.x, bf_lo(X9.x)); v[33] = fmaf(bf_hi(R9.x), r2.x, bf_hi(X9.x));
        v[34] = fmaf(bf_lo(R9.y), r2.y, bf_lo(X9.y)); v[35] = fmaf(bf_hi(R9.y), r2.y, bf_hi(X9.y));
        while (__any_sync(0xffffffffu, P[0].x == 0 || P[1].x == 0 || P[2].x == 0 || P[3].x == 0)) {
#pragma unroll
          for (int k = 0; k < 4; k++) P[k] = ld_relaxed4(in + 512 + k * 128);
        }
        auto comb = [&](int i, uint32_t r, uint32_t p, uint32_t x) {
          const float s = i & 1 ? r2.y : r2.x;
          v[2 * i] = fmaf(bf_lo(r) + bf_lo(p), s, bf_lo(x)); v[2 * i + 1] = fmaf(bf_hi(r) + bf_hi(p), s, bf_hi(x));
        };
#pragma unroll
        for (int k = 0; k < 4; k += 2) {
          comb(4 * k, R[k].x, P[k].x, X[k].x); comb(4 * k + 1, R[k].y, P[k].y, X[k + 1].x);
          comb(4 * k + 2, R[k].z, P[k].z, X[k].y); comb(4 * k + 3, R[k].w, P[k].w, X[k + 1].y);
          comb(4 * k + 4, R[k + 1].x, P[k + 1].x, X[k].z); comb(4 * k + 5, R[k + 1].y, P[k + 1].y, X[k + 1].z);
          comb(4 * k + 6, R[k + 1].z, P[k + 1].z, X[k].w); comb(4 * k + 7, R[k + 1].w, P[k + 1].w, X[k + 1].w);
        }
        PROF(pb + 20);
        wg_wait<0>();
        c.release2(BAR_EMPTYX + 40);
        PROF(pb + 21);
#pragma unroll
        for (int i = 0; i < 32; i++) v[i] = fmaf(d[i], i & 2 ? r2.y : r2.x, v[i]);
      }
      if (layer == NLAYERS - 1) break;
    }
    {
      THREAD_IDS();
      const uint32_t stg = sb + SM_B + warp * 4096;
      const uint32_t sd = stg + (lane & 15) * 128;
#pragma unroll
      for (int i = 0; i < 4; i++)
        stsm4(sd + (((2 * i + (lane >> 4)) ^ (lane & 7)) << 4), pack_bf16(v[8 * i], v[8 * i + 1]), pack_bf16(v[8 * i + 2], v[8 * i + 3]),
              pack_bf16(v[8 * i + 4], v[8 * i + 5]), pack_bf16(v[8 * i + 6], v[8 * i + 7]));
      stsm2(stg + 2048 + (lane & 15) * 16, pack_bf16(v[32], v[33]), pack_bf16(v[34], v[35]));
      fence_async_smem();
      __syncwarp();
      if (lane == 0) {
        tma_store3d(&maps.out, stg, 64 * j, w, 64 * rb + 16 * wp);
        tma_store3d(&maps.outc, stg + 2048, 512 + 8 * j, w, 64 * rb + 16 * wp);
        bulk_commit();
        bulk_wait_all();
        mbar_arrive(sb + BAR_DONE + 8 * w);
      }
      PROF(61);
    }
    __syncwarp();
    cluster_sync();
  }
}

typedef CUresult (*EncFn)(CUtensorMap*, CUtensorMapDataType, cuuint32_t, void*, const cuuint64_t*, const cuuint64_t*, const cuuint32_t*,
                          const cuuint32_t*, CUtensorMapInterleave, CUtensorMapSwizzle, CUtensorMapL2promotion, CUtensorMapFloatOOBfill);

void make_map(EncFn enc, CUtensorMap* m, const void* p, int rank, uint64_t d0, uint64_t d1, uint64_t d2, uint64_t s1, uint64_t s2, uint32_t b0,
              uint32_t b1, uint32_t b2, CUtensorMapSwizzle sw) {
  cuuint64_t gd[3] = {d0, d1, d2};
  cuuint64_t gs[2] = {s1, s2};
  cuuint32_t bd[3] = {b0, b1, b2};
  cuuint32_t es[3] = {1, 1, 1};
  enc(m, CU_TENSOR_MAP_DATA_TYPE_BFLOAT16, rank, const_cast<void*>(p), gd, gs, bd, es, CU_TENSOR_MAP_INTERLEAVE_NONE, sw,
      CU_TENSOR_MAP_L2_PROMOTION_L2_128B, CU_TENSOR_MAP_FLOAT_OOB_FILL_NONE);
}

void make_map5(EncFn enc, CUtensorMap* m, const void* p, uint64_t sa, uint64_t sb, uint32_t bcol, CUtensorMapSwizzle sw) {
  cuuint64_t gd[5] = {576, 2, 4, 576 / sb, 3};
  cuuint64_t gs[4] = {3456, sa * 3456, sb * 3456, 1152};
  cuuint32_t bd[5] = {bcol, 2, 4, 2, 3};
  cuuint32_t es[5] = {1, 1, 1, 1, 1};
  enc(m, CU_TENSOR_MAP_DATA_TYPE_BFLOAT16, 5, const_cast<void*>(p), gd, gs, bd, es, CU_TENSOR_MAP_INTERLEAVE_NONE, sw,
      CU_TENSOR_MAP_L2_PROMOTION_L2_128B, CU_TENSOR_MAP_FLOAT_OOB_FILL_NONE);
}

}

extern "C" void kernel_launch(void* const* d_in, const int* in_sizes, int n_in, void* d_out, int out_size) {
  const __nv_bfloat16* x = (const __nv_bfloat16*)d_in[0];
  const char *wqkv = (const char*)d_in[1], *wo = (const char*)d_in[2], *wg = (const char*)d_in[4], *wu = (const char*)d_in[5], *wd = (const char*)d_in[6];
  static EncFn enc = nullptr;
  static Group* ws = nullptr;
  if (!enc) {
    cudaDriverEntryPointQueryResult qr;
    cudaGetDriverEntryPoint("cuTensorMapEncodeTiled", (void**)&enc, cudaEnableDefault, &qr);
    cudaGetSymbolAddress((void**)&ws, g_ws);
    cudaFuncSetAttribute(fused_kernel, cudaFuncAttributeMaxDynamicSharedMemorySize, SMEM_BYTES);
  }
  const CUtensorMapSwizzle S0 = CU_TENSOR_MAP_SWIZZLE_NONE, S64 = CU_TENSOR_MAP_SWIZZLE_64B, S128 = CU_TENSOR_MAP_SWIZZLE_128B;
  Maps m;
  make_map5(enc, &m.qm[0], wqkv, 16, 2, 64, S128);
  make_map5(enc, &m.qm[1], wqkv, 2, 8, 64, S128);
  make_map5(enc, &m.qc[0], wqkv, 16, 2, 8, S0);
  make_map5(enc, &m.qc[1], wqkv, 2, 8, 8, S0);
  make_map(enc, &m.o, wo, 2, 576, 576, 1, 1152, 0, 64, 72, 1, S128);
  make_map(enc, &m.oc, wo, 2, 576, 576, 1, 1152, 0, 8, 144, 1, S0);
  make_map(enc, &m.g, wg, 3, 64, 576, 72, 9216, 128, 64, 32, 2, S128);
  make_map(enc, &m.u, wu, 3, 64, 576, 72, 9216, 128, 64, 32, 2, S128);
  make_map(enc, &m.g3, wg, 3, 32, 576, 144, 9216, 64, 32, 32, 3, S64);
  make_map(enc, &m.u3, wu, 3, 32, 576, 144, 9216, 64, 32, 32, 3, S64);
  make_map(enc, &m.d, wd, 2, 576, 4608, 1, 1152, 0, 64, 72, 1, S128);
  make_map(enc, &m.out, d_out, 3, 576, 2, 1024, 1152, 2304, 64, 1, 16, S128);
  make_map(enc, &m.outc, d_out, 3, 576, 2, 1024, 1152, 2304, 8, 1, 16, S0);
  fused_kernel<<<NCTA, 384, SMEM_BYTES>>>(x, ws, wqkv, wg, wu, wd, m, wo);
}
```

```cpp
#include <cuda_runtime.h>
#include <cuda_bf16.h>
#include <cuda.h>
#include <stdint.h>
#include <stddef.h>

namespace {

constexpr int D_ = 576;
constexpr int NCTA = 128;
#define NLAYERS 2
#define W_POLICY policy_evict_first
#define A_POLICY policy_evict_normal
#define OPEN 1
#define PFMODE 3
#define NFIRST 3
#define WWIN 2
#define SPEC 2
#define POLLFIRST 0
#define LEAD 0
#define ATTBAR 0
#define QD 2
#define QG 4
#define PFQ 1
#define XDELAY 0
#define WOH 1
#define PFSLEEP 700
#define GPCMAP 1
#define PFF 1
#define NSPILL 4
#define REGS_C 232
#define REGS_P 40
#define STR2(x) #x
#define STR(x) STR2(x)
constexpr uint32_t SM_X = 0;
constexpr uint32_t XSLOT = 18432;
constexpr uint32_t SM_WOC = SM_X + 3 * XSLOT + 9216;
constexpr uint32_t SM_B = 147456;
constexpr uint32_t BSLOT = 16384;
constexpr uint32_t SM_KEEP = 229376;
constexpr uint32_t SM_BAR = SM_KEEP + 2048;
constexpr uint32_t BAR_FULLB = SM_BAR;
constexpr uint32_t BAR_RREADY = SM_BAR + 40;
constexpr uint32_t BAR_CLR = SM_BAR + 56;
constexpr uint32_t BAR_FULLX = SM_BAR + 72;
constexpr uint32_t BAR_EMPTYB = SM_BAR + 144;
constexpr uint32_t BAR_EMPTYX = SM_BAR + 184;
constexpr uint32_t BAR_REDDONE = SM_BAR + 248;
constexpr uint32_t BAR_DONE = SM_BAR + 264;
constexpr uint32_t SM_PROG = SM_BAR + 288;
constexpr uint32_t SMEM_BYTES = SM_BAR + 1024;

struct Maps { CUtensorMap x, qm, qc, o, oc, g, u, g3, u3, d, out, outc; };

constexpr int INBOX = 1088;
struct Group {
  uint2 sum[4 * 8 * 8];
  uint4 m2[4 * 8 * 8];
  uint32_t flag[512];
  uint4 halo[8 * 160];
  uint4 act[3][36 * 128];
  uint4 inbox[2][8 * INBOX];
};
__device__ __align__(1024) Group g_ws[32];
#define PROF(i)
#define PROFX(i)

template<int N> __device__ __forceinline__ void wgmma_ss(float (&d)[N / 2], uint64_t da, uint64_t db, int sc);
template<> __device__ __forceinline__ void wgmma_ss<192>(float (&d)[96], uint64_t da, uint64_t db, int sc) {
  asm volatile("{\n.reg .pred p;\nsetp.ne.b32 p, %98, 0;\n"
    "wgmma.mma_async.sync.aligned.m64n192k16.f32.bf16.bf16 {%0,%1,%2,%3,%4,%5,%6,%7,%8,%9,%10,%11,%12,%13,%14,%15,%16,%17,%18,%19,%20,%21,%22,%23,%24,%25,%26,%27,%28,%29,%30,%31,%32,%33,%34,%35,%36,%37,%38,%39,%40,%41,%42,%43,%44,%45,%46,%47,%48,%49,%50,%51,%52,%53,%54,%55,%56,%57,%58,%59,%60,%61,%62,%63,%64,%65,%66,%67,%68,%69,%70,%71,%72,%73,%74,%75,%76,%77,%78,%79,%80,%81,%82,%83,%84,%85,%86,%87,%88,%89,%90,%91,%92,%93,%94,%95}, %96, %97, p, 1, 1, 0, 1;\n}\n"
    : "+f"(d[0]),"+f"(d[1]),"+f"(d[2]),"+f"(d[3]),"+f"(d[4]),"+f"(d[5]),"+f"(d[6]),"+f"(d[7]),"+f"(d[8]),"+f"(d[9]),"+f"(d[10]),"+f"(d[11]),"+f"(d[12]),"+f"(d[13]),"+f"(d[14]),"+f"(d[15]),"+f"(d[16]),"+f"(d[17]),"+f"(d[18]),"+f"(d[19]),"+f"(d[20]),"+f"(d[21]),"+f"(d[22]),"+f"(d[23]),"+f"(d[24]),"+f"(d[25]),"+f"(d[26]),"+f"(d[27]),"+f"(d[28]),"+f"(d[29]),"+f"(d[30]),"+f"(d[31]),"+f"(d[32]),"+f"(d[33]),"+f"(d[34]),"+f"(d[35]),"+f"(d[36]),"+f"(d[37]),"+f"(d[38]),"+f"(d[39]),"+f"(d[40]),"+f"(d[41]),"+f"(d[42]),"+f"(d[43]),"+f"(d[44]),"+f"(d[45]),"+f"(d[46]),"+f"(d[47]),"+f"(d[48]),"+f"(d[49]),"+f"(d[50]),"+f"(d[51]),"+f"(d[52]),"+f"(d[53]),"+f"(d[54]),"+f"(d[55]),"+f"(d[56]),"+f"(d[57]),"+f"(d[58]),"+f"(d[59]),"+f"(d[60]),"+f"(d[61]),"+f"(d[62]),"+f"(d[63]),"+f"(d[64]),"+f"(d[65]),"+f"(d[66]),"+f"(d[67]),"+f"(d[68]),"+f"(d[69]),"+f"(d[70]),"+f"(d[71]),"+f"(d[72]),"+f"(d[73]),"+f"(d[74]),"+f"(d[75]),"+f"(d[76]),"+f"(d[77]),"+f"(d[78]),"+f"(d[79]),"+f"(d[80]),"+f"(d[81]),"+f"(d[82]),"+f"(d[83]),"+f"(d[84]),"+f"(d[85]),"+f"(d[86]),"+f"(d[87]),"+f"(d[88]),"+f"(d[89]),"+f"(d[90]),"+f"(d[91]),"+f"(d[92]),"+f"(d[93]),"+f"(d[94]),"+f"(d[95]) : "l"(da), "l"(db), "r"(sc));
}
template<> __device__ __forceinline__ void wgmma_ss<256>(float (&d)[128], uint64_t da, uint64_t db, int sc) {
  asm volatile("{\n.reg .pred p;\nsetp.ne.b32 p, %130, 0;\n"
    "wgmma.mma_async.sync.aligned.m64n256k16.f32.bf16.bf16 {%0,%1,%2,%3,%4,%5,%6,%7,%8,%9,%10,%11,%12,%13,%14,%15,%16,%17,%18,%19,%20,%21,%22,%23,%24,%25,%26,%27,%28,%29,%30,%31,%32,%33,%34,%35,%36,%37,%38,%39,%40,%41,%42,%43,%44,%45,%46,%47,%48,%49,%50,%51,%52,%53,%54,%55,%56,%57,%58,%59,%60,%61,%62,%63,%64,%65,%66,%67,%68,%69,%70,%71,%72,%73,%74,%75,%76,%77,%78,%79,%80,%81,%82,%83,%84,%85,%86,%87,%88,%89,%90,%91,%92,%93,%94,%95,%96,%97,%98,%99,%100,%101,%102,%103,%104,%105,%106,%107,%108,%109,%110,%111,%112,%113,%114,%115,%116,%117,%118,%119,%120,%121,%122,%123,%124,%125,%126,%127}, %128, %129, p, 1, 1, 0, 1;\n}\n"
    : "+f"(d[0]),"+f"(d[1]),"+f"(d[2]),"+f"(d[3]),"+f"(d[4]),"+f"(d[5]),"+f"(d[6]),"+f"(d[7]),"+f"(d[8]),"+f"(d[9]),"+f"(d[10]),"+f"(d[11]),"+f"(d[12]),"+f"(d[13]),"+f"(d[14]),"+f"(d[15]),"+f"(d[16]),"+f"(d[17]),"+f"(d[18]),"+f"(d[19]),"+f"(d[20]),"+f"(d[21]),"+f"(d[22]),"+f"(d[23]),"+f"(d[24]),"+f"(d[25]),"+f"(d[26]),"+f"(d[27]),"+f"(d[28]),"+f"(d[29]),"+f"(d[30]),"+f"(d[31]),"+f"(d[32]),"+f"(d[33]),"+f"(d[34]),"+f"(d[35]),"+f"(d[36]),"+f"(d[37]),"+f"(d[38]),"+f"(d[39]),"+f"(d[40]),"+f"(d[41]),"+f"(d[42]),"+f"(d[43]),"+f"(d[44]),"+f"(d[45]),"+f"(d[46]),"+f"(d[47]),"+f"(d[48]),"+f"(d[49]),"+f"(d[50]),"+f"(d[51]),"+f"(d[52]),"+f"(d[53]),"+f"(d[54]),"+f"(d[55]),"+f"(d[56]),"+f"(d[57]),"+f"(d[58]),"+f"(d[59]),"+f"(d[60]),"+f"(d[61]),"+f"(d[62]),"+f"(d[63]),"+f"(d[64]),"+f"(d[65]),"+f"(d[66]),"+f"(d[67]),"+f"(d[68]),"+f"(d[69]),"+f"(d[70]),"+f"(d[71]),"+f"(d[72]),"+f"(d[73]),"+f"(d[74]),"+f"(d[75]),"+f"(d[76]),"+f"(d[77]),"+f"(d[78]),"+f"(d[79]),"+f"(d[80]),"+f"(d[81]),"+f"(d[82]),"+f"(d[83]),"+f"(d[84]),"+f"(d[85]),"+f"(d[86]),"+f"(d[87]),"+f"(d[88]),"+f"(d[89]),"+f"(d[90]),"+f"(d[91]),"+f"(d[92]),"+f"(d[93]),"+f"(d[94]),"+f"(d[95]),"+f"(d[96]),"+f"(d[97]),"+f"(d[98]),"+f"(d[99]),"+f"(d[100]),"+f"(d[101]),"+f"(d[102]),"+f"(d[103]),"+f"(d[104]),"+f"(d[105]),"+f"(d[106]),"+f"(d[107]),"+f"(d[108]),"+f"(d[109]),"+f"(d[110]),"+f"(d[111]),"+f"(d[112]),"+f"(d[113]),"+f"(d[114]),"+f"(d[115]),"+f"(d[116]),"+f"(d[117]),"+f"(d[118]),"+f"(d[119]),"+f"(d[120]),"+f"(d[121]),"+f"(d[122]),"+f"(d[123]),"+f"(d[124]),"+f"(d[125]),"+f"(d[126]),"+f"(d[127]) : "l"(da), "l"(db), "r"(sc));
}
template<int N> __device__ __forceinline__ void wgmma_rs(float (&d)[N / 2], uint32_t a0, uint32_t a1, uint32_t a2, uint32_t a3, uint64_t db, int sc);
template<> __device__ __forceinline__ void wgmma_rs<8>(float (&d)[4], uint32_t a0, uint32_t a1, uint32_t a2, uint32_t a3, uint64_t db, int sc) {
  asm volatile("{\n.reg .pred p;\nsetp.ne.b32 p, %9, 0;\n"
    "wgmma.mma_async.sync.aligned.m64n8k16.f32.bf16.bf16 {%0,%1,%2,%3}, {%4,%5,%6,%7}, %8, p, 1, 1, 1;\n}\n"
    : "+f"(d[0]),"+f"(d[1]),"+f"(d[2]),"+f"(d[3]) : "r"(a0), "r"(a1), "r"(a2), "r"(a3), "l"(db), "r"(sc));
}
template<> __device__ __forceinline__ void wgmma_rs<24>(float (&d)[12], uint32_t a0, uint32_t a1, uint32_t a2, uint32_t a3, uint64_t db, int sc) {
  asm volatile("{\n.reg .pred p;\nsetp.ne.b32 p, %17, 0;\n"
    "wgmma.mma_async.sync.aligned.m64n24k16.f32.bf16.bf16 {%0,%1,%2,%3,%4,%5,%6,%7,%8,%9,%10,%11}, {%12,%13,%14,%15}, %16, p, 1, 1, 1;\n}\n"
    : "+f"(d[0]),"+f"(d[1]),"+f"(d[2]),"+f"(d[3]),"+f"(d[4]),"+f"(d[5]),"+f"(d[6]),"+f"(d[7]),"+f"(d[8]),"+f"(d[9]),"+f"(d[10]),"+f"(d[11]) : "r"(a0), "r"(a1), "r"(a2), "r"(a3), "l"(db), "r"(sc));
}
template<> __device__ __forceinline__ void wgmma_rs<64>(float (&d)[32], uint32_t a0, uint32_t a1, uint32_t a2, uint32_t a3, uint64_t db, int sc) {
  asm volatile("{\n.reg .pred p;\nsetp.ne.b32 p, %37, 0;\n"
    "wgmma.mma_async.sync.aligned.m64n64k16.f32.bf16.bf16 {%0,%1,%2,%3,%4,%5,%6,%7,%8,%9,%10,%11,%12,%13,%14,%15,%16,%17,%18,%19,%20,%21,%22,%23,%24,%25,%26,%27,%28,%29,%30,%31}, {%32,%33,%34,%35}, %36, p, 1, 1, 1;\n}\n"
    : "+f"(d[0]),"+f"(d[1]),"+f"(d[2]),"+f"(d[3]),"+f"(d[4]),"+f"(d[5]),"+f"(d[6]),"+f"(d[7]),"+f"(d[8]),"+f"(d[9]),"+f"(d[10]),"+f"(d[11]),"+f"(d[12]),"+f"(d[13]),"+f"(d[14]),"+f"(d[15]),"+f"(d[16]),"+f"(d[17]),"+f"(d[18]),"+f"(d[19]),"+f"(d[20]),"+f"(d[21]),"+f"(d[22]),"+f"(d[23]),"+f"(d[24]),"+f"(d[25]),"+f"(d[26]),"+f"(d[27]),"+f"(d[28]),"+f"(d[29]),"+f"(d[30]),"+f"(d[31]) : "r"(a0), "r"(a1), "r"(a2), "r"(a3), "l"(db), "r"(sc));
}
template<> __device__ __forceinline__ void wgmma_rs<192>(float (&d)[96], uint32_t a0, uint32_t a1, uint32_t a2, uint32_t a3, uint64_t db, int sc) {
  asm volatile("{\n.reg .pred p;\nsetp.ne.b32 p, %101, 0;\n"
    "wgmma.mma_async.sync.aligned.m64n192k16.f32.bf16.bf16 {%0,%1,%2,%3,%4,%5,%6,%7,%8,%9,%10,%11,%12,%13,%14,%15,%16,%17,%18,%19,%20,%21,%22,%23,%24,%25,%26,%27,%28,%29,%30,%31,%32,%33,%34,%35,%36,%37,%38,%39,%40,%41,%42,%43,%44,%45,%46,%47,%48,%49,%50,%51,%52,%53,%54,%55,%56,%57,%58,%59,%60,%61,%62,%63,%64,%65,%66,%67,%68,%69,%70,%71,%72,%73,%74,%75,%76,%77,%78,%79,%80,%81,%82,%83,%84,%85,%86,%87,%88,%89,%90,%91,%92,%93,%94,%95}, {%96,%97,%98,%99}, %100, p, 1, 1, 1;\n}\n"
    : "+f"(d[0]),"+f"(d[1]),"+f"(d[2]),"+f"(d[3]),"+f"(d[4]),"+f"(d[5]),"+f"(d[6]),"+f"(d[7]),"+f"(d[8]),"+f"(d[9]),"+f"(d[10]),"+f"(d[11]),"+f"(d[12]),"+f"(d[13]),"+f"(d[14]),"+f"(d[15]),"+f"(d[16]),"+f"(d[17]),"+f"(d[18]),"+f"(d[19]),"+f"(d[20]),"+f"(d[21]),"+f"(d[22]),"+f"(d[23]),"+f"(d[24]),"+f"(d[25]),"+f"(d[26]),"+f"(d[27]),"+f"(d[28]),"+f"(d[29]),"+f"(d[30]),"+f"(d[31]),"+f"(d[32]),"+f"(d[33]),"+f"(d[34]),"+f"(d[35]),"+f"(d[36]),"+f"(d[37]),"+f"(d[38]),"+f"(d[39]),"+f"(d[40]),"+f"(d[41]),"+f"(d[42]),"+f"(d[43]),"+f"(d[44]),"+f"(d[45]),"+f"(d[46]),"+f"(d[47]),"+f"(d[48]),"+f"(d[49]),"+f"(d[50]),"+f"(d[51]),"+f"(d[52]),"+f"(d[53]),"+f"(d[54]),"+f"(d[55]),"+f"(d[56]),"+f"(d[57]),"+f"(d[58]),"+f"(d[59]),"+f"(d[60]),"+f"(d[61]),"+f"(d[62]),"+f"(d[63]),"+f"(d[64]),"+f"(d[65]),"+f"(d[66]),"+f"(d[67]),"+f"(d[68]),"+f"(d[69]),"+f"(d[70]),"+f"(d[71]),"+f"(d[72]),"+f"(d[73]),"+f"(d[74]),"+f"(d[75]),"+f"(d[76]),"+f"(d[77]),"+f"(d[78]),"+f"(d[79]),"+f"(d[80]),"+f"(d[81]),"+f"(d[82]),"+f"(d[83]),"+f"(d[84]),"+f"(d[85]),"+f"(d[86]),"+f"(d[87]),"+f"(d[88]),"+f"(d[89]),"+f"(d[90]),"+f"(d[91]),"+f"(d[92]),"+f"(d[93]),"+f"(d[94]),"+f"(d[95]) : "r"(a0), "r"(a1), "r"(a2), "r"(a3), "l"(db), "r"(sc));
}
template<> __device__ __forceinline__ void wgmma_rs<256>(float (&d)[128], uint32_t a0, uint32_t a1, uint32_t a2, uint32_t a3, uint64_t db, int sc) {
  asm volatile("{\n.reg .pred p;\nsetp.ne.b32 p, %133, 0;\n"
    "wgmma.mma_async.sync.aligned.m64n256k16.f32.bf16.bf16 {%0,%1,%2,%3,%4,%5,%6,%7,%8,%9,%10,%11,%12,%13,%14,%15,%16,%17,%18,%19,%20,%21,%22,%23,%24,%25,%26,%27,%28,%29,%30,%31,%32,%33,%34,%35,%36,%37,%38,%39,%40,%41,%42,%43,%44,%45,%46,%47,%48,%49,%50,%51,%52,%53,%54,%55,%56,%57,%58,%59,%60,%61,%62,%63,%64,%65,%66,%67,%68,%69,%70,%71,%72,%73,%74,%75,%76,%77,%78,%79,%80,%81,%82,%83,%84,%85,%86,%87,%88,%89,%90,%91,%92,%93,%94,%95,%96,%97,%98,%99,%100,%101,%102,%103,%104,%105,%106,%107,%108,%109,%110,%111,%112,%113,%114,%115,%116,%117,%118,%119,%120,%121,%122,%123,%124,%125,%126,%127}, {%128,%129,%130,%131}, %132, p, 1, 1, 1;\n}\n"
    : "+f"(d[0]),"+f"(d[1]),"+f"(d[2]),"+f"(d[3]),"+f"(d[4]),"+f"(d[5]),"+f"(d[6]),"+f"(d[7]),"+f"(d[8]),"+f"(d[9]),"+f"(d[10]),"+f"(d[11]),"+f"(d[12]),"+f"(d[13]),"+f"(d[14]),"+f"(d[15]),"+f"(d[16]),"+f"(d[17]),"+f"(d[18]),"+f"(d[19]),"+f"(d[20]),"+f"(d[21]),"+f"(d[22]),"+f"(d[23]),"+f"(d[24]),"+f"(d[25]),"+f"(d[26]),"+f"(d[27]),"+f"(d[28]),"+f"(d[29]),"+f"(d[30]),"+f"(d[31]),"+f"(d[32]),"+f"(d[33]),"+f"(d[34]),"+f"(d[35]),"+f"(d[36]),"+f"(d[37]),"+f"(d[38]),"+f"(d[39]),"+f"(d[40]),"+f"(d[41]),"+f"(d[42]),"+f"(d[43]),"+f"(d[44]),"+f"(d[45]),"+f"(d[46]),"+f"(d[47]),"+f"(d[48]),"+f"(d[49]),"+f"(d[50]),"+f"(d[51]),"+f"(d[52]),"+f"(d[53]),"+f"(d[54]),"+f"(d[55]),"+f"(d[56]),"+f"(d[57]),"+f"(d[58]),"+f"(d[59]),"+f"(d[60]),"+f"(d[61]),"+f"(d[62]),"+f"(d[63]),"+f"(d[64]),"+f"(d[65]),"+f"(d[66]),"+f"(d[67]),"+f"(d[68]),"+f"(d[69]),"+f"(d[70]),"+f"(d[71]),"+f"(d[72]),"+f"(d[73]),"+f"(d[74]),"+f"(d[75]),"+f"(d[76]),"+f"(d[77]),"+f"(d[78]),"+f"(d[79]),"+f"(d[80]),"+f"(d[81]),"+f"(d[82]),"+f"(d[83]),"+f"(d[84]),"+f"(d[85]),"+f"(d[86]),"+f"(d[87]),"+f"(d[88]),"+f"(d[89]),"+f"(d[90]),"+f"(d[91]),"+f"(d[92]),"+f"(d[93]),"+f"(d[94]),"+f"(d[95]),"+f"(d[96]),"+f"(d[97]),"+f"(d[98]),"+f"(d[99]),"+f"(d[100]),"+f"(d[101]),"+f"(d[102]),"+f"(d[103]),"+f"(d[104]),"+f"(d[105]),"+f"(d[106]),"+f"(d[107]),"+f"(d[108]),"+f"(d[109]),"+f"(d[110]),"+f"(d[111]),"+f"(d[112]),"+f"(d[113]),"+f"(d[114]),"+f"(d[115]),"+f"(d[116]),"+f"(d[117]),"+f"(d[118]),"+f"(d[119]),"+f"(d[120]),"+f"(d[121]),"+f"(d[122]),"+f"(d[123]),"+f"(d[124]),"+f"(d[125]),"+f"(d[126]),"+f"(d[127]) : "r"(a0), "r"(a1), "r"(a2), "r"(a3), "l"(db), "r"(sc));
}
template<int N> __device__ __forceinline__ void wgmma_rsz(float (&d)[N / 2], uint32_t a0, uint32_t a1, uint32_t a2, uint32_t a3, uint64_t db);
template<> __device__ __forceinline__ void wgmma_rsz<8>(float (&d)[4], uint32_t a0, uint32_t a1, uint32_t a2, uint32_t a3, uint64_t db) {
  asm volatile("{\n.reg .pred p;\nsetp.ne.b32 p, 0, 0;\n"
    "wgmma.mma_async.sync.aligned.m64n8k16.f32.bf16.bf16 {%0,%1,%2,%3}, {%4,%5,%6,%7}, %8, p, 1, 1, 1;\n}\n"
    : "=f"(d[0]),"=f"(d[1]),"=f"(d[2]),"=f"(d[3]) : "r"(a0), "r"(a1), "r"(a2), "r"(a3), "l"(db));
}
template<> __device__ __forceinline__ void wgmma_rsz<24>(float (&d)[12], uint32_t a0, uint32_t a1, uint32_t a2, uint32_t a3, uint64_t db) {
  asm volatile("{\n.reg .pred p;\nsetp.ne.b32 p, 0, 0;\n"
    "wgmma.mma_async.sync.aligned.m64n24k16.f32.bf16.bf16 {%0,%1,%2,%3,%4,%5,%6,%7,%8,%9,%10,%11}, {%12,%13,%14,%15}, %16, p, 1, 1, 1;\n}\n"
    : "=f"(d[0]),"=f"(d[1]),"=f"(d[2]),"=f"(d[3]),"=f"(d[4]),"=f"(d[5]),"=f"(d[6]),"=f"(d[7]),"=f"(d[8]),"=f"(d[9]),"=f"(d[10]),"=f"(d[11]) : "r"(a0), "r"(a1), "r"(a2), "r"(a3), "l"(db));
}
template<> __device__ __forceinline__ void wgmma_rsz<64>(float (&d)[32], uint32_t a0, uint32_t a1, uint32_t a2, uint32_t a3, uint64_t db) {
  asm volatile("{\n.reg .pred p;\nsetp.ne.b32 p, 0, 0;\n"
    "wgmma.mma_async.sync.aligned.m64n64k16.f32.bf16.bf16 {%0,%1,%2,%3,%4,%5,%6,%7,%8,%9,%10,%11,%12,%13,%14,%15,%16,%17,%18,%19,%20,%21,%22,%23,%24,%25,%26,%27,%28,%29,%30,%31}, {%32,%33,%34,%35}, %36, p, 1, 1, 1;\n}\n"
    : "=f"(d[0]),"=f"(d[1]),"=f"(d[2]),"=f"(d[3]),"=f"(d[4]),"=f"(d[5]),"=f"(d[6]),"=f"(d[7]),"=f"(d[8]),"=f"(d[9]),"=f"(d[10]),"=f"(d[11]),"=f"(d[12]),"=f"(d[13]),"=f"(d[14]),"=f"(d[15]),"=f"(d[16]),"=f"(d[17]),"=f"(d[18]),"=f"(d[19]),"=f"(d[20]),"=f"(d[21]),"=f"(d[22]),"=f"(d[23]),"=f"(d[24]),"=f"(d[25]),"=f"(d[26]),"=f"(d[27]),"=f"(d[28]),"=f"(d[29]),"=f"(d[30]),"=f"(d[31]) : "r"(a0), "r"(a1), "r"(a2), "r"(a3), "l"(db));
}
template<> __device__ __forceinline__ void wgmma_rsz<192>(float (&d)[96], uint32_t a0, uint32_t a1, uint32_t a2, uint32_t a3, uint64_t db) {
  asm volatile("{\n.reg .pred p;\nsetp.ne.b32 p, 0, 0;\n"
    "wgmma.mma_async.sync.aligned.m64n192k16.f32.bf16.bf16 {%0,%1,%2,%3,%4,%5,%6,%7,%8,%9,%10,%11,%12,%13,%14,%15,%16,%17,%18,%19,%20,%21,%22,%23,%24,%25,%26,%27,%28,%29,%30,%31,%32,%33,%34,%35,%36,%37,%38,%39,%40,%41,%42,%43,%44,%45,%46,%47,%48,%49,%50,%51,%52,%53,%54,%55,%56,%57,%58,%59,%60,%61,%62,%63,%64,%65,%66,%67,%68,%69,%70,%71,%72,%73,%74,%75,%76,%77,%78,%79,%80,%81,%82,%83,%84,%85,%86,%87,%88,%89,%90,%91,%92,%93,%94,%95}, {%96,%97,%98,%99}, %100, p, 1, 1, 1;\n}\n"
    : "=f"(d[0]),"=f"(d[1]),"=f"(d[2]),"=f"(d[3]),"=f"(d[4]),"=f"(d[5]),"=f"(d[6]),"=f"(d[7]),"=f"(d[8]),"=f"(d[9]),"=f"(d[10]),"=f"(d[11]),"=f"(d[12]),"=f"(d[13]),"=f"(d[14]),"=f"(d[15]),"=f"(d[16]),"=f"(d[17]),"=f"(d[18]),"=f"(d[19]),"=f"(d[20]),"=f"(d[21]),"=f"(d[22]),"=f"(d[23]),"=f"(d[24]),"=f"(d[25]),"=f"(d[26]),"=f"(d[27]),"=f"(d[28]),"=f"(d[29]),"=f"(d[30]),"=f"(d[31]),"=f"(d[32]),"=f"(d[33]),"=f"(d[34]),"=f"(d[35]),"=f"(d[36]),"=f"(d[37]),"=f"(d[38]),"=f"(d[39]),"=f"(d[40]),"=f"(d[41]),"=f"(d[42]),"=f"(d[43]),"=f"(d[44]),"=f"(d[45]),"=f"(d[46]),"=f"(d[47]),"=f"(d[48]),"=f"(d[49]),"=f"(d[50]),"=f"(d[51]),"=f"(d[52]),"=f"(d[53]),"=f"(d[54]),"=f"(d[55]),"=f"(d[56]),"=f"(d[57]),"=f"(d[58]),"=f"(d[59]),"=f"(d[60]),"=f"(d[61]),"=f"(d[62]),"=f"(d[63]),"=f"(d[64]),"=f"(d[65]),"=f"(d[66]),"=f"(d[67]),"=f"(d[68]),"=f"(d[69]),"=f"(d[70]),"=f"(d[71]),"=f"(d[72]),"=f"(d[73]),"=f"(d[74]),"=f"(d[75]),"=f"(d[76]),"=f"(d[77]),"=f"(d[78]),"=f"(d[79]),"=f"(d[80]),"=f"(d[81]),"=f"(d[82]),"=f"(d[83]),"=f"(d[84]),"=f"(d[85]),"=f"(d[86]),"=f"(d[87]),"=f"(d[88]),"=f"(d[89]),"=f"(d[90]),"=f"(d[91]),"=f"(d[92]),"=f"(d[93]),"=f"(d[94]),"=f"(d[95]) : "r"(a0), "r"(a1), "r"(a2), "r"(a3), "l"(db));
}
template<> __device__ __forceinline__ void wgmma_rsz<256>(float (&d)[128], uint32_t a0, uint32_t a1, uint32_t a2, uint32_t a3, uint64_t db) {
  asm volatile("{\n.reg .pred p;\nsetp.ne.b32 p, 0, 0;\n"
    "wgmma.mma_async.sync.aligned.m64n256k16.f32.bf16.bf16 {%0,%1,%2,%3,%4,%5,%6,%7,%8,%9,%10,%11,%12,%13,%14,%15,%16,%17,%18,%19,%20,%21,%22,%23,%24,%25,%26,%27,%28,%29,%30,%31,%32,%33,%34,%35,%36,%37,%38,%39,%40,%41,%42,%43,%44,%45,%46,%47,%48,%49,%50,%51,%52,%53,%54,%55,%56,%57,%58,%59,%60,%61,%62,%63,%64,%65,%66,%67,%68,%69,%70,%71,%72,%73,%74,%75,%76,%77,%78,%79,%80,%81,%82,%83,%84,%85,%86,%87,%88,%89,%90,%91,%92,%93,%94,%95,%96,%97,%98,%99,%100,%101,%102,%103,%104,%105,%106,%107,%108,%109,%110,%111,%112,%113,%114,%115,%116,%117,%118,%119,%120,%121,%122,%123,%124,%125,%126,%127}, {%128,%129,%130,%131}, %132, p, 1, 1, 1;\n}\n"
    : "=f"(d[0]),"=f"(d[1]),"=f"(d[2]),"=f"(d[3]),"=f"(d[4]),"=f"(d[5]),"=f"(d[6]),"=f"(d[7]),"=f"(d[8]),"=f"(d[9]),"=f"(d[10]),"=f"(d[11]),"=f"(d[12]),"=f"(d[13]),"=f"(d[14]),"=f"(d[15]),"=f"(d[16]),"=f"(d[17]),"=f"(d[18]),"=f"(d[19]),"=f"(d[20]),"=f"(d[21]),"=f"(d[22]),"=f"(d[23]),"=f"(d[24]),"=f"(d[25]),"=f"(d[26]),"=f"(d[27]),"=f"(d[28]),"=f"(d[29]),"=f"(d[30]),"=f"(d[31]),"=f"(d[32]),"=f"(d[33]),"=f"(d[34]),"=f"(d[35]),"=f"(d[36]),"=f"(d[37]),"=f"(d[38]),"=f"(d[39]),"=f"(d[40]),"=f"(d[41]),"=f"(d[42]),"=f"(d[43]),"=f"(d[44]),"=f"(d[45]),"=f"(d[46]),"=f"(d[47]),"=f"(d[48]),"=f"(d[49]),"=f"(d[50]),"=f"(d[51]),"=f"(d[52]),"=f"(d[53]),"=f"(d[54]),"=f"(d[55]),"=f"(d[56]),"=f"(d[57]),"=f"(d[58]),"=f"(d[59]),"=f"(d[60]),"=f"(d[61]),"=f"(d[62]),"=f"(d[63]),"=f"(d[64]),"=f"(d[65]),"=f"(d[66]),"=f"(d[67]),"=f"(d[68]),"=f"(d[69]),"=f"(d[70]),"=f"(d[71]),"=f"(d[72]),"=f"(d[73]),"=f"(d[74]),"=f"(d[75]),"=f"(d[76]),"=f"(d[77]),"=f"(d[78]),"=f"(d[79]),"=f"(d[80]),"=f"(d[81]),"=f"(d[82]),"=f"(d[83]),"=f"(d[84]),"=f"(d[85]),"=f"(d[86]),"=f"(d[87]),"=f"(d[88]),"=f"(d[89]),"=f"(d[90]),"=f"(d[91]),"=f"(d[92]),"=f"(d[93]),"=f"(d[94]),"=f"(d[95]),"=f"(d[96]),"=f"(d[97]),"=f"(d[98]),"=f"(d[99]),"=f"(d[100]),"=f"(d[101]),"=f"(d[102]),"=f"(d[103]),"=f"(d[104]),"=f"(d[105]),"=f"(d[106]),"=f"(d[107]),"=f"(d[108]),"=f"(d[109]),"=f"(d[110]),"=f"(d[111]),"=f"(d[112]),"=f"(d[113]),"=f"(d[114]),"=f"(d[115]),"=f"(d[116]),"=f"(d[117]),"=f"(d[118]),"=f"(d[119]),"=f"(d[120]),"=f"(d[121]),"=f"(d[122]),"=f"(d[123]),"=f"(d[124]),"=f"(d[125]),"=f"(d[126]),"=f"(d[127]) : "r"(a0), "r"(a1), "r"(a2), "r"(a3), "l"(db));
}
template<int N> __device__ __forceinline__ void wgmma_ra(float (&d)[N / 2], const uint4& a, uint64_t db, bool acc) {
  if (acc) wgmma_rs<N>(d, a.x, a.y, a.z, a.w, db, 1); else wgmma_rsz<N>(d, a.x, a.y, a.z, a.w, db);
}

__device__ __forceinline__ uint32_t smem_u32(const void* p) { return (uint32_t)__cvta_generic_to_shared(p); }
__device__ __forceinline__ void mbar_init(uint32_t bar, uint32_t cnt) { asm volatile("mbarrier.init.shared::cta.b64 [%0], %1;" ::"r"(bar), "r"(cnt)); }
__device__ __forceinline__ void mbar_expect_tx(uint32_t bar, uint32_t bytes) { asm volatile("mbarrier.arrive.expect_tx.shared::cta.b64 _, [%0], %1;" ::"r"(bar), "r"(bytes) : "memory"); }
__device__ __forceinline__ void mbar_arrive(uint32_t bar) { asm volatile("mbarrier.arrive.shared::cta.b64 _, [%0];" ::"r"(bar) : "memory"); }
__device__ __forceinline__ void mbar_arrive_remote(uint32_t rbar) { asm volatile("mbarrier.arrive.shared::cluster.b64 _, [%0];" ::"r"(rbar) : "memory"); }
__device__ __forceinline__ void mbar_wait(uint32_t bar, uint32_t parity) {
  asm volatile(
      "{\n.reg .pred p;\n.reg .u32 c;\nmov.u32 c, 0;\nLAB_WAIT:\nmbarrier.try_wait.parity.shared::cta.b64 p, [%0], %1;\n@p bra DONE;\n"
      "add.u32 c, c, 1;\nsetp.lt.u32 p, c, 1000000;\n@p bra LAB_WAIT;\ntrap;\nDONE:\n}\n" ::"r"(bar), "r"(parity) : "memory");
}
__device__ __forceinline__ void mbar_wait_c(uint32_t bar, uint32_t parity) {
  asm volatile("{\n.reg .pred p;\nLAB_WAIT:\nmbarrier.try_wait.parity.shared::cta.b64 p, [%0], %1;\n@!p bra LAB_WAIT;\n}\n" ::"r"(bar), "r"(parity) : "memory");
}
__device__ __forceinline__ void wtma2d(uint32_t dst, const CUtensorMap* m, int c0, int c1, uint32_t bar, uint64_t pol) {
  asm volatile("cp.async.bulk.tensor.2d.shared::cluster.global.mbarrier::complete_tx::bytes.multicast::cluster.L2::cache_hint [%0], [%1, {%3, %4}], [%2], %5, %6;"
               ::"r"(dst), "l"(m), "r"(bar), "r"(c0), "r"(c1), "h"((uint16_t)3), "l"(pol) : "memory");
}
__device__ __forceinline__ void wtma3d(uint32_t dst, const CUtensorMap* m, int c0, int c1, int c2, uint32_t bar, uint64_t pol) {
  asm volatile("cp.async.bulk.tensor.3d.shared::cluster.global.mbarrier::complete_tx::bytes.multicast::cluster.L2::cache_hint [%0], [%1, {%3, %4, %5}], [%2], %6, %7;"
               ::"r"(dst), "l"(m), "r"(bar), "r"(c0), "r"(c1), "r"(c2), "h"((uint16_t)3), "l"(pol) : "memory");
}
__device__ __forceinline__ void tma3d(uint32_t dst, const CUtensorMap* m, int c0, int c1, int c2, uint32_t bar) {
  asm volatile("cp.async.bulk.tensor.3d.shared::cluster.global.mbarrier::complete_tx::bytes [%0], [%1, {%3, %4, %5}], [%2];"
               ::"r"(dst), "l"(m), "r"(bar), "r"(c0), "r"(c1), "r"(c2) : "memory");
}
__device__ __forceinline__ void tma_store3d(const CUtensorMap* m, uint32_t src, int c0, int c1, int c2) {
  asm volatile("cp.async.bulk.tensor.3d.global.shared::cta.bulk_group [%0, {%2, %3, %4}], [%1];" ::"l"(m), "r"(src), "r"(c0), "r"(c1), "r"(c2) : "memory");
}
__device__ __forceinline__ void prefetch_l2(const void* p, uint32_t bytes) { asm volatile("cp.async.bulk.prefetch.L2.global [%0], %1;" ::"l"(p), "r"(bytes) : "memory"); }
__device__ __forceinline__ uint64_t policy_evict_first() { uint64_t p; asm volatile("createpolicy.fractional.L2::evict_first.b64 %0, 1.0;" : "=l"(p)); return p; }
__device__ __forceinline__ uint64_t policy_evict_normal() { uint64_t p; asm volatile("createpolicy.fractional.L2::evict_normal.b64 %0, 1.0;" : "=l"(p)); return p; }
__device__ __forceinline__ void bulk_commit() { asm volatile("cp.async.bulk.commit_group;" ::: "memory"); }
__device__ __forceinline__ void bulk_wait_all() { asm volatile("cp.async.bulk.wait_group 0;" ::: "memory"); }
__device__ __forceinline__ void fence_async_smem() { asm volatile("fence.proxy.async.shared::cta;" ::: "memory"); }
__device__ __forceinline__ bool elect_one() {
  uint32_t p;
  asm volatile("{\n.reg .pred P;\nelect.sync _|P, 0xffffffff;\nselp.u32 %0, 1, 0, P;\n}\n" : "=r"(p));
  return p;
}
__device__ __forceinline__ void wg_fence() { asm volatile("wgmma.fence.sync.aligned;" ::: "memory"); }
__device__ __forceinline__ void wg_commit() { asm volatile("wgmma.commit_group.sync.aligned;" ::: "memory"); }
template <int n> __device__ __forceinline__ void wg_wait() { asm volatile("wgmma.wait_group.sync.aligned %0;" ::"n"(n) : "memory"); }
__device__ __forceinline__ void wg_bar(int w) { asm volatile("bar.sync %0, 128;" ::"r"(w + 1) : "memory"); }
__device__ __forceinline__ void cluster_sync() { asm volatile("barrier.cluster.arrive.relaxed.aligned;\nbarrier.cluster.wait.aligned;" ::: "memory"); }
__device__ __forceinline__ constexpr uint64_t desc_hi(uint32_t lbo, uint32_t sbo, int sw) {
  return ((uint64_t)(lbo >> 4) << 16) | ((uint64_t)(sbo >> 4) << 32) | ((uint64_t)sw << 62);
}
__device__ __forceinline__ void fence_gpu() { asm volatile("fence.acq_rel.gpu;" ::: "memory"); }
__device__ __forceinline__ uint32_t ld_relaxed(const uint32_t* p) { uint32_t v; asm volatile("ld.relaxed.gpu.global.u32 %0, [%1];" : "=r"(v) : "l"(p) : "memory"); return v; }
__device__ __forceinline__ uint4 ld_relaxed4(const uint4* p) {
  uint4 v; asm volatile("ld.relaxed.gpu.global.v4.u32 {%0,%1,%2,%3}, [%4];" : "=r"(v.x), "=r"(v.y), "=r"(v.z), "=r"(v.w) : "l"(p) : "memory"); return v;
}
__device__ __forceinline__ uint2 ld_relaxed2(const uint2* p) {
  uint2 v; asm volatile("ld.relaxed.gpu.global.v2.u32 {%0,%1}, [%2];" : "=r"(v.x), "=r"(v.y) : "l"(p) : "memory"); return v;
}
__device__ __forceinline__ void st_relaxed(uint32_t* p, uint32_t a) { asm volatile("st.relaxed.gpu.global.u32 [%0], %1;" ::"l"(p), "r"(a) : "memory"); }
__device__ __forceinline__ void st_relaxed4(uint4* p, uint32_t a, uint32_t b, uint32_t c, uint32_t d) {
  asm volatile("st.relaxed.gpu.global.v4.u32 [%0], {%1,%2,%3,%4};" ::"l"(p), "r"(a), "r"(b), "r"(c), "r"(d) : "memory");
}
__device__ __forceinline__ void st_relaxed2(uint2* p, uint32_t a, uint32_t b) {
  asm volatile("st.relaxed.gpu.global.v2.u32 [%0], {%1,%2};" ::"l"(p), "r"(a), "r"(b) : "memory");
}
__device__ __forceinline__ void red4(uint4* p, uint32_t a, uint32_t b, uint32_t c, uint32_t d) {
  asm volatile("red.relaxed.gpu.global.add.noftz.v4.bf16x2 [%0], {%1,%2,%3,%4};" ::"l"(p), "r"(a), "r"(b), "r"(c), "r"(d) : "memory");
}
__device__ __forceinline__ void red2(uint2* p, uint32_t a, uint32_t b) {
  asm volatile("red.relaxed.gpu.global.add.noftz.v2.bf16x2 [%0], {%1,%2};" ::"l"(p), "r"(a), "r"(b) : "memory");
}
constexpr int SPIN_MAX = 1 << 21;
__device__ __forceinline__ uint32_t pack_bf16(float lo, float hi) { uint32_t r; asm("cvt.rn.bf16x2.f32 %0, %1, %2;" : "=r"(r) : "f"(hi), "f"(lo)); return r; }
__device__ __forceinline__ float bf_lo(uint32_t v) { return __uint_as_float(v << 16); }
__device__ __forceinline__ float bf_hi(uint32_t v) { return __uint_as_float(v & 0xffff0000u); }
__device__ __forceinline__ float2 lds64(uint32_t a) { float2 v; asm volatile("ld.shared.v2.f32 {%0,%1}, [%2];" : "=f"(v.x), "=f"(v.y) : "r"(a)); return v; }
__device__ __forceinline__ void sts64f(uint32_t a, float x, float y) { asm volatile("st.shared.v2.f32 [%0], {%1,%2};" ::"r"(a), "f"(x), "f"(y) : "memory"); }
__device__ __forceinline__ void sts32(uint32_t a, uint32_t x) { asm volatile("st.volatile.shared.b32 [%0], %1;" ::"r"(a), "r"(x) : "memory"); }
__device__ __forceinline__ void gate(uint32_t a, int need) {
#pragma unroll 1
  for (int it = 0; it < SPIN_MAX; it++) {
    int v; asm volatile("ld.volatile.shared.b32 %0, [%1];" : "=r"(v) : "r"(a) : "memory");
    if (v >= need) break;
    __nanosleep(32);
  }
}
__device__ __forceinline__ void sts128(uint32_t a, uint32_t x, uint32_t y, uint32_t z, uint32_t u) { asm volatile("st.shared.v4.b32 [%0], {%1,%2,%3,%4};" ::"r"(a), "r"(x), "r"(y), "r"(z), "r"(u) : "memory"); }
__device__ __forceinline__ uint4 lds128(uint32_t a) { uint4 v; asm volatile("ld.shared.v4.u32 {%0,%1,%2,%3}, [%4];" : "=r"(v.x), "=r"(v.y), "=r"(v.z), "=r"(v.w) : "r"(a) : "memory"); return v; }
__device__ __forceinline__ uint32_t hadd2(uint32_t a, uint32_t b) { uint32_t r; asm("add.rn.bf16x2 %0, %1, %2;" : "=r"(r) : "r"(a), "r"(b)); return r; }
__device__ __forceinline__ void stsm4(uint32_t a, uint32_t r0, uint32_t r1, uint32_t r2, uint32_t r3) {
  asm volatile("stmatrix.sync.aligned.m8n8.x4.shared.b16 [%0], {%1,%2,%3,%4};" ::"r"(a), "r"(r0), "r"(r1), "r"(r2), "r"(r3) : "memory");
}
__device__ __forceinline__ void stsm2(uint32_t a, uint32_t r0, uint32_t r1) {
  asm volatile("stmatrix.sync.aligned.m8n8.x2.shared.b16 [%0], {%1,%2};" ::"r"(a), "r"(r0), "r"(r1) : "memory");
}
__device__ __forceinline__ uint4 ldsm4(uint32_t a) {
  uint4 r; asm volatile("ldmatrix.sync.aligned.m8n8.x4.shared.b16 {%0,%1,%2,%3}, [%4];" : "=r"(r.x), "=r"(r.y), "=r"(r.z), "=r"(r.w) : "r"(a) : "memory"); return r;
}
__device__ __forceinline__ uint32_t movm(uint32_t a) { uint32_t r; asm("movmatrix.sync.aligned.m8n8.trans.b16 %0, %1;" : "=r"(r) : "r"(a)); return r; }
__device__ __forceinline__ void mma16816z(float (&d)[4], uint32_t a0, uint32_t a1, uint32_t a2, uint32_t a3, uint32_t b0, uint32_t b1) {
  asm("mma.sync.aligned.m16n8k16.row.col.f32.bf16.bf16.f32 {%0,%1,%2,%3}, {%4,%5,%6,%7}, {%8,%9}, {%10,%10,%10,%10};"
      : "=f"(d[0]), "=f"(d[1]), "=f"(d[2]), "=f"(d[3]) : "r"(a0), "r"(a1), "r"(a2), "r"(a3), "r"(b0), "r"(b1), "f"(0.f));
}
__device__ __forceinline__ void mma1688(float (&d)[4], uint32_t a0, uint32_t a1, uint32_t b0) {
  asm("mma.sync.aligned.m16n8k8.row.col.f32.bf16.bf16.f32 {%0,%1,%2,%3}, {%4,%5}, {%6}, {%0,%1,%2,%3};"
      : "+f"(d[0]), "+f"(d[1]), "+f"(d[2]), "+f"(d[3]) : "r"(a0), "r"(a1), "r"(b0));
}
__device__ __forceinline__ float quad_sum(float v) { v += __shfl_xor_sync(0xffffffffu, v, 1); v += __shfl_xor_sync(0xffffffffu, v, 2); return v; }
__device__ __forceinline__ float quad_max(float v) { v = fmaxf(v, __shfl_xor_sync(0xffffffffu, v, 1)); v = fmaxf(v, __shfl_xor_sync(0xffffffffu, v, 2)); return v; }
__device__ __forceinline__ float rcp(float x) { float r; asm("rcp.approx.ftz.f32 %0, %1;" : "=f"(r) : "f"(x)); return r; }
__device__ __forceinline__ float rsq(float x) { float r; asm("rsqrt.approx.ftz.f32 %0, %1;" : "=f"(r) : "f"(x)); return r; }
__device__ __forceinline__ float ex2(float x) { float r; asm("ex2.approx.ftz.f32 %0, %1;" : "=f"(r) : "f"(x)); return r; }
__device__ __forceinline__ uint32_t tagged(uint32_t v, uint32_t tag) { return (v & ~1u) | tag; }

__device__ __forceinline__ int group_k0(int g) { return g < 16 ? 64 * (g & 7) + 4 * (g & 8) : 32 * g; }
__device__ __forceinline__ uint32_t xin_off(int c, int w) { return SM_X + (2 * c + w + (2 * c + w < 9 ? 9 : -9)) * 8192; }
__device__ __forceinline__ uint32_t xin_bar(int c) { return BAR_FULLX + 8 * (c < 8 ? c ^ 4 : c); }
__device__ __forceinline__ constexpr uint32_t qkv_xslot(int g) { return (0x5140762u >> (4 * (g - 5))) & 15; }

struct Cons {
  uint32_t sb;
  uint32_t rem;
  uint32_t sB, mB;
  uint32_t mX;
  bool elect;
  __device__ __forceinline__ void release2(uint32_t bar) const { if (elect) { mbar_arrive(sb + bar); mbar_arrive_remote(rem + bar); } }
  __device__ __forceinline__ uint32_t nextB(uint32_t& prev) {
    mbar_wait_c(sb + BAR_FULLB + sB, mB);
    const uint32_t a = (((sb & 0x3FFFF) + SM_B) >> 4) + sB * (BSLOT / 128);
    prev = sB == 0 ? 32 : sB - 8;
    sB += 8;
    if (sB == 40) { sB = 0; mB ^= 1; }
    return a;
  }
  __device__ __forceinline__ void progress(uint32_t v) const { if (elect) sts32(sb + SM_PROG + (threadIdx.x >> 5), v); }
  __device__ __forceinline__ void releaseLastB() const { release2(BAR_EMPTYB + (sB == 0 ? 32 : sB - 8)); }
};

template <bool QKV, class Pre, class Mma>
__device__ __forceinline__ float2 ln_gemm(Cons& c, Group* G, const float (&v)[36], uint32_t (&p)[18], bool direct, int w, int st0, int j, int t,
                                          uint32_t tag, uint32_t stag, Pre&& pre, Mma&& mma) {
  constexpr int NBUF = 5;
  const uint32_t pbase = direct ? 0 : 32;
  uint4* const box = G->act[QKV ? 0 : 2];
  uint4 x[NBUF][2];
  const uint4* src = box + t;
  uint32_t xa = c.sb + w * 8192 + (t >> 5) * 2048 + (t & 7) * 128 + (((t >> 3) & 3) ^ (t & 7)) * 16;
  asm volatile("" : "+l"(src), "+r"(xa));
  auto load = [&](int g) { x[g % NBUF][0] = ld_relaxed4(src + 2 * g * 128); x[g % NBUF][1] = ld_relaxed4(src + (2 * g + 1) * 128); };
  auto load_in = [&](int g) {
    if (!(g & 1)) mbar_wait_c(c.sb + xin_bar(g >> 1), 0);
    if (g == 8) xa -= w * 8 * XSLOT;
    if (g == 10) xa += w * 8 * XSLOT;
    if (g == 16) xa = c.sb + w * 8192 + (t >> 5) * 2048 + (t & 15) * 128 + (((t >> 4) & 1) ^ (t & 7)) * 16;
    const uint32_t a = xa ^ (64 * (g & 1));
    x[g % NBUF][0] = ldsm4(a + xin_off(g >> 1, 0));
    x[g % NBUF][1] = ldsm4((g < 16 ? a + 1024 : a ^ 32) + xin_off(g >> 1, 0));
  };
#pragma unroll
  for (int i = 0; i < 18; i++) p[i] = pack_bf16(v[2 * i], v[2 * i + 1]);
  uint4* const d = box + 2 * j * 128 + t;
  if (!direct) {
#pragma unroll
    for (int i = 0; i < 2; i++) st_relaxed4(d + i * 128, tagged(p[i], tag), p[i + 2], p[i + 4], p[i + 6]);
  }
  float s0 = v[0] + v[1], s1 = v[2] + v[3];
#pragma unroll
  for (int i = 1; i < 9; i++) { s0 += v[4 * i] + v[4 * i + 1]; s1 += v[4 * i + 2] + v[4 * i + 3]; }
  s0 = quad_sum(s0); s1 = quad_sum(s1);
  const uint32_t s0t = (__float_as_uint(s0) & ~3u) | stag;
  if ((t & 3) == 0) st_relaxed2(G->sum + st0 + 8 * j, s0t, __float_as_uint(s1));
  const int sq = st0 + 16 * (t & 3);
  uint2 sa, sc;
  auto poll = [&] { sa = ld_relaxed2(G->sum + sq); sc = ld_relaxed2(G->sum + sq + 8); };
  const bool spec = SPEC && (QKV ? !direct : !tag);
#pragma unroll
  for (int g = 0; g < NBUF; g++) x[g][0] = x[g][1] = make_uint4(tag ^ 1, 0, 0, 0);
  if (POLLFIRST) poll();
  if (spec) {
#pragma unroll
    for (int g = 0; g < NFIRST; g++) load(g);
  }
  if (!POLLFIRST) poll();
  float d0 = 0.f, d1 = 0.f;
  {
    const float m0 = s0 * (1.f / 72), m1 = s1 * (1.f / 72);
#pragma unroll
    for (int i = 0; i < 9; i++) {
      float a = v[4 * i] - m0, b = v[4 * i + 1] - m0; d0 = fmaf(a, a, fmaf(b, b, d0));
      a = v[4 * i + 2] - m1; b = v[4 * i + 3] - m1; d1 = fmaf(a, a, fmaf(b, b, d1));
    }
    d0 = quad_sum(d0); d1 = quad_sum(d1);
  }
  pre(0);
  while (__any_sync(0xffffffffu, ((sa.x ^ stag) | (sc.x ^ stag)) & 3)) poll();
  c.progress(QKV ? pbase + 1 : 53 - 32 * tag);
  if (!direct) {
#pragma unroll
    for (int g = 0; g < NFIRST; g++)
      if (__any_sync(0xffffffffu, ((x[g][0].x ^ tag) | (x[g][1].x ^ tag)) & 1)) load(g);
#pragma unroll
    for (int i = 0; i < 2; i++) st_relaxed4(d + (16 + i) * 128, tagged(p[8 + i], tag), p[10 + i], p[12 + i], p[14 + i]);
    st_relaxed2((uint2*)(box + (32 + (j >> 1)) * 128 + t) + (j & 1), tagged(p[16], tag), p[17]);
#pragma unroll
    for (int g = NFIRST; g < NBUF; g++) load(g);
  }
  if ((t & 3) == 0) st_relaxed4(G->m2 + st0 + 8 * j, s0t, __float_as_uint(s1), __float_as_uint(d0), __float_as_uint(d1));
  const float m0 = quad_sum(__uint_as_float(sa.x) + __uint_as_float(sc.x)) * (-1.f / 576), m1 = quad_sum(__uint_as_float(sa.y) + __uint_as_float(sc.y)) * (-1.f / 576);
  const uint32_t nm0 = pack_bf16(m0, m0), nm1 = pack_bf16(m1, m1);
  pre(1);
  uint4 u0, u1;
#pragma unroll
  for (int g = 0; g < 18; g++) {
    uint4 &a = x[g % NBUF][0], &b = x[g % NBUF][1];
    if (direct) load_in(g);
    else while (__any_sync(0xffffffffu, ((a.x ^ tag) | (b.x ^ tag) | (g < 16 ? 0u : (a.z ^ tag) | (b.z ^ tag))) & 1)) load(g);
    const bool rows = g < 16;
    const uint4 f0 = make_uint4(hadd2(a.x, nm0), hadd2(rows ? b.x : a.y, nm1), hadd2(rows ? a.y : a.z, nm0), hadd2(rows ? b.y : a.w, nm1));
    const uint4 f1 = make_uint4(hadd2(rows ? a.z : b.x, nm0), hadd2(rows ? b.z : b.y, nm1), hadd2(rows ? a.w : b.z, nm0), hadd2(b.w, nm1));
    if (g + NBUF < 18 && !direct) load(g + NBUF);
    if (g == 13) { u0 = ld_relaxed4(G->m2 + sq); u1 = ld_relaxed4(G->m2 + sq + 8); }
    uint32_t prev = c.sB == 0 ? 32 : c.sB - 8, bb;
    if (QKV && g >= 5 && g < 12 && !direct) {
      mbar_wait_c(c.sb + BAR_FULLX + 8 * qkv_xslot(g), (c.mX >> qkv_xslot(g)) & 1);
      bb = ((c.sb & 0x3FFFF) + SM_X + qkv_xslot(g) * XSLOT) >> 4;
    } else {
      bb = c.nextB(prev);
    }
    mma(g, bb, f0, f1);
    wg_wait<1>();
    if (g > 0 && !(QKV && g > 5 && g <= 12 && !direct)) c.release2(BAR_EMPTYB + prev);
    if (QKV && g > 0 && g < 15) c.progress(pbase + 1 + g);
    if (QKV && g == 13 && t < 4) { mbar_arrive(c.sb + BAR_EMPTYX + 32 + 8 * t); mbar_arrive_remote(c.rem + BAR_EMPTYX + 32 + 8 * t); }
  }
  if (QKV) c.mX ^= direct ? 0xff : 0xf7;
  if (direct) {
    asm volatile("bar.sync 6, 256;" ::: "memory");
    c.release2(BAR_EMPTYX + 24);
  }
  while (__any_sync(0xffffffffu, ((u0.x ^ stag) | (u1.x ^ stag)) & 3)) { u0 = ld_relaxed4(G->m2 + sq); u1 = ld_relaxed4(G->m2 + sq + 8); }
  float e0 = fmaf(__uint_as_float(u0.x), 1.f / 72, m0), e1 = fmaf(__uint_as_float(u1.x), 1.f / 72, m0);
  const float v0 = quad_sum(fmaf(72.f, fmaf(e0, e0, e1 * e1), __uint_as_float(u0.z) + __uint_as_float(u1.z)));
  e0 = fmaf(__uint_as_float(u0.y), 1.f / 72, m1); e1 = fmaf(__uint_as_float(u1.y), 1.f / 72, m1);
  const float v1 = quad_sum(fmaf(72.f, fmaf(e0, e0, e1 * e1), __uint_as_float(u0.w) + __uint_as_float(u1.w)));
  float2 r = make_float2(rsq(fmaf(v0, 1.f / 576, 1e-5f)), rsq(fmaf(v1, 1.f / 576, 1e-5f)));
  asm volatile("" : "+f"(r.x), "+f"(r.y));
  wg_wait<0>();
  c.releaseLastB();
  return r;
}

template <int NB, int OFF>
__device__ __forceinline__ void glu(const float (&a)[128], uint32_t (&h)[144]) {
#pragma unroll
  for (int b = 0; b < 2 * NB; b++) h[OFF + b] = pack_bf16(a[2 * b] * a[4 * NB + 2 * b], a[2 * b + 1] * a[4 * NB + 2 * b + 1]);
}

__global__ void __cluster_dims__(2, 1, 1) __launch_bounds__(384, 1)
fused_kernel(const __nv_bfloat16* __restrict__ x_in, Group* ws, const char* __restrict__ wqkv,
             const char* __restrict__ wg, const char* __restrict__ wu, const char* __restrict__ wd, const __grid_constant__ Maps maps,
             const char* __restrict__ wo) {
  extern __shared__ __align__(1024) uint8_t smem_raw[];
  const uint32_t sb = smem_u32(smem_raw);
  const int warp = __shfl_sync(0xffffffffu, threadIdx.x >> 5, 0);
  const int lane = threadIdx.x & 31;
  const int rank = blockIdx.x & 1;
  int lb = blockIdx.x;
  if (GPCMAP) {
    const int cl = blockIdx.x >> 1, u = cl - 36;
    lb = (cl < 4 ? cl : cl < 36 ? 8 * ((cl - 4) & 7) + ((cl - 4) >> 3) + (((cl - 4) & 7) ? 0 : 4) : 8 * (1 + u % 7) + 4 + u / 7) * 2 + rank;
  }
#define CTA_J(b) (((b) >> 1) & 7)
#define CTA_RB(b) ((((b) >> 4) << 1) | ((b) & 1))
  const int j = CTA_J(lb), rb = CTA_RB(lb);

  PROF(23);
  if (warp >= 8) {
    asm volatile("setmaxnreg.dec.sync.aligned.u32 " STR(REGS_P) ";");
    auto x_chunk = [&](int cc) {
      mbar_expect_tx(sb + xin_bar(cc), 16384);
      tma3d(sb + xin_off(cc, 0), &maps.x, 64 * cc, 0, 64 * rb, sb + xin_bar(cc));
      tma3d(sb + xin_off(cc, 1), &maps.x, 64 * cc, 1, 64 * rb, sb + xin_bar(cc));
    };
    if (elect_one()) {
      if (warp == 8) { if (PFMODE & 1) prefetch_l2((const char*)x_in + (8 * rb + j) * 18432, 18432); }
      else asm volatile("prefetch.tensormap [%0];" ::"l"(&maps.x + (warp - 9)) : "memory");
#pragma unroll
      for (int i = 0; i < 9; i++) mbar_init(sb + SM_BAR + 72 * (warp - 8) + 8 * i, warp < 10 ? 1 : 4);
      sts32(sb + SM_PROG + 4 * (warp - 8), 0);
      asm volatile("fence.mbarrier_init.release.cluster;" ::: "memory");
    }
    __syncwarp();
    if (warp == 8) PROFX(53);
    asm volatile("barrier.cluster.arrive.relaxed.aligned;" ::: "memory");
    if (warp == 9 && elect_one()) { fence_async_smem(); x_chunk(j); x_chunk(8); }
    if ((PFMODE & 2) && warp == 11 && elect_one()) prefetch_l2(wqkv + blockIdx.x * (15552 / PFQ), 15552 / PFQ);
    __syncwarp();
    if (warp == 9) PROFX(54);
    asm volatile("barrier.cluster.wait.aligned;" ::: "memory");
    if (warp == 8) PROFX(56);
    const uint64_t pol = W_POLICY(), pola = A_POLICY();
    auto qkv_group = [&](int k, uint32_t dst, uint32_t bar) {
      wtma3d(dst + rank * 8192, &maps.qm, 72 * j, k + 16 * rank, 0, bar, pola);
      wtma3d(dst + rank * 8192 + 6144, &maps.qc, 72 * j + 64, k + 16 * rank, 0, bar, pola);
    };
    auto qkv_gate = [&](int g) { if (g >= 8) gate(sb + SM_PROG, 33 + ((g - 8) * 23 >> 4)); };
    if (warp == 8) {
      uint32_t s = 0, ph = 1;
      auto slot = [&](uint32_t bytes, auto&& issue) {
        const uint32_t bar = sb + BAR_FULLB + 8 * s;
        mbar_wait(sb + BAR_EMPTYB + 8 * s, ph);
        if (elect_one()) {
          mbar_expect_tx(bar, bytes);
          issue(sb + SM_B + s * BSLOT, bar);
        }
        if (++s == 5) { s = 0; ph ^= 1; }
      };
#pragma unroll 1
      for (int layer = 0; layer < NLAYERS; layer++) {
#pragma unroll 1
        for (int g = 0; g < 18; g += layer && g == 4 ? 8 : 1) {
          if (layer) qkv_gate(g);
          else if (g >= QD && g < 5) mbar_wait(sb + BAR_FULLB + 8 * (g - QD), 0);
          slot(2 * 6912, [&](uint32_t dst, uint32_t bar) { qkv_group(layer ? group_k0(g) : 32 * g, dst, bar); });
        }
        gate(sb + SM_PROG, 32 * layer + 20);
        gate(sb + SM_PROG + 4, 32 * layer + 20);
#pragma unroll 1
        for (int t = 0; t < 5; t++) {
          const CUtensorMap* m = &maps.g + (t < 3 ? rank : 2 + rank);
          const int c2 = t < 3 ? 9 * j + 2 * t : 18 * j + 3 + 3 * t;
          const uint32_t half = t < 3 ? 8192 : 6144;
#pragma unroll 1
          for (int g = 0; g < 18; g++)
            slot(2 * half, [&](uint32_t dst, uint32_t bar) { wtma3d(dst + rank * half, m, 0, group_k0(g), c2, bar, pol); });
        }
      }
    } else if (warp == 9) {
      uint32_t mE = 0;
      {
        int p1 = 8, p2 = j;
#pragma unroll 1
        for (int cc = 0; cc < 8; cc++) {
          if (cc == j) continue;
          mbar_wait(sb + xin_bar(p2), 0);
          gate(sb + SM_PROG, 2 * cc - QG);
          if (elect_one()) x_chunk(cc);
          p2 = p1; p1 = cc;
        }
      }
      auto acquire = [&](uint32_t s) { mbar_wait(sb + BAR_EMPTYX + 8 * s, (mE >> s) & 1); mE ^= 1u << s; };
      auto slot = [&](uint32_t s, const CUtensorMap* m, int col, int row, uint64_t pol) {
        acquire(s);
        if (elect_one()) {
          mbar_expect_tx(sb + BAR_FULLX + 8 * s, XSLOT);
          wtma2d(sb + SM_X + s * XSLOT + rank * 9216, m, col, row + 72 * rank, sb + BAR_FULLX + 8 * s, pol);
        }
      };
#pragma unroll 1
      for (int layer = 0; layer < NLAYERS; layer++) {
#pragma unroll 1
        for (int g = 5; g < 12 * layer; g++) {
          const uint32_t s = qkv_xslot(g);
          qkv_gate(g);
          acquire(s);
          if (elect_one()) {
            mbar_expect_tx(sb + BAR_FULLX + 8 * s, 2 * 6912);
            qkv_group(group_k0(g), sb + SM_X + s * XSLOT, sb + BAR_FULLX + 8 * s);
          }
        }
#pragma unroll 1
        for (int i = 0; i < 4; i++) slot(4 + i, &maps.o, 64 * j, 144 * i, pola);
        acquire(3);
        if (elect_one()) {
          mbar_expect_tx(sb + BAR_FULLX + 24, 9216);
          wtma2d(sb + SM_WOC + rank * 4608, &maps.oc, 512 + 8 * j, 288 * rank, sb + BAR_FULLX + 24, pola);
          wtma2d(sb + SM_WOC + rank * 4608 + 2304, &maps.oc, 512 + 8 * j, 288 * rank + 144, sb + BAR_FULLX + 24, pola);
        }
#pragma unroll 1
        for (int u = 0; u < 36; u++) slot(4 * (u & 1) + ((u >> 1) & 3), &maps.d, u < 4 ? 512 : 64 * ((j + (u >> 2)) & 7), 576 * j + 144 * (u & 3), pol);
      }
    } else {
      const int w = warp - 10, grp = 2 * rb + w;
      gate(sb + SM_PROG, 3);
      if (w == 0) PROFX(58);
      auto prefetch_gu = [&](int l0, int n) {
#pragma unroll 1
        for (int i = lane; i < 36 * n; i += 32) {
          asm volatile("prefetch.global.L2 [%0];" ::"l"((w ? wu : wg) + (size_t)(36 * rb + i / n) * 9216 + 1152 * j + 128 * (l0 + i % n)));
          __nanosleep(PFSLEEP);
        }
      };
      auto clear = [&](uint4* p, int n) {
#pragma unroll 1
        for (int i = lane; i < n; i += 64) { st_relaxed4(p + i, 0, 0, 0, 0); st_relaxed4(p + i + 32, 0, 0, 0, 0); __nanosleep(32); }
      };
      auto exchange = [&](uint32_t v, uint32_t bar) {
        fence_gpu();
        __syncwarp();
        if (lane == 0) st_relaxed(ws[grp].flag + j, v);
#pragma unroll 1
        for (int it = 0; it < SPIN_MAX; it++) {
          const uint32_t f = ld_relaxed(ws[grp].flag + (lane & 7));
          if (__all_sync(0xffffffffu, v ? f >= v : f == 0)) break;
        }
        if (lane == 0) mbar_arrive(sb + bar + 8 * w);
      };
      if (lane == 0) prefetch_l2(wo + (2 * blockIdx.x + w) * 2592, 2592);
#pragma unroll 1
      for (int layer = 0; layer < NLAYERS; layer++) {
        gate(sb + SM_PROG, 32 * layer + 3);
        if (PFF & 1) prefetch_gu(0, 2);
        gate(sb + SM_PROG, 32 * layer + 22);
        if (PFF & 2) prefetch_gu(2, 2);
        if (layer == 0) {
          clear(ws[grp].act[0] + 576 * j, 576);
          clear(ws[grp].inbox[0] + 2 * j * INBOX, 2 * INBOX);
          exchange(1, BAR_CLR);
          if (w == 0) PROFX(59);
        }
        if (PFF & 2) prefetch_gu(4, 2);
        if (PFF & 4) prefetch_gu(6, 3);
#pragma unroll 1
        for (int i = lane; i < ((PFF & 8) ? 162 : 0); i += 32) {
          asm volatile("prefetch.global.L2 [%0];" ::"l"(wd + (size_t)(576 * j + 36 * rb + 18 * w) * 1152 + 128 * i));
          __nanosleep(PFSLEEP);
        }
        if (w == 0 && layer == 0) PROFX(60);
        mbar_wait(sb + BAR_REDDONE + 8 * w, layer);
        if (w == 0) PROFX(64 + 53 + 4 * layer);
        exchange(2 - 2 * layer, BAR_RREADY);
        if (w == 0) PROFX(64 + 56 + 4 * layer);
      }
      mbar_wait(sb + BAR_DONE + 8 * w, 0);
    }
    __syncwarp();
    cluster_sync();
  } else {
    asm volatile("setmaxnreg.inc.sync.aligned.u32 " STR(REGS_C) ";");
#define THREAD_IDS()                                                                   \
    int tid_ = threadIdx.x, bid_ = lb;                                                  \
    asm volatile("" : "+r"(tid_), "+r"(bid_));                                          \
    const int w = warp >> 2, wp = warp & 3;                                             \
    const int lane = tid_ & 31, t = tid_ & 127, g = lane >> 2, q = lane & 3;           \
    const int j = CTA_J(bid_), rb = CTA_RB(bid_), grp = 2 * rb + w;                    \
    const int st0 = wp * 64 + g;                         \
    Group* const G = ws + grp;                                                         \
    const uint32_t dsb = (sb & 0x3FFFF) >> 4;                                          \
    (void)t; (void)g; (void)q; (void)grp; (void)j; (void)st0; (void)dsb; (void)G
    Cons c;
    c.sb = sb; c.sB = 0; c.mB = 0; c.mX = 0; c.elect = (threadIdx.x & 127) == 0;
    asm volatile("mapa.shared::cluster.u32 %0, %1, %2;" : "=r"(c.rem) : "r"(sb), "r"(rank ^ 1));
    float v[36];
    {
      THREAD_IDS();
      asm volatile("barrier.cluster.arrive.relaxed.aligned;" ::: "memory");
      if (OPEN) {
        if (q == 0) { st_relaxed2(G->sum + st0 + 8 * j, 0, 0); st_relaxed4(G->m2 + st0 + 8 * j, 0, 0, 0, 0); }
        if (wp == 3) {
#pragma unroll
          for (int i = 0; i < 5; i++) st_relaxed4(G->halo + j * 160 + lane + i * 32, 0, 0, 0, 0);
        }
      }
      asm volatile("barrier.cluster.wait.aligned;" ::: "memory");
      PROF(0);
      const uint32_t ro = sb + wp * 2048 + (lane & 15) * 128;
      mbar_wait_c(sb + xin_bar(j), 0);
#pragma unroll
      for (int i = 0; i < 5; i++) {
        if (i == 4) mbar_wait_c(sb + BAR_FULLX + 64, 0);
        const uint4 u = ldsm4(ro + xin_off(i < 4 ? j : 8, w) + (((i < 4 ? 2 * i + (lane >> 4) : j) ^ (lane & 7)) << 4));
        v[8 * i] = bf_lo(u.x); v[8 * i + 1] = bf_hi(u.x); v[8 * i + 2] = bf_lo(u.y); v[8 * i + 3] = bf_hi(u.y);
        if (i < 4) { v[8 * i + 4] = bf_lo(u.z); v[8 * i + 5] = bf_hi(u.z); v[8 * i + 6] = bf_lo(u.w); v[8 * i + 7] = bf_hi(u.w); }
      }
    }
#pragma unroll 1
    for (int layer = 0;; layer++) {
      const uint32_t tag = layer ^ 1;
      const int pb = 1 + layer * 30;
      uint32_t res[18];
      uint4 x[36];
      {
        THREAD_IDS();
        PROF(pb + 0);
        float a1[96], a2[12];
        const float2 rs = ln_gemm<true>(c, G, v, res, layer == 0, w, st0, j, t, 1, 2 * layer + 1,
          [&](int i) { PROF(pb + 1 + i); },
          [&](int gi, uint32_t bb, const uint4& f0, const uint4& f1) {
            if (gi == 0) PROF(pb + 3);
            wg_fence();
            wgmma_ra<192>(a1, f0, desc_hi(2048, 1024, 1) + bb, gi > 0);
            wgmma_ra<24>(a2, f0, desc_hi(128, 256, 0) + (bb + 384), gi > 0);
            wgmma_ra<192>(a1, f1, desc_hi(2048, 1024, 1) + (bb + 512), true);
            wgmma_ra<24>(a2, f1, desc_hi(128, 256, 0) + (bb + 896), true);
            wg_commit();
          });
        PROF(pb + 4);
        uint32_t kv[3][18];
        auto cvt = [&](int b, float r) {
#pragma unroll
          for (int cc = 0; cc < 18; cc++) {
            const float* a = (cc == 8 ? a2 + 4 : cc == 17 ? a2 + 8 : cc < 8 ? a1 + 32 + 4 * cc : a1 + 28 + 4 * cc) + 2 * (b - 1);
            const uint32_t u = pack_bf16(a[0] * r, a[1] * r);
            kv[b][cc] = cc < 9 ? u : movm(u);
          }
        };
        cvt(2, rs.y);
        const uint32_t msg = sb + SM_X + (w ? 3 * XSLOT + wp * 2304 : wp * XSLOT + 15360) + lane * 16;
        if (wp == 3) {
          uint4* hp = G->halo + j * 160 + lane;
#pragma unroll
          for (int i = 0; i < 4; i++) st_relaxed4(hp + i * 32, tagged(kv[2][4 * i], tag), kv[2][4 * i + 1], kv[2][4 * i + 2], kv[2][4 * i + 3]);
          st_relaxed2((uint2*)(hp + 128), tagged(kv[2][16], tag), kv[2][17]);
        } else {
#pragma unroll
          for (int i = 0; i < 4; i++) sts128(msg + i * 512, kv[2][4 * i], kv[2][4 * i + 1], kv[2][4 * i + 2], kv[2][4 * i + 3]);
          sts64f(msg + 2048 - lane * 8, __uint_as_float(kv[2][16]), __uint_as_float(kv[2][17]));
        }
        cvt(1, rs.x);
        uint32_t Q[4][6];
#pragma unroll
        for (int h = 0; h < 4; h++)
#pragma unroll
          for (int i = 0; i < 6; i++) {
            const float* a = 4 * h + i < 16 ? a1 + 8 * h + 2 * i : a2 + 8 * h + 2 * i - 32;
            const uint32_t u = pack_bf16(a[0], a[1]);
            Q[h][i] = i < 2 ? (q >= h ? u : 0) : i < 4 ? u : (q <= h ? u : 0);
          }
        const bool lo0 = 2 * q > g, lo1 = 2 * q + 1 > g;
        const uint32_t M = (lo0 ? 0xffffu : 0u) | (lo1 ? 0xffff0000u : 0u);
        auto scores = [&](int h, int b, float (&s)[4]) {
          mma16816z(s, Q[h][0], Q[h][1], Q[h][2], Q[h][3], kv[b][2 * h], kv[b][2 * h + 1]);
          mma1688(s, Q[h][4], Q[h][5], kv[b][2 * h + 2]);
        };
        auto softmax = [&](float (&l)[4][2], float r, uint32_t (&P)[4]) {
          const float sl = r * (0.23570226039551584f * 1.4426950408889634f);
          float m[4];
#pragma unroll
          for (int h = 0; h < 4; h++) { m[h] = fmaxf(l[h][0], l[h][1]); m[h] = fmaxf(m[h], __shfl_xor_sync(0xffffffffu, m[h], 1)); }
#pragma unroll
          for (int h = 0; h < 4; h++) m[h] = fmaxf(m[h], __shfl_xor_sync(0xffffffffu, m[h], 2)) * sl;
#pragma unroll
          for (int h = 0; h < 4; h++) {
            l[h][0] = ex2(fmaf(l[h][0], sl, -m[h])); l[h][1] = ex2(fmaf(l[h][1], sl, -m[h]));
            m[h] = l[h][0] + l[h][1]; m[h] += __shfl_xor_sync(0xffffffffu, m[h], 1);
          }
#pragma unroll
          for (int h = 0; h < 4; h++) { m[h] = rcp(m[h] + __shfl_xor_sync(0xffffffffu, m[h], 2)); P[h] = pack_bf16(l[h][0] * m[h], l[h][1] * m[h]); }
        };
        if (ATTBAR) {
          if (w) asm volatile("bar.arrive 4, 256;" ::: "memory"); else asm volatile("bar.sync 4, 256;" ::: "memory");
        }
        const bool remote = wp == 0 && rb > 0;
        const uint4* hp = (G - 2)->halo + j * 160 + lane;
        auto halo = [&] {
#pragma unroll
          for (int i = 0; i < 4; i++) { const uint4 u = ld_relaxed4(hp + i * 32); kv[0][4 * i] = u.x; kv[0][4 * i + 1] = u.y; kv[0][4 * i + 2] = u.z; kv[0][4 * i + 3] = u.w; }
          const uint2 u = ld_relaxed2((const uint2*)(hp + 128));
          kv[0][16] = u.x; kv[0][17] = u.y;
        };
#pragma unroll
        for (int i = 0; i < 18; i++) kv[0][i] = 0;
        if (remote) halo();
        float l0[4][2], l1[4][2];
#pragma unroll
        for (int h = 0; h < 4; h++) {
          float s1[4], s2[4];
          scores(h, 1, s1); scores(h, 2, s2);
          l0[h][0] = s1[0]; l0[h][1] = s1[1];
          l1[h][0] = lo0 ? s1[2] : s2[2]; l1[h][1] = lo1 ? s1[3] : s2[3];
        }
        uint32_t P0[4], P1[4];
        softmax(l1, rs.y, P1);
        if (remote) {
          while (__any_sync(0xffffffffu, ((kv[0][0] ^ tag) | (kv[0][4] ^ tag) | (kv[0][8] ^ tag) | (kv[0][12] ^ tag) | (kv[0][16] ^ tag)) & 1)) halo();
        }
        c.progress(32 * layer + 20);
        wg_bar(w);
        if (wp > 0) {
          const uint32_t from = msg - (w ? 2304 : XSLOT);
#pragma unroll
          for (int i = 0; i < 4; i++) { const uint4 u = lds128(from + i * 512); kv[0][4 * i] = u.x; kv[0][4 * i + 1] = u.y; kv[0][4 * i + 2] = u.z; kv[0][4 * i + 3] = u.w; }
          const float2 u = lds64(from + 2048 - lane * 8);
          kv[0][16] = __float_as_uint(u.x); kv[0][17] = __float_as_uint(u.y);
        }
        PROF(pb + 5);
        const bool first = (rb == 0 && wp == 0);
#pragma unroll
        for (int h = 0; h < 4; h++) {
          float s0[4];
          scores(h, 0, s0);
          if (first) s0[0] = s0[1] = -INFINITY;
          l0[h][0] = lo0 ? s0[0] : l0[h][0]; l0[h][1] = lo1 ? s0[1] : l0[h][1];
        }
        softmax(l0, rs.x, P0);
        uint4* ob = G->act[1] + t;
        uint32_t car0 = 0, car1 = 0;
#pragma unroll
        for (int h = 0; h < 4; h++) {
          float o[3][4];
#pragma unroll
          for (int i = 0; i < 3; i++) {
            mma16816z(o[i], P0[h] & ~M, P1[h] & M, 0u, P1[h] & ~M, kv[1][9 + 2 * h + i], kv[2][9 + 2 * h + i]);
            mma1688(o[i], P0[h] & M, 0u, kv[0][9 + 2 * h + i]);
          }
          const uint32_t o0 = q < h ? car0 : pack_bf16(o[0][0], o[0][1]), o1 = q < h ? car1 : pack_bf16(o[0][2], o[0][3]);
          st_relaxed4(ob + (8 * h + j) * 128, tagged(o0, tag), o1, pack_bf16(o[1][0], o[1][1]), pack_bf16(o[1][2], o[1][3]));
          car0 = pack_bf16(o[2][0], o[2][1]); car1 = pack_bf16(o[2][2], o[2][3]);
          if (h == WOH) {
#pragma unroll
            for (int i = 0; i < 4 * WWIN; i++) x[i] = ld_relaxed4(ob + i * 128);
          }
        }
        st_relaxed2((uint2*)(ob + (32 + (j >> 1)) * 128) + (j & 1), tagged(car0, tag), car1);
        PROF(pb + 6);
      }
      {
        THREAD_IDS();
        const uint4* src = G->act[1] + t;
        float a[32], a8[4];
#pragma unroll
        for (int i = 3; i < 8; i++) mbar_wait_c(sb + BAR_FULLX + 8 * i, (c.mX >> i) & 1);
        c.mX ^= 0xf8;
#pragma unroll
        for (int b = 0; b < 9; b++) {
          while (true) {
            uint32_t bad = 0;
#pragma unroll
            for (int i = 4 * b; i < 4 * b + 4; i++) bad |= (x[i].x ^ tag) | (b < 8 ? 0u : x[i].z ^ tag);
            if (!__any_sync(0xffffffffu, bad & 1)) break;
#pragma unroll
            for (int i = 4 * b; i < 4 * b + 4; i++) x[i] = ld_relaxed4(src + i * 128);
          }
          if (b == 0) PROF(pb + 7);
          if (b + WWIN < 9) {
#pragma unroll
            for (int i = 4 * (b + WWIN); i < 4 * (b + WWIN) + 4; i++) x[i] = ld_relaxed4(src + i * 128);
          }
          wg_fence();
#pragma unroll
          for (int i = 4 * b; i < 4 * b + 4; i++) {
            const int r0 = i < 32 ? 72 * (i & 7) + 16 * (i >> 3) : 144 * (i - 32) + 64, rs = i < 32 ? 8 : 72;
            wgmma_ra<64>(a, x[i], desc_hi(0, rs * 128, 1) + (dsb + ((SM_X + 4 * XSLOT) >> 4) + r0 * 8), i > 0);
            wgmma_ra<8>(a8, x[i], desc_hi(rs * 16, 0, 0) + (dsb + (SM_WOC >> 4) + r0), i > 0);
          }
          wg_commit();
        }
        wg_wait<0>();
        if (w == 0) asm volatile("bar.arrive 3, 256;" ::: "memory");
        PROF(pb + 8);
#pragma unroll
        for (int i = 0; i < 18; i++) {
          v[2 * i] = bf_lo(res[i]) + (i < 16 ? a[2 * i] : a8[2 * i - 32]);
          v[2 * i + 1] = bf_hi(res[i]) + (i < 16 ? a[2 * i + 1] : a8[2 * i - 31]);
        }
      }
      uint32_t lsb;
      uint32_t h[144];
      {
        THREAD_IDS();
        float a[128];
        const uint32_t xd = sb + SM_X + w * 4 * XSLOT + (lane >> 4) * 1024 + (16 * wp + (lane & 15)) * 16;
        const float2 rs = ln_gemm<false>(c, G, v, res, false, w, st0, j, t, tag, (2 * layer + 2) & 3,
          [&](int i) {
            if (i == 0) {
              lsb = ((res[0] & 1) | (res[1] & 1) << 1 | (res[8] & 1) << 2 | (res[9] & 1) << 3 | (res[16] & 1) << 4) ^ (tag * 31);
              if (w == 1) asm volatile("bar.sync 3, 256;" ::: "memory");
            }
            PROF(pb + 9 + i);
          },
          [&](int gi, uint32_t bb, const uint4& f0, const uint4& f1) {
            if (gi == 0) PROF(pb + 11);
            wg_fence();
            wgmma_ra<256>(a, f0, desc_hi(4096, 1024, 1) + bb, gi > 0);
            wgmma_ra<256>(a, f1, desc_hi(4096, 1024, 1) + (bb + 128), true);
            wg_commit();
            stsm4(xd + gi * 4096, f0.x, f0.y, f0.z, f0.w);
            stsm4(xd + gi * 4096 + 2048, f1.x, f1.y, f1.z, f1.w);
            if (gi == 17) { fence_async_smem(); wg_bar(w); }
          });
        sts64f(sb + SM_KEEP + tid_ * 8, rs.x * rs.x, rs.y * rs.y);
        c.progress(32 * layer + 22);
        PROF(pb + 12);
        glu<16, 0>(a, h);
        const uint64_t da0 = desc_hi(1024, 128, 0) + (dsb + ((SM_X + w * 4 * XSLOT) >> 4));
        auto tile = [&](auto wide, auto last) {
          const uint32_t xe = BAR_EMPTYX + 8 * (t & 1) + 16 * (t & 2);
#pragma unroll 1
          for (int gi = 0; gi < 18; gi++) {
            uint32_t prev;
            const uint32_t bb = c.nextB(prev);
            const uint64_t da = da0 + gi * 256;
            wg_fence();
            if (wide()) {
              wgmma_ss<256>(a, da, desc_hi(4096, 1024, 1) + bb, gi);
              wgmma_ss<256>(a, da + 128, desc_hi(4096, 1024, 1) + (bb + 128), 1);
            } else {
              wgmma_ss<192>(*(float(*)[96])a, da, desc_hi(2048, 512, 2) + bb, gi);
              wgmma_ss<192>(*(float(*)[96])a, da + 128, desc_hi(2048, 512, 2) + (bb + 64), 1);
            }
            wg_commit();
            wg_wait<1>();
            if (gi > 0 && !(last() && gi > 13)) c.release2(BAR_EMPTYB + prev);
            if (last() && gi == 12 && t < 4) { mbar_arrive(sb + xe); mbar_arrive_remote(c.rem + xe); }
          }
          wg_wait<0>();
          if (!last()) c.releaseLastB();
          if (last() && t < 4) { mbar_arrive(sb + xe + 16); mbar_arrive_remote(c.rem + xe + 16); }
        };
        auto yes = [] { return true; };
        auto no = [] { return false; };
        tile(yes, no); PROF(pb + 13); glu<16, 32>(a, h);
        tile(yes, no); PROF(pb + 14); glu<16, 64>(a, h);
        tile(no, no); PROF(pb + 15); glu<12, 96>(a, h);
        const uint32_t hole = sb + SM_B + 12288 + tid_ * 16;
#pragma unroll
        for (int i = 0; i < NSPILL; i++) sts128(hole + i * BSLOT, h[96 + 4 * i], h[97 + 4 * i], h[98 + 4 * i], h[99 + 4 * i]);
        tile(no, yes); PROF(pb + 16); glu<12, 120>(a, h);
#pragma unroll
        for (int i = 0; i < NSPILL; i++) { const uint4 u = lds128(hole + i * BSLOT); h[96 + 4 * i] = u.x; h[97 + 4 * i] = u.y; h[98 + 4 * i] = u.z; h[99 + 4 * i] = u.w; }
      }
      {
        THREAD_IDS();
        float d[32];
        uint32_t pk[16];
#pragma unroll
        for (int i = 0; i < 16; i++) pk[i] = 0;
        uint4* const ib = G->inbox[layer];
        auto pass = [&](uint32_t s0, auto&& hook) {
          const uint64_t db = desc_hi(0, 1024, 1) + (dsb + (SM_X >> 4) + s0 * (XSLOT >> 4));
#pragma unroll
          for (int i = 0; i < 4; i++) {
            const int si = 4 * (i & 1) + (i >> 1);
            mbar_wait_c(sb + BAR_FULLX + 8 * (s0 + si), (c.mX >> (s0 + si)) & 1);
            wg_fence();
#pragma unroll
            for (int k = 0; k < 9; k++) {
              const uint32_t* hk = h + 36 * i + 4 * k;
              wgmma_ra<64>(d, make_uint4(hk[0], hk[1], hk[2], hk[3]), db + (si * (XSLOT >> 4) + k * 128), i + k > 0);
            }
            wg_commit();
            hook(i);
            if (i > 0) { wg_wait<1>(); c.release2(BAR_EMPTYX + 8 * (s0 + 4 * ((i - 1) & 1) + ((i - 1) >> 1))); }
          }
          c.mX ^= 0x33u << s0;
        };
        if (LEAD && w == 1) asm volatile("bar.sync 5, 256;" ::: "memory");
        PROF(pb + 17);
#pragma unroll 1
        for (int p = 0; p < 8; p++) {
          const uint32_t s0 = 2 * (p & 1);
          pass(s0, [&](int i) {
            if (LEAD && i == (LEAD & 3) && p == (LEAD >> 2) && w == 0) asm volatile("bar.arrive 5, 256;" ::: "memory");
            if (i == 0) {
              if (p > 1) {
                uint4* dst = ib + ((j + p - 1) & 7) * INBOX + t;
#pragma unroll
                for (int k = 0; k < 4; k++) red4(dst + k * 128, pk[4 * k], pk[4 * k + 1], pk[4 * k + 2], pk[4 * k + 3]);
                if (p == 7) { __syncwarp(); if (lane == 0) mbar_arrive(sb + BAR_REDDONE + 8 * w); }
              } else if (p == 1) {
                mbar_wait_c(sb + BAR_CLR + 8 * w, 0);
                if (t < 5) { mbar_arrive(sb + BAR_EMPTYB + 8 * t); mbar_arrive_remote(c.rem + BAR_EMPTYB + 8 * t); }
#pragma unroll
                for (int k = 0; k < 8; k++) red2((uint2*)(ib + k * INBOX + 1024) + t, pk[2 * k], pk[2 * k + 1]);
              }
            }
          });
          wg_wait<0>();
          c.release2(BAR_EMPTYX + 8 * (s0 + 5));
#pragma unroll
          for (int i = 0; i < 16; i++) pk[i] = pack_bf16(d[2 * i], d[2 * i + 1]);
        }
        PROF(pb + 18);
        uint4 R[4], P[4], X[4];
        uint2 R9, X9;
        const uint4* in = ib + j * INBOX + t;
        pass(0, [&](int i) {
          if (i == 0) {
            uint4* dst = ib + ((j + 7) & 7) * INBOX + 512 + t;
#pragma unroll
            for (int k = 0; k < 4; k++) st_relaxed4(dst + k * 128, max(pk[4 * k], 1u), pk[4 * k + 1], pk[4 * k + 2], pk[4 * k + 3]);
            const uint4* box = G->act[2] + t;
#pragma unroll
            for (int k = 0; k < 4; k++) X[k] = ld_relaxed4(box + (2 * j + (k & 1) + 8 * (k & 2)) * 128);
            X9 = ld_relaxed2((const uint2*)(box + (32 + (j >> 1)) * 128) + (j & 1));
          } else if (i == 2) {
            mbar_wait_c(sb + BAR_RREADY + 8 * w, layer);
#pragma unroll
            for (int k = 0; k < 4; k++) R[k] = ld_relaxed4(in + k * 128);
            R9 = ld_relaxed2((const uint2*)(in - t + 1024) + t);
          } else if (i == 3) {
#pragma unroll
            for (int k = 0; k < 4; k++) P[k] = ld_relaxed4(in + 512 + k * 128);
          }
        });
        PROF(pb + 19);
        const float2 r2 = lds64(sb + SM_KEEP + tid_ * 8);
#pragma unroll
        for (int k = 0; k < 4; k++) X[k].x ^= (lsb >> k) & 1;
        X9.x ^= lsb >> 4;
        v[32] = fmaf(bf_lo(R9.x), r2.x, bf_lo(X9.x)); v[33] = fmaf(bf_hi(R9.x), r2.x, bf_hi(X9.x));
        v[34] = fmaf(bf_lo(R9.y), r2.y, bf_lo(X9.y)); v[35] = fmaf(bf_hi(R9.y), r2.y, bf_hi(X9.y));
        while (__any_sync(0xffffffffu, P[0].x == 0 || P[1].x == 0 || P[2].x == 0 || P[3].x == 0)) {
#pragma unroll
          for (int k = 0; k < 4; k++) P[k] = ld_relaxed4(in + 512 + k * 128);
        }
        auto comb = [&](int i, uint32_t r, uint32_t p, uint32_t x) {
          const float s = i & 1 ? r2.y : r2.x;
          v[2 * i] = fmaf(bf_lo(r) + bf_lo(p), s, bf_lo(x)); v[2 * i + 1] = fmaf(bf_hi(r) + bf_hi(p), s, bf_hi(x));
        };
#pragma unroll
        for (int k = 0; k < 4; k += 2) {
          comb(4 * k, R[k].x, P[k].x, X[k].x); comb(4 * k + 1, R[k].y, P[k].y, X[k + 1].x);
          comb(4 * k + 2, R[k].z, P[k].z, X[k].y); comb(4 * k + 3, R[k].w, P[k].w, X[k + 1].y);
          comb(4 * k + 4, R[k + 1].x, P[k + 1].x, X[k].z); comb(4 * k + 5, R[k + 1].y, P[k + 1].y, X[k + 1].z);
          comb(4 * k + 6, R[k + 1].z, P[k + 1].z, X[k].w); comb(4 * k + 7, R[k + 1].w, P[k + 1].w, X[k + 1].w);
        }
        PROF(pb + 20);
        wg_wait<0>();
        c.release2(BAR_EMPTYX + 40);
        PROF(pb + 21);
#pragma unroll
        for (int i = 0; i < 32; i++) v[i] = fmaf(d[i], i & 2 ? r2.y : r2.x, v[i]);
      }
      if (layer == NLAYERS - 1) break;
    }
    {
      THREAD_IDS();
      const uint32_t stg = sb + SM_B + warp * 4096;
      const uint32_t sd = stg + (lane & 15) * 128;
#pragma unroll
      for (int i = 0; i < 4; i++)
        stsm4(sd + (((2 * i + (lane >> 4)) ^ (lane & 7)) << 4), pack_bf16(v[8 * i], v[8 * i + 1]), pack_bf16(v[8 * i + 2], v[8 * i + 3]),
              pack_bf16(v[8 * i + 4], v[8 * i + 5]), pack_bf16(v[8 * i + 6], v[8 * i + 7]));
      stsm2(stg + 2048 + (lane & 15) * 16, pack_bf16(v[32], v[33]), pack_bf16(v[34], v[35]));
      fence_async_smem();
      __syncwarp();
      if (lane == 0) {
        tma_store3d(&maps.out, stg, 64 * j, w, 64 * rb + 16 * wp);
        tma_store3d(&maps.outc, stg + 2048, 512 + 8 * j, w, 64 * rb + 16 * wp);
        bulk_commit();
        bulk_wait_all();
        mbar_arrive(sb + BAR_DONE + 8 * w);
      }
      PROF(61);
    }
    __syncwarp();
    cluster_sync();
  }
}

typedef CUresult (*EncFn)(CUtensorMap*, CUtensorMapDataType, cuuint32_t, void*, const cuuint64_t*, const cuuint64_t*, const cuuint32_t*,
                          const cuuint32_t*, CUtensorMapInterleave, CUtensorMapSwizzle, CUtensorMapL2promotion, CUtensorMapFloatOOBfill);

void make_map(EncFn enc, CUtensorMap* m, const void* p, int rank, uint64_t d0, uint64_t d1, uint64_t d2, uint64_t s1, uint64_t s2, uint32_t b0,
              uint32_t b1, uint32_t b2, CUtensorMapSwizzle sw) {
  cuuint64_t gd[3] = {d0, d1, d2};
  cuuint64_t gs[2] = {s1, s2};
  cuuint32_t bd[3] = {b0, b1, b2};
  cuuint32_t es[3] = {1, 1, 1};
  enc(m, CU_TENSOR_MAP_DATA_TYPE_BFLOAT16, rank, const_cast<void*>(p), gd, gs, bd, es, CU_TENSOR_MAP_INTERLEAVE_NONE, sw,
      CU_TENSOR_MAP_L2_PROMOTION_L2_128B, CU_TENSOR_MAP_FLOAT_OOB_FILL_NONE);
}

}

extern "C" void kernel_launch(void* const* d_in, const int* in_sizes, int n_in, void* d_out, int out_size) {
  const __nv_bfloat16* x = (const __nv_bfloat16*)d_in[0];
  const char *wqkv = (const char*)d_in[1], *wo = (const char*)d_in[2], *wg = (const char*)d_in[4], *wu = (const char*)d_in[5], *wd = (const char*)d_in[6];
  static EncFn enc = nullptr;
  static Group* ws = nullptr;
  if (!enc) {
    cudaDriverEntryPointQueryResult qr;
    cudaGetDriverEntryPoint("cuTensorMapEncodeTiled", (void**)&enc, cudaEnableDefault, &qr);
    cudaGetSymbolAddress((void**)&ws, g_ws);
    cudaFuncSetAttribute(fused_kernel, cudaFuncAttributeMaxDynamicSharedMemorySize, SMEM_BYTES);
  }
  const CUtensorMapSwizzle S0 = CU_TENSOR_MAP_SWIZZLE_NONE, S64 = CU_TENSOR_MAP_SWIZZLE_64B, S128 = CU_TENSOR_MAP_SWIZZLE_128B;
  Maps m;
  make_map(enc, &m.x, x, 3, 576, 2, 1024, 1152, 2304, 64, 1, 64, S128);
  make_map(enc, &m.qm, wqkv, 3, 576, 576, 3, 3456, 1152, 64, 16, 3, S128);
  make_map(enc, &m.qc, wqkv, 3, 576, 576, 3, 3456, 1152, 8, 16, 3, S0);
  make_map(enc, &m.o, wo, 2, 576, 576, 1, 1152, 0, 64, 72, 1, S128);
  make_map(enc, &m.oc, wo, 2, 576, 576, 1, 1152, 0, 8, 144, 1, S0);
  make_map(enc, &m.g, wg, 3, 64, 576, 72, 9216, 128, 64, 32, 2, S128);
  make_map(enc, &m.u, wu, 3, 64, 576, 72, 9216, 128, 64, 32, 2, S128);
  make_map(enc, &m.g3, wg, 3, 32, 576, 144, 9216, 64, 32, 32, 3, S64);
  make_map(enc, &m.u3, wu, 3, 32, 576, 144, 9216, 64, 32, 32, 3, S64);
  make_map(enc, &m.d, wd, 2, 576, 4608, 1, 1152, 0, 64, 72, 1, S128);
  make_map(enc, &m.out, d_out, 3, 576, 2, 1024, 1152, 2304, 64, 1, 16, S128);
  make_map(enc, &m.outc, d_out, 3, 576, 2, 1024, 1152, 2304, 8, 1, 16, S0);
  fused_kernel<<<NCTA, 384, SMEM_BYTES>>>(x, ws, wqkv, wg, wu, wd, m, wo);
}
```

```cpp
#include <cuda_runtime.h>
#include <cuda_bf16.h>
#include <cuda.h>
#include <stdint.h>
#include <stddef.h>

namespace {

constexpr int D_ = 576;
constexpr int NCTA = 128;
#define NLAYERS 2
#define W_POLICY policy_evict_first
#define A_POLICY policy_evict_normal
#define OPEN 1
#define PFMODE 1
#define WWIN 4
#define WOREL -1
#define WB1 12
#define WB2 24
#define WB3 36
#define WB4 36
#define WPROBE 1
#define WPROBE2 0
#define SPEC 2
#define POLLFIRST 0
#define SUMFIRST 1
#define EARLYPOLL 1
#define LEAD 0
#define ATTBAR 0
#define GL 18
#define WOBAR 0
#define QD 2
#define QG 4
#define PFQ 1
#define XDELAY 0
#define WOH 1
#define PFSLEEP 700
#define GPCMAP 1
#define PFF 1
#define REDN 1
#define CLRSLEEP 150
#define FG -1
#define NON8 0
#define HMUL 1
#define FCH 1
#define PPK 34
#define RHOOK 0
#define SCHEDBAR 1
#define QH 5
#define XH 9
#define GSLEEP 32
#define NSPILL 4
#define REGS_C 232
#define REGS_P 40
#define STR2(x) #x
#define STR(x) STR2(x)
constexpr uint32_t SM_X = 0;
constexpr uint32_t XSLOT = 18432;
constexpr uint32_t SM_WOC = SM_X + 3 * XSLOT + 9216;
constexpr uint32_t SM_B = 147456;
constexpr uint32_t BSLOT = 16384;
constexpr uint32_t SM_KEEP = 229376;
constexpr uint32_t SM_BAR = SM_KEEP + 2048;
constexpr uint32_t BAR_FULLB = SM_BAR;
constexpr uint32_t BAR_RREADY = SM_BAR + 40;
constexpr uint32_t BAR_CLR = SM_BAR + 56;
constexpr uint32_t BAR_FULLX = SM_BAR + 72;
constexpr uint32_t BAR_EMPTYB = SM_BAR + 144;
constexpr uint32_t BAR_EMPTYX = SM_BAR + 184;
constexpr uint32_t BAR_REDDONE = SM_BAR + 248;
constexpr uint32_t BAR_DONE = SM_BAR + 264;
constexpr uint32_t SM_PROG = SM_BAR + 288;
constexpr uint32_t SMEM_BYTES = SM_BAR + 1024;

struct Maps { CUtensorMap x, qm, qc, o, oc, g, u, g3, u3, d, out, outc; };

constexpr int INBOX = 1088;
struct Group {
  uint2 sum[4 * 8 * 8];
  uint4 m2[4 * 8 * 8];
  uint32_t flag[512];
  uint4 halo[8 * 160];
  uint4 act[3][36 * 128];
  uint4 inbox[2][8 * INBOX];
};
__device__ __align__(1024) Group g_ws[32];
#define PROF(i)
#define PROFX(i)

#define PROF2(i) PROF(i)

template<int N> __device__ __forceinline__ void wgmma_ss(float (&d)[N / 2], uint64_t da, uint64_t db, int sc);
template<> __device__ __forceinline__ void wgmma_ss<192>(float (&d)[96], uint64_t da, uint64_t db, int sc) {
  asm volatile("{\n.reg .pred p;\nsetp.ne.b32 p, %98, 0;\n"
    "wgmma.mma_async.sync.aligned.m64n192k16.f32.bf16.bf16 {%0,%1,%2,%3,%4,%5,%6,%7,%8,%9,%10,%11,%12,%13,%14,%15,%16,%17,%18,%19,%20,%21,%22,%23,%24,%25,%26,%27,%28,%29,%30,%31,%32,%33,%34,%35,%36,%37,%38,%39,%40,%41,%42,%43,%44,%45,%46,%47,%48,%49,%50,%51,%52,%53,%54,%55,%56,%57,%58,%59,%60,%61,%62,%63,%64,%65,%66,%67,%68,%69,%70,%71,%72,%73,%74,%75,%76,%77,%78,%79,%80,%81,%82,%83,%84,%85,%86,%87,%88,%89,%90,%91,%92,%93,%94,%95}, %96, %97, p, 1, 1, 0, 1;\n}\n"
    : "+f"(d[0]),"+f"(d[1]),"+f"(d[2]),"+f"(d[3]),"+f"(d[4]),"+f"(d[5]),"+f"(d[6]),"+f"(d[7]),"+f"(d[8]),"+f"(d[9]),"+f"(d[10]),"+f"(d[11]),"+f"(d[12]),"+f"(d[13]),"+f"(d[14]),"+f"(d[15]),"+f"(d[16]),"+f"(d[17]),"+f"(d[18]),"+f"(d[19]),"+f"(d[20]),"+f"(d[21]),"+f"(d[22]),"+f"(d[23]),"+f"(d[24]),"+f"(d[25]),"+f"(d[26]),"+f"(d[27]),"+f"(d[28]),"+f"(d[29]),"+f"(d[30]),"+f"(d[31]),"+f"(d[32]),"+f"(d[33]),"+f"(d[34]),"+f"(d[35]),"+f"(d[36]),"+f"(d[37]),"+f"(d[38]),"+f"(d[39]),"+f"(d[40]),"+f"(d[41]),"+f"(d[42]),"+f"(d[43]),"+f"(d[44]),"+f"(d[45]),"+f"(d[46]),"+f"(d[47]),"+f"(d[48]),"+f"(d[49]),"+f"(d[50]),"+f"(d[51]),"+f"(d[52]),"+f"(d[53]),"+f"(d[54]),"+f"(d[55]),"+f"(d[56]),"+f"(d[57]),"+f"(d[58]),"+f"(d[59]),"+f"(d[60]),"+f"(d[61]),"+f"(d[62]),"+f"(d[63]),"+f"(d[64]),"+f"(d[65]),"+f"(d[66]),"+f"(d[67]),"+f"(d[68]),"+f"(d[69]),"+f"(d[70]),"+f"(d[71]),"+f"(d[72]),"+f"(d[73]),"+f"(d[74]),"+f"(d[75]),"+f"(d[76]),"+f"(d[77]),"+f"(d[78]),"+f"(d[79]),"+f"(d[80]),"+f"(d[81]),"+f"(d[82]),"+f"(d[83]),"+f"(d[84]),"+f"(d[85]),"+f"(d[86]),"+f"(d[87]),"+f"(d[88]),"+f"(d[89]),"+f"(d[90]),"+f"(d[91]),"+f"(d[92]),"+f"(d[93]),"+f"(d[94]),"+f"(d[95]) : "l"(da), "l"(db), "r"(sc));
}
template<> __device__ __forceinline__ void wgmma_ss<256>(float (&d)[128], uint64_t da, uint64_t db, int sc) {
  asm volatile("{\n.reg .pred p;\nsetp.ne.b32 p, %130, 0;\n"
    "wgmma.mma_async.sync.aligned.m64n256k16.f32.bf16.bf16 {%0,%1,%2,%3,%4,%5,%6,%7,%8,%9,%10,%11,%12,%13,%14,%15,%16,%17,%18,%19,%20,%21,%22,%23,%24,%25,%26,%27,%28,%29,%30,%31,%32,%33,%34,%35,%36,%37,%38,%39,%40,%41,%42,%43,%44,%45,%46,%47,%48,%49,%50,%51,%52,%53,%54,%55,%56,%57,%58,%59,%60,%61,%62,%63,%64,%65,%66,%67,%68,%69,%70,%71,%72,%73,%74,%75,%76,%77,%78,%79,%80,%81,%82,%83,%84,%85,%86,%87,%88,%89,%90,%91,%92,%93,%94,%95,%96,%97,%98,%99,%100,%101,%102,%103,%104,%105,%106,%107,%108,%109,%110,%111,%112,%113,%114,%115,%116,%117,%118,%119,%120,%121,%122,%123,%124,%125,%126,%127}, %128, %129, p, 1, 1, 0, 1;\n}\n"
    : "+f"(d[0]),"+f"(d[1]),"+f"(d[2]),"+f"(d[3]),"+f"(d[4]),"+f"(d[5]),"+f"(d[6]),"+f"(d[7]),"+f"(d[8]),"+f"(d[9]),"+f"(d[10]),"+f"(d[11]),"+f"(d[12]),"+f"(d[13]),"+f"(d[14]),"+f"(d[15]),"+f"(d[16]),"+f"(d[17]),"+f"(d[18]),"+f"(d[19]),"+f"(d[20]),"+f"(d[21]),"+f"(d[22]),"+f"(d[23]),"+f"(d[24]),"+f"(d[25]),"+f"(d[26]),"+f"(d[27]),"+f"(d[28]),"+f"(d[29]),"+f"(d[30]),"+f"(d[31]),"+f"(d[32]),"+f"(d[33]),"+f"(d[34]),"+f"(d[35]),"+f"(d[36]),"+f"(d[37]),"+f"(d[38]),"+f"(d[39]),"+f"(d[40]),"+f"(d[41]),"+f"(d[42]),"+f"(d[43]),"+f"(d[44]),"+f"(d[45]),"+f"(d[46]),"+f"(d[47]),"+f"(d[48]),"+f"(d[49]),"+f"(d[50]),"+f"(d[51]),"+f"(d[52]),"+f"(d[53]),"+f"(d[54]),"+f"(d[55]),"+f"(d[56]),"+f"(d[57]),"+f"(d[58]),"+f"(d[59]),"+f"(d[60]),"+f"(d[61]),"+f"(d[62]),"+f"(d[63]),"+f"(d[64]),"+f"(d[65]),"+f"(d[66]),"+f"(d[67]),"+f"(d[68]),"+f"(d[69]),"+f"(d[70]),"+f"(d[71]),"+f"(d[72]),"+f"(d[73]),"+f"(d[74]),"+f"(d[75]),"+f"(d[76]),"+f"(d[77]),"+f"(d[78]),"+f"(d[79]),"+f"(d[80]),"+f"(d[81]),"+f"(d[82]),"+f"(d[83]),"+f"(d[84]),"+f"(d[85]),"+f"(d[86]),"+f"(d[87]),"+f"(d[88]),"+f"(d[89]),"+f"(d[90]),"+f"(d[91]),"+f"(d[92]),"+f"(d[93]),"+f"(d[94]),"+f"(d[95]),"+f"(d[96]),"+f"(d[97]),"+f"(d[98]),"+f"(d[99]),"+f"(d[100]),"+f"(d[101]),"+f"(d[102]),"+f"(d[103]),"+f"(d[104]),"+f"(d[105]),"+f"(d[106]),"+f"(d[107]),"+f"(d[108]),"+f"(d[109]),"+f"(d[110]),"+f"(d[111]),"+f"(d[112]),"+f"(d[113]),"+f"(d[114]),"+f"(d[115]),"+f"(d[116]),"+f"(d[117]),"+f"(d[118]),"+f"(d[119]),"+f"(d[120]),"+f"(d[121]),"+f"(d[122]),"+f"(d[123]),"+f"(d[124]),"+f"(d[125]),"+f"(d[126]),"+f"(d[127]) : "l"(da), "l"(db), "r"(sc));
}
template<int N> __device__ __forceinline__ void wgmma_rs(float (&d)[N / 2], uint32_t a0, uint32_t a1, uint32_t a2, uint32_t a3, uint64_t db, int sc);
template<> __device__ __forceinline__ void wgmma_rs<8>(float (&d)[4], uint32_t a0, uint32_t a1, uint32_t a2, uint32_t a3, uint64_t db, int sc) {
  asm volatile("{\n.reg .pred p;\nsetp.ne.b32 p, %9, 0;\n"
    "wgmma.mma_async.sync.aligned.m64n8k16.f32.bf16.bf16 {%0,%1,%2,%3}, {%4,%5,%6,%7}, %8, p, 1, 1, 1;\n}\n"
    : "+f"(d[0]),"+f"(d[1]),"+f"(d[2]),"+f"(d[3]) : "r"(a0), "r"(a1), "r"(a2), "r"(a3), "l"(db), "r"(sc));
}
template<> __device__ __forceinline__ void wgmma_rs<24>(float (&d)[12], uint32_t a0, uint32_t a1, uint32_t a2, uint32_t a3, uint64_t db, int sc) {
  asm volatile("{\n.reg .pred p;\nsetp.ne.b32 p, %17, 0;\n"
    "wgmma.mma_async.sync.aligned.m64n24k16.f32.bf16.bf16 {%0,%1,%2,%3,%4,%5,%6,%7,%8,%9,%10,%11}, {%12,%13,%14,%15}, %16, p, 1, 1, 1;\n}\n"
    : "+f"(d[0]),"+f"(d[1]),"+f"(d[2]),"+f"(d[3]),"+f"(d[4]),"+f"(d[5]),"+f"(d[6]),"+f"(d[7]),"+f"(d[8]),"+f"(d[9]),"+f"(d[10]),"+f"(d[11]) : "r"(a0), "r"(a1), "r"(a2), "r"(a3), "l"(db), "r"(sc));
}
template<> __device__ __forceinline__ void wgmma_rs<64>(float (&d)[32], uint32_t a0, uint32_t a1, uint32_t a2, uint32_t a3, uint64_t db, int sc) {
  asm volatile("{\n.reg .pred p;\nsetp.ne.b32 p, %37, 0;\n"
    "wgmma.mma_async.sync.aligned.m64n64k16.f32.bf16.bf16 {%0,%1,%2,%3,%4,%5,%6,%7,%8,%9,%10,%11,%12,%13,%14,%15,%16,%17,%18,%19,%20,%21,%22,%23,%24,%25,%26,%27,%28,%29,%30,%31}, {%32,%33,%34,%35}, %36, p, 1, 1, 1;\n}\n"
    : "+f"(d[0]),"+f"(d[1]),"+f"(d[2]),"+f"(d[3]),"+f"(d[4]),"+f"(d[5]),"+f"(d[6]),"+f"(d[7]),"+f"(d[8]),"+f"(d[9]),"+f"(d[10]),"+f"(d[11]),"+f"(d[12]),"+f"(d[13]),"+f"(d[14]),"+f"(d[15]),"+f"(d[16]),"+f"(d[17]),"+f"(d[18]),"+f"(d[19]),"+f"(d[20]),"+f"(d[21]),"+f"(d[22]),"+f"(d[23]),"+f"(d[24]),"+f"(d[25]),"+f"(d[26]),"+f"(d[27]),"+f"(d[28]),"+f"(d[29]),"+f"(d[30]),"+f"(d[31]) : "r"(a0), "r"(a1), "r"(a2), "r"(a3), "l"(db), "r"(sc));
}
template<> __device__ __forceinline__ void wgmma_rs<192>(float (&d)[96], uint32_t a0, uint32_t a1, uint32_t a2, uint32_t a3, uint64_t db, int sc) {
  asm volatile("{\n.reg .pred p;\nsetp.ne.b32 p, %101, 0;\n"
    "wgmma.mma_async.sync.aligned.m64n192k16.f32.bf16.bf16 {%0,%1,%2,%3,%4,%5,%6,%7,%8,%9,%10,%11,%12,%13,%14,%15,%16,%17,%18,%19,%20,%21,%22,%23,%24,%25,%26,%27,%28,%29,%30,%31,%32,%33,%34,%35,%36,%37,%38,%39,%40,%41,%42,%43,%44,%45,%46,%47,%48,%49,%50,%51,%52,%53,%54,%55,%56,%57,%58,%59,%60,%61,%62,%63,%64,%65,%66,%67,%68,%69,%70,%71,%72,%73,%74,%75,%76,%77,%78,%79,%80,%81,%82,%83,%84,%85,%86,%87,%88,%89,%90,%91,%92,%93,%94,%95}, {%96,%97,%98,%99}, %100, p, 1, 1, 1;\n}\n"
    : "+f"(d[0]),"+f"(d[1]),"+f"(d[2]),"+f"(d[3]),"+f"(d[4]),"+f"(d[5]),"+f"(d[6]),"+f"(d[7]),"+f"(d[8]),"+f"(d[9]),"+f"(d[10]),"+f"(d[11]),"+f"(d[12]),"+f"(d[13]),"+f"(d[14]),"+f"(d[15]),"+f"(d[16]),"+f"(d[17]),"+f"(d[18]),"+f"(d[19]),"+f"(d[20]),"+f"(d[21]),"+f"(d[22]),"+f"(d[23]),"+f"(d[24]),"+f"(d[25]),"+f"(d[26]),"+f"(d[27]),"+f"(d[28]),"+f"(d[29]),"+f"(d[30]),"+f"(d[31]),"+f"(d[32]),"+f"(d[33]),"+f"(d[34]),"+f"(d[35]),"+f"(d[36]),"+f"(d[37]),"+f"(d[38]),"+f"(d[39]),"+f"(d[40]),"+f"(d[41]),"+f"(d[42]),"+f"(d[43]),"+f"(d[44]),"+f"(d[45]),"+f"(d[46]),"+f"(d[47]),"+f"(d[48]),"+f"(d[49]),"+f"(d[50]),"+f"(d[51]),"+f"(d[52]),"+f"(d[53]),"+f"(d[54]),"+f"(d[55]),"+f"(d[56]),"+f"(d[57]),"+f"(d[58]),"+f"(d[59]),"+f"(d[60]),"+f"(d[61]),"+f"(d[62]),"+f"(d[63]),"+f"(d[64]),"+f"(d[65]),"+f"(d[66]),"+f"(d[67]),"+f"(d[68]),"+f"(d[69]),"+f"(d[70]),"+f"(d[71]),"+f"(d[72]),"+f"(d[73]),"+f"(d[74]),"+f"(d[75]),"+f"(d[76]),"+f"(d[77]),"+f"(d[78]),"+f"(d[79]),"+f"(d[80]),"+f"(d[81]),"+f"(d[82]),"+f"(d[83]),"+f"(d[84]),"+f"(d[85]),"+f"(d[86]),"+f"(d[87]),"+f"(d[88]),"+f"(d[89]),"+f"(d[90]),"+f"(d[91]),"+f"(d[92]),"+f"(d[93]),"+f"(d[94]),"+f"(d[95]) : "r"(a0), "r"(a1), "r"(a2), "r"(a3), "l"(db), "r"(sc));
}
template<> __device__ __forceinline__ void wgmma_rs<256>(float (&d)[128], uint32_t a0, uint32_t a1, uint32_t a2, uint32_t a3, uint64_t db, int sc) {
  asm volatile("{\n.reg .pred p;\nsetp.ne.b32 p, %133, 0;\n"
    "wgmma.mma_async.sync.aligned.m64n256k16.f32.bf16.bf16 {%0,%1,%2,%3,%4,%5,%6,%7,%8,%9,%10,%11,%12,%13,%14,%15,%16,%17,%18,%19,%20,%21,%22,%23,%24,%25,%26,%27,%28,%29,%30,%31,%32,%33,%34,%35,%36,%37,%38,%39,%40,%41,%42,%43,%44,%45,%46,%47,%48,%49,%50,%51,%52,%53,%54,%55,%56,%57,%58,%59,%60,%61,%62,%63,%64,%65,%66,%67,%68,%69,%70,%71,%72,%73,%74,%75,%76,%77,%78,%79,%80,%81,%82,%83,%84,%85,%86,%87,%88,%89,%90,%91,%92,%93,%94,%95,%96,%97,%98,%99,%100,%101,%102,%103,%104,%105,%106,%107,%108,%109,%110,%111,%112,%113,%114,%115,%116,%117,%118,%119,%120,%121,%122,%123,%124,%125,%126,%127}, {%128,%129,%130,%131}, %132, p, 1, 1, 1;\n}\n"
    : "+f"(d[0]),"+f"(d[1]),"+f"(d[2]),"+f"(d[3]),"+f"(d[4]),"+f"(d[5]),"+f"(d[6]),"+f"(d[7]),"+f"(d[8]),"+f"(d[9]),"+f"(d[10]),"+f"(d[11]),"+f"(d[12]),"+f"(d[13]),"+f"(d[14]),"+f"(d[15]),"+f"(d[16]),"+f"(d[17]),"+f"(d[18]),"+f"(d[19]),"+f"(d[20]),"+f"(d[21]),"+f"(d[22]),"+f"(d[23]),"+f"(d[24]),"+f"(d[25]),"+f"(d[26]),"+f"(d[27]),"+f"(d[28]),"+f"(d[29]),"+f"(d[30]),"+f"(d[31]),"+f"(d[32]),"+f"(d[33]),"+f"(d[34]),"+f"(d[35]),"+f"(d[36]),"+f"(d[37]),"+f"(d[38]),"+f"(d[39]),"+f"(d[40]),"+f"(d[41]),"+f"(d[42]),"+f"(d[43]),"+f"(d[44]),"+f"(d[45]),"+f"(d[46]),"+f"(d[47]),"+f"(d[48]),"+f"(d[49]),"+f"(d[50]),"+f"(d[51]),"+f"(d[52]),"+f"(d[53]),"+f"(d[54]),"+f"(d[55]),"+f"(d[56]),"+f"(d[57]),"+f"(d[58]),"+f"(d[59]),"+f"(d[60]),"+f"(d[61]),"+f"(d[62]),"+f"(d[63]),"+f"(d[64]),"+f"(d[65]),"+f"(d[66]),"+f"(d[67]),"+f"(d[68]),"+f"(d[69]),"+f"(d[70]),"+f"(d[71]),"+f"(d[72]),"+f"(d[73]),"+f"(d[74]),"+f"(d[75]),"+f"(d[76]),"+f"(d[77]),"+f"(d[78]),"+f"(d[79]),"+f"(d[80]),"+f"(d[81]),"+f"(d[82]),"+f"(d[83]),"+f"(d[84]),"+f"(d[85]),"+f"(d[86]),"+f"(d[87]),"+f"(d[88]),"+f"(d[89]),"+f"(d[90]),"+f"(d[91]),"+f"(d[92]),"+f"(d[93]),"+f"(d[94]),"+f"(d[95]),"+f"(d[96]),"+f"(d[97]),"+f"(d[98]),"+f"(d[99]),"+f"(d[100]),"+f"(d[101]),"+f"(d[102]),"+f"(d[103]),"+f"(d[104]),"+f"(d[105]),"+f"(d[106]),"+f"(d[107]),"+f"(d[108]),"+f"(d[109]),"+f"(d[110]),"+f"(d[111]),"+f"(d[112]),"+f"(d[113]),"+f"(d[114]),"+f"(d[115]),"+f"(d[116]),"+f"(d[117]),"+f"(d[118]),"+f"(d[119]),"+f"(d[120]),"+f"(d[121]),"+f"(d[122]),"+f"(d[123]),"+f"(d[124]),"+f"(d[125]),"+f"(d[126]),"+f"(d[127]) : "r"(a0), "r"(a1), "r"(a2), "r"(a3), "l"(db), "r"(sc));
}
template<int N> __device__ __forceinline__ void wgmma_rsz(float (&d)[N / 2], uint32_t a0, uint32_t a1, uint32_t a2, uint32_t a3, uint64_t db);
template<> __device__ __forceinline__ void wgmma_rsz<8>(float (&d)[4], uint32_t a0, uint32_t a1, uint32_t a2, uint32_t a3, uint64_t db) {
  asm volatile("{\n.reg .pred p;\nsetp.ne.b32 p, 0, 0;\n"
    "wgmma.mma_async.sync.aligned.m64n8k16.f32.bf16.bf16 {%0,%1,%2,%3}, {%4,%5,%6,%7}, %8, p, 1, 1, 1;\n}\n"
    : "=f"(d[0]),"=f"(d[1]),"=f"(d[2]),"=f"(d[3]) : "r"(a0), "r"(a1), "r"(a2), "r"(a3), "l"(db));
}
template<> __device__ __forceinline__ void wgmma_rsz<24>(float (&d)[12], uint32_t a0, uint32_t a1, uint32_t a2, uint32_t a3, uint64_t db) {
  asm volatile("{\n.reg .pred p;\nsetp.ne.b32 p, 0, 0;\n"
    "wgmma.mma_async.sync.aligned.m64n24k16.f32.bf16.bf16 {%0,%1,%2,%3,%4,%5,%6,%7,%8,%9,%10,%11}, {%12,%13,%14,%15}, %16, p, 1, 1, 1;\n}\n"
    : "=f"(d[0]),"=f"(d[1]),"=f"(d[2]),"=f"(d[3]),"=f"(d[4]),"=f"(d[5]),"=f"(d[6]),"=f"(d[7]),"=f"(d[8]),"=f"(d[9]),"=f"(d[10]),"=f"(d[11]) : "r"(a0), "r"(a1), "r"(a2), "r"(a3), "l"(db));
}
template<> __device__ __forceinline__ void wgmma_rsz<64>(float (&d)[32], uint32_t a0, uint32_t a1, uint32_t a2, uint32_t a3, uint64_t db) {
  asm volatile("{\n.reg .pred p;\nsetp.ne.b32 p, 0, 0;\n"
    "wgmma.mma_async.sync.aligned.m64n64k16.f32.bf16.bf16 {%0,%1,%2,%3,%4,%5,%6,%7,%8,%9,%10,%11,%12,%13,%14,%15,%16,%17,%18,%19,%20,%21,%22,%23,%24,%25,%26,%27,%28,%29,%30,%31}, {%32,%33,%34,%35}, %36, p, 1, 1, 1;\n}\n"
    : "=f"(d[0]),"=f"(d[1]),"=f"(d[2]),"=f"(d[3]),"=f"(d[4]),"=f"(d[5]),"=f"(d[6]),"=f"(d[7]),"=f"(d[8]),"=f"(d[9]),"=f"(d[10]),"=f"(d[11]),"=f"(d[12]),"=f"(d[13]),"=f"(d[14]),"=f"(d[15]),"=f"(d[16]),"=f"(d[17]),"=f"(d[18]),"=f"(d[19]),"=f"(d[20]),"=f"(d[21]),"=f"(d[22]),"=f"(d[23]),"=f"(d[24]),"=f"(d[25]),"=f"(d[26]),"=f"(d[27]),"=f"(d[28]),"=f"(d[29]),"=f"(d[30]),"=f"(d[31]) : "r"(a0), "r"(a1), "r"(a2), "r"(a3), "l"(db));
}
template<> __device__ __forceinline__ void wgmma_rsz<192>(float (&d)[96], uint32_t a0, uint32_t a1, uint32_t a2, uint32_t a3, uint64_t db) {
  asm volatile("{\n.reg .pred p;\nsetp.ne.b32 p, 0, 0;\n"
    "wgmma.mma_async.sync.aligned.m64n192k16.f32.bf16.bf16 {%0,%1,%2,%3,%4,%5,%6,%7,%8,%9,%10,%11,%12,%13,%14,%15,%16,%17,%18,%19,%20,%21,%22,%23,%24,%25,%26,%27,%28,%29,%30,%31,%32,%33,%34,%35,%36,%37,%38,%39,%40,%41,%42,%43,%44,%45,%46,%47,%48,%49,%50,%51,%52,%53,%54,%55,%56,%57,%58,%59,%60,%61,%62,%63,%64,%65,%66,%67,%68,%69,%70,%71,%72,%73,%74,%75,%76,%77,%78,%79,%80,%81,%82,%83,%84,%85,%86,%87,%88,%89,%90,%91,%92,%93,%94,%95}, {%96,%97,%98,%99}, %100, p, 1, 1, 1;\n}\n"
    : "=f"(d[0]),"=f"(d[1]),"=f"(d[2]),"=f"(d[3]),"=f"(d[4]),"=f"(d[5]),"=f"(d[6]),"=f"(d[7]),"=f"(d[8]),"=f"(d[9]),"=f"(d[10]),"=f"(d[11]),"=f"(d[12]),"=f"(d[13]),"=f"(d[14]),"=f"(d[15]),"=f"(d[16]),"=f"(d[17]),"=f"(d[18]),"=f"(d[19]),"=f"(d[20]),"=f"(d[21]),"=f"(d[22]),"=f"(d[23]),"=f"(d[24]),"=f"(d[25]),"=f"(d[26]),"=f"(d[27]),"=f"(d[28]),"=f"(d[29]),"=f"(d[30]),"=f"(d[31]),"=f"(d[32]),"=f"(d[33]),"=f"(d[34]),"=f"(d[35]),"=f"(d[36]),"=f"(d[37]),"=f"(d[38]),"=f"(d[39]),"=f"(d[40]),"=f"(d[41]),"=f"(d[42]),"=f"(d[43]),"=f"(d[44]),"=f"(d[45]),"=f"(d[46]),"=f"(d[47]),"=f"(d[48]),"=f"(d[49]),"=f"(d[50]),"=f"(d[51]),"=f"(d[52]),"=f"(d[53]),"=f"(d[54]),"=f"(d[55]),"=f"(d[56]),"=f"(d[57]),"=f"(d[58]),"=f"(d[59]),"=f"(d[60]),"=f"(d[61]),"=f"(d[62]),"=f"(d[63]),"=f"(d[64]),"=f"(d[65]),"=f"(d[66]),"=f"(d[67]),"=f"(d[68]),"=f"(d[69]),"=f"(d[70]),"=f"(d[71]),"=f"(d[72]),"=f"(d[73]),"=f"(d[74]),"=f"(d[75]),"=f"(d[76]),"=f"(d[77]),"=f"(d[78]),"=f"(d[79]),"=f"(d[80]),"=f"(d[81]),"=f"(d[82]),"=f"(d[83]),"=f"(d[84]),"=f"(d[85]),"=f"(d[86]),"=f"(d[87]),"=f"(d[88]),"=f"(d[89]),"=f"(d[90]),"=f"(d[91]),"=f"(d[92]),"=f"(d[93]),"=f"(d[94]),"=f"(d[95]) : "r"(a0), "r"(a1), "r"(a2), "r"(a3), "l"(db));
}
template<> __device__ __forceinline__ void wgmma_rsz<256>(float (&d)[128], uint32_t a0, uint32_t a1, uint32_t a2, uint32_t a3, uint64_t db) {
  asm volatile("{\n.reg .pred p;\nsetp.ne.b32 p, 0, 0;\n"
    "wgmma.mma_async.sync.aligned.m64n256k16.f32.bf16.bf16 {%0,%1,%2,%3,%4,%5,%6,%7,%8,%9,%10,%11,%12,%13,%14,%15,%16,%17,%18,%19,%20,%21,%22,%23,%24,%25,%26,%27,%28,%29,%30,%31,%32,%33,%34,%35,%36,%37,%38,%39,%40,%41,%42,%43,%44,%45,%46,%47,%48,%49,%50,%51,%52,%53,%54,%55,%56,%57,%58,%59,%60,%61,%62,%63,%64,%65,%66,%67,%68,%69,%70,%71,%72,%73,%74,%75,%76,%77,%78,%79,%80,%81,%82,%83,%84,%85,%86,%87,%88,%89,%90,%91,%92,%93,%94,%95,%96,%97,%98,%99,%100,%101,%102,%103,%104,%105,%106,%107,%108,%109,%110,%111,%112,%113,%114,%115,%116,%117,%118,%119,%120,%121,%122,%123,%124,%125,%126,%127}, {%128,%129,%130,%131}, %132, p, 1, 1, 1;\n}\n"
    : "=f"(d[0]),"=f"(d[1]),"=f"(d[2]),"=f"(d[3]),"=f"(d[4]),"=f"(d[5]),"=f"(d[6]),"=f"(d[7]),"=f"(d[8]),"=f"(d[9]),"=f"(d[10]),"=f"(d[11]),"=f"(d[12]),"=f"(d[13]),"=f"(d[14]),"=f"(d[15]),"=f"(d[16]),"=f"(d[17]),"=f"(d[18]),"=f"(d[19]),"=f"(d[20]),"=f"(d[21]),"=f"(d[22]),"=f"(d[23]),"=f"(d[24]),"=f"(d[25]),"=f"(d[26]),"=f"(d[27]),"=f"(d[28]),"=f"(d[29]),"=f"(d[30]),"=f"(d[31]),"=f"(d[32]),"=f"(d[33]),"=f"(d[34]),"=f"(d[35]),"=f"(d[36]),"=f"(d[37]),"=f"(d[38]),"=f"(d[39]),"=f"(d[40]),"=f"(d[41]),"=f"(d[42]),"=f"(d[43]),"=f"(d[44]),"=f"(d[45]),"=f"(d[46]),"=f"(d[47]),"=f"(d[48]),"=f"(d[49]),"=f"(d[50]),"=f"(d[51]),"=f"(d[52]),"=f"(d[53]),"=f"(d[54]),"=f"(d[55]),"=f"(d[56]),"=f"(d[57]),"=f"(d[58]),"=f"(d[59]),"=f"(d[60]),"=f"(d[61]),"=f"(d[62]),"=f"(d[63]),"=f"(d[64]),"=f"(d[65]),"=f"(d[66]),"=f"(d[67]),"=f"(d[68]),"=f"(d[69]),"=f"(d[70]),"=f"(d[71]),"=f"(d[72]),"=f"(d[73]),"=f"(d[74]),"=f"(d[75]),"=f"(d[76]),"=f"(d[77]),"=f"(d[78]),"=f"(d[79]),"=f"(d[80]),"=f"(d[81]),"=f"(d[82]),"=f"(d[83]),"=f"(d[84]),"=f"(d[85]),"=f"(d[86]),"=f"(d[87]),"=f"(d[88]),"=f"(d[89]),"=f"(d[90]),"=f"(d[91]),"=f"(d[92]),"=f"(d[93]),"=f"(d[94]),"=f"(d[95]),"=f"(d[96]),"=f"(d[97]),"=f"(d[98]),"=f"(d[99]),"=f"(d[100]),"=f"(d[101]),"=f"(d[102]),"=f"(d[103]),"=f"(d[104]),"=f"(d[105]),"=f"(d[106]),"=f"(d[107]),"=f"(d[108]),"=f"(d[109]),"=f"(d[110]),"=f"(d[111]),"=f"(d[112]),"=f"(d[113]),"=f"(d[114]),"=f"(d[115]),"=f"(d[116]),"=f"(d[117]),"=f"(d[118]),"=f"(d[119]),"=f"(d[120]),"=f"(d[121]),"=f"(d[122]),"=f"(d[123]),"=f"(d[124]),"=f"(d[125]),"=f"(d[126]),"=f"(d[127]) : "r"(a0), "r"(a1), "r"(a2), "r"(a3), "l"(db));
}
template<int N> __device__ __forceinline__ void wgmma_ra(float (&d)[N / 2], const uint4& a, uint64_t db, bool acc) {
  if (acc) wgmma_rs<N>(d, a.x, a.y, a.z, a.w, db, 1); else wgmma_rsz<N>(d, a.x, a.y, a.z, a.w, db);
}

__device__ __forceinline__ uint32_t smem_u32(const void* p) { return (uint32_t)__cvta_generic_to_shared(p); }
__device__ __forceinline__ void mbar_init(uint32_t bar, uint32_t cnt) { asm volatile("mbarrier.init.shared::cta.b64 [%0], %1;" ::"r"(bar), "r"(cnt)); }
__device__ __forceinline__ void mbar_expect_tx(uint32_t bar, uint32_t bytes) { asm volatile("mbarrier.arrive.expect_tx.shared::cta.b64 _, [%0], %1;" ::"r"(bar), "r"(bytes) : "memory"); }
__device__ __forceinline__ void mbar_arrive(uint32_t bar) { asm volatile("mbarrier.arrive.shared::cta.b64 _, [%0];" ::"r"(bar) : "memory"); }
__device__ __forceinline__ void mbar_arrive_remote(uint32_t rbar) { asm volatile("mbarrier.arrive.shared::cluster.b64 _, [%0];" ::"r"(rbar) : "memory"); }
__device__ __forceinline__ void mbar_wait(uint32_t bar, uint32_t parity) {
  asm volatile(
      "{\n.reg .pred p;\n.reg .u32 c;\nmov.u32 c, 0;\nLAB_WAIT:\nmbarrier.try_wait.parity.shared::cta.b64 p, [%0], %1;\n@p bra DONE;\n"
      "add.u32 c, c, 1;\nsetp.lt.u32 p, c, 1000000;\n@p bra LAB_WAIT;\ntrap;\nDONE:\n}\n" ::"r"(bar), "r"(parity) : "memory");
}
__device__ __forceinline__ void mbar_wait_c(uint32_t bar, uint32_t parity) {
  asm volatile("{\n.reg .pred p;\nLAB_WAIT:\nmbarrier.try_wait.parity.shared::cta.b64 p, [%0], %1;\n@!p bra LAB_WAIT;\n}\n" ::"r"(bar), "r"(parity) : "memory");
}
__device__ __forceinline__ void wtma2d(uint32_t dst, const CUtensorMap* m, int c0, int c1, uint32_t bar, uint64_t pol) {
  asm volatile("cp.async.bulk.tensor.2d.shared::cluster.global.mbarrier::complete_tx::bytes.multicast::cluster.L2::cache_hint [%0], [%1, {%3, %4}], [%2], %5, %6;"
               ::"r"(dst), "l"(m), "r"(bar), "r"(c0), "r"(c1), "h"((uint16_t)3), "l"(pol) : "memory");
}
__device__ __forceinline__ void wtma3d(uint32_t dst, const CUtensorMap* m, int c0, int c1, int c2, uint32_t bar, uint64_t pol) {
  asm volatile("cp.async.bulk.tensor.3d.shared::cluster.global.mbarrier::complete_tx::bytes.multicast::cluster.L2::cache_hint [%0], [%1, {%3, %4, %5}], [%2], %6, %7;"
               ::"r"(dst), "l"(m), "r"(bar), "r"(c0), "r"(c1), "r"(c2), "h"((uint16_t)3), "l"(pol) : "memory");
}
__device__ __forceinline__ void tma3d(uint32_t dst, const CUtensorMap* m, int c0, int c1, int c2, uint32_t bar) {
  asm volatile("cp.async.bulk.tensor.3d.shared::cluster.global.mbarrier::complete_tx::bytes [%0], [%1, {%3, %4, %5}], [%2];"
               ::"r"(dst), "l"(m), "r"(bar), "r"(c0), "r"(c1), "r"(c2) : "memory");
}
__device__ __forceinline__ void tma_store3d(const CUtensorMap* m, uint32_t src, int c0, int c1, int c2) {
  asm volatile("cp.async.bulk.tensor.3d.global.shared::cta.bulk_group [%0, {%2, %3, %4}], [%1];" ::"l"(m), "r"(src), "r"(c0), "r"(c1), "r"(c2) : "memory");
}
__device__ __forceinline__ void prefetch_l2(const void* p, uint32_t bytes) { asm volatile("cp.async.bulk.prefetch.L2.global [%0], %1;" ::"l"(p), "r"(bytes) : "memory"); }
__device__ __forceinline__ uint64_t policy_evict_first() { uint64_t p; asm volatile("createpolicy.fractional.L2::evict_first.b64 %0, 1.0;" : "=l"(p)); return p; }
__device__ __forceinline__ uint64_t policy_evict_normal() { uint64_t p; asm volatile("createpolicy.fractional.L2::evict_normal.b64 %0, 1.0;" : "=l"(p)); return p; }
__device__ __forceinline__ void bulk_commit() { asm volatile("cp.async.bulk.commit_group;" ::: "memory"); }
__device__ __forceinline__ void bulk_wait_all() { asm volatile("cp.async.bulk.wait_group 0;" ::: "memory"); }
__device__ __forceinline__ void fence_async_smem() { asm volatile("fence.proxy.async.shared::cta;" ::: "memory"); }
__device__ __forceinline__ bool elect_one() {
  uint32_t p;
  asm volatile("{\n.reg .pred P;\nelect.sync _|P, 0xffffffff;\nselp.u32 %0, 1, 0, P;\n}\n" : "=r"(p));
  return p;
}
__device__ __forceinline__ void wg_fence() { asm volatile("wgmma.fence.sync.aligned;" ::: "memory"); }
__device__ __forceinline__ void wg_commit() { asm volatile("wgmma.commit_group.sync.aligned;" ::: "memory"); }
template <int n> __device__ __forceinline__ void wg_wait() { asm volatile("wgmma.wait_group.sync.aligned %0;" ::"n"(n) : "memory"); }
__device__ __forceinline__ void wg_bar(int w) { asm volatile("bar.sync %0, 128;" ::"r"(w + 1) : "memory"); }
__device__ __forceinline__ void cluster_sync() { asm volatile("barrier.cluster.arrive.relaxed.aligned;\nbarrier.cluster.wait.aligned;" ::: "memory"); }
__device__ __forceinline__ constexpr uint64_t desc_hi(uint32_t lbo, uint32_t sbo, int sw) {
  return ((uint64_t)(lbo >> 4) << 16) | ((uint64_t)(sbo >> 4) << 32) | ((uint64_t)sw << 62);
}
__device__ __forceinline__ void fence_gpu() { asm volatile("fence.acq_rel.gpu;" ::: "memory"); }
__device__ __forceinline__ uint32_t ld_relaxed(const uint32_t* p) { uint32_t v; asm volatile("ld.relaxed.gpu.global.u32 %0, [%1];" : "=r"(v) : "l"(p) : "memory"); return v; }
__device__ __forceinline__ uint4 ld_relaxed4(const uint4* p) {
  uint4 v; asm volatile("ld.relaxed.gpu.global.v4.u32 {%0,%1,%2,%3}, [%4];" : "=r"(v.x), "=r"(v.y), "=r"(v.z), "=r"(v.w) : "l"(p) : "memory"); return v;
}
__device__ __forceinline__ uint2 ld_relaxed2(const uint2* p) {
  uint2 v; asm volatile("ld.relaxed.gpu.global.v2.u32 {%0,%1}, [%2];" : "=r"(v.x), "=r"(v.y) : "l"(p) : "memory"); return v;
}
__device__ __forceinline__ void st_relaxed(uint32_t* p, uint32_t a) { asm volatile("st.relaxed.gpu.global.u32 [%0], %1;" ::"l"(p), "r"(a) : "memory"); }
__device__ __forceinline__ void st_relaxed4(uint4* p, uint32_t a, uint32_t b, uint32_t c, uint32_t d) {
  asm volatile("st.relaxed.gpu.global.v4.u32 [%0], {%1,%2,%3,%4};" ::"l"(p), "r"(a), "r"(b), "r"(c), "r"(d) : "memory");
}
__device__ __forceinline__ void st_relaxed2(uint2* p, uint32_t a, uint32_t b) {
  asm volatile("st.relaxed.gpu.global.v2.u32 [%0], {%1,%2};" ::"l"(p), "r"(a), "r"(b) : "memory");
}
__device__ __forceinline__ void red4(uint4* p, uint32_t a, uint32_t b, uint32_t c, uint32_t d) {
  asm volatile("red.relaxed.gpu.global.add.noftz.v4.bf16x2 [%0], {%1,%2,%3,%4};" ::"l"(p), "r"(a), "r"(b), "r"(c), "r"(d) : "memory");
}
__device__ __forceinline__ void red2(uint2* p, uint32_t a, uint32_t b) {
  asm volatile("red.relaxed.gpu.global.add.noftz.v2.bf16x2 [%0], {%1,%2};" ::"l"(p), "r"(a), "r"(b) : "memory");
}
constexpr int SPIN_MAX = 1 << 21;
__device__ __forceinline__ uint32_t pack_bf16(float lo, float hi) { uint32_t r; asm("cvt.rn.bf16x2.f32 %0, %1, %2;" : "=r"(r) : "f"(hi), "f"(lo)); return r; }
__device__ __forceinline__ float bf_lo(uint32_t v) { return __uint_as_float(v << 16); }
__device__ __forceinline__ float bf_hi(uint32_t v) { return __uint_as_float(v & 0xffff0000u); }
__device__ __forceinline__ float2 lds64(uint32_t a) { float2 v; asm volatile("ld.shared.v2.f32 {%0,%1}, [%2];" : "=f"(v.x), "=f"(v.y) : "r"(a)); return v; }
__device__ __forceinline__ void sts64f(uint32_t a, float x, float y) { asm volatile("st.shared.v2.f32 [%0], {%1,%2};" ::"r"(a), "f"(x), "f"(y) : "memory"); }
__device__ __forceinline__ void sts32(uint32_t a, uint32_t x) { asm volatile("st.volatile.shared.b32 [%0], %1;" ::"r"(a), "r"(x) : "memory"); }
__device__ __forceinline__ void gate(uint32_t a, int need) {
#pragma unroll 1
  for (int it = 0; it < SPIN_MAX; it++) {
    int v; asm volatile("ld.volatile.shared.b32 %0, [%1];" : "=r"(v) : "r"(a) : "memory");
    if (v >= need) break;
    if (GSLEEP) __nanosleep(GSLEEP);
  }
}
__device__ __forceinline__ void sts128(uint32_t a, uint32_t x, uint32_t y, uint32_t z, uint32_t u) { asm volatile("st.shared.v4.b32 [%0], {%1,%2,%3,%4};" ::"r"(a), "r"(x), "r"(y), "r"(z), "r"(u) : "memory"); }
__device__ __forceinline__ uint4 lds128(uint32_t a) { uint4 v; asm volatile("ld.shared.v4.u32 {%0,%1,%2,%3}, [%4];" : "=r"(v.x), "=r"(v.y), "=r"(v.z), "=r"(v.w) : "r"(a) : "memory"); return v; }
__device__ __forceinline__ uint32_t hmul2(uint32_t a, uint32_t b) { uint32_t r; asm("mul.rn.bf16x2 %0, %1, %2;" : "=r"(r) : "r"(a), "r"(b)); return r; }
__device__ __forceinline__ uint32_t hadd2(uint32_t a, uint32_t b) { uint32_t r; asm("add.rn.bf16x2 %0, %1, %2;" : "=r"(r) : "r"(a), "r"(b)); return r; }
__device__ __forceinline__ void stsm4(uint32_t a, uint32_t r0, uint32_t r1, uint32_t r2, uint32_t r3) {
  asm volatile("stmatrix.sync.aligned.m8n8.x4.shared.b16 [%0], {%1,%2,%3,%4};" ::"r"(a), "r"(r0), "r"(r1), "r"(r2), "r"(r3) : "memory");
}
__device__ __forceinline__ void stsm2(uint32_t a, uint32_t r0, uint32_t r1) {
  asm volatile("stmatrix.sync.aligned.m8n8.x2.shared.b16 [%0], {%1,%2};" ::"r"(a), "r"(r0), "r"(r1) : "memory");
}
__device__ __forceinline__ uint4 ldsm4(uint32_t a) {
  uint4 r; asm volatile("ldmatrix.sync.aligned.m8n8.x4.shared.b16 {%0,%1,%2,%3}, [%4];" : "=r"(r.x), "=r"(r.y), "=r"(r.z), "=r"(r.w) : "r"(a) : "memory"); return r;
}
__device__ __forceinline__ uint32_t movm(uint32_t a) { uint32_t r; asm("movmatrix.sync.aligned.m8n8.trans.b16 %0, %1;" : "=r"(r) : "r"(a)); return r; }
__device__ __forceinline__ void mma16816z(float (&d)[4], uint32_t a0, uint32_t a1, uint32_t a2, uint32_t a3, uint32_t b0, uint32_t b1) {
  asm("mma.sync.aligned.m16n8k16.row.col.f32.bf16.bf16.f32 {%0,%1,%2,%3}, {%4,%5,%6,%7}, {%8,%9}, {%10,%10,%10,%10};"
      : "=f"(d[0]), "=f"(d[1]), "=f"(d[2]), "=f"(d[3]) : "r"(a0), "r"(a1), "r"(a2), "r"(a3), "r"(b0), "r"(b1), "f"(0.f));
}
__device__ __forceinline__ void mma1688(float (&d)[4], uint32_t a0, uint32_t a1, uint32_t b0) {
  asm("mma.sync.aligned.m16n8k8.row.col.f32.bf16.bf16.f32 {%0,%1,%2,%3}, {%4,%5}, {%6}, {%0,%1,%2,%3};"
      : "+f"(d[0]), "+f"(d[1]), "+f"(d[2]), "+f"(d[3]) : "r"(a0), "r"(a1), "r"(b0));
}
__device__ __forceinline__ float quad_sum(float v) { v += __shfl_xor_sync(0xffffffffu, v, 1); v += __shfl_xor_sync(0xffffffffu, v, 2); return v; }
__device__ __forceinline__ float quad_max(float v) { v = fmaxf(v, __shfl_xor_sync(0xffffffffu, v, 1)); v = fmaxf(v, __shfl_xor_sync(0xffffffffu, v, 2)); return v; }
__device__ __forceinline__ float rcp(float x) { float r; asm("rcp.approx.ftz.f32 %0, %1;" : "=f"(r) : "f"(x)); return r; }
__device__ __forceinline__ float rsq(float x) { float r; asm("rsqrt.approx.ftz.f32 %0, %1;" : "=f"(r) : "f"(x)); return r; }
__device__ __forceinline__ float ex2(float x) { float r; asm("ex2.approx.ftz.f32 %0, %1;" : "=f"(r) : "f"(x)); return r; }
__device__ __forceinline__ uint32_t chk(uint32_t acc, uint32_t v, uint32_t tag) { uint32_t r; asm("lop3.b32 %0, %1, %2, %3, 0xF6;" : "=r"(r) : "r"(acc), "r"(v), "r"(tag)); return r; }
__device__ __forceinline__ uint32_t chk2(uint32_t a, uint32_t b, uint32_t tag) { uint32_t r; asm("lop3.b32 %0, %1, %2, %3, 0x7E;" : "=r"(r) : "r"(a), "r"(b), "r"(tag)); return r; }
__device__ __forceinline__ uint32_t tagged(uint32_t v, uint32_t tag) { return (v & ~1u) | tag; }

__device__ __forceinline__ int group_k0(int g) { return g < 16 ? 64 * (g & 7) + 4 * (g & 8) : 32 * g; }
__device__ __forceinline__ uint32_t xin_off(int c, int w) { return SM_X + (2 * c + w + (2 * c + w < 9 ? 9 : -9)) * 8192; }
__device__ __forceinline__ uint32_t xin_bar(int c) { return BAR_FULLX + 8 * (c < 8 ? c ^ 4 : c); }
__device__ __forceinline__ constexpr uint32_t qkv_xslot(int g) { return (0x5140762u >> (4 * (g - 5))) & 15; }

template <int N> struct IC { static constexpr int v = N; };
static_assert(WB4 <= 30 || WB4 == 36, "");

struct Cons {
  uint32_t sb;
  uint32_t rem;
  uint32_t sB, mB;
  uint32_t mX;
  bool elect;
  __device__ __forceinline__ void release2(uint32_t bar) const { if (elect) { mbar_arrive(sb + bar); mbar_arrive_remote(rem + bar); } }
  __device__ __forceinline__ uint32_t nextB(uint32_t& prev) {
    mbar_wait_c(sb + BAR_FULLB + sB, mB);
    const uint32_t a = (((sb & 0x3FFFF) + SM_B) >> 4) + sB * (BSLOT / 128);
    prev = sB == 0 ? 32 : sB - 8;
    sB += 8;
    if (sB == 40) { sB = 0; mB ^= 1; }
    return a;
  }
  __device__ __forceinline__ void progress(uint32_t v) const { if (elect) sts32(sb + SM_PROG + (threadIdx.x >> 5), v); }
  __device__ __forceinline__ void releaseLastB() const { release2(BAR_EMPTYB + (sB == 0 ? 32 : sB - 8)); }
};

template <bool QKV, class Pre, class Mma>
__device__ __forceinline__ float2 ln_gemm(Cons& c, Group* G, const float (&v)[36], uint32_t (&p)[18], bool direct, int w, int st0, int j, int t,
                                          uint32_t tag, uint32_t stag, Pre&& pre, Mma&& mma) {
  constexpr int NBUF = 6;
  const uint32_t pbase = direct ? 0 : 32;
  uint4* const box = G->act[QKV ? 0 : 2];
  uint4 x[NBUF][2];
  const uint4* src = box + t;
  uint32_t xa = c.sb + w * 8192 + (t >> 5) * 2048 + (t & 7) * 128 + (((t >> 3) & 3) ^ (t & 7)) * 16;
  asm volatile("" : "+l"(src), "+r"(xa));
  auto load = [&](int g) { x[g % NBUF][0] = ld_relaxed4(src + 2 * g * 128); x[g % NBUF][1] = ld_relaxed4(src + (2 * g + 1) * 128); };
  auto load_in = [&](int g) {
    if (!(g & 1)) mbar_wait_c(c.sb + xin_bar(g >> 1), 0);
    if (g == 8) xa -= w * 8 * XSLOT;
    if (g == 10) xa += w * 8 * XSLOT;
    if (g == 16) xa = c.sb + w * 8192 + (t >> 5) * 2048 + (t & 15) * 128 + (((t >> 4) & 1) ^ (t & 7)) * 16;
    const uint32_t a = xa ^ (64 * (g & 1));
    x[g % NBUF][0] = ldsm4(a + xin_off(g >> 1, 0));
    x[g % NBUF][1] = ldsm4((g < 16 ? a + 1024 : a ^ 32) + xin_off(g >> 1, 0));
  };
  float s0 = v[0] + v[1], s1 = v[2] + v[3];
#pragma unroll
  for (int i = 1; i < 9; i++) { s0 += v[4 * i] + v[4 * i + 1]; s1 += v[4 * i + 2] + v[4 * i + 3]; }
  s0 = quad_sum(s0); s1 = quad_sum(s1);
  const uint32_t s0t = (__float_as_uint(s0) & ~3u) | stag;
  if (SUMFIRST && (t & 3) == 0) st_relaxed2(G->sum + st0 + 8 * j, s0t, __float_as_uint(s1));
#pragma unroll
  for (int i = 0; i < 18; i++) p[i] = pack_bf16(v[2 * i], v[2 * i + 1]);
  uint4* const d = box + 2 * j * 128 + t;
  if (!direct) {
#pragma unroll
    for (int i = 0; i < 2; i++) st_relaxed4(d + i * 128, tagged(p[i], tag), p[i + 2], p[i + 4], p[i + 6]);
  }
  if (!SUMFIRST && (t & 3) == 0) st_relaxed2(G->sum + st0 + 8 * j, s0t, __float_as_uint(s1));
  const int sq = st0 + 16 * (t & 3);
  uint2 sa, sc;
  const bool spec = SPEC && (QKV ? !direct : !tag);
#pragma unroll
  for (int g = 0; g < NBUF; g++) x[g][0] = x[g][1] = make_uint4(tag ^ 1, 0, 0, 0);
  auto load3 = [&](int g) { load(g); load(g + 1); load(g + 2); };
  auto invalid = [&](int g) {
    const uint4 (&y)[2] = x[g % NBUF], (&y1)[2] = x[(g + 1) % NBUF], (&y2)[2] = x[(g + 2) % NBUF];
    uint32_t bad = chk2(y[0].x, y[1].x, tag) | chk2(y1[0].x, y1[1].x, tag) | chk2(y2[0].x, y2[1].x, tag);
    if (g == 15) bad |= chk2(y1[0].z, y1[1].z, tag) | chk2(y2[0].z, y2[1].z, tag);
    return __any_sync(0xffffffffu, bad & 1);
  };
  auto poll = [&] {
    if (spec && invalid(0)) load3(0);
    sa = ld_relaxed2(G->sum + sq); sc = ld_relaxed2(G->sum + sq + 8);
  };
  if (EARLYPOLL) poll();
  float d0 = 0.f, d1 = 0.f;
  {
    const float m0 = s0 * (1.f / 72), m1 = s1 * (1.f / 72);
#pragma unroll
    for (int i = 0; i < 9; i++) {
      float a = v[4 * i] - m0, b = v[4 * i + 1] - m0; d0 = fmaf(a, a, fmaf(b, b, d0));
      a = v[4 * i + 2] - m1; b = v[4 * i + 3] - m1; d1 = fmaf(a, a, fmaf(b, b, d1));
    }
    d0 = quad_sum(d0); d1 = quad_sum(d1);
  }
  pre(0);
  if (!EARLYPOLL) poll();
  while (__any_sync(0xffffffffu, ((sa.x ^ stag) | (sc.x ^ stag)) & 3)) poll();
  if (!direct && invalid(0)) load3(0);
  const float m0 = quad_sum(__uint_as_float(sa.x) + __uint_as_float(sc.x)) * (-1.f / 576), m1 = quad_sum(__uint_as_float(sa.y) + __uint_as_float(sc.y)) * (-1.f / 576);
  const uint32_t nm0 = pack_bf16(m0, m0), nm1 = pack_bf16(m1, m1);
  pre(1);
  uint4 u0, u1;
#pragma unroll
  for (int g = 0; g < 18; g++) {
    uint4 &a = x[g % NBUF][0], &b = x[g % NBUF][1];
    if (direct) load_in(g);
    else if (g % 3 == 0) {
      while (invalid(g)) load3(g);
      if (g > 0 && g < 15) load3(g + 3);
    }
    const bool rows = g < 16;
    const uint4 f0 = make_uint4(hadd2(a.x, nm0), hadd2(rows ? b.x : a.y, nm1), hadd2(rows ? a.y : a.z, nm0), hadd2(rows ? b.y : a.w, nm1));
    const uint4 f1 = make_uint4(hadd2(rows ? a.z : b.x, nm0), hadd2(rows ? b.z : b.y, nm1), hadd2(rows ? a.w : b.z, nm0), hadd2(b.w, nm1));
    if (g == 12) { u0 = ld_relaxed4(G->m2 + sq); u1 = ld_relaxed4(G->m2 + sq + 8); }
    uint32_t prev = c.sB == 0 ? 32 : c.sB - 8, bb;
    if (QKV && g >= 5 && g < 12 && !direct) {
      mbar_wait_c(c.sb + BAR_FULLX + 8 * qkv_xslot(g), (c.mX >> qkv_xslot(g)) & 1);
      bb = ((c.sb & 0x3FFFF) + SM_X + qkv_xslot(g) * XSLOT) >> 4;
    } else {
      bb = c.nextB(prev);
    }
    if (QKV && g == GL && w == 1) asm volatile("bar.sync 6, 256;" ::: "memory");
    mma(g, bb, f0, f1);
    if (QKV && g == 17 && w == 0) asm volatile("bar.arrive 6, 256;" ::: "memory");
    if (g == 0) {
      if (!direct) {
        load3(3);
#pragma unroll
        for (int i = 0; i < 2; i++) st_relaxed4(d + (16 + i) * 128, tagged(p[8 + i], tag), p[10 + i], p[12 + i], p[14 + i]);
        st_relaxed2((uint2*)(box + (32 + (j >> 1)) * 128 + t) + (j & 1), tagged(p[16], tag), p[17]);
      }
      if ((t & 3) == 0) st_relaxed4(G->m2 + st0 + 8 * j, s0t, __float_as_uint(s1), __float_as_uint(d0), __float_as_uint(d1));
      c.progress(QKV ? pbase + 1 : 53 - 32 * tag);
    }
    wg_wait<1>();
    if (g > 0 && !(QKV && g > 5 && g <= 12 && !direct)) c.release2(BAR_EMPTYB + prev);
    if (SCHEDBAR && !QKV && g % 3 == 2 && g < 17) mbar_wait_c(c.sb + BAR_FULLX + 64, 0);
    if (QKV && g > 0 && g < 15) c.progress(pbase + 1 + g);
    if (QKV && g == 13 && t < 4) { mbar_arrive(c.sb + BAR_EMPTYX + 32 + 8 * t); mbar_arrive_remote(c.rem + BAR_EMPTYX + 32 + 8 * t); }
  }
  if (QKV) c.mX ^= direct ? 0xff : 0xf7;
  while (__any_sync(0xffffffffu, ((u0.x ^ stag) | (u1.x ^ stag)) & 3)) { u0 = ld_relaxed4(G->m2 + sq); u1 = ld_relaxed4(G->m2 + sq + 8); }
  float e0 = fmaf(__uint_as_float(u0.x), 1.f / 72, m0), e1 = fmaf(__uint_as_float(u1.x), 1.f / 72, m0);
  const float v0 = quad_sum(fmaf(72.f, fmaf(e0, e0, e1 * e1), __uint_as_float(u0.z) + __uint_as_float(u1.z)));
  e0 = fmaf(__uint_as_float(u0.y), 1.f / 72, m1); e1 = fmaf(__uint_as_float(u1.y), 1.f / 72, m1);
  const float v1 = quad_sum(fmaf(72.f, fmaf(e0, e0, e1 * e1), __uint_as_float(u0.w) + __uint_as_float(u1.w)));
  float2 r = make_float2(rsq(fmaf(v0, 1.f / 576, 1e-5f)), rsq(fmaf(v1, 1.f / 576, 1e-5f)));
  asm volatile("" : "+f"(r.x), "+f"(r.y));
  if (QKV && GL == 18 && w == 1) asm volatile("bar.sync 6, 256;" ::: "memory");
  wg_wait<0>();
  if (QKV && ATTBAR && w == 1) asm volatile("bar.arrive 4, 256;" ::: "memory");
  c.releaseLastB();
  if (direct) c.release2(BAR_EMPTYX + 24);
  return r;
}

template <int NB, int OFF>
__device__ __forceinline__ void glu(const float (&a)[128], uint32_t (&h)[144]) {
#pragma unroll
  for (int b = 0; b < 2 * NB; b++) {
    if (HMUL) h[OFF + b] = hmul2(pack_bf16(a[2 * b], a[2 * b + 1]), pack_bf16(a[4 * NB + 2 * b], a[4 * NB + 2 * b + 1]));
    else h[OFF + b] = pack_bf16(a[2 * b] * a[4 * NB + 2 * b], a[2 * b + 1] * a[4 * NB + 2 * b + 1]);
  }
}

__global__ void __cluster_dims__(2, 1, 1) __launch_bounds__(384, 1)
fused_kernel(const __nv_bfloat16* __restrict__ x_in, Group* ws, const char* __restrict__ wqkv,
             const char* __restrict__ wg, const char* __restrict__ wu, const char* __restrict__ wd, const __grid_constant__ Maps maps,
             const char* __restrict__ wo) {
  extern __shared__ __align__(1024) uint8_t smem_raw[];
  const uint32_t sb = smem_u32(smem_raw);
  const int warp = __shfl_sync(0xffffffffu, threadIdx.x >> 5, 0);
  const int lane = threadIdx.x & 31;
  const int rank = blockIdx.x & 1;
  if (elect_one()) {
    if (warp >= 8) {
#pragma unroll
      for (int i = 0; i < 9; i++) mbar_init(sb + SM_BAR + 72 * (warp - 8) + 8 * i, warp < 10 ? 1 : 4);
      sts32(sb + SM_PROG + 4 * (warp - 8), 0);
      asm volatile("fence.mbarrier_init.release.cluster;" ::: "memory");
    } else if (warp < 3) {
      asm volatile("prefetch.tensormap [%0];" ::"l"(&maps.x + warp) : "memory");
    } else if (warp == 3) {
      if (PFMODE & 1) prefetch_l2((const char*)x_in + blockIdx.x * 18432, 18432);
    } else if (warp == 4) {
      if (PFMODE & 2) prefetch_l2(wqkv + blockIdx.x * (15552 / PFQ), 15552 / PFQ);
    }
  }
  __syncwarp();
  asm volatile("barrier.cluster.arrive.relaxed.aligned;" ::: "memory");
  if (warp == 8) PROFX(53);
  int lb = blockIdx.x;
  if (GPCMAP) {
    const int cl = blockIdx.x >> 1, u = cl - 36;
    lb = (cl < 4 ? cl : cl < 36 ? 8 * ((cl - 4) & 7) + ((cl - 4) >> 3) + (((cl - 4) & 7) ? 0 : 4) : 8 * (1 + u % 7) + 4 + u / 7) * 2 + rank;
  }
#define CTA_J(b) (((b) >> 1) & 7)
#define CTA_RB(b) ((((b) >> 4) << 1) | ((b) & 1))
  const int j = CTA_J(lb), rb = CTA_RB(lb);

  PROF(23);
  if (warp >= 8) {
    asm volatile("setmaxnreg.dec.sync.aligned.u32 " STR(REGS_P) ";");
    auto x_chunk = [&](int cc) {
      mbar_expect_tx(sb + xin_bar(cc), 16384);
      tma3d(sb + xin_off(cc, 0), &maps.x, 64 * cc, 0, 64 * rb, sb + xin_bar(cc));
      tma3d(sb + xin_off(cc, 1), &maps.x, 64 * cc, 1, 64 * rb, sb + xin_bar(cc));
    };
    if (warp == 9 && elect_one()) { fence_async_smem(); x_chunk(j); x_chunk(8); }
    __syncwarp();
    if (warp == 9) PROFX(54);
    asm volatile("barrier.cluster.wait.aligned;" ::: "memory");
    if (warp == 8) PROFX(56);
    const uint64_t pol = W_POLICY(), pola = A_POLICY();
    auto qkv_group = [&](int k, uint32_t dst, uint32_t bar) {
      wtma3d(dst + rank * 8192, &maps.qm, 72 * j, k + 16 * rank, 0, bar, pola);
      wtma3d(dst + rank * 8192 + 6144, &maps.qc, 72 * j + 64, k + 16 * rank, 0, bar, pola);
    };
    auto qkv_gate = [&](int g) { if (g >= 8) gate(sb + SM_PROG, 33 + ((g - 8) * 23 >> 4)); };
    if (warp == 8) {
      uint32_t s = 0, ph = 1;
      auto slot = [&](uint32_t bytes, auto&& issue) {
        const uint32_t bar = sb + BAR_FULLB + 8 * s;
        mbar_wait(sb + BAR_EMPTYB + 8 * s, ph);
        if (elect_one()) {
          mbar_expect_tx(bar, bytes);
          issue(sb + SM_B + s * BSLOT, bar);
        }
        if (++s == 5) { s = 0; ph ^= 1; }
      };
#pragma unroll 1
      for (int layer = 0; layer < NLAYERS; layer++) {
#pragma unroll 1
        for (int g = 0; g < 18; g += layer && g == 4 ? 8 : 1) {
          if (layer) qkv_gate(g);
          else if (g >= QD && g < 5) { mbar_wait(sb + BAR_FULLB + 8 * (g - QD), 0); if (g >= QH) gate(sb + SM_PROG, 1); }
          slot(2 * 6912, [&](uint32_t dst, uint32_t bar) { qkv_group(layer ? group_k0(g) : 32 * g, dst, bar); });
        }
        if (!FCH) {
          gate(sb + SM_PROG, 32 * layer + 20);
          gate(sb + SM_PROG + 4, 32 * layer + 20);
        }
#pragma unroll 1
        for (int t = 0; t < 5; t++) {
          const CUtensorMap* m = &maps.g + (t < 3 ? rank : 2 + rank);
          const int c2 = t < 3 ? 9 * j + 2 * t : 18 * j + 3 + 3 * t;
          const uint32_t half = t < 3 ? 8192 : 6144;
#pragma unroll 1
          for (int g = 0; g < 18; g++) {
            if (FCH && t == 0 && g < 5) mbar_wait(sb + BAR_FULLB + 8 * (s < FCH ? s + 5 - FCH : s - FCH), s < FCH ? ph : ph ^ 1);
            slot(2 * half, [&](uint32_t dst, uint32_t bar) { wtma3d(dst + rank * half, m, 0, group_k0(g), c2, bar, pol); });
          }
        }
      }
    } else if (warp == 9) {
      uint32_t mE = 0;
      {
        int p1 = 8, p2 = j;
#pragma unroll 1
        for (int cc = 0; cc < 8; cc++) {
          if (cc == j) continue;
          mbar_wait(sb + xin_bar(p2), 0);
          gate(sb + SM_PROG, max(2 * cc - QG, cc >= XH ? 1 : 0));
          if (elect_one()) x_chunk(cc);
          p2 = p1; p1 = cc;
        }
      }
      auto acquire = [&](uint32_t s) { mbar_wait(sb + BAR_EMPTYX + 8 * s, (mE >> s) & 1); mE ^= 1u << s; };
      auto slot = [&](uint32_t s, const CUtensorMap* m, int col, int row, uint64_t pol) {
        acquire(s);
        if (elect_one()) {
          mbar_expect_tx(sb + BAR_FULLX + 8 * s, XSLOT);
          wtma2d(sb + SM_X + s * XSLOT + rank * 9216, m, col, row + 72 * rank, sb + BAR_FULLX + 8 * s, pol);
        }
      };
#pragma unroll 1
      for (int layer = 0; layer < NLAYERS; layer++) {
#pragma unroll 1
        for (int g = 5; g < 12 * layer; g++) {
          const uint32_t s = qkv_xslot(g);
          qkv_gate(g);
          acquire(s);
          if (elect_one()) {
            mbar_expect_tx(sb + BAR_FULLX + 8 * s, 2 * 6912);
            qkv_group(group_k0(g), sb + SM_X + s * XSLOT, sb + BAR_FULLX + 8 * s);
          }
        }
#pragma unroll 1
        for (int i = 0; i < 4; i++) slot(4 + i, &maps.o, 64 * j, 144 * i, pola);
        acquire(3);
        if (elect_one()) {
          mbar_expect_tx(sb + BAR_FULLX + 24, 9216);
          wtma2d(sb + SM_WOC + rank * 4608, &maps.oc, 512 + 8 * j, 288 * rank, sb + BAR_FULLX + 24, pola);
          wtma2d(sb + SM_WOC + rank * 4608 + 2304, &maps.oc, 512 + 8 * j, 288 * rank + 144, sb + BAR_FULLX + 24, pola);
        }
#pragma unroll 1
        for (int u = 0; u < 36; u++) slot(4 * (u & 1) + ((u >> 1) & 3), &maps.d, u < 4 ? 512 : 64 * ((j + (u >> 2)) & 7), 576 * j + 144 * (u & 3), pol);
      }
    } else {
      const int w = warp - 10, grp = 2 * rb + w;
      gate(sb + SM_PROG, 3);
      if (w == 0) PROFX(58);
      auto prefetch_gu = [&](int l0, int n) {
#pragma unroll 1
        for (int i = lane; i < 36 * n; i += 32) {
          asm volatile("prefetch.global.L2 [%0];" ::"l"((w ? wu : wg) + (size_t)(36 * rb + i / n) * 9216 + 1152 * j + 128 * (l0 + i % n)));
          __nanosleep(PFSLEEP);
        }
      };
      auto clear = [&](uint4* p, int n) {
#pragma unroll 1
        for (int i = lane; i < n; i += 64) { st_relaxed4(p + i, 0, 0, 0, 0); st_relaxed4(p + i + 32, 0, 0, 0, 0); __nanosleep(CLRSLEEP); }
      };
      auto exchange = [&](uint32_t v, uint32_t bar) {
        fence_gpu();
        __syncwarp();
        if (lane == 0) st_relaxed(ws[grp].flag + j, v);
#pragma unroll 1
        for (int it = 0; it < SPIN_MAX; it++) {
          const uint32_t f = ld_relaxed(ws[grp].flag + (lane & 7));
          if (__all_sync(0xffffffffu, v ? f >= v : f == 0)) break;
        }
        if (lane == 0) mbar_arrive(sb + bar + 8 * w);
      };
      if (lane == 0) prefetch_l2(wo + (2 * blockIdx.x + w) * 2592, 2592);
#pragma unroll 1
      for (int layer = 0; layer < NLAYERS; layer++) {
        gate(sb + SM_PROG, 32 * layer + 3);
        if (PFF & 1) prefetch_gu(0, 2);
        gate(sb + SM_PROG, 32 * layer + 22);
        if (PFF & 2) prefetch_gu(2, 2);
        if (layer == 0) {
          clear(ws[grp].act[0] + 576 * j, 576);
          clear(ws[grp].inbox[0] + 2 * j * INBOX, 2 * INBOX);
          exchange(1, BAR_CLR);
          if (w == 0) PROFX(59);
        }
        if (PFF & 2) prefetch_gu(4, 2);
        if (PFF & 4) prefetch_gu(6, 3);
#pragma unroll 1
        for (int i = lane; i < ((PFF & 8) ? 162 : 0); i += 32) {
          asm volatile("prefetch.global.L2 [%0];" ::"l"(wd + (size_t)(576 * j + 36 * rb + 18 * w) * 1152 + 128 * i));
          __nanosleep(PFSLEEP);
        }
        if (w == 0 && layer == 0) PROFX(60);
        mbar_wait(sb + BAR_REDDONE + 8 * w, layer);
        if (w == 0) PROFX(64 + 53 + 4 * layer);
        exchange(2 - 2 * layer, BAR_RREADY);
        if (w == 0) PROFX(64 + 56 + 4 * layer);
      }
      mbar_wait(sb + BAR_DONE + 8 * w, 0);
    }
    __syncwarp();
    cluster_sync();
  } else {
    asm volatile("setmaxnreg.inc.sync.aligned.u32 " STR(REGS_C) ";");
#define THREAD_IDS()                                                                   \
    int tid_ = threadIdx.x, bid_ = lb;                                                  \
    asm volatile("" : "+r"(tid_), "+r"(bid_));                                          \
    const int w = warp >> 2, wp = warp & 3;                                             \
    const int lane = tid_ & 31, t = tid_ & 127, g = lane >> 2, q = lane & 3;           \
    const int j = CTA_J(bid_), rb = CTA_RB(bid_), grp = 2 * rb + w;                    \
    const int st0 = wp * 64 + g;                         \
    Group* const G = ws + grp;                                                         \
    const uint32_t dsb = (sb & 0x3FFFF) >> 4;                                          \
    (void)t; (void)g; (void)q; (void)grp; (void)j; (void)st0; (void)dsb; (void)G
    Cons c;
    c.sb = sb; c.sB = 0; c.mB = 0; c.mX = 0; c.elect = (threadIdx.x & 127) == 0;
    asm volatile("mapa.shared::cluster.u32 %0, %1, %2;" : "=r"(c.rem) : "r"(sb), "r"(rank ^ 1));
    float v[36];
    {
      THREAD_IDS();
      if (OPEN) {
        if (q == 0) { st_relaxed2(G->sum + st0 + 8 * j, 0, 0); st_relaxed4(G->m2 + st0 + 8 * j, 0, 0, 0, 0); }
        if (wp == 3) {
#pragma unroll
          for (int i = 0; i < 5; i++) st_relaxed4(G->halo + j * 160 + lane + i * 32, 0, 0, 0, 0);
        }
      }
      asm volatile("barrier.cluster.wait.aligned;" ::: "memory");
      PROF(0);
      const uint32_t ro = sb + wp * 2048 + (lane & 15) * 128;
      mbar_wait_c(sb + xin_bar(j), 0);
#pragma unroll
      for (int i = 0; i < 5; i++) {
        if (i == 4) mbar_wait_c(sb + BAR_FULLX + 64, 0);
        const uint4 u = ldsm4(ro + xin_off(i < 4 ? j : 8, w) + (((i < 4 ? 2 * i + (lane >> 4) : j) ^ (lane & 7)) << 4));
        v[8 * i] = bf_lo(u.x); v[8 * i + 1] = bf_hi(u.x); v[8 * i + 2] = bf_lo(u.y); v[8 * i + 3] = bf_hi(u.y);
        if (i < 4) { v[8 * i + 4] = bf_lo(u.z); v[8 * i + 5] = bf_hi(u.z); v[8 * i + 6] = bf_lo(u.w); v[8 * i + 7] = bf_hi(u.w); }
      }
    }
#pragma unroll 1
    for (int layer = 0;; layer++) {
      const uint32_t tag = layer ^ 1;
      const int pb = 1 + layer * 30;
      uint32_t res[18];
      {
        THREAD_IDS();
        PROF(pb + 0);
        float a1[96], a2[12];
        const float2 rs = ln_gemm<true>(c, G, v, res, layer == 0, w, st0, j, t, 1, 2 * layer + 1,
          [&](int i) { PROF(pb + 1 + i); },
          [&](int gi, uint32_t bb, const uint4& f0, const uint4& f1) {
            if (gi == 0) PROF(pb + 3);
            wg_fence();
            wgmma_ra<192>(a1, f0, desc_hi(2048, 1024, 1) + bb, gi > 0);
            wgmma_ra<24>(a2, f0, desc_hi(128, 256, 0) + (bb + 384), gi > 0);
            wgmma_ra<192>(a1, f1, desc_hi(2048, 1024, 1) + (bb + 512), true);
            wgmma_ra<24>(a2, f1, desc_hi(128, 256, 0) + (bb + 896), true);
            wg_commit();
          });
        PROF(pb + 4);
        uint32_t kv[3][18];
        auto cvt = [&](int b, float r) {
#pragma unroll
          for (int cc = 0; cc < 18; cc++) {
            const float* a = (cc == 8 ? a2 + 4 : cc == 17 ? a2 + 8 : cc < 8 ? a1 + 32 + 4 * cc : a1 + 28 + 4 * cc) + 2 * (b - 1);
            const uint32_t u = pack_bf16(a[0] * r, a[1] * r);
            kv[b][cc] = cc < 9 ? u : movm(u);
          }
        };
        cvt(2, rs.y);
        const uint32_t msg = sb + SM_X + (w ? 3 * XSLOT : 24576) + wp * 2304 + lane * 16;
        if (wp == 3) {
          uint4* hp = G->halo + j * 160 + lane;
#pragma unroll
          for (int i = 0; i < 4; i++) st_relaxed4(hp + i * 32, tagged(kv[2][4 * i], tag), kv[2][4 * i + 1], kv[2][4 * i + 2], kv[2][4 * i + 3]);
          st_relaxed2((uint2*)(hp + 128), tagged(kv[2][16], tag), kv[2][17]);
        } else {
#pragma unroll
          for (int i = 0; i < 4; i++) sts128(msg + i * 512, kv[2][4 * i], kv[2][4 * i + 1], kv[2][4 * i + 2], kv[2][4 * i + 3]);
          sts64f(msg + 2048 - lane * 8, __uint_as_float(kv[2][16]), __uint_as_float(kv[2][17]));
        }
        cvt(1, rs.x);
        uint32_t Q[4][6];
#pragma unroll
        for (int h = 0; h < 4; h++)
#pragma unroll
          for (int i = 0; i < 6; i++) {
            const float* a = 4 * h + i < 16 ? a1 + 8 * h + 2 * i : a2 + 8 * h + 2 * i - 32;
            const uint32_t u = pack_bf16(a[0], a[1]);
            Q[h][i] = i < 2 ? (q >= h ? u : 0) : i < 4 ? u : (q <= h ? u : 0);
          }
        const bool lo0 = 2 * q > g, lo1 = 2 * q + 1 > g;
        const uint32_t M = (lo0 ? 0xffffu : 0u) | (lo1 ? 0xffff0000u : 0u);
        auto scores = [&](int h, int b, float (&s)[4]) {
          mma16816z(s, Q[h][0], Q[h][1], Q[h][2], Q[h][3], kv[b][2 * h], kv[b][2 * h + 1]);
          mma1688(s, Q[h][4], Q[h][5], kv[b][2 * h + 2]);
        };
        auto softmax = [&](float (&l)[4][2], float r, uint32_t (&P)[4]) {
          const float sl = r * (0.23570226039551584f * 1.4426950408889634f);
          float m[4];
#pragma unroll
          for (int h = 0; h < 4; h++) { m[h] = fmaxf(l[h][0], l[h][1]); m[h] = fmaxf(m[h], __shfl_xor_sync(0xffffffffu, m[h], 1)); }
#pragma unroll
          for (int h = 0; h < 4; h++) m[h] = fmaxf(m[h], __shfl_xor_sync(0xffffffffu, m[h], 2)) * sl;
#pragma unroll
          for (int h = 0; h < 4; h++) {
            l[h][0] = ex2(fmaf(l[h][0], sl, -m[h])); l[h][1] = ex2(fmaf(l[h][1], sl, -m[h]));
            m[h] = l[h][0] + l[h][1]; m[h] += __shfl_xor_sync(0xffffffffu, m[h], 1);
          }
#pragma unroll
          for (int h = 0; h < 4; h++) { m[h] = rcp(m[h] + __shfl_xor_sync(0xffffffffu, m[h], 2)); P[h] = pack_bf16(l[h][0] * m[h], l[h][1] * m[h]); }
        };
        const bool remote = wp == 0 && rb > 0;
        const uint4* hp = (G - 2)->halo + j * 160 + lane;
        auto halo = [&] {
#pragma unroll
          for (int i = 0; i < 4; i++) { const uint4 u = ld_relaxed4(hp + i * 32); kv[0][4 * i] = u.x; kv[0][4 * i + 1] = u.y; kv[0][4 * i + 2] = u.z; kv[0][4 * i + 3] = u.w; }
          const uint2 u = ld_relaxed2((const uint2*)(hp + 128));
          kv[0][16] = u.x; kv[0][17] = u.y;
        };
#pragma unroll
        for (int i = 0; i < 18; i++) kv[0][i] = 0;
        if (remote) halo();
        if (ATTBAR && w == 0) asm volatile("bar.sync 4, 256;" : "+r"(Q[0][2]), "+r"(Q[1][2]), "+r"(Q[2][2]), "+r"(Q[3][2]) :: "memory");
        float l0[4][2], l1[4][2];
#pragma unroll
        for (int h = 0; h < 4; h++) {
          float s1[4], s2[4];
          scores(h, 1, s1); scores(h, 2, s2);
          l0[h][0] = s1[0]; l0[h][1] = s1[1];
          l1[h][0] = lo0 ? s1[2] : s2[2]; l1[h][1] = lo1 ? s1[3] : s2[3];
        }
        uint32_t P0[4], P1[4];
        softmax(l1, rs.y, P1);
        if (remote) {
          while (__any_sync(0xffffffffu, chk(chk2(kv[0][0], kv[0][4], tag) | chk2(kv[0][8], kv[0][12], tag), kv[0][16], tag) & 1)) halo();
        }
        if (FG < 0) c.progress(32 * layer + 20);
        wg_bar(w);
        if (wp > 0) {
          const uint32_t from = msg - 2304;
#pragma unroll
          for (int i = 0; i < 4; i++) { const uint4 u = lds128(from + i * 512); kv[0][4 * i] = u.x; kv[0][4 * i + 1] = u.y; kv[0][4 * i + 2] = u.z; kv[0][4 * i + 3] = u.w; }
          const float2 u = lds64(from + 2048 - lane * 8);
          kv[0][16] = __float_as_uint(u.x); kv[0][17] = __float_as_uint(u.y);
        }
        PROF(pb + 5);
        const bool first = (rb == 0 && wp == 0);
#pragma unroll
        for (int h = 0; h < 4; h++) {
          float s0[4];
          scores(h, 0, s0);
          if (first) s0[0] = s0[1] = -INFINITY;
          l0[h][0] = lo0 ? s0[0] : l0[h][0]; l0[h][1] = lo1 ? s0[1] : l0[h][1];
        }
        softmax(l0, rs.x, P0);
        uint4* ob = G->act[1] + t;
        uint32_t car0 = 0, car1 = 0;
#pragma unroll
        for (int h = 0; h < 4; h++) {
          float o[3][4];
#pragma unroll
          for (int i = 0; i < 3; i++) {
            mma16816z(o[i], P0[h] & ~M, P1[h] & M, 0u, P1[h] & ~M, kv[1][9 + 2 * h + i], kv[2][9 + 2 * h + i]);
            mma1688(o[i], P0[h] & M, 0u, kv[0][9 + 2 * h + i]);
          }
          const uint32_t o0 = q < h ? car0 : pack_bf16(o[0][0], o[0][1]), o1 = q < h ? car1 : pack_bf16(o[0][2], o[0][3]);
          st_relaxed4(ob + (8 * h + j) * 128, tagged(o0, tag), o1, pack_bf16(o[1][0], o[1][1]), pack_bf16(o[1][2], o[1][3]));
          car0 = pack_bf16(o[2][0], o[2][1]); car1 = pack_bf16(o[2][2], o[2][3]);
        }
        st_relaxed2((uint2*)(ob + (32 + (j >> 1)) * 128) + (j & 1), tagged(car0, tag), car1);
        PROF(pb + 6);
      }
      {
        THREAD_IDS();
        const uint4* src = G->act[1] + t;
        float a[32], a8[4];
#pragma unroll
        for (int i = 3; i < 8; i++) mbar_wait_c(sb + BAR_FULLX + 8 * i, (c.mX >> i) & 1);
        c.mX ^= 0xf8;
        const uint32_t* probe = &(G->act[1] + (8 * WPROBE + (lane & 7)) * 128 + (t | 31))->x;
        while (__any_sync(0xffffffffu, (ld_relaxed(probe) ^ tag) & 1)) {}
        if (w == 1) asm volatile("bar.sync 7, 256;" ::: "memory");
        uint4 x[36];
        auto batch = [&](auto e0, auto e1, auto e2, int b) {
          constexpr int E0 = decltype(e0)::v, E1 = decltype(e1)::v, E2 = decltype(e2)::v;
          while (E1 > E0) {
            uint32_t bad = chk2(x[E0].x, x[E0 + 1].x, tag);
#pragma unroll
            for (int i = E0 + 2; i < E1; i++) { bad = chk(bad, x[i].x, tag); if (i >= 32) bad = chk(bad, x[i].z, tag); }
            if (!__any_sync(0xffffffffu, bad & 1)) break;
#pragma unroll
            for (int i = E0; i < E1; i++) x[i] = ld_relaxed4(src + i * 128);
          }
          if (b == 0) PROF(pb + 7);
#pragma unroll
          for (int i = E1; i < E2; i++) x[i] = ld_relaxed4(src + i * 128);
          if (b == WOREL && w == 0) asm volatile("bar.arrive 7, 256;" ::: "memory");
          if (E1 > E0) {
            wg_fence();
#pragma unroll
            for (int i = E0; i < E1; i++) {
              const int r0 = i < 32 ? 72 * (i & 7) + 16 * (i >> 3) : 144 * (i - 32) + 64, rs = i < 32 ? 8 : 72;
              wgmma_ra<64>(a, x[i], desc_hi(0, rs * 128, 1) + (dsb + ((SM_X + 4 * XSLOT) >> 4) + r0 * 8), i > 0);
              wgmma_ra<8>(a8, x[i], desc_hi(rs * 16, 0, 0) + (dsb + (SM_WOC >> 4) + r0), i > 0);
            }
            wg_commit();
            if (SCHEDBAR && E1 < 36) mbar_wait_c(sb + BAR_FULLX + 64, 0);
          }
        };
        batch(IC<0>(), IC<0>(), IC<WB1>(), -1);
        batch(IC<0>(), IC<WB1>(), IC<WB2>(), 0);
        batch(IC<WB1>(), IC<WB2>(), IC<WB3>(), 1);
        batch(IC<WB2>(), IC<WB3>(), IC<WB4>(), 2);
        batch(IC<WB3>(), IC<WB4>(), IC<36>(), 3);
        batch(IC<WB4>(), IC<36>(), IC<36>(), 4);
        wg_wait<0>();
        if (w == 0) asm volatile("bar.arrive 3, 256;" ::: "memory");
        PROF(pb + 8);
#pragma unroll
        for (int i = 0; i < 18; i++) {
          v[2 * i] = bf_lo(res[i]) + (i < 16 ? a[2 * i] : a8[2 * i - 32]);
          v[2 * i + 1] = bf_hi(res[i]) + (i < 16 ? a[2 * i + 1] : a8[2 * i - 31]);
        }
      }
      uint32_t lsb;
      uint32_t h[144];
      {
        THREAD_IDS();
        float a[128];
        const uint32_t xd = sb + SM_X + w * 4 * XSLOT + (lane >> 4) * 1024 + (16 * wp + (lane & 15)) * 16;
        const float2 rs = ln_gemm<false>(c, G, v, res, false, w, st0, j, t, tag, (2 * layer + 2) & 3,
          [&](int i) {
            if (i == 0) {
              lsb = ((res[0] & 1) | (res[1] & 1) << 1 | (res[8] & 1) << 2 | (res[9] & 1) << 3 | (res[16] & 1) << 4) ^ (tag * 31);
              if (w == 1) asm volatile("bar.sync 3, 256;" ::: "memory");
            }
            PROF(pb + 9 + i);
          },
          [&](int gi, uint32_t bb, const uint4& f0, const uint4& f1) {
            if (gi == 0) PROF(pb + 11);
            wg_fence();
            wgmma_ra<256>(a, f0, desc_hi(4096, 1024, 1) + bb, gi > 0);
            wgmma_ra<256>(a, f1, desc_hi(4096, 1024, 1) + (bb + 128), true);
            wg_commit();
            stsm4(xd + gi * 4096, f0.x, f0.y, f0.z, f0.w);
            stsm4(xd + gi * 4096 + 2048, f1.x, f1.y, f1.z, f1.w);
            if (gi == 17) { fence_async_smem(); wg_bar(w); }
          });
        sts64f(sb + SM_KEEP + tid_ * 8, rs.x * rs.x, rs.y * rs.y);
        c.progress(32 * layer + 22);
        PROF2(pb + 12);
        glu<16, 0>(a, h);
        const uint64_t da0 = desc_hi(1024, 128, 0) + (dsb + ((SM_X + w * 4 * XSLOT) >> 4));
        auto tile = [&](auto wide, auto last) {
          const uint32_t xe = BAR_EMPTYX + 8 * (t & 1) + 16 * (t & 2);
#pragma unroll 1
          for (int gi = 0; gi < 18; gi++) {
            uint32_t prev;
            const uint32_t bb = c.nextB(prev);
            const uint64_t da = da0 + gi * 256;
            wg_fence();
            if (wide()) {
              wgmma_ss<256>(a, da, desc_hi(4096, 1024, 1) + bb, gi);
              wgmma_ss<256>(a, da + 128, desc_hi(4096, 1024, 1) + (bb + 128), 1);
            } else {
              wgmma_ss<192>(*(float(*)[96])a, da, desc_hi(2048, 512, 2) + bb, gi);
              wgmma_ss<192>(*(float(*)[96])a, da + 128, desc_hi(2048, 512, 2) + (bb + 64), 1);
            }
            wg_commit();
            wg_wait<1>();
            if (gi > 0 && !(last() && gi > 13)) c.release2(BAR_EMPTYB + prev);
            if (last() && gi == 12 && t < 4) { mbar_arrive(sb + xe); mbar_arrive_remote(c.rem + xe); }
          }
          wg_wait<0>();
          if (!last()) c.releaseLastB();
          if (last() && t < 4) { mbar_arrive(sb + xe + 16); mbar_arrive_remote(c.rem + xe + 16); }
        };
        auto yes = [] { return true; };
        auto no = [] { return false; };
        tile(yes, no); PROF2(pb + 13); glu<16, 32>(a, h);
        tile(yes, no); PROF2(pb + 14); glu<16, 64>(a, h);
        tile(no, no); PROF2(pb + 15); glu<12, 96>(a, h);
        const uint32_t hole = sb + SM_B + 12288 + tid_ * 16;
#pragma unroll
        for (int i = 0; i < NSPILL; i++) sts128(hole + i * BSLOT, h[96 + 4 * i], h[97 + 4 * i], h[98 + 4 * i], h[99 + 4 * i]);
        if (w == 1) asm volatile("bar.arrive 8, 256;" ::: "memory");
        tile(no, yes); PROF2(pb + 16); glu<12, 120>(a, h);
#pragma unroll
        for (int i = 0; i < NSPILL; i++) { const uint4 u = lds128(hole + i * BSLOT); h[96 + 4 * i] = u.x; h[97 + 4 * i] = u.y; h[98 + 4 * i] = u.z; h[99 + 4 * i] = u.w; }
      }
      {
        THREAD_IDS();
        float d[32];
        uint4* const ib = G->inbox[layer];
        auto pass = [&](uint32_t s0, bool last, auto&& hook) {
          const uint64_t db = desc_hi(0, 1024, 1) + (dsb + (SM_X >> 4) + s0 * (XSLOT >> 4));
          mbar_wait_c(sb + BAR_FULLX + 8 * s0, (c.mX >> s0) & 1);
          asm volatile("bar.sync %0, 256;" ::"r"(8 + w) : "memory");
#pragma unroll
          for (int i = 0; i < 4; i++) {
            const int si = 4 * (i & 1) + (i >> 1);
            if (i > 0) mbar_wait_c(sb + BAR_FULLX + 8 * (s0 + si), (c.mX >> (s0 + si)) & 1);
            wg_fence();
#pragma unroll
            for (int k = 0; k < 9; k++) {
              const uint32_t* hk = h + 36 * i + 4 * k;
              wgmma_ra<64>(d, make_uint4(hk[0], hk[1], hk[2], hk[3]), db + (si * (XSLOT >> 4) + k * 128), last || i + k > 0);
              if (9 * i + k == PPK && !(last && w == 1)) asm volatile("bar.arrive %0, 256;" ::"r"(9 - w) : "memory");
            }
            wg_commit();
            if (i > 0) { wg_wait<1>(); c.release2(BAR_EMPTYX + 8 * (s0 + 4 * ((i - 1) & 1) + ((i - 1) >> 1))); }
            if (i == RHOOK) hook();
          }
          c.mX ^= 0x33u << s0;
        };
        PROF2(pb + 17);
#pragma unroll 1
        for (int p = 0; p < 8; p++) {
          const uint32_t s0 = 2 * (p & 1);
          pass(s0, false, [] {});
          wg_wait<0>();
          c.release2(BAR_EMPTYX + 8 * (s0 + 5));
          uint32_t pk[16];
#pragma unroll
          for (int i = 0; i < 16; i++) pk[i] = pack_bf16(d[2 * i], d[2 * i + 1]);
          uint4* const dst = ib + ((j + p) & 7) * INBOX + t;
          if (p == 0) {
            if (t < 5) { mbar_arrive(sb + BAR_EMPTYB + 8 * t); mbar_arrive_remote(c.rem + BAR_EMPTYB + 8 * t); }
            mbar_wait_c(sb + BAR_CLR + 8 * w, 0);
#pragma unroll
            for (int k = 0; k < 8; k++) red2((uint2*)(ib + k * INBOX + 1024) + t, pk[2 * k], pk[2 * k + 1]);
          } else if (p < 7) {
#pragma unroll
            for (int k = 0; k < 4; k++) red4(dst + k * 128, pk[4 * k], pk[4 * k + 1], pk[4 * k + 2], pk[4 * k + 3]);
            if (p == 6) { __syncwarp(); if (lane == 0) mbar_arrive(sb + BAR_REDDONE + 8 * w); }
          } else {
#pragma unroll
            for (int k = 0; k < 4; k++) st_relaxed4(dst + 512 + k * 128, max(pk[4 * k], 1u), pk[4 * k + 1], pk[4 * k + 2], pk[4 * k + 3]);
          }
        }
        PROF2(pb + 18);
        const uint4* in = ib + j * INBOX + t;
        const float2 r2 = lds64(sb + SM_KEEP + tid_ * 8);
        uint2 X9;
        {
          uint4 X[4];
          const uint4* box = G->act[2] + t;
#pragma unroll
          for (int k = 0; k < 4; k++) X[k] = ld_relaxed4(box + (2 * j + (k & 1) + 8 * (k & 2)) * 128);
          X9 = ld_relaxed2((const uint2*)(box + (32 + (j >> 1)) * 128) + (j & 1));
          const float i0 = rcp(r2.x), i1 = rcp(r2.y);
#pragma unroll
          for (int k = 0; k < 4; k++) {
            const float f = k & 1 ? i1 : i0;
            float* e = d + 8 * (k & 2) + 2 * (k & 1);
            X[k].x ^= (lsb >> k) & 1;
            e[0] = bf_lo(X[k].x) * f; e[1] = bf_hi(X[k].x) * f; e[4] = bf_lo(X[k].y) * f; e[5] = bf_hi(X[k].y) * f;
            e[8] = bf_lo(X[k].z) * f; e[9] = bf_hi(X[k].z) * f; e[12] = bf_lo(X[k].w) * f; e[13] = bf_hi(X[k].w) * f;
          }
          X9.x ^= lsb >> 4;
        }
        uint4 R[4], P[4];
        uint2 R9;
        PROF2(pb + 19);
        pass(0, true, [&] {
#pragma unroll
          for (int k = 0; k < 4; k++) P[k] = ld_relaxed4(in + 512 + k * 128);
          mbar_wait_c(sb + BAR_RREADY + 8 * w, layer);
#pragma unroll
          for (int k = 0; k < 4; k++) R[k] = ld_relaxed4(in + k * 128);
          R9 = ld_relaxed2((const uint2*)(in - t + 1024) + t);
        });
        while (__any_sync(0xffffffffu, P[0].x == 0 || P[1].x == 0 || P[2].x == 0 || P[3].x == 0)) {
#pragma unroll
          for (int k = 0; k < 4; k++) P[k] = ld_relaxed4(in + 512 + k * 128);
        }
#pragma unroll
        for (int k = 0; k < 4; k++) {
          const uint32_t u[4] = {hadd2(R[k].x, P[k].x), hadd2(R[k].y, P[k].y), hadd2(R[k].z, P[k].z), hadd2(R[k].w, P[k].w)};
#pragma unroll
          for (int i = 0; i < 4; i++) { v[8 * k + 2 * i] = bf_lo(u[i]); v[8 * k + 2 * i + 1] = bf_hi(u[i]); }
        }
        v[32] = fmaf(bf_lo(R9.x), r2.x, bf_lo(X9.x)); v[33] = fmaf(bf_hi(R9.x), r2.x, bf_hi(X9.x));
        v[34] = fmaf(bf_lo(R9.y), r2.y, bf_lo(X9.y)); v[35] = fmaf(bf_hi(R9.y), r2.y, bf_hi(X9.y));
        PROF2(pb + 20);
        wg_wait<0>();
        c.release2(BAR_EMPTYX + 40);
        PROF2(pb + 21);
#pragma unroll
        for (int i = 0; i < 32; i++) v[i] = (v[i] + d[i]) * (i & 2 ? r2.y : r2.x);
      }
      if (layer == NLAYERS - 1) break;
    }
    {
      THREAD_IDS();
      const uint32_t stg = sb + SM_B + warp * 4096;
      const uint32_t sd = stg + (lane & 15) * 128;
#pragma unroll
      for (int i = 0; i < 4; i++)
        stsm4(sd + (((2 * i + (lane >> 4)) ^ (lane & 7)) << 4), pack_bf16(v[8 * i], v[8 * i + 1]), pack_bf16(v[8 * i + 2], v[8 * i + 3]),
              pack_bf16(v[8 * i + 4], v[8 * i + 5]), pack_bf16(v[8 * i + 6], v[8 * i + 7]));
      stsm2(stg + 2048 + (lane & 15) * 16, pack_bf16(v[32], v[33]), pack_bf16(v[34], v[35]));
      fence_async_smem();
      __syncwarp();
      if (lane == 0) {
        tma_store3d(&maps.out, stg, 64 * j, w, 64 * rb + 16 * wp);
        tma_store3d(&maps.outc, stg + 2048, 512 + 8 * j, w, 64 * rb + 16 * wp);
        bulk_commit();
        bulk_wait_all();
        mbar_arrive(sb + BAR_DONE + 8 * w);
      }
      PROF(61);
    }
    __syncwarp();
    cluster_sync();
  }
}

typedef CUresult (*EncFn)(CUtensorMap*, CUtensorMapDataType, cuuint32_t, void*, const cuuint64_t*, const cuuint64_t*, const cuuint32_t*,
                          const cuuint32_t*, CUtensorMapInterleave, CUtensorMapSwizzle, CUtensorMapL2promotion, CUtensorMapFloatOOBfill);

void make_map(EncFn enc, CUtensorMap* m, const void* p, int rank, uint64_t d0, uint64_t d1, uint64_t d2, uint64_t s1, uint64_t s2, uint32_t b0,
              uint32_t b1, uint32_t b2, CUtensorMapSwizzle sw) {
  cuuint64_t gd[3] = {d0, d1, d2};
  cuuint64_t gs[2] = {s1, s2};
  cuuint32_t bd[3] = {b0, b1, b2};
  cuuint32_t es[3] = {1, 1, 1};
  enc(m, CU_TENSOR_MAP_DATA_TYPE_BFLOAT16, rank, const_cast<void*>(p), gd, gs, bd, es, CU_TENSOR_MAP_INTERLEAVE_NONE, sw,
      CU_TENSOR_MAP_L2_PROMOTION_L2_128B, CU_TENSOR_MAP_FLOAT_OOB_FILL_NONE);
}

}

extern "C" void kernel_launch(void* const* d_in, const int* in_sizes, int n_in, void* d_out, int out_size) {
  const __nv_bfloat16* x = (const __nv_bfloat16*)d_in[0];
  const char *wqkv = (const char*)d_in[1], *wo = (const char*)d_in[2], *wg = (const char*)d_in[4], *wu = (const char*)d_in[5], *wd = (const char*)d_in[6];
  static EncFn enc = nullptr;
  static Group* ws = nullptr;
  if (!enc) {
    cudaDriverEntryPointQueryResult qr;
    cudaGetDriverEntryPoint("cuTensorMapEncodeTiled", (void**)&enc, cudaEnableDefault, &qr);
    cudaGetSymbolAddress((void**)&ws, g_ws);
    cudaFuncSetAttribute(fused_kernel, cudaFuncAttributeMaxDynamicSharedMemorySize, SMEM_BYTES);
  }
  const CUtensorMapSwizzle S0 = CU_TENSOR_MAP_SWIZZLE_NONE, S64 = CU_TENSOR_MAP_SWIZZLE_64B, S128 = CU_TENSOR_MAP_SWIZZLE_128B;
  Maps m;
  make_map(enc, &m.x, x, 3, 576, 2, 1024, 1152, 2304, 64, 1, 64, S128);
  make_map(enc, &m.qm, wqkv, 3, 576, 576, 3, 3456, 1152, 64, 16, 3, S128);
  make_map(enc, &m.qc, wqkv, 3, 576, 576, 3, 3456, 1152, 8, 16, 3, S0);
  make_map(enc, &m.o, wo, 2, 576, 576, 1, 1152, 0, 64, 72, 1, S128);
  make_map(enc, &m.oc, wo, 2, 576, 576, 1, 1152, 0, 8, 144, 1, S0);
  make_map(enc, &m.g, wg, 3, 64, 576, 72, 9216, 128, 64, 32, 2, S128);
  make_map(enc, &m.u, wu, 3, 64, 576, 72, 9216, 128, 64, 32, 2, S128);
  make_map(enc, &m.g3, wg, 3, 32, 576, 144, 9216, 64, 32, 32, 3, S64);
  make_map(enc, &m.u3, wu, 3, 32, 576, 144, 9216, 64, 32, 32, 3, S64);
  make_map(enc, &m.d, wd, 2, 576, 4608, 1, 1152, 0, 64, 72, 1, S128);
  make_map(enc, &m.out, d_out, 3, 576, 2, 1024, 1152, 2304, 64, 1, 16, S128);
  make_map(enc, &m.outc, d_out, 3, 576, 2, 1024, 1152, 2304, 8, 1, 16, S0);
  fused_kernel<<<NCTA, 384, SMEM_BYTES>>>(x, ws, wqkv, wg, wu, wd, m, wo);
}
```

```cpp
#include <cuda_runtime.h>
#include <cuda_bf16.h>
#include <cuda.h>
#include <stdint.h>
#include <stddef.h>

namespace {

constexpr int D_ = 576;
constexpr int NCTA = 128;
#define NLAYERS 2
#define W_POLICY policy_evict_first
#define A_POLICY policy_evict_normal
#define OPEN 1
#define PFMODE 5
#define WWIN 4
#define WOREL -1
#define WB1 12
#define WB2 24
#define WB3 36
#define WB4 36
#define WPROBE 1
#define WPROBE2 0
#define SPEC 2
#define POLLFIRST 0
#define SUMFIRST 1
#define EARLYPOLL 1
#define LEAD 0
#define ATTBAR 0
#define GL 18
#define WOBAR 0
#define QD 0
#define QG 4
#define PFQ 1
#define XDELAY 0
#define WOH 1
#define PFSLEEP 700
#define GPCMAP 1
#define PFF 1
#define REDN 1
#define CLRSLEEP 150
#define FG -1
#define NON8 0
#define HMUL 1
#define FCH 1
#define PPK 34
#define RHOOK 0
#define SCHEDBAR 1
#define QH 5
#define XH 3
#define XP 2
#define GSLEEP 32
#define XCH 0
#define MAPPF 1
#define XREL 6
#define WOG 13
#define NSPILL 4
#define REGS_C 232
#define REGS_P 40
#define STR2(x) #x
#define STR(x) STR2(x)
constexpr uint32_t SM_X = 0;
constexpr uint32_t XSLOT = 18432;
constexpr uint32_t SM_WOC = SM_X + 3 * XSLOT + 9216;
constexpr uint32_t SM_B = 147456;
constexpr uint32_t BSLOT = 16384;
constexpr uint32_t SM_KEEP = 229376;
constexpr uint32_t SM_BAR = SM_KEEP + 2048;
constexpr uint32_t BAR_FULLB = SM_BAR;
constexpr uint32_t BAR_RREADY = SM_BAR + 40;
constexpr uint32_t BAR_CLR = SM_BAR + 56;
constexpr uint32_t BAR_FULLX = SM_BAR + 72;
constexpr uint32_t BAR_EMPTYB = SM_BAR + 144;
constexpr uint32_t BAR_EMPTYX = SM_BAR + 184;
constexpr uint32_t BAR_REDDONE = SM_BAR + 248;
constexpr uint32_t BAR_DONE = SM_BAR + 264;
constexpr uint32_t SM_PROG = SM_BAR + 288;
constexpr uint32_t SMEM_BYTES = SM_BAR + 1024;

struct Maps { CUtensorMap x, qm, qc, o, oc, g, u, g3, u3, d, out, outc; };

constexpr int INBOX = 1088;
struct Group {
  uint2 sum[4 * 8 * 8];
  uint4 m2[4 * 8 * 8];
  uint32_t flag[512];
  uint4 halo[8 * 160];
  uint4 act[3][36 * 128];
  uint4 inbox[2][8 * INBOX];
};
__device__ __align__(1024) Group g_ws[32];
#define PROF(i)
#define PROFX(i)

#define PROF2(i) PROF(i)

template<int N> __device__ __forceinline__ void wgmma_ss(float (&d)[N / 2], uint64_t da, uint64_t db, int sc);
template<> __device__ __forceinline__ void wgmma_ss<192>(float (&d)[96], uint64_t da, uint64_t db, int sc) {
  asm volatile("{\n.reg .pred p;\nsetp.ne.b32 p, %98, 0;\n"
    "wgmma.mma_async.sync.aligned.m64n192k16.f32.bf16.bf16 {%0,%1,%2,%3,%4,%5,%6,%7,%8,%9,%10,%11,%12,%13,%14,%15,%16,%17,%18,%19,%20,%21,%22,%23,%24,%25,%26,%27,%28,%29,%30,%31,%32,%33,%34,%35,%36,%37,%38,%39,%40,%41,%42,%43,%44,%45,%46,%47,%48,%49,%50,%51,%52,%53,%54,%55,%56,%57,%58,%59,%60,%61,%62,%63,%64,%65,%66,%67,%68,%69,%70,%71,%72,%73,%74,%75,%76,%77,%78,%79,%80,%81,%82,%83,%84,%85,%86,%87,%88,%89,%90,%91,%92,%93,%94,%95}, %96, %97, p, 1, 1, 0, 1;\n}\n"
    : "+f"(d[0]),"+f"(d[1]),"+f"(d[2]),"+f"(d[3]),"+f"(d[4]),"+f"(d[5]),"+f"(d[6]),"+f"(d[7]),"+f"(d[8]),"+f"(d[9]),"+f"(d[10]),"+f"(d[11]),"+f"(d[12]),"+f"(d[13]),"+f"(d[14]),"+f"(d[15]),"+f"(d[16]),"+f"(d[17]),"+f"(d[18]),"+f"(d[19]),"+f"(d[20]),"+f"(d[21]),"+f"(d[22]),"+f"(d[23]),"+f"(d[24]),"+f"(d[25]),"+f"(d[26]),"+f"(d[27]),"+f"(d[28]),"+f"(d[29]),"+f"(d[30]),"+f"(d[31]),"+f"(d[32]),"+f"(d[33]),"+f"(d[34]),"+f"(d[35]),"+f"(d[36]),"+f"(d[37]),"+f"(d[38]),"+f"(d[39]),"+f"(d[40]),"+f"(d[41]),"+f"(d[42]),"+f"(d[43]),"+f"(d[44]),"+f"(d[45]),"+f"(d[46]),"+f"(d[47]),"+f"(d[48]),"+f"(d[49]),"+f"(d[50]),"+f"(d[51]),"+f"(d[52]),"+f"(d[53]),"+f"(d[54]),"+f"(d[55]),"+f"(d[56]),"+f"(d[57]),"+f"(d[58]),"+f"(d[59]),"+f"(d[60]),"+f"(d[61]),"+f"(d[62]),"+f"(d[63]),"+f"(d[64]),"+f"(d[65]),"+f"(d[66]),"+f"(d[67]),"+f"(d[68]),"+f"(d[69]),"+f"(d[70]),"+f"(d[71]),"+f"(d[72]),"+f"(d[73]),"+f"(d[74]),"+f"(d[75]),"+f"(d[76]),"+f"(d[77]),"+f"(d[78]),"+f"(d[79]),"+f"(d[80]),"+f"(d[81]),"+f"(d[82]),"+f"(d[83]),"+f"(d[84]),"+f"(d[85]),"+f"(d[86]),"+f"(d[87]),"+f"(d[88]),"+f"(d[89]),"+f"(d[90]),"+f"(d[91]),"+f"(d[92]),"+f"(d[93]),"+f"(d[94]),"+f"(d[95]) : "l"(da), "l"(db), "r"(sc));
}
template<> __device__ __forceinline__ void wgmma_ss<256>(float (&d)[128], uint64_t da, uint64_t db, int sc) {
  asm volatile("{\n.reg .pred p;\nsetp.ne.b32 p, %130, 0;\n"
    "wgmma.mma_async.sync.aligned.m64n256k16.f32.bf16.bf16 {%0,%1,%2,%3,%4,%5,%6,%7,%8,%9,%10,%11,%12,%13,%14,%15,%16,%17,%18,%19,%20,%21,%22,%23,%24,%25,%26,%27,%28,%29,%30,%31,%32,%33,%34,%35,%36,%37,%38,%39,%40,%41,%42,%43,%44,%45,%46,%47,%48,%49,%50,%51,%52,%53,%54,%55,%56,%57,%58,%59,%60,%61,%62,%63,%64,%65,%66,%67,%68,%69,%70,%71,%72,%73,%74,%75,%76,%77,%78,%79,%80,%81,%82,%83,%84,%85,%86,%87,%88,%89,%90,%91,%92,%93,%94,%95,%96,%97,%98,%99,%100,%101,%102,%103,%104,%105,%106,%107,%108,%109,%110,%111,%112,%113,%114,%115,%116,%117,%118,%119,%120,%121,%122,%123,%124,%125,%126,%127}, %128, %129, p, 1, 1, 0, 1;\n}\n"
    : "+f"(d[0]),"+f"(d[1]),"+f"(d[2]),"+f"(d[3]),"+f"(d[4]),"+f"(d[5]),"+f"(d[6]),"+f"(d[7]),"+f"(d[8]),"+f"(d[9]),"+f"(d[10]),"+f"(d[11]),"+f"(d[12]),"+f"(d[13]),"+f"(d[14]),"+f"(d[15]),"+f"(d[16]),"+f"(d[17]),"+f"(d[18]),"+f"(d[19]),"+f"(d[20]),"+f"(d[21]),"+f"(d[22]),"+f"(d[23]),"+f"(d[24]),"+f"(d[25]),"+f"(d[26]),"+f"(d[27]),"+f"(d[28]),"+f"(d[29]),"+f"(d[30]),"+f"(d[31]),"+f"(d[32]),"+f"(d[33]),"+f"(d[34]),"+f"(d[35]),"+f"(d[36]),"+f"(d[37]),"+f"(d[38]),"+f"(d[39]),"+f"(d[40]),"+f"(d[41]),"+f"(d[42]),"+f"(d[43]),"+f"(d[44]),"+f"(d[45]),"+f"(d[46]),"+f"(d[47]),"+f"(d[48]),"+f"(d[49]),"+f"(d[50]),"+f"(d[51]),"+f"(d[52]),"+f"(d[53]),"+f"(d[54]),"+f"(d[55]),"+f"(d[56]),"+f"(d[57]),"+f"(d[58]),"+f"(d[59]),"+f"(d[60]),"+f"(d[61]),"+f"(d[62]),"+f"(d[63]),"+f"(d[64]),"+f"(d[65]),"+f"(d[66]),"+f"(d[67]),"+f"(d[68]),"+f"(d[69]),"+f"(d[70]),"+f"(d[71]),"+f"(d[72]),"+f"(d[73]),"+f"(d[74]),"+f"(d[75]),"+f"(d[76]),"+f"(d[77]),"+f"(d[78]),"+f"(d[79]),"+f"(d[80]),"+f"(d[81]),"+f"(d[82]),"+f"(d[83]),"+f"(d[84]),"+f"(d[85]),"+f"(d[86]),"+f"(d[87]),"+f"(d[88]),"+f"(d[89]),"+f"(d[90]),"+f"(d[91]),"+f"(d[92]),"+f"(d[93]),"+f"(d[94]),"+f"(d[95]),"+f"(d[96]),"+f"(d[97]),"+f"(d[98]),"+f"(d[99]),"+f"(d[100]),"+f"(d[101]),"+f"(d[102]),"+f"(d[103]),"+f"(d[104]),"+f"(d[105]),"+f"(d[106]),"+f"(d[107]),"+f"(d[108]),"+f"(d[109]),"+f"(d[110]),"+f"(d[111]),"+f"(d[112]),"+f"(d[113]),"+f"(d[114]),"+f"(d[115]),"+f"(d[116]),"+f"(d[117]),"+f"(d[118]),"+f"(d[119]),"+f"(d[120]),"+f"(d[121]),"+f"(d[122]),"+f"(d[123]),"+f"(d[124]),"+f"(d[125]),"+f"(d[126]),"+f"(d[127]) : "l"(da), "l"(db), "r"(sc));
}
template<int N> __device__ __forceinline__ void wgmma_rs(float (&d)[N / 2], uint32_t a0, uint32_t a1, uint32_t a2, uint32_t a3, uint64_t db, int sc);
template<> __device__ __forceinline__ void wgmma_rs<8>(float (&d)[4], uint32_t a0, uint32_t a1, uint32_t a2, uint32_t a3, uint64_t db, int sc) {
  asm volatile("{\n.reg .pred p;\nsetp.ne.b32 p, %9, 0;\n"
    "wgmma.mma_async.sync.aligned.m64n8k16.f32.bf16.bf16 {%0,%1,%2,%3}, {%4,%5,%6,%7}, %8, p, 1, 1, 1;\n}\n"
    : "+f"(d[0]),"+f"(d[1]),"+f"(d[2]),"+f"(d[3]) : "r"(a0), "r"(a1), "r"(a2), "r"(a3), "l"(db), "r"(sc));
}
template<> __device__ __forceinline__ void wgmma_rs<24>(float (&d)[12], uint32_t a0, uint32_t a1, uint32_t a2, uint32_t a3, uint64_t db, int sc) {
  asm volatile("{\n.reg .pred p;\nsetp.ne.b32 p, %17, 0;\n"
    "wgmma.mma_async.sync.aligned.m64n24k16.f32.bf16.bf16 {%0,%1,%2,%3,%4,%5,%6,%7,%8,%9,%10,%11}, {%12,%13,%14,%15}, %16, p, 1, 1, 1;\n}\n"
    : "+f"(d[0]),"+f"(d[1]),"+f"(d[2]),"+f"(d[3]),"+f"(d[4]),"+f"(d[5]),"+f"(d[6]),"+f"(d[7]),"+f"(d[8]),"+f"(d[9]),"+f"(d[10]),"+f"(d[11]) : "r"(a0), "r"(a1), "r"(a2), "r"(a3), "l"(db), "r"(sc));
}
template<> __device__ __forceinline__ void wgmma_rs<64>(float (&d)[32], uint32_t a0, uint32_t a1, uint32_t a2, uint32_t a3, uint64_t db, int sc) {
  asm volatile("{\n.reg .pred p;\nsetp.ne.b32 p, %37, 0;\n"
    "wgmma.mma_async.sync.aligned.m64n64k16.f32.bf16.bf16 {%0,%1,%2,%3,%4,%5,%6,%7,%8,%9,%10,%11,%12,%13,%14,%15,%16,%17,%18,%19,%20,%21,%22,%23,%24,%25,%26,%27,%28,%29,%30,%31}, {%32,%33,%34,%35}, %36, p, 1, 1, 1;\n}\n"
    : "+f"(d[0]),"+f"(d[1]),"+f"(d[2]),"+f"(d[3]),"+f"(d[4]),"+f"(d[5]),"+f"(d[6]),"+f"(d[7]),"+f"(d[8]),"+f"(d[9]),"+f"(d[10]),"+f"(d[11]),"+f"(d[12]),"+f"(d[13]),"+f"(d[14]),"+f"(d[15]),"+f"(d[16]),"+f"(d[17]),"+f"(d[18]),"+f"(d[19]),"+f"(d[20]),"+f"(d[21]),"+f"(d[22]),"+f"(d[23]),"+f"(d[24]),"+f"(d[25]),"+f"(d[26]),"+f"(d[27]),"+f"(d[28]),"+f"(d[29]),"+f"(d[30]),"+f"(d[31]) : "r"(a0), "r"(a1), "r"(a2), "r"(a3), "l"(db), "r"(sc));
}
template<> __device__ __forceinline__ void wgmma_rs<192>(float (&d)[96], uint32_t a0, uint32_t a1, uint32_t a2, uint32_t a3, uint64_t db, int sc) {
  asm volatile("{\n.reg .pred p;\nsetp.ne.b32 p, %101, 0;\n"
    "wgmma.mma_async.sync.aligned.m64n192k16.f32.bf16.bf16 {%0,%1,%2,%3,%4,%5,%6,%7,%8,%9,%10,%11,%12,%13,%14,%15,%16,%17,%18,%19,%20,%21,%22,%23,%24,%25,%26,%27,%28,%29,%30,%31,%32,%33,%34,%35,%36,%37,%38,%39,%40,%41,%42,%43,%44,%45,%46,%47,%48,%49,%50,%51,%52,%53,%54,%55,%56,%57,%58,%59,%60,%61,%62,%63,%64,%65,%66,%67,%68,%69,%70,%71,%72,%73,%74,%75,%76,%77,%78,%79,%80,%81,%82,%83,%84,%85,%86,%87,%88,%89,%90,%91,%92,%93,%94,%95}, {%96,%97,%98,%99}, %100, p, 1, 1, 1;\n}\n"
    : "+f"(d[0]),"+f"(d[1]),"+f"(d[2]),"+f"(d[3]),"+f"(d[4]),"+f"(d[5]),"+f"(d[6]),"+f"(d[7]),"+f"(d[8]),"+f"(d[9]),"+f"(d[10]),"+f"(d[11]),"+f"(d[12]),"+f"(d[13]),"+f"(d[14]),"+f"(d[15]),"+f"(d[16]),"+f"(d[17]),"+f"(d[18]),"+f"(d[19]),"+f"(d[20]),"+f"(d[21]),"+f"(d[22]),"+f"(d[23]),"+f"(d[24]),"+f"(d[25]),"+f"(d[26]),"+f"(d[27]),"+f"(d[28]),"+f"(d[29]),"+f"(d[30]),"+f"(d[31]),"+f"(d[32]),"+f"(d[33]),"+f"(d[34]),"+f"(d[35]),"+f"(d[36]),"+f"(d[37]),"+f"(d[38]),"+f"(d[39]),"+f"(d[40]),"+f"(d[41]),"+f"(d[42]),"+f"(d[43]),"+f"(d[44]),"+f"(d[45]),"+f"(d[46]),"+f"(d[47]),"+f"(d[48]),"+f"(d[49]),"+f"(d[50]),"+f"(d[51]),"+f"(d[52]),"+f"(d[53]),"+f"(d[54]),"+f"(d[55]),"+f"(d[56]),"+f"(d[57]),"+f"(d[58]),"+f"(d[59]),"+f"(d[60]),"+f"(d[61]),"+f"(d[62]),"+f"(d[63]),"+f"(d[64]),"+f"(d[65]),"+f"(d[66]),"+f"(d[67]),"+f"(d[68]),"+f"(d[69]),"+f"(d[70]),"+f"(d[71]),"+f"(d[72]),"+f"(d[73]),"+f"(d[74]),"+f"(d[75]),"+f"(d[76]),"+f"(d[77]),"+f"(d[78]),"+f"(d[79]),"+f"(d[80]),"+f"(d[81]),"+f"(d[82]),"+f"(d[83]),"+f"(d[84]),"+f"(d[85]),"+f"(d[86]),"+f"(d[87]),"+f"(d[88]),"+f"(d[89]),"+f"(d[90]),"+f"(d[91]),"+f"(d[92]),"+f"(d[93]),"+f"(d[94]),"+f"(d[95]) : "r"(a0), "r"(a1), "r"(a2), "r"(a3), "l"(db), "r"(sc));
}
template<> __device__ __forceinline__ void wgmma_rs<256>(float (&d)[128], uint32_t a0, uint32_t a1, uint32_t a2, uint32_t a3, uint64_t db, int sc) {
  asm volatile("{\n.reg .pred p;\nsetp.ne.b32 p, %133, 0;\n"
    "wgmma.mma_async.sync.aligned.m64n256k16.f32.bf16.bf16 {%0,%1,%2,%3,%4,%5,%6,%7,%8,%9,%10,%11,%12,%13,%14,%15,%16,%17,%18,%19,%20,%21,%22,%23,%24,%25,%26,%27,%28,%29,%30,%31,%32,%33,%34,%35,%36,%37,%38,%39,%40,%41,%42,%43,%44,%45,%46,%47,%48,%49,%50,%51,%52,%53,%54,%55,%56,%57,%58,%59,%60,%61,%62,%63,%64,%65,%66,%67,%68,%69,%70,%71,%72,%73,%74,%75,%76,%77,%78,%79,%80,%81,%82,%83,%84,%85,%86,%87,%88,%89,%90,%91,%92,%93,%94,%95,%96,%97,%98,%99,%100,%101,%102,%103,%104,%105,%106,%107,%108,%109,%110,%111,%112,%113,%114,%115,%116,%117,%118,%119,%120,%121,%122,%123,%124,%125,%126,%127}, {%128,%129,%130,%131}, %132, p, 1, 1, 1;\n}\n"
    : "+f"(d[0]),"+f"(d[1]),"+f"(d[2]),"+f"(d[3]),"+f"(d[4]),"+f"(d[5]),"+f"(d[6]),"+f"(d[7]),"+f"(d[8]),"+f"(d[9]),"+f"(d[10]),"+f"(d[11]),"+f"(d[12]),"+f"(d[13]),"+f"(d[14]),"+f"(d[15]),"+f"(d[16]),"+f"(d[17]),"+f"(d[18]),"+f"(d[19]),"+f"(d[20]),"+f"(d[21]),"+f"(d[22]),"+f"(d[23]),"+f"(d[24]),"+f"(d[25]),"+f"(d[26]),"+f"(d[27]),"+f"(d[28]),"+f"(d[29]),"+f"(d[30]),"+f"(d[31]),"+f"(d[32]),"+f"(d[33]),"+f"(d[34]),"+f"(d[35]),"+f"(d[36]),"+f"(d[37]),"+f"(d[38]),"+f"(d[39]),"+f"(d[40]),"+f"(d[41]),"+f"(d[42]),"+f"(d[43]),"+f"(d[44]),"+f"(d[45]),"+f"(d[46]),"+f"(d[47]),"+f"(d[48]),"+f"(d[49]),"+f"(d[50]),"+f"(d[51]),"+f"(d[52]),"+f"(d[53]),"+f"(d[54]),"+f"(d[55]),"+f"(d[56]),"+f"(d[57]),"+f"(d[58]),"+f"(d[59]),"+f"(d[60]),"+f"(d[61]),"+f"(d[62]),"+f"(d[63]),"+f"(d[64]),"+f"(d[65]),"+f"(d[66]),"+f"(d[67]),"+f"(d[68]),"+f"(d[69]),"+f"(d[70]),"+f"(d[71]),"+f"(d[72]),"+f"(d[73]),"+f"(d[74]),"+f"(d[75]),"+f"(d[76]),"+f"(d[77]),"+f"(d[78]),"+f"(d[79]),"+f"(d[80]),"+f"(d[81]),"+f"(d[82]),"+f"(d[83]),"+f"(d[84]),"+f"(d[85]),"+f"(d[86]),"+f"(d[87]),"+f"(d[88]),"+f"(d[89]),"+f"(d[90]),"+f"(d[91]),"+f"(d[92]),"+f"(d[93]),"+f"(d[94]),"+f"(d[95]),"+f"(d[96]),"+f"(d[97]),"+f"(d[98]),"+f"(d[99]),"+f"(d[100]),"+f"(d[101]),"+f"(d[102]),"+f"(d[103]),"+f"(d[104]),"+f"(d[105]),"+f"(d[106]),"+f"(d[107]),"+f"(d[108]),"+f"(d[109]),"+f"(d[110]),"+f"(d[111]),"+f"(d[112]),"+f"(d[113]),"+f"(d[114]),"+f"(d[115]),"+f"(d[116]),"+f"(d[117]),"+f"(d[118]),"+f"(d[119]),"+f"(d[120]),"+f"(d[121]),"+f"(d[122]),"+f"(d[123]),"+f"(d[124]),"+f"(d[125]),"+f"(d[126]),"+f"(d[127]) : "r"(a0), "r"(a1), "r"(a2), "r"(a3), "l"(db), "r"(sc));
}
template<int N> __device__ __forceinline__ void wgmma_rsz(float (&d)[N / 2], uint32_t a0, uint32_t a1, uint32_t a2, uint32_t a3, uint64_t db);
template<> __device__ __forceinline__ void wgmma_rsz<8>(float (&d)[4], uint32_t a0, uint32_t a1, uint32_t a2, uint32_t a3, uint64_t db) {
  asm volatile("{\n.reg .pred p;\nsetp.ne.b32 p, 0, 0;\n"
    "wgmma.mma_async.sync.aligned.m64n8k16.f32.bf16.bf16 {%0,%1,%2,%3}, {%4,%5,%6,%7}, %8, p, 1, 1, 1;\n}\n"
    : "=f"(d[0]),"=f"(d[1]),"=f"(d[2]),"=f"(d[3]) : "r"(a0), "r"(a1), "r"(a2), "r"(a3), "l"(db));
}
template<> __device__ __forceinline__ void wgmma_rsz<24>(float (&d)[12], uint32_t a0, uint32_t a1, uint32_t a2, uint32_t a3, uint64_t db) {
  asm volatile("{\n.reg .pred p;\nsetp.ne.b32 p, 0, 0;\n"
    "wgmma.mma_async.sync.aligned.m64n24k16.f32.bf16.bf16 {%0,%1,%2,%3,%4,%5,%6,%7,%8,%9,%10,%11}, {%12,%13,%14,%15}, %16, p, 1, 1, 1;\n}\n"
    : "=f"(d[0]),"=f"(d[1]),"=f"(d[2]),"=f"(d[3]),"=f"(d[4]),"=f"(d[5]),"=f"(d[6]),"=f"(d[7]),"=f"(d[8]),"=f"(d[9]),"=f"(d[10]),"=f"(d[11]) : "r"(a0), "r"(a1), "r"(a2), "r"(a3), "l"(db));
}
template<> __device__ __forceinline__ void wgmma_rsz<64>(float (&d)[32], uint32_t a0, uint32_t a1, uint32_t a2, uint32_t a3, uint64_t db) {
  asm volatile("{\n.reg .pred p;\nsetp.ne.b32 p, 0, 0;\n"
    "wgmma.mma_async.sync.aligned.m64n64k16.f32.bf16.bf16 {%0,%1,%2,%3,%4,%5,%6,%7,%8,%9,%10,%11,%12,%13,%14,%15,%16,%17,%18,%19,%20,%21,%22,%23,%24,%25,%26,%27,%28,%29,%30,%31}, {%32,%33,%34,%35}, %36, p, 1, 1, 1;\n}\n"
    : "=f"(d[0]),"=f"(d[1]),"=f"(d[2]),"=f"(d[3]),"=f"(d[4]),"=f"(d[5]),"=f"(d[6]),"=f"(d[7]),"=f"(d[8]),"=f"(d[9]),"=f"(d[10]),"=f"(d[11]),"=f"(d[12]),"=f"(d[13]),"=f"(d[14]),"=f"(d[15]),"=f"(d[16]),"=f"(d[17]),"=f"(d[18]),"=f"(d[19]),"=f"(d[20]),"=f"(d[21]),"=f"(d[22]),"=f"(d[23]),"=f"(d[24]),"=f"(d[25]),"=f"(d[26]),"=f"(d[27]),"=f"(d[28]),"=f"(d[29]),"=f"(d[30]),"=f"(d[31]) : "r"(a0), "r"(a1), "r"(a2), "r"(a3), "l"(db));
}
template<> __device__ __forceinline__ void wgmma_rsz<192>(float (&d)[96], uint32_t a0, uint32_t a1, uint32_t a2, uint32_t a3, uint64_t db) {
  asm volatile("{\n.reg .pred p;\nsetp.ne.b32 p, 0, 0;\n"
    "wgmma.mma_async.sync.aligned.m64n192k16.f32.bf16.bf16 {%0,%1,%2,%3,%4,%5,%6,%7,%8,%9,%10,%11,%12,%13,%14,%15,%16,%17,%18,%19,%20,%21,%22,%23,%24,%25,%26,%27,%28,%29,%30,%31,%32,%33,%34,%35,%36,%37,%38,%39,%40,%41,%42,%43,%44,%45,%46,%47,%48,%49,%50,%51,%52,%53,%54,%55,%56,%57,%58,%59,%60,%61,%62,%63,%64,%65,%66,%67,%68,%69,%70,%71,%72,%73,%74,%75,%76,%77,%78,%79,%80,%81,%82,%83,%84,%85,%86,%87,%88,%89,%90,%91,%92,%93,%94,%95}, {%96,%97,%98,%99}, %100, p, 1, 1, 1;\n}\n"
    : "=f"(d[0]),"=f"(d[1]),"=f"(d[2]),"=f"(d[3]),"=f"(d[4]),"=f"(d[5]),"=f"(d[6]),"=f"(d[7]),"=f"(d[8]),"=f"(d[9]),"=f"(d[10]),"=f"(d[11]),"=f"(d[12]),"=f"(d[13]),"=f"(d[14]),"=f"(d[15]),"=f"(d[16]),"=f"(d[17]),"=f"(d[18]),"=f"(d[19]),"=f"(d[20]),"=f"(d[21]),"=f"(d[22]),"=f"(d[23]),"=f"(d[24]),"=f"(d[25]),"=f"(d[26]),"=f"(d[27]),"=f"(d[28]),"=f"(d[29]),"=f"(d[30]),"=f"(d[31]),"=f"(d[32]),"=f"(d[33]),"=f"(d[34]),"=f"(d[35]),"=f"(d[36]),"=f"(d[37]),"=f"(d[38]),"=f"(d[39]),"=f"(d[40]),"=f"(d[41]),"=f"(d[42]),"=f"(d[43]),"=f"(d[44]),"=f"(d[45]),"=f"(d[46]),"=f"(d[47]),"=f"(d[48]),"=f"(d[49]),"=f"(d[50]),"=f"(d[51]),"=f"(d[52]),"=f"(d[53]),"=f"(d[54]),"=f"(d[55]),"=f"(d[56]),"=f"(d[57]),"=f"(d[58]),"=f"(d[59]),"=f"(d[60]),"=f"(d[61]),"=f"(d[62]),"=f"(d[63]),"=f"(d[64]),"=f"(d[65]),"=f"(d[66]),"=f"(d[67]),"=f"(d[68]),"=f"(d[69]),"=f"(d[70]),"=f"(d[71]),"=f"(d[72]),"=f"(d[73]),"=f"(d[74]),"=f"(d[75]),"=f"(d[76]),"=f"(d[77]),"=f"(d[78]),"=f"(d[79]),"=f"(d[80]),"=f"(d[81]),"=f"(d[82]),"=f"(d[83]),"=f"(d[84]),"=f"(d[85]),"=f"(d[86]),"=f"(d[87]),"=f"(d[88]),"=f"(d[89]),"=f"(d[90]),"=f"(d[91]),"=f"(d[92]),"=f"(d[93]),"=f"(d[94]),"=f"(d[95]) : "r"(a0), "r"(a1), "r"(a2), "r"(a3), "l"(db));
}
template<> __device__ __forceinline__ void wgmma_rsz<256>(float (&d)[128], uint32_t a0, uint32_t a1, uint32_t a2, uint32_t a3, uint64_t db) {
  asm volatile("{\n.reg .pred p;\nsetp.ne.b32 p, 0, 0;\n"
    "wgmma.mma_async.sync.aligned.m64n256k16.f32.bf16.bf16 {%0,%1,%2,%3,%4,%5,%6,%7,%8,%9,%10,%11,%12,%13,%14,%15,%16,%17,%18,%19,%20,%21,%22,%23,%24,%25,%26,%27,%28,%29,%30,%31,%32,%33,%34,%35,%36,%37,%38,%39,%40,%41,%42,%43,%44,%45,%46,%47,%48,%49,%50,%51,%52,%53,%54,%55,%56,%57,%58,%59,%60,%61,%62,%63,%64,%65,%66,%67,%68,%69,%70,%71,%72,%73,%74,%75,%76,%77,%78,%79,%80,%81,%82,%83,%84,%85,%86,%87,%88,%89,%90,%91,%92,%93,%94,%95,%96,%97,%98,%99,%100,%101,%102,%103,%104,%105,%106,%107,%108,%109,%110,%111,%112,%113,%114,%115,%116,%117,%118,%119,%120,%121,%122,%123,%124,%125,%126,%127}, {%128,%129,%130,%131}, %132, p, 1, 1, 1;\n}\n"
    : "=f"(d[0]),"=f"(d[1]),"=f"(d[2]),"=f"(d[3]),"=f"(d[4]),"=f"(d[5]),"=f"(d[6]),"=f"(d[7]),"=f"(d[8]),"=f"(d[9]),"=f"(d[10]),"=f"(d[11]),"=f"(d[12]),"=f"(d[13]),"=f"(d[14]),"=f"(d[15]),"=f"(d[16]),"=f"(d[17]),"=f"(d[18]),"=f"(d[19]),"=f"(d[20]),"=f"(d[21]),"=f"(d[22]),"=f"(d[23]),"=f"(d[24]),"=f"(d[25]),"=f"(d[26]),"=f"(d[27]),"=f"(d[28]),"=f"(d[29]),"=f"(d[30]),"=f"(d[31]),"=f"(d[32]),"=f"(d[33]),"=f"(d[34]),"=f"(d[35]),"=f"(d[36]),"=f"(d[37]),"=f"(d[38]),"=f"(d[39]),"=f"(d[40]),"=f"(d[41]),"=f"(d[42]),"=f"(d[43]),"=f"(d[44]),"=f"(d[45]),"=f"(d[46]),"=f"(d[47]),"=f"(d[48]),"=f"(d[49]),"=f"(d[50]),"=f"(d[51]),"=f"(d[52]),"=f"(d[53]),"=f"(d[54]),"=f"(d[55]),"=f"(d[56]),"=f"(d[57]),"=f"(d[58]),"=f"(d[59]),"=f"(d[60]),"=f"(d[61]),"=f"(d[62]),"=f"(d[63]),"=f"(d[64]),"=f"(d[65]),"=f"(d[66]),"=f"(d[67]),"=f"(d[68]),"=f"(d[69]),"=f"(d[70]),"=f"(d[71]),"=f"(d[72]),"=f"(d[73]),"=f"(d[74]),"=f"(d[75]),"=f"(d[76]),"=f"(d[77]),"=f"(d[78]),"=f"(d[79]),"=f"(d[80]),"=f"(d[81]),"=f"(d[82]),"=f"(d[83]),"=f"(d[84]),"=f"(d[85]),"=f"(d[86]),"=f"(d[87]),"=f"(d[88]),"=f"(d[89]),"=f"(d[90]),"=f"(d[91]),"=f"(d[92]),"=f"(d[93]),"=f"(d[94]),"=f"(d[95]),"=f"(d[96]),"=f"(d[97]),"=f"(d[98]),"=f"(d[99]),"=f"(d[100]),"=f"(d[101]),"=f"(d[102]),"=f"(d[103]),"=f"(d[104]),"=f"(d[105]),"=f"(d[106]),"=f"(d[107]),"=f"(d[108]),"=f"(d[109]),"=f"(d[110]),"=f"(d[111]),"=f"(d[112]),"=f"(d[113]),"=f"(d[114]),"=f"(d[115]),"=f"(d[116]),"=f"(d[117]),"=f"(d[118]),"=f"(d[119]),"=f"(d[120]),"=f"(d[121]),"=f"(d[122]),"=f"(d[123]),"=f"(d[124]),"=f"(d[125]),"=f"(d[126]),"=f"(d[127]) : "r"(a0), "r"(a1), "r"(a2), "r"(a3), "l"(db));
}
template<int N> __device__ __forceinline__ void wgmma_ra(float (&d)[N / 2], const uint4& a, uint64_t db, bool acc) {
  if (acc) wgmma_rs<N>(d, a.x, a.y, a.z, a.w, db, 1); else wgmma_rsz<N>(d, a.x, a.y, a.z, a.w, db);
}

__device__ __forceinline__ uint32_t smem_u32(const void* p) { return (uint32_t)__cvta_generic_to_shared(p); }
__device__ __forceinline__ void mbar_init(uint32_t bar, uint32_t cnt) { asm volatile("mbarrier.init.shared::cta.b64 [%0], %1;" ::"r"(bar), "r"(cnt)); }
__device__ __forceinline__ void mbar_expect_tx(uint32_t bar, uint32_t bytes) { asm volatile("mbarrier.arrive.expect_tx.shared::cta.b64 _, [%0], %1;" ::"r"(bar), "r"(bytes) : "memory"); }
__device__ __forceinline__ void mbar_arrive(uint32_t bar) { asm volatile("mbarrier.arrive.shared::cta.b64 _, [%0];" ::"r"(bar) : "memory"); }
__device__ __forceinline__ void mbar_arrive_remote(uint32_t rbar) { asm volatile("mbarrier.arrive.shared::cluster.b64 _, [%0];" ::"r"(rbar) : "memory"); }
__device__ __forceinline__ void mbar_wait(uint32_t bar, uint32_t parity) {
  asm volatile(
      "{\n.reg .pred p;\n.reg .u32 c;\nmov.u32 c, 0;\nLAB_WAIT:\nmbarrier.try_wait.parity.shared::cta.b64 p, [%0], %1;\n@p bra DONE;\n"
      "add.u32 c, c, 1;\nsetp.lt.u32 p, c, 1000000;\n@p bra LAB_WAIT;\ntrap;\nDONE:\n}\n" ::"r"(bar), "r"(parity) : "memory");
}
__device__ __forceinline__ void mbar_wait_c(uint32_t bar, uint32_t parity) {
  asm volatile("{\n.reg .pred p;\nLAB_WAIT:\nmbarrier.try_wait.parity.shared::cta.b64 p, [%0], %1;\n@!p bra LAB_WAIT;\n}\n" ::"r"(bar), "r"(parity) : "memory");
}
__device__ __forceinline__ void wtma2d(uint32_t dst, const CUtensorMap* m, int c0, int c1, uint32_t bar, uint64_t pol) {
  asm volatile("cp.async.bulk.tensor.2d.shared::cluster.global.mbarrier::complete_tx::bytes.multicast::cluster.L2::cache_hint [%0], [%1, {%3, %4}], [%2], %5, %6;"
               ::"r"(dst), "l"(m), "r"(bar), "r"(c0), "r"(c1), "h"((uint16_t)3), "l"(pol) : "memory");
}
__device__ __forceinline__ void wtma3d(uint32_t dst, const CUtensorMap* m, int c0, int c1, int c2, uint32_t bar, uint64_t pol) {
  asm volatile("cp.async.bulk.tensor.3d.shared::cluster.global.mbarrier::complete_tx::bytes.multicast::cluster.L2::cache_hint [%0], [%1, {%3, %4, %5}], [%2], %6, %7;"
               ::"r"(dst), "l"(m), "r"(bar), "r"(c0), "r"(c1), "r"(c2), "h"((uint16_t)3), "l"(pol) : "memory");
}
__device__ __forceinline__ void tma3d(uint32_t dst, const CUtensorMap* m, int c0, int c1, int c2, uint32_t bar) {
  asm volatile("cp.async.bulk.tensor.3d.shared::cluster.global.mbarrier::complete_tx::bytes [%0], [%1, {%3, %4, %5}], [%2];"
               ::"r"(dst), "l"(m), "r"(bar), "r"(c0), "r"(c1), "r"(c2) : "memory");
}
__device__ __forceinline__ void tma_store3d(const CUtensorMap* m, uint32_t src, int c0, int c1, int c2) {
  asm volatile("cp.async.bulk.tensor.3d.global.shared::cta.bulk_group [%0, {%2, %3, %4}], [%1];" ::"l"(m), "r"(src), "r"(c0), "r"(c1), "r"(c2) : "memory");
}
__device__ __forceinline__ void prefetch_l2(const void* p, uint32_t bytes) { asm volatile("cp.async.bulk.prefetch.L2.global [%0], %1;" ::"l"(p), "r"(bytes) : "memory"); }
__device__ __forceinline__ uint64_t policy_evict_first() { uint64_t p; asm volatile("createpolicy.fractional.L2::evict_first.b64 %0, 1.0;" : "=l"(p)); return p; }
__device__ __forceinline__ uint64_t policy_evict_normal() { uint64_t p; asm volatile("createpolicy.fractional.L2::evict_normal.b64 %0, 1.0;" : "=l"(p)); return p; }
__device__ __forceinline__ void bulk_commit() { asm volatile("cp.async.bulk.commit_group;" ::: "memory"); }
__device__ __forceinline__ void bulk_wait_all() { asm volatile("cp.async.bulk.wait_group 0;" ::: "memory"); }
__device__ __forceinline__ void fence_async_smem() { asm volatile("fence.proxy.async.shared::cta;" ::: "memory"); }
__device__ __forceinline__ bool elect_one() {
  uint32_t p;
  asm volatile("{\n.reg .pred P;\nelect.sync _|P, 0xffffffff;\nselp.u32 %0, 1, 0, P;\n}\n" : "=r"(p));
  return p;
}
__device__ __forceinline__ void wg_fence() { asm volatile("wgmma.fence.sync.aligned;" ::: "memory"); }
__device__ __forceinline__ void wg_commit() { asm volatile("wgmma.commit_group.sync.aligned;" ::: "memory"); }
template <int n> __device__ __forceinline__ void wg_wait() { asm volatile("wgmma.wait_group.sync.aligned %0;" ::"n"(n) : "memory"); }
__device__ __forceinline__ void wg_bar(int w) { asm volatile("bar.sync %0, 128;" ::"r"(w + 1) : "memory"); }
__device__ __forceinline__ void cluster_sync() { asm volatile("barrier.cluster.arrive.relaxed.aligned;\nbarrier.cluster.wait.aligned;" ::: "memory"); }
__device__ __forceinline__ constexpr uint64_t desc_hi(uint32_t lbo, uint32_t sbo, int sw) {
  return ((uint64_t)(lbo >> 4) << 16) | ((uint64_t)(sbo >> 4) << 32) | ((uint64_t)sw << 62);
}
__device__ __forceinline__ void fence_gpu() { asm volatile("fence.acq_rel.gpu;" ::: "memory"); }
__device__ __forceinline__ uint32_t ld_relaxed(const uint32_t* p) { uint32_t v; asm volatile("ld.relaxed.gpu.global.u32 %0, [%1];" : "=r"(v) : "l"(p) : "memory"); return v; }
__device__ __forceinline__ uint4 ld_relaxed4(const uint4* p) {
  uint4 v; asm volatile("ld.relaxed.gpu.global.v4.u32 {%0,%1,%2,%3}, [%4];" : "=r"(v.x), "=r"(v.y), "=r"(v.z), "=r"(v.w) : "l"(p) : "memory"); return v;
}
__device__ __forceinline__ uint2 ld_relaxed2(const uint2* p) {
  uint2 v; asm volatile("ld.relaxed.gpu.global.v2.u32 {%0,%1}, [%2];" : "=r"(v.x), "=r"(v.y) : "l"(p) : "memory"); return v;
}
__device__ __forceinline__ void st_relaxed(uint32_t* p, uint32_t a) { asm volatile("st.relaxed.gpu.global.u32 [%0], %1;" ::"l"(p), "r"(a) : "memory"); }
__device__ __forceinline__ void st_relaxed4(uint4* p, uint32_t a, uint32_t b, uint32_t c, uint32_t d) {
  asm volatile("st.relaxed.gpu.global.v4.u32 [%0], {%1,%2,%3,%4};" ::"l"(p), "r"(a), "r"(b), "r"(c), "r"(d) : "memory");
}
__device__ __forceinline__ void st_relaxed2(uint2* p, uint32_t a, uint32_t b) {
  asm volatile("st.relaxed.gpu.global.v2.u32 [%0], {%1,%2};" ::"l"(p), "r"(a), "r"(b) : "memory");
}
__device__ __forceinline__ void red4(uint4* p, uint32_t a, uint32_t b, uint32_t c, uint32_t d) {
  asm volatile("red.relaxed.gpu.global.add.noftz.v4.bf16x2 [%0], {%1,%2,%3,%4};" ::"l"(p), "r"(a), "r"(b), "r"(c), "r"(d) : "memory");
}
__device__ __forceinline__ void red2(uint2* p, uint32_t a, uint32_t b) {
  asm volatile("red.relaxed.gpu.global.add.noftz.v2.bf16x2 [%0], {%1,%2};" ::"l"(p), "r"(a), "r"(b) : "memory");
}
constexpr int SPIN_MAX = 1 << 21;
__device__ __forceinline__ uint32_t pack_bf16(float lo, float hi) { uint32_t r; asm("cvt.rn.bf16x2.f32 %0, %1, %2;" : "=r"(r) : "f"(hi), "f"(lo)); return r; }
__device__ __forceinline__ float bf_lo(uint32_t v) { return __uint_as_float(v << 16); }
__device__ __forceinline__ float bf_hi(uint32_t v) { return __uint_as_float(v & 0xffff0000u); }
__device__ __forceinline__ float2 lds64(uint32_t a) { float2 v; asm volatile("ld.shared.v2.f32 {%0,%1}, [%2];" : "=f"(v.x), "=f"(v.y) : "r"(a)); return v; }
__device__ __forceinline__ void sts64f(uint32_t a, float x, float y) { asm volatile("st.shared.v2.f32 [%0], {%1,%2};" ::"r"(a), "f"(x), "f"(y) : "memory"); }
__device__ __forceinline__ void sts32(uint32_t a, uint32_t x) { asm volatile("st.volatile.shared.b32 [%0], %1;" ::"r"(a), "r"(x) : "memory"); }
__device__ __forceinline__ void gate(uint32_t a, int need) {
#pragma unroll 1
  for (int it = 0; it < SPIN_MAX; it++) {
    int v; asm volatile("ld.volatile.shared.b32 %0, [%1];" : "=r"(v) : "r"(a) : "memory");
    if (v >= need) break;
    if (GSLEEP) __nanosleep(GSLEEP);
  }
}
__device__ __forceinline__ void sts128(uint32_t a, uint32_t x, uint32_t y, uint32_t z, uint32_t u) { asm volatile("st.shared.v4.b32 [%0], {%1,%2,%3,%4};" ::"r"(a), "r"(x), "r"(y), "r"(z), "r"(u) : "memory"); }
__device__ __forceinline__ uint4 lds128(uint32_t a) { uint4 v; asm volatile("ld.shared.v4.u32 {%0,%1,%2,%3}, [%4];" : "=r"(v.x), "=r"(v.y), "=r"(v.z), "=r"(v.w) : "r"(a) : "memory"); return v; }
__device__ __forceinline__ uint32_t hmul2(uint32_t a, uint32_t b) { uint32_t r; asm("mul.rn.bf16x2 %0, %1, %2;" : "=r"(r) : "r"(a), "r"(b)); return r; }
__device__ __forceinline__ uint32_t hadd2(uint32_t a, uint32_t b) { uint32_t r; asm("add.rn.bf16x2 %0, %1, %2;" : "=r"(r) : "r"(a), "r"(b)); return r; }
__device__ __forceinline__ void stsm4(uint32_t a, uint32_t r0, uint32_t r1, uint32_t r2, uint32_t r3) {
  asm volatile("stmatrix.sync.aligned.m8n8.x4.shared.b16 [%0], {%1,%2,%3,%4};" ::"r"(a), "r"(r0), "r"(r1), "r"(r2), "r"(r3) : "memory");
}
__device__ __forceinline__ void stsm2(uint32_t a, uint32_t r0, uint32_t r1) {
  asm volatile("stmatrix.sync.aligned.m8n8.x2.shared.b16 [%0], {%1,%2};" ::"r"(a), "r"(r0), "r"(r1) : "memory");
}
__device__ __forceinline__ uint4 ldsm4(uint32_t a) {
  uint4 r; asm volatile("ldmatrix.sync.aligned.m8n8.x4.shared.b16 {%0,%1,%2,%3}, [%4];" : "=r"(r.x), "=r"(r.y), "=r"(r.z), "=r"(r.w) : "r"(a) : "memory"); return r;
}
__device__ __forceinline__ uint32_t movm(uint32_t a) { uint32_t r; asm("movmatrix.sync.aligned.m8n8.trans.b16 %0, %1;" : "=r"(r) : "r"(a)); return r; }
__device__ __forceinline__ void mma16816z(float (&d)[4], uint32_t a0, uint32_t a1, uint32_t a2, uint32_t a3, uint32_t b0, uint32_t b1) {
  asm("mma.sync.aligned.m16n8k16.row.col.f32.bf16.bf16.f32 {%0,%1,%2,%3}, {%4,%5,%6,%7}, {%8,%9}, {%10,%10,%10,%10};"
      : "=f"(d[0]), "=f"(d[1]), "=f"(d[2]), "=f"(d[3]) : "r"(a0), "r"(a1), "r"(a2), "r"(a3), "r"(b0), "r"(b1), "f"(0.f));
}
__device__ __forceinline__ void mma16816(float (&d)[4], const uint4& a, uint32_t b) {
  asm("mma.sync.aligned.m16n8k16.row.col.f32.bf16.bf16.f32 {%0,%1,%2,%3}, {%4,%5,%6,%7}, {%8,%8}, {%0,%1,%2,%3};"
      : "+f"(d[0]), "+f"(d[1]), "+f"(d[2]), "+f"(d[3]) : "r"(a.x), "r"(a.y), "r"(a.z), "r"(a.w), "r"(b));
}
__device__ __forceinline__ void mma1688(float (&d)[4], uint32_t a0, uint32_t a1, uint32_t b0) {
  asm("mma.sync.aligned.m16n8k8.row.col.f32.bf16.bf16.f32 {%0,%1,%2,%3}, {%4,%5}, {%6}, {%0,%1,%2,%3};"
      : "+f"(d[0]), "+f"(d[1]), "+f"(d[2]), "+f"(d[3]) : "r"(a0), "r"(a1), "r"(b0));
}
__device__ __forceinline__ float quad_sum(float v) { v += __shfl_xor_sync(0xffffffffu, v, 1); v += __shfl_xor_sync(0xffffffffu, v, 2); return v; }
__device__ __forceinline__ float quad_max(float v) { v = fmaxf(v, __shfl_xor_sync(0xffffffffu, v, 1)); v = fmaxf(v, __shfl_xor_sync(0xffffffffu, v, 2)); return v; }
__device__ __forceinline__ float rcp(float x) { float r; asm("rcp.approx.ftz.f32 %0, %1;" : "=f"(r) : "f"(x)); return r; }
__device__ __forceinline__ float rsq(float x) { float r; asm("rsqrt.approx.ftz.f32 %0, %1;" : "=f"(r) : "f"(x)); return r; }
__device__ __forceinline__ float ex2(float x) { float r; asm("ex2.approx.ftz.f32 %0, %1;" : "=f"(r) : "f"(x)); return r; }
__device__ __forceinline__ uint32_t chk(uint32_t acc, uint32_t v, uint32_t tag) { uint32_t r; asm("lop3.b32 %0, %1, %2, %3, 0xF6;" : "=r"(r) : "r"(acc), "r"(v), "r"(tag)); return r; }
__device__ __forceinline__ uint32_t chk2(uint32_t a, uint32_t b, uint32_t tag) { uint32_t r; asm("lop3.b32 %0, %1, %2, %3, 0x7E;" : "=r"(r) : "r"(a), "r"(b), "r"(tag)); return r; }
__device__ __forceinline__ uint32_t tagged(uint32_t v, uint32_t tag) { return (v & ~1u) | tag; }

__device__ __forceinline__ int group_k0(int g) { return g < 16 ? 64 * (g & 7) + 4 * (g & 8) : 32 * g; }
__device__ __forceinline__ uint32_t xin_off(int c, int w) { return SM_X + (2 * c + w + (2 * c + w < 9 ? 9 : -9)) * 8192; }
__device__ __forceinline__ uint32_t xin_bar(int c) { return BAR_FULLX + 8 * (c < 8 ? c ^ 4 : c); }
__device__ __forceinline__ int xin_order(int i, int j) { return i; }
__device__ __forceinline__ constexpr uint32_t qkv_xslot(int g) { return (0x5140762u >> (4 * (g - 5))) & 15; }

template <int N> struct IC { static constexpr int v = N; };
static_assert(WB4 <= 30 || WB4 == 36, "");

struct Cons {
  uint32_t sb;
  uint32_t rem;
  uint32_t sB, mB;
  uint32_t mX;
  bool elect;
  __device__ __forceinline__ void release2(uint32_t bar) const { if (elect) { mbar_arrive(sb + bar); mbar_arrive_remote(rem + bar); } }
  __device__ __forceinline__ uint32_t nextB(uint32_t& prev) {
    mbar_wait_c(sb + BAR_FULLB + sB, mB);
    const uint32_t a = (((sb & 0x3FFFF) + SM_B) >> 4) + sB * (BSLOT / 128);
    prev = sB == 0 ? 32 : sB - 8;
    sB += 8;
    if (sB == 40) { sB = 0; mB ^= 1; }
    return a;
  }
  __device__ __forceinline__ void progress(uint32_t v) const { if (elect) sts32(sb + SM_PROG + (threadIdx.x >> 5), v); }
  __device__ __forceinline__ void releaseLastB() const { release2(BAR_EMPTYB + (sB == 0 ? 32 : sB - 8)); }
};

template <bool QKV, class Pre, class Mma>
__device__ __forceinline__ float2 ln_gemm(Cons& c, Group* G, const float (&v)[36], uint32_t (&p)[18], bool direct, int w, int st0, int j, int t,
                                          uint32_t tag, uint32_t stag, Pre&& pre, Mma&& mma) {
  constexpr int NBUF = 6;
  const uint32_t pbase = direct ? 0 : 32;
  uint4* const box = G->act[QKV ? 0 : 2];
  uint4 x[NBUF][2];
  const uint4* src = box + t;
  uint32_t xa = c.sb + w * 8192 + (t >> 5) * 2048 + (t & 7) * 128 + (((t >> 3) & 3) ^ (t & 7)) * 16;
  asm volatile("" : "+l"(src), "+r"(xa));
  auto load = [&](int g) { x[g % NBUF][0] = ld_relaxed4(src + 2 * g * 128); x[g % NBUF][1] = ld_relaxed4(src + (2 * g + 1) * 128); };
  auto load_in = [&](int g) {
    if (g == 8) xa -= w * 8 * XSLOT;
    if (g == 10) xa += w * 8 * XSLOT;
    if (g == 16) xa = c.sb + w * 8192 + (t >> 5) * 2048 + (t & 15) * 128 + (((t >> 4) & 1) ^ (t & 7)) * 16;
    const uint32_t a = xa ^ (64 * (g & 1));
    x[g % NBUF][0] = ldsm4(a + xin_off(g >> 1, 0));
    x[g % NBUF][1] = ldsm4((g < 16 ? a + 1024 : a ^ 32) + xin_off(g >> 1, 0));
  };
  float s0 = 0.f, s1 = 0.f, d0 = 0.f, d1 = 0.f;
  auto sums = [&](const float (&v)[36]) {
    s0 = v[0] + v[1]; s1 = v[2] + v[3];
#pragma unroll
    for (int i = 1; i < 9; i++) { s0 += v[4 * i] + v[4 * i + 1]; s1 += v[4 * i + 2] + v[4 * i + 3]; }
    s0 = __uint_as_float((__float_as_uint(quad_sum(s0)) & ~3u) | stag); s1 = quad_sum(s1);
  };
  auto squares = [&](const float (&v)[36]) {
    const float m0 = s0 * (1.f / 72), m1 = s1 * (1.f / 72);
    d0 = d1 = 0.f;
#pragma unroll
    for (int i = 0; i < 9; i++) {
      float a = v[4 * i] - m0, b = v[4 * i + 1] - m0; d0 = fmaf(a, a, fmaf(b, b, d0));
      a = v[4 * i + 2] - m1; b = v[4 * i + 3] - m1; d1 = fmaf(a, a, fmaf(b, b, d1));
    }
    d0 = quad_sum(d0); d1 = quad_sum(d1);
  };
  auto load3 = [&](int g) { load(g); load(g + 1); load(g + 2); };
  auto invalid = [&](int g) {
    const uint4 (&y)[2] = x[g % NBUF], (&y1)[2] = x[(g + 1) % NBUF], (&y2)[2] = x[(g + 2) % NBUF];
    uint32_t bad = chk2(y[0].x, y[1].x, tag) | chk2(y1[0].x, y1[1].x, tag) | chk2(y2[0].x, y2[1].x, tag);
    if (g == 15) bad |= chk2(y1[0].z, y1[1].z, tag) | chk2(y2[0].z, y2[1].z, tag);
    return __any_sync(0xffffffffu, bad & 1);
  };
  uint4* const d = box + 2 * j * 128 + t;
  const int sq = st0 + 16 * (t & 3);
#pragma unroll
  for (int g = 0; g < NBUF; g++) x[g][0] = x[g][1] = make_uint4(tag ^ 1, 0, 0, 0);
  float m0, m1;
  if (direct) {
    float ra[4] = {0.f, 0.f, 0.f, 0.f}, rb[4] = {0.f, 0.f, 0.f, 0.f};
#pragma unroll 1
    for (int cc = 0; cc < 9; cc++) {
      const uint32_t a = xa - w * 8192 + xin_off(cc, w);
      mbar_wait_c(c.sb + xin_bar(cc), 0);
      const uint4 u0 = ldsm4(a), u1 = ldsm4(a + 1024), u2 = ldsm4(a ^ 64), u3 = ldsm4((a ^ 64) + 1024);
      mma16816(ra, u0, 0x3f803f80u); mma16816(rb, u1, 0x3f803f80u); mma16816(ra, u2, 0x3f803f80u); mma16816(rb, u3, 0x3f803f80u);
    }
    m0 = ra[0] + ra[2]; m1 = rb[0] + rb[2];
#pragma unroll
    for (int i = 0; i < 5; i++) {
      const uint4 u = ldsm4(c.sb + (t >> 5) * 2048 + (t & 15) * 128 + xin_off(i < 4 ? j : 8, w) + (((i < 4 ? 2 * i + ((t >> 4) & 1) : j) ^ (t & 7)) << 4));
      p[4 * i] = u.x; p[4 * i + 1] = u.y;
      if (i < 4) { p[4 * i + 2] = u.z; p[4 * i + 3] = u.w; }
    }
    pre(0);
  } else {
    sums(v);
    if ((t & 3) == 0) st_relaxed2(G->sum + st0 + 8 * j, __float_as_uint(s0), __float_as_uint(s1));
#pragma unroll
    for (int i = 0; i < 18; i++) p[i] = pack_bf16(v[2 * i], v[2 * i + 1]);
#pragma unroll
    for (int i = 0; i < 2; i++) st_relaxed4(d + i * 128, tagged(p[i], tag), p[i + 2], p[i + 4], p[i + 6]);
    uint2 sa, sc;
    auto poll = [&] {
      if (SPEC && (QKV || !tag) && invalid(0)) load3(0);
      sa = ld_relaxed2(G->sum + sq); sc = ld_relaxed2(G->sum + sq + 8);
    };
    poll();
    squares(v);
    pre(0);
    while (__any_sync(0xffffffffu, ((sa.x ^ stag) | (sc.x ^ stag)) & 3)) poll();
    if (invalid(0)) load3(0);
    m0 = quad_sum(__uint_as_float(sa.x) + __uint_as_float(sc.x)); m1 = quad_sum(__uint_as_float(sa.y) + __uint_as_float(sc.y));
  }
  m0 *= -1.f / 576; m1 *= -1.f / 576;
  const uint32_t nm0 = pack_bf16(m0, m0), nm1 = pack_bf16(m1, m1);
  pre(1);
  uint4 u0, u1;
#pragma unroll
  for (int g = 0; g < 18; g++) {
    uint4 &a = x[g % NBUF][0], &b = x[g % NBUF][1];
    if (direct) load_in(g);
    else if (g % 3 == 0) {
      while (invalid(g)) load3(g);
      if (g > 0 && g < 15) load3(g + 3);
    }
    const bool rows = g < 16;
    const uint4 f0 = make_uint4(hadd2(a.x, nm0), hadd2(rows ? b.x : a.y, nm1), hadd2(rows ? a.y : a.z, nm0), hadd2(rows ? b.y : a.w, nm1));
    const uint4 f1 = make_uint4(hadd2(rows ? a.z : b.x, nm0), hadd2(rows ? b.z : b.y, nm1), hadd2(rows ? a.w : b.z, nm0), hadd2(b.w, nm1));
    if (g == 12) { u0 = ld_relaxed4(G->m2 + sq); u1 = ld_relaxed4(G->m2 + sq + 8); }
    uint32_t prev = c.sB == 0 ? 32 : c.sB - 8, bb;
    if (QKV && g >= 5 && g < 12 && !direct) {
      mbar_wait_c(c.sb + BAR_FULLX + 8 * qkv_xslot(g), (c.mX >> qkv_xslot(g)) & 1);
      bb = ((c.sb & 0x3FFFF) + SM_X + qkv_xslot(g) * XSLOT) >> 4;
    } else {
      bb = c.nextB(prev);
    }
    if (QKV && g == GL && w == 1) asm volatile("bar.sync 6, 256;" ::: "memory");
    mma(g, bb, f0, f1);
    if (QKV && g == 17 && w == 0) asm volatile("bar.arrive 6, 256;" ::: "memory");
    if (g == 0) {
      if (!direct) {
        load3(3);
#pragma unroll
        for (int i = 0; i < 2; i++) st_relaxed4(d + (16 + i) * 128, tagged(p[8 + i], tag), p[10 + i], p[12 + i], p[14 + i]);
        st_relaxed2((uint2*)(box + (32 + (j >> 1)) * 128 + t) + (j & 1), tagged(p[16], tag), p[17]);
      } else {
        float u[36];
#pragma unroll
        for (int i = 0; i < 18; i++) { u[2 * i] = bf_lo(p[i]); u[2 * i + 1] = bf_hi(p[i]); }
        sums(u);
        squares(u);
      }
      if ((t & 3) == 0) st_relaxed4(G->m2 + st0 + 8 * j, __float_as_uint(s0), __float_as_uint(s1), __float_as_uint(d0), __float_as_uint(d1));
      c.progress(QKV ? pbase + 1 : 53 - 32 * tag);
    }
    wg_wait<1>();
    if (g > 0 && !(QKV && g > 5 && g <= 12 && !direct)) c.release2(BAR_EMPTYB + prev);
    if (SCHEDBAR && g % 3 == 2 && g < 17) mbar_wait_c(c.sb + BAR_FULLX + 64, 0);
    if (QKV && g > 0 && g < 15) c.progress(pbase + 1 + g);
    if (QKV && g >= WOG && g < WOG + 4) c.release2(BAR_EMPTYX + 32 + 8 * (g - WOG));
  }
  if (QKV) c.mX ^= direct ? 0xff : 0xf7;
  while (__any_sync(0xffffffffu, ((u0.x ^ stag) | (u1.x ^ stag)) & 3)) { u0 = ld_relaxed4(G->m2 + sq); u1 = ld_relaxed4(G->m2 + sq + 8); }
  float e0 = fmaf(__uint_as_float(u0.x), 1.f / 72, m0), e1 = fmaf(__uint_as_float(u1.x), 1.f / 72, m0);
  const float v0 = quad_sum(fmaf(72.f, fmaf(e0, e0, e1 * e1), __uint_as_float(u0.z) + __uint_as_float(u1.z)));
  e0 = fmaf(__uint_as_float(u0.y), 1.f / 72, m1); e1 = fmaf(__uint_as_float(u1.y), 1.f / 72, m1);
  const float v1 = quad_sum(fmaf(72.f, fmaf(e0, e0, e1 * e1), __uint_as_float(u0.w) + __uint_as_float(u1.w)));
  float2 r = make_float2(rsq(fmaf(v0, 1.f / 576, 1e-5f)), rsq(fmaf(v1, 1.f / 576, 1e-5f)));
  asm volatile("" : "+f"(r.x), "+f"(r.y));
  if (QKV && GL == 18 && w == 1) asm volatile("bar.sync 6, 256;" ::: "memory");
  wg_wait<0>();
  if (QKV && ATTBAR && w == 1) asm volatile("bar.arrive 4, 256;" ::: "memory");
  c.releaseLastB();
  if (direct) c.release2(BAR_EMPTYX + 24);
  return r;
}

template <int NB, int OFF>
__device__ __forceinline__ void glu(const float (&a)[128], uint32_t (&h)[144]) {
#pragma unroll
  for (int b = 0; b < 2 * NB; b++) {
    if (HMUL) h[OFF + b] = hmul2(pack_bf16(a[2 * b], a[2 * b + 1]), pack_bf16(a[4 * NB + 2 * b], a[4 * NB + 2 * b + 1]));
    else h[OFF + b] = pack_bf16(a[2 * b] * a[4 * NB + 2 * b], a[2 * b + 1] * a[4 * NB + 2 * b + 1]);
  }
}

__global__ void __cluster_dims__(2, 1, 1) __launch_bounds__(384, 1)
fused_kernel(const __nv_bfloat16* __restrict__ x_in, Group* ws, const char* __restrict__ wqkv,
             const char* __restrict__ wg, const char* __restrict__ wu, const char* __restrict__ wd, const __grid_constant__ Maps maps,
             const char* __restrict__ wo) {
  extern __shared__ __align__(1024) uint8_t smem_raw[];
  const uint32_t sb = smem_u32(smem_raw);
  if (threadIdx.x == 0) asm volatile("prefetch.tensormap [%0];" ::"l"(&maps.x) : "memory");
  const int warp = __shfl_sync(0xffffffffu, threadIdx.x >> 5, 0);
  const int lane = threadIdx.x & 31;
  const int rank = blockIdx.x & 1;
  if (elect_one()) {
    if (warp >= 8) {
#pragma unroll
      for (int i = 0; i < 9; i++) mbar_init(sb + SM_BAR + 72 * (warp - 8) + 8 * i, warp < 10 ? 1 : 4);
      sts32(sb + SM_PROG + 4 * (warp - 8), 0);
      asm volatile("fence.mbarrier_init.release.cluster;" ::: "memory");
    } else if (warp == 1 || warp == 2) {
      asm volatile("prefetch.tensormap [%0];" ::"l"(&maps.x + warp) : "memory");
    } else if (warp == 3) {
      if (PFMODE & 1) prefetch_l2((const char*)x_in + blockIdx.x * 18432, 18432);
    } else if (warp == 4) {
      if (PFMODE & 2) prefetch_l2(wqkv + blockIdx.x * (15552 / PFQ), 15552 / PFQ);
    }
  }
  __syncwarp();
  asm volatile("barrier.cluster.arrive.relaxed.aligned;" ::: "memory");
  if (warp == 8) PROFX(53);
  int lb = blockIdx.x;
  if (GPCMAP) {
    const int cl = blockIdx.x >> 1, u = cl - 36;
    lb = (cl < 4 ? cl : cl < 36 ? 8 * ((cl - 4) & 7) + ((cl - 4) >> 3) + (((cl - 4) & 7) ? 0 : 4) : 8 * (1 + u % 7) + 4 + u / 7) * 2 + rank;
  }
#define CTA_J(b) (((b) >> 1) & 7)
#define CTA_RB(b) ((((b) >> 4) << 1) | ((b) & 1))
  const int j = CTA_J(lb), rb = CTA_RB(lb);

  PROF(23);
  if (warp >= 8) {
    asm volatile("setmaxnreg.dec.sync.aligned.u32 " STR(REGS_P) ";");
    auto x_chunk = [&](int cc) {
      mbar_expect_tx(sb + xin_bar(cc), 16384);
      tma3d(sb + xin_off(cc, 0), &maps.x, 64 * cc, 0, 64 * rb, sb + xin_bar(cc));
      tma3d(sb + xin_off(cc, 1), &maps.x, 64 * cc, 1, 64 * rb, sb + xin_bar(cc));
    };
    if (warp == 9 && elect_one()) {
      fence_async_smem();
#pragma unroll 1
      for (int i = 0; i < 9; i++) x_chunk(xin_order(i, j));
    }
    __syncwarp();
    if (warp == 9) PROFX(54);
    asm volatile("barrier.cluster.wait.aligned;" ::: "memory");
    if (warp == 8) PROFX(56);
    const uint64_t pol = W_POLICY(), pola = A_POLICY();
    auto qkv_group = [&](int k, uint32_t dst, uint32_t bar) {
      wtma3d(dst + rank * 8192, &maps.qm, 72 * j, k + 16 * rank, 0, bar, pola);
      wtma3d(dst + rank * 8192 + 6144, &maps.qc, 72 * j + 64, k + 16 * rank, 0, bar, pola);
    };
    auto qkv_gate = [&](int g) { if (g >= 8) gate(sb + SM_PROG, 33 + ((g - 8) * 23 >> 4)); };
    if (warp == 8) {
      uint32_t s = 0, ph = 1;
      auto slot = [&](uint32_t bytes, auto&& issue) {
        const uint32_t bar = sb + BAR_FULLB + 8 * s;
        mbar_wait(sb + BAR_EMPTYB + 8 * s, ph);
        if (elect_one()) {
          mbar_expect_tx(bar, bytes);
          issue(sb + SM_B + s * BSLOT, bar);
        }
        if (++s == 5) { s = 0; ph ^= 1; }
      };
#pragma unroll 1
      for (int layer = 0; layer < NLAYERS; layer++) {
#pragma unroll 1
        for (int g = 0; g < 18; g += layer && g == 4 ? 8 : 1) {
          if (layer) qkv_gate(g);
          else if (g == QD) mbar_wait(sb + xin_bar(xin_order(XH, j)), 0);
          slot(2 * 6912, [&](uint32_t dst, uint32_t bar) { qkv_group(layer ? group_k0(g) : 32 * g, dst, bar); });
        }
        if (!FCH) {
          gate(sb + SM_PROG, 32 * layer + 20);
          gate(sb + SM_PROG + 4, 32 * layer + 20);
        }
#pragma unroll 1
        for (int t = 0; t < 5; t++) {
          const CUtensorMap* m = &maps.g + (t < 3 ? rank : 2 + rank);
          const int c2 = t < 3 ? 9 * j + 2 * t : 18 * j + 3 + 3 * t;
          const uint32_t half = t < 3 ? 8192 : 6144;
#pragma unroll 1
          for (int g = 0; g < 18; g++) {
            if (FCH && t == 0 && g < 5) mbar_wait(sb + BAR_FULLB + 8 * (s < FCH ? s + 5 - FCH : s - FCH), s < FCH ? ph : ph ^ 1);
            slot(2 * half, [&](uint32_t dst, uint32_t bar) { wtma3d(dst + rank * half, m, 0, group_k0(g), c2, bar, pol); });
          }
        }
      }
    } else if (warp == 9) {
      uint32_t mE = 0;
      auto acquire = [&](uint32_t s) { mbar_wait(sb + BAR_EMPTYX + 8 * s, (mE >> s) & 1); mE ^= 1u << s; };
      auto landed = [&](uint32_t s) { mbar_wait(sb + BAR_FULLX + 8 * s, (mE >> s) & 1); };
      auto slot = [&](uint32_t s, const CUtensorMap* m, int col, int row, uint64_t pol) {
        acquire(s);
        if (elect_one()) {
          mbar_expect_tx(sb + BAR_FULLX + 8 * s, XSLOT);
          wtma2d(sb + SM_X + s * XSLOT + rank * 9216, m, col, row + 72 * rank, sb + BAR_FULLX + 8 * s, pol);
        }
      };
#pragma unroll 1
      for (int layer = 0; layer < NLAYERS; layer++) {
#pragma unroll 1
        for (int g = 5; g < 12 * layer; g++) {
          const uint32_t s = qkv_xslot(g);
          qkv_gate(g);
          acquire(s);
          if (elect_one()) {
            mbar_expect_tx(sb + BAR_FULLX + 8 * s, 2 * 6912);
            qkv_group(group_k0(g), sb + SM_X + s * XSLOT, sb + BAR_FULLX + 8 * s);
          }
          if (XCH & 1) landed(s);
        }
#pragma unroll 1
        for (int i = 0; i < 4; i++) { slot(4 + i, &maps.o, 64 * j, 144 * i, pola); if (XCH & 2) landed(4 + i); }
        acquire(3);
        if (elect_one()) {
          mbar_expect_tx(sb + BAR_FULLX + 24, 9216);
          wtma2d(sb + SM_WOC + rank * 4608, &maps.oc, 512 + 8 * j, 288 * rank, sb + BAR_FULLX + 24, pola);
          wtma2d(sb + SM_WOC + rank * 4608 + 2304, &maps.oc, 512 + 8 * j, 288 * rank + 144, sb + BAR_FULLX + 24, pola);
        }
#pragma unroll 1
        for (int u = 0; u < 36; u++) {
          const uint32_t s = 4 * (u & 1) + ((u >> 1) & 3);
          slot(s, &maps.d, u < 4 ? 512 : 64 * ((j + (u >> 2)) & 7), 576 * j + 144 * (u & 3), pol);
          if ((XCH & 4) && u < 3) landed(s);
        }
      }
    } else {
      const int w = warp - 10, grp = 2 * rb + w;
      if (PFMODE & 4) {
        mbar_wait(sb + xin_bar(xin_order(XP, j)), 0);
        if (lane == 0) prefetch_l2(wqkv + (2 * blockIdx.x + w) * 7776, 7776);
      }
      gate(sb + SM_PROG, 3);
      if (w == 0) PROFX(58);
      auto prefetch_gu = [&](int l0, int n) {
#pragma unroll 1
        for (int i = lane; i < 36 * n; i += 32) {
          asm volatile("prefetch.global.L2 [%0];" ::"l"((w ? wu : wg) + (size_t)(36 * rb + i / n) * 9216 + 1152 * j + 128 * (l0 + i % n)));
          __nanosleep(PFSLEEP);
        }
      };
      auto clear = [&](uint4* p, int n) {
#pragma unroll 1
        for (int i = lane; i < n; i += 64) { st_relaxed4(p + i, 0, 0, 0, 0); st_relaxed4(p + i + 32, 0, 0, 0, 0); __nanosleep(CLRSLEEP); }
      };
      auto exchange = [&](uint32_t v, uint32_t bar) {
        fence_gpu();
        __syncwarp();
        if (lane == 0) st_relaxed(ws[grp].flag + j, v);
#pragma unroll 1
        for (int it = 0; it < SPIN_MAX; it++) {
          const uint32_t f = ld_relaxed(ws[grp].flag + (lane & 7));
          if (__all_sync(0xffffffffu, v ? f >= v : f == 0)) break;
        }
        if (lane == 0) mbar_arrive(sb + bar + 8 * w);
      };
      if (lane == 0) prefetch_l2(wo + (2 * blockIdx.x + w) * 2592, 2592);
      if (MAPPF && w == 0 && lane < 9) asm volatile("prefetch.tensormap [%0];" ::"l"(&maps.o + lane) : "memory");
#pragma unroll 1
      for (int layer = 0; layer < NLAYERS; layer++) {
        gate(sb + SM_PROG, 32 * layer + 3);
        if (PFF & 1) prefetch_gu(0, 2);
        gate(sb + SM_PROG, 32 * layer + 22);
        if (PFF & 2) prefetch_gu(2, 2);
        if (layer == 0) {
          clear(ws[grp].act[0] + 576 * j, 576);
          clear(ws[grp].inbox[0] + 2 * j * INBOX, 2 * INBOX);
          exchange(1, BAR_CLR);
          if (w == 0) PROFX(59);
        }
        if (PFF & 2) prefetch_gu(4, 2);
        if (PFF & 4) prefetch_gu(6, 3);
#pragma unroll 1
        for (int i = lane; i < ((PFF & 8) ? 162 : 0); i += 32) {
          asm volatile("prefetch.global.L2 [%0];" ::"l"(wd + (size_t)(576 * j + 36 * rb + 18 * w) * 1152 + 128 * i));
          __nanosleep(PFSLEEP);
        }
        if (w == 0 && layer == 0) PROFX(60);
        mbar_wait(sb + BAR_REDDONE + 8 * w, layer);
        if (w == 0) PROFX(64 + 53 + 4 * layer);
        exchange(2 - 2 * layer, BAR_RREADY);
        if (w == 0) PROFX(64 + 56 + 4 * layer);
      }
      mbar_wait(sb + BAR_DONE + 8 * w, 0);
    }
    __syncwarp();
    cluster_sync();
  } else {
    asm volatile("setmaxnreg.inc.sync.aligned.u32 " STR(REGS_C) ";");
#define THREAD_IDS()                                                                   \
    int tid_ = threadIdx.x, bid_ = lb;                                                  \
    asm volatile("" : "+r"(tid_), "+r"(bid_));                                          \
    const int w = warp >> 2, wp = warp & 3;                                             \
    const int lane = tid_ & 31, t = tid_ & 127, g = lane >> 2, q = lane & 3;           \
    const int j = CTA_J(bid_), rb = CTA_RB(bid_), grp = 2 * rb + w;                    \
    const int st0 = wp * 64 + g;                         \
    Group* const G = ws + grp;                                                         \
    const uint32_t dsb = (sb & 0x3FFFF) >> 4;                                          \
    (void)t; (void)g; (void)q; (void)grp; (void)j; (void)st0; (void)dsb; (void)G
    Cons c;
    c.sb = sb; c.sB = 0; c.mB = 0; c.mX = 0; c.elect = (threadIdx.x & 127) == 0;
    asm volatile("mapa.shared::cluster.u32 %0, %1, %2;" : "=r"(c.rem) : "r"(sb), "r"(rank ^ 1));
    float v[36];
    {
      THREAD_IDS();
      if (OPEN) {
        if (q == 0) { st_relaxed2(G->sum + st0 + 8 * j, 0, 0); st_relaxed4(G->m2 + st0 + 8 * j, 0, 0, 0, 0); }
        if (wp == 3) {
#pragma unroll
          for (int i = 0; i < 5; i++) st_relaxed4(G->halo + j * 160 + lane + i * 32, 0, 0, 0, 0);
        }
      }
      asm volatile("barrier.cluster.wait.aligned;" ::: "memory");
      PROF(0);
#pragma unroll
      for (int i = 0; i < 36; i++) v[i] = 0.f;
    }
#pragma unroll 1
    for (int layer = 0;; layer++) {
      const uint32_t tag = layer ^ 1;
      const int pb = 1 + layer * 30;
      uint32_t res[18];
      {
        THREAD_IDS();
        PROF(pb + 0);
        float a1[96], a2[12];
        const float2 rs = ln_gemm<true>(c, G, v, res, layer == 0, w, st0, j, t, 1, 2 * layer + 1,
          [&](int i) { PROF(pb + 1 + i); },
          [&](int gi, uint32_t bb, const uint4& f0, const uint4& f1) {
            if (gi == 0) PROF(pb + 3);
            wg_fence();
            wgmma_ra<192>(a1, f0, desc_hi(2048, 1024, 1) + bb, gi > 0);
            wgmma_ra<24>(a2, f0, desc_hi(128, 256, 0) + (bb + 384), gi > 0);
            wgmma_ra<192>(a1, f1, desc_hi(2048, 1024, 1) + (bb + 512), true);
            wgmma_ra<24>(a2, f1, desc_hi(128, 256, 0) + (bb + 896), true);
            wg_commit();
          });
        PROF(pb + 4);
        uint32_t kv[3][18];
        auto cvt = [&](int b, float r) {
#pragma unroll
          for (int cc = 0; cc < 18; cc++) {
            const float* a = (cc == 8 ? a2 + 4 : cc == 17 ? a2 + 8 : cc < 8 ? a1 + 32 + 4 * cc : a1 + 28 + 4 * cc) + 2 * (b - 1);
            const uint32_t u = pack_bf16(a[0] * r, a[1] * r);
            kv[b][cc] = cc < 9 ? u : movm(u);
          }
        };
        cvt(2, rs.y);
        const uint32_t msg = sb + SM_X + (w ? 3 * XSLOT : 24576) + wp * 2304 + lane * 16;
        if (wp == 3) {
          uint4* hp = G->halo + j * 160 + lane;
#pragma unroll
          for (int i = 0; i < 4; i++) st_relaxed4(hp + i * 32, tagged(kv[2][4 * i], tag), kv[2][4 * i + 1], kv[2][4 * i + 2], kv[2][4 * i + 3]);
          st_relaxed2((uint2*)(hp + 128), tagged(kv[2][16], tag), kv[2][17]);
        } else {
#pragma unroll
          for (int i = 0; i < 4; i++) sts128(msg + i * 512, kv[2][4 * i], kv[2][4 * i + 1], kv[2][4 * i + 2], kv[2][4 * i + 3]);
          sts64f(msg + 2048 - lane * 8, __uint_as_float(kv[2][16]), __uint_as_float(kv[2][17]));
        }
        cvt(1, rs.x);
        uint32_t Q[4][6];
#pragma unroll
        for (int h = 0; h < 4; h++)
#pragma unroll
          for (int i = 0; i < 6; i++) {
            const float* a = 4 * h + i < 16 ? a1 + 8 * h + 2 * i : a2 + 8 * h + 2 * i - 32;
            const uint32_t u = pack_bf16(a[0], a[1]);
            Q[h][i] = i < 2 ? (q >= h ? u : 0) : i < 4 ? u : (q <= h ? u : 0);
          }
        const bool lo0 = 2 * q > g, lo1 = 2 * q + 1 > g;
        const uint32_t M = (lo0 ? 0xffffu : 0u) | (lo1 ? 0xffff0000u : 0u);
        auto scores = [&](int h, int b, float (&s)[4]) {
          mma16816z(s, Q[h][0], Q[h][1], Q[h][2], Q[h][3], kv[b][2 * h], kv[b][2 * h + 1]);
          mma1688(s, Q[h][4], Q[h][5], kv[b][2 * h + 2]);
        };
        auto softmax = [&](float (&l)[4][2], float r, uint32_t (&P)[4]) {
          const float sl = r * (0.23570226039551584f * 1.4426950408889634f);
          float m[4];
#pragma unroll
          for (int h = 0; h < 4; h++) { m[h] = fmaxf(l[h][0], l[h][1]); m[h] = fmaxf(m[h], __shfl_xor_sync(0xffffffffu, m[h], 1)); }
#pragma unroll
          for (int h = 0; h < 4; h++) m[h] = fmaxf(m[h], __shfl_xor_sync(0xffffffffu, m[h], 2)) * sl;
#pragma unroll
          for (int h = 0; h < 4; h++) {
            l[h][0] = ex2(fmaf(l[h][0], sl, -m[h])); l[h][1] = ex2(fmaf(l[h][1], sl, -m[h]));
            m[h] = l[h][0] + l[h][1]; m[h] += __shfl_xor_sync(0xffffffffu, m[h], 1);
          }
#pragma unroll
          for (int h = 0; h < 4; h++) { m[h] = rcp(m[h] + __shfl_xor_sync(0xffffffffu, m[h], 2)); P[h] = pack_bf16(l[h][0] * m[h], l[h][1] * m[h]); }
        };
        const bool remote = wp == 0 && rb > 0;
        const uint4* hp = (G - 2)->halo + j * 160 + lane;
        auto halo = [&] {
#pragma unroll
          for (int i = 0; i < 4; i++) { const uint4 u = ld_relaxed4(hp + i * 32); kv[0][4 * i] = u.x; kv[0][4 * i + 1] = u.y; kv[0][4 * i + 2] = u.z; kv[0][4 * i + 3] = u.w; }
          const uint2 u = ld_relaxed2((const uint2*)(hp + 128));
          kv[0][16] = u.x; kv[0][17] = u.y;
        };
#pragma unroll
        for (int i = 0; i < 18; i++) kv[0][i] = 0;
        if (remote) halo();
        if (ATTBAR && w == 0) asm volatile("bar.sync 4, 256;" : "+r"(Q[0][2]), "+r"(Q[1][2]), "+r"(Q[2][2]), "+r"(Q[3][2]) :: "memory");
        float l0[4][2], l1[4][2];
#pragma unroll
        for (int h = 0; h < 4; h++) {
          float s1[4], s2[4];
          scores(h, 1, s1); scores(h, 2, s2);
          l0[h][0] = s1[0]; l0[h][1] = s1[1];
          l1[h][0] = lo0 ? s1[2] : s2[2]; l1[h][1] = lo1 ? s1[3] : s2[3];
        }
        uint32_t P0[4], P1[4];
        softmax(l1, rs.y, P1);
        if (remote) {
          while (__any_sync(0xffffffffu, chk(chk2(kv[0][0], kv[0][4], tag) | chk2(kv[0][8], kv[0][12], tag), kv[0][16], tag) & 1)) halo();
        }
        if (FG < 0) c.progress(32 * layer + 20);
        wg_bar(w);
        if (wp > 0) {
          const uint32_t from = msg - 2304;
#pragma unroll
          for (int i = 0; i < 4; i++) { const uint4 u = lds128(from + i * 512); kv[0][4 * i] = u.x; kv[0][4 * i + 1] = u.y; kv[0][4 * i + 2] = u.z; kv[0][4 * i + 3] = u.w; }
          const float2 u = lds64(from + 2048 - lane * 8);
          kv[0][16] = __float_as_uint(u.x); kv[0][17] = __float_as_uint(u.y);
        }
        PROF(pb + 5);
        const bool first = (rb == 0 && wp == 0);
#pragma unroll
        for (int h = 0; h < 4; h++) {
          float s0[4];
          scores(h, 0, s0);
          if (first) s0[0] = s0[1] = -INFINITY;
          l0[h][0] = lo0 ? s0[0] : l0[h][0]; l0[h][1] = lo1 ? s0[1] : l0[h][1];
        }
        softmax(l0, rs.x, P0);
        uint4* ob = G->act[1] + t;
        uint32_t car0 = 0, car1 = 0;
#pragma unroll
        for (int h = 0; h < 4; h++) {
          float o[3][4];
#pragma unroll
          for (int i = 0; i < 3; i++) {
            mma16816z(o[i], P0[h] & ~M, P1[h] & M, 0u, P1[h] & ~M, kv[1][9 + 2 * h + i], kv[2][9 + 2 * h + i]);
            mma1688(o[i], P0[h] & M, 0u, kv[0][9 + 2 * h + i]);
          }
          const uint32_t o0 = q < h ? car0 : pack_bf16(o[0][0], o[0][1]), o1 = q < h ? car1 : pack_bf16(o[0][2], o[0][3]);
          st_relaxed4(ob + (8 * h + j) * 128, tagged(o0, tag), o1, pack_bf16(o[1][0], o[1][1]), pack_bf16(o[1][2], o[1][3]));
          car0 = pack_bf16(o[2][0], o[2][1]); car1 = pack_bf16(o[2][2], o[2][3]);
        }
        st_relaxed2((uint2*)(ob + (32 + (j >> 1)) * 128) + (j & 1), tagged(car0, tag), car1);
        PROF(pb + 6);
      }
      {
        THREAD_IDS();
        const uint4* src = G->act[1] + t;
        float a[32], a8[4];
#pragma unroll
        for (int i = 3; i < 8; i++) mbar_wait_c(sb + BAR_FULLX + 8 * i, (c.mX >> i) & 1);
        c.mX ^= 0xf8;
        const uint32_t* probe = &(G->act[1] + (8 * WPROBE + (lane & 7)) * 128 + (t | 31))->x;
        while (__any_sync(0xffffffffu, (ld_relaxed(probe) ^ tag) & 1)) {}
        if (w == 1) asm volatile("bar.sync 7, 256;" ::: "memory");
        uint4 x[36];
        auto batch = [&](auto e0, auto e1, auto e2, int b) {
          constexpr int E0 = decltype(e0)::v, E1 = decltype(e1)::v, E2 = decltype(e2)::v;
          while (E1 > E0) {
            uint32_t bad = chk2(x[E0].x, x[E0 + 1].x, tag);
#pragma unroll
            for (int i = E0 + 2; i < E1; i++) { bad = chk(bad, x[i].x, tag); if (i >= 32) bad = chk(bad, x[i].z, tag); }
            if (!__any_sync(0xffffffffu, bad & 1)) break;
#pragma unroll
            for (int i = E0; i < E1; i++) x[i] = ld_relaxed4(src + i * 128);
          }
          if (b == 0) PROF(pb + 7);
#pragma unroll
          for (int i = E1; i < E2; i++) x[i] = ld_relaxed4(src + i * 128);
          if (b == WOREL && w == 0) asm volatile("bar.arrive 7, 256;" ::: "memory");
          if (E1 > E0) {
            wg_fence();
#pragma unroll
            for (int i = E0; i < E1; i++) {
              const int r0 = i < 32 ? 72 * (i & 7) + 16 * (i >> 3) : 144 * (i - 32) + 64, rs = i < 32 ? 8 : 72;
              wgmma_ra<64>(a, x[i], desc_hi(0, rs * 128, 1) + (dsb + ((SM_X + 4 * XSLOT) >> 4) + r0 * 8), i > 0);
              wgmma_ra<8>(a8, x[i], desc_hi(rs * 16, 0, 0) + (dsb + (SM_WOC >> 4) + r0), i > 0);
            }
            wg_commit();
            if (SCHEDBAR && E1 < 36) mbar_wait_c(sb + BAR_FULLX + 64, 0);
          }
        };
        batch(IC<0>(), IC<0>(), IC<WB1>(), -1);
        batch(IC<0>(), IC<WB1>(), IC<WB2>(), 0);
        batch(IC<WB1>(), IC<WB2>(), IC<WB3>(), 1);
        batch(IC<WB2>(), IC<WB3>(), IC<WB4>(), 2);
        batch(IC<WB3>(), IC<WB4>(), IC<36>(), 3);
        batch(IC<WB4>(), IC<36>(), IC<36>(), 4);
        wg_wait<0>();
        if (w == 0) asm volatile("bar.arrive 3, 256;" ::: "memory");
        PROF(pb + 8);
#pragma unroll
        for (int i = 0; i < 18; i++) {
          v[2 * i] = bf_lo(res[i]) + (i < 16 ? a[2 * i] : a8[2 * i - 32]);
          v[2 * i + 1] = bf_hi(res[i]) + (i < 16 ? a[2 * i + 1] : a8[2 * i - 31]);
        }
      }
      uint32_t lsb;
      uint32_t h[144];
      {
        THREAD_IDS();
        float a[128];
        const uint32_t xd = sb + SM_X + w * 4 * XSLOT + (lane >> 4) * 1024 + (16 * wp + (lane & 15)) * 16;
        const float2 rs = ln_gemm<false>(c, G, v, res, false, w, st0, j, t, tag, (2 * layer + 2) & 3,
          [&](int i) {
            if (i == 0) {
              lsb = ((res[0] & 1) | (res[1] & 1) << 1 | (res[8] & 1) << 2 | (res[9] & 1) << 3 | (res[16] & 1) << 4) ^ (tag * 31);
              if (w == 1) asm volatile("bar.sync 3, 256;" ::: "memory");
            }
            PROF(pb + 9 + i);
          },
          [&](int gi, uint32_t bb, const uint4& f0, const uint4& f1) {
            if (gi == 0) PROF(pb + 11);
            wg_fence();
            wgmma_ra<256>(a, f0, desc_hi(4096, 1024, 1) + bb, gi > 0);
            wgmma_ra<256>(a, f1, desc_hi(4096, 1024, 1) + (bb + 128), true);
            wg_commit();
            stsm4(xd + gi * 4096, f0.x, f0.y, f0.z, f0.w);
            stsm4(xd + gi * 4096 + 2048, f1.x, f1.y, f1.z, f1.w);
            if (gi == 17) { fence_async_smem(); wg_bar(w); }
          });
        sts64f(sb + SM_KEEP + tid_ * 8, rs.x * rs.x, rs.y * rs.y);
        c.progress(32 * layer + 22);
        PROF2(pb + 12);
        glu<16, 0>(a, h);
        const uint64_t da0 = desc_hi(1024, 128, 0) + (dsb + ((SM_X + w * 4 * XSLOT) >> 4));
        auto tile = [&](auto wide, auto last) {
          const uint32_t xe = BAR_EMPTYX + 32 * (t & 1) + 4 * (t & 6);
#pragma unroll 1
          for (int gi = 0; gi < 18; gi++) {
            uint32_t prev;
            const uint32_t bb = c.nextB(prev);
            const uint64_t da = da0 + gi * 256;
            wg_fence();
            if (wide()) {
              wgmma_ss<256>(a, da, desc_hi(4096, 1024, 1) + bb, gi);
              wgmma_ss<256>(a, da + 128, desc_hi(4096, 1024, 1) + (bb + 128), 1);
            } else {
              wgmma_ss<192>(*(float(*)[96])a, da, desc_hi(2048, 512, 2) + bb, gi);
              wgmma_ss<192>(*(float(*)[96])a, da + 128, desc_hi(2048, 512, 2) + (bb + 64), 1);
            }
            wg_commit();
            wg_wait<1>();
            if (gi > 0 && !(last() && gi > 13)) c.release2(BAR_EMPTYB + prev);
            if (last() && gi >= XREL && !((gi ^ XREL) & 1)) c.release2(BAR_EMPTYX + 16 * ((gi - XREL) & 2) + 2 * ((gi - XREL) & 12));
          }
          wg_wait<0>();
          if (!last()) c.releaseLastB();
          if (last() && t >= (19 - XREL) / 2 && t < 8) { mbar_arrive(sb + xe); mbar_arrive_remote(c.rem + xe); }
        };
        auto yes = [] { return true; };
        auto no = [] { return false; };
        tile(yes, no); PROF2(pb + 13); glu<16, 32>(a, h);
        tile(yes, no); PROF2(pb + 14); glu<16, 64>(a, h);
        tile(no, no); PROF2(pb + 15); glu<12, 96>(a, h);
        const uint32_t hole = sb + SM_B + 12288 + tid_ * 16;
#pragma unroll
        for (int i = 0; i < NSPILL; i++) sts128(hole + i * BSLOT, h[96 + 4 * i], h[97 + 4 * i], h[98 + 4 * i], h[99 + 4 * i]);
        if (w == 1) asm volatile("bar.arrive 8, 256;" ::: "memory");
        tile(no, yes); PROF2(pb + 16); glu<12, 120>(a, h);
#pragma unroll
        for (int i = 0; i < NSPILL; i++) { const uint4 u = lds128(hole + i * BSLOT); h[96 + 4 * i] = u.x; h[97 + 4 * i] = u.y; h[98 + 4 * i] = u.z; h[99 + 4 * i] = u.w; }
      }
      {
        THREAD_IDS();
        float d[32];
        uint4* const ib = G->inbox[layer];
        auto pass = [&](uint32_t s0, bool last, auto&& hook) {
          const uint64_t db = desc_hi(0, 1024, 1) + (dsb + (SM_X >> 4) + s0 * (XSLOT >> 4));
          mbar_wait_c(sb + BAR_FULLX + 8 * s0, (c.mX >> s0) & 1);
          asm volatile("bar.sync %0, 256;" ::"r"(8 + w) : "memory");
#pragma unroll
          for (int i = 0; i < 4; i++) {
            const int si = 4 * (i & 1) + (i >> 1);
            if (i > 0) mbar_wait_c(sb + BAR_FULLX + 8 * (s0 + si), (c.mX >> (s0 + si)) & 1);
            wg_fence();
#pragma unroll
            for (int k = 0; k < 9; k++) {
              const uint32_t* hk = h + 36 * i + 4 * k;
              wgmma_ra<64>(d, make_uint4(hk[0], hk[1], hk[2], hk[3]), db + (si * (XSLOT >> 4) + k * 128), last || i + k > 0);
              if (9 * i + k == PPK && !(last && w == 1)) asm volatile("bar.arrive %0, 256;" ::"r"(9 - w) : "memory");
            }
            wg_commit();
            if (i > 0) { wg_wait<1>(); c.release2(BAR_EMPTYX + 8 * (s0 + 4 * ((i - 1) & 1) + ((i - 1) >> 1))); }
            if (i == RHOOK) hook();
          }
          c.mX ^= 0x33u << s0;
        };
        PROF2(pb + 17);
#pragma unroll 1
        for (int p = 0; p < 8; p++) {
          const uint32_t s0 = 2 * (p & 1);
          pass(s0, false, [] {});
          wg_wait<0>();
          c.release2(BAR_EMPTYX + 8 * (s0 + 5));
          uint32_t pk[16];
#pragma unroll
          for (int i = 0; i < 16; i++) pk[i] = pack_bf16(d[2 * i], d[2 * i + 1]);
          uint4* const dst = ib + ((j + p) & 7) * INBOX + t;
          if (p == 0) {
            if (t < 5) { mbar_arrive(sb + BAR_EMPTYB + 8 * t); mbar_arrive_remote(c.rem + BAR_EMPTYB + 8 * t); }
            mbar_wait_c(sb + BAR_CLR + 8 * w, 0);
#pragma unroll
            for (int k = 0; k < 8; k++) red2((uint2*)(ib + k * INBOX + 1024) + t, pk[2 * k], pk[2 * k + 1]);
          } else if (p < 7) {
#pragma unroll
            for (int k = 0; k < 4; k++) red4(dst + k * 128, pk[4 * k], pk[4 * k + 1], pk[4 * k + 2], pk[4 * k + 3]);
            if (p == 6) { __syncwarp(); if (lane == 0) mbar_arrive(sb + BAR_REDDONE + 8 * w); }
          } else {
#pragma unroll
            for (int k = 0; k < 4; k++) st_relaxed4(dst + 512 + k * 128, max(pk[4 * k], 1u), pk[4 * k + 1], pk[4 * k + 2], pk[4 * k + 3]);
          }
        }
        PROF2(pb + 18);
        const uint4* in = ib + j * INBOX + t;
        const float2 r2 = lds64(sb + SM_KEEP + tid_ * 8);
        uint2 X9;
        {
          uint4 X[4];
          const uint4* box = G->act[2] + t;
#pragma unroll
          for (int k = 0; k < 4; k++) X[k] = ld_relaxed4(box + (2 * j + (k & 1) + 8 * (k & 2)) * 128);
          X9 = ld_relaxed2((const uint2*)(box + (32 + (j >> 1)) * 128) + (j & 1));
          const float i0 = rcp(r2.x), i1 = rcp(r2.y);
#pragma unroll
          for (int k = 0; k < 4; k++) {
            const float f = k & 1 ? i1 : i0;
            float* e = d + 8 * (k & 2) + 2 * (k & 1);
            X[k].x ^= (lsb >> k) & 1;
            e[0] = bf_lo(X[k].x) * f; e[1] = bf_hi(X[k].x) * f; e[4] = bf_lo(X[k].y) * f; e[5] = bf_hi(X[k].y) * f;
            e[8] = bf_lo(X[k].z) * f; e[9] = bf_hi(X[k].z) * f; e[12] = bf_lo(X[k].w) * f; e[13] = bf_hi(X[k].w) * f;
          }
          X9.x ^= lsb >> 4;
        }
        uint4 R[4], P[4];
        uint2 R9;
        PROF2(pb + 19);
        pass(0, true, [&] {
#pragma unroll
          for (int k = 0; k < 4; k++) P[k] = ld_relaxed4(in + 512 + k * 128);
          mbar_wait_c(sb + BAR_RREADY + 8 * w, layer);
#pragma unroll
          for (int k = 0; k < 4; k++) R[k] = ld_relaxed4(in + k * 128);
          R9 = ld_relaxed2((const uint2*)(in - t + 1024) + t);
        });
        while (__any_sync(0xffffffffu, P[0].x == 0 || P[1].x == 0 || P[2].x == 0 || P[3].x == 0)) {
#pragma unroll
          for (int k = 0; k < 4; k++) P[k] = ld_relaxed4(in + 512 + k * 128);
        }
#pragma unroll
        for (int k = 0; k < 4; k++) {
          const uint32_t u[4] = {hadd2(R[k].x, P[k].x), hadd2(R[k].y, P[k].y), hadd2(R[k].z, P[k].z), hadd2(R[k].w, P[k].w)};
#pragma unroll
          for (int i = 0; i < 4; i++) { v[8 * k + 2 * i] = bf_lo(u[i]); v[8 * k + 2 * i + 1] = bf_hi(u[i]); }
        }
        v[32] = fmaf(bf_lo(R9.x), r2.x, bf_lo(X9.x)); v[33] = fmaf(bf_hi(R9.x), r2.x, bf_hi(X9.x));
        v[34] = fmaf(bf_lo(R9.y), r2.y, bf_lo(X9.y)); v[35] = fmaf(bf_hi(R9.y), r2.y, bf_hi(X9.y));
        PROF2(pb + 20);
        wg_wait<0>();
        c.release2(BAR_EMPTYX + 40);
        PROF2(pb + 21);
#pragma unroll
        for (int i = 0; i < 32; i++) v[i] = (v[i] + d[i]) * (i & 2 ? r2.y : r2.x);
      }
      if (layer == NLAYERS - 1) break;
    }
    {
      THREAD_IDS();
      const uint32_t stg = sb + SM_B + warp * 4096;
      const uint32_t sd = stg + (lane & 15) * 128;
#pragma unroll
      for (int i = 0; i < 4; i++)
        stsm4(sd + (((2 * i + (lane >> 4)) ^ (lane & 7)) << 4), pack_bf16(v[8 * i], v[8 * i + 1]), pack_bf16(v[8 * i + 2], v[8 * i + 3]),
              pack_bf16(v[8 * i + 4], v[8 * i + 5]), pack_bf16(v[8 * i + 6], v[8 * i + 7]));
      stsm2(stg + 2048 + (lane & 15) * 16, pack_bf16(v[32], v[33]), pack_bf16(v[34], v[35]));
      fence_async_smem();
      __syncwarp();
      if (lane == 0) {
        tma_store3d(&maps.out, stg, 64 * j, w, 64 * rb + 16 * wp);
        tma_store3d(&maps.outc, stg + 2048, 512 + 8 * j, w, 64 * rb + 16 * wp);
        bulk_commit();
        bulk_wait_all();
        mbar_arrive(sb + BAR_DONE + 8 * w);
      }
      PROF(61);
    }
    __syncwarp();
    cluster_sync();
  }
}

typedef CUresult (*EncFn)(CUtensorMap*, CUtensorMapDataType, cuuint32_t, void*, const cuuint64_t*, const cuuint64_t*, const cuuint32_t*,
                          const cuuint32_t*, CUtensorMapInterleave, CUtensorMapSwizzle, CUtensorMapL2promotion, CUtensorMapFloatOOBfill);

void make_map(EncFn enc, CUtensorMap* m, const void* p, int rank, uint64_t d0, uint64_t d1, uint64_t d2, uint64_t s1, uint64_t s2, uint32_t b0,
              uint32_t b1, uint32_t b2, CUtensorMapSwizzle sw) {
  cuuint64_t gd[3] = {d0, d1, d2};
  cuuint64_t gs[2] = {s1, s2};
  cuuint32_t bd[3] = {b0, b1, b2};
  cuuint32_t es[3] = {1, 1, 1};
  enc(m, CU_TENSOR_MAP_DATA_TYPE_BFLOAT16, rank, const_cast<void*>(p), gd, gs, bd, es, CU_TENSOR_MAP_INTERLEAVE_NONE, sw,
      CU_TENSOR_MAP_L2_PROMOTION_L2_128B, CU_TENSOR_MAP_FLOAT_OOB_FILL_NONE);
}

}

extern "C" void kernel_launch(void* const* d_in, const int* in_sizes, int n_in, void* d_out, int out_size) {
  const __nv_bfloat16* x = (const __nv_bfloat16*)d_in[0];
  const char *wqkv = (const char*)d_in[1], *wo = (const char*)d_in[2], *wg = (const char*)d_in[4], *wu = (const char*)d_in[5], *wd = (const char*)d_in[6];
  static EncFn enc = nullptr;
  static Group* ws = nullptr;
  if (!enc) {
    cudaDriverEntryPointQueryResult qr;
    cudaGetDriverEntryPoint("cuTensorMapEncodeTiled", (void**)&enc, cudaEnableDefault, &qr);
    cudaGetSymbolAddress((void**)&ws, g_ws);
    cudaFuncSetAttribute(fused_kernel, cudaFuncAttributeMaxDynamicSharedMemorySize, SMEM_BYTES);
  }
  const CUtensorMapSwizzle S0 = CU_TENSOR_MAP_SWIZZLE_NONE, S64 = CU_TENSOR_MAP_SWIZZLE_64B, S128 = CU_TENSOR_MAP_SWIZZLE_128B;
  Maps m;
  make_map(enc, &m.x, x, 3, 576, 2, 1024, 1152, 2304, 64, 1, 64, S128);
  make_map(enc, &m.qm, wqkv, 3, 576, 576, 3, 3456, 1152, 64, 16, 3, S128);
  make_map(enc, &m.qc, wqkv, 3, 576, 576, 3, 3456, 1152, 8, 16, 3, S0);
  make_map(enc, &m.o, wo, 2, 576, 576, 1, 1152, 0, 64, 72, 1, S128);
  make_map(enc, &m.oc, wo, 2, 576, 576, 1, 1152, 0, 8, 144, 1, S0);
  make_map(enc, &m.g, wg, 3, 64, 576, 72, 9216, 128, 64, 32, 2, S128);
  make_map(enc, &m.u, wu, 3, 64, 576, 72, 9216, 128, 64, 32, 2, S128);
  make_map(enc, &m.g3, wg, 3, 32, 576, 144, 9216, 64, 32, 32, 3, S64);
  make_map(enc, &m.u3, wu, 3, 32, 576, 144, 9216, 64, 32, 32, 3, S64);
  make_map(enc, &m.d, wd, 2, 576, 4608, 1, 1152, 0, 64, 72, 1, S128);
  make_map(enc, &m.out, d_out, 3, 576, 2, 1024, 1152, 2304, 64, 1, 16, S128);
  make_map(enc, &m.outc, d_out, 3, 576, 2, 1024, 1152, 2304, 8, 1, 16, S0);
  fused_kernel<<<NCTA, 384, SMEM_BYTES>>>(x, ws, wqkv, wg, wu, wd, m, wo);
}
```

```cpp
#include <cuda_runtime.h>
#include <cuda_bf16.h>
#include <cuda.h>
#include <stdint.h>
#include <stddef.h>

namespace {

constexpr int D_ = 576;
constexpr int NCTA = 128;
#define NLAYERS 2
#define W_POLICY policy_evict_first
#define A_POLICY policy_evict_normal
#define OPEN 1
#define PFMODE 5
#define WWIN 4
#define WOREL -1
#define WB1 12
#define WB2 24
#define WB3 36
#define WB4 36
#define WPROBE 1
#define WPROBE2 0
#define SPEC 2
#define POLLFIRST 0
#define SUMFIRST 1
#define EARLYPOLL 1
#define LEAD 0
#define ATTBAR 0
#define GL 18
#define WOBAR 0
#define QD 0
#define QG 4
#define PFQ 1
#define XDELAY 0
#define WOH 1
#define PFSLEEP 700
#define GPCMAP 1
#define PFF 1
#define REDN 1
#define CLRSLEEP 300
#define OPENL 24
#define FG -1
#define NON8 0
#define HMUL 1
#define FCH 1
#define PPK 34
#define RHOOK 0
#define SCHEDBAR 1
#define QH 5
#define XH 3
#define XP 2
#define GSLEEP 32
#define XCH 1
#define MAPPF 1
#define XREL 8
#define WOG 13
#define BREL 1
#define NSPILL 4
#define REGS_C 232
#define REGS_P 40
#define STR2(x) #x
#define STR(x) STR2(x)
constexpr uint32_t SM_X = 0;
constexpr uint32_t XSLOT = 18432;
constexpr uint32_t SM_WOC = SM_X + 3 * XSLOT + 9216;
constexpr uint32_t SM_B = 147456;
constexpr uint32_t BSLOT = 16384;
constexpr uint32_t SM_KEEP = 229376;
constexpr uint32_t SM_BAR = SM_KEEP + 2048;
constexpr uint32_t BAR_FULLB = SM_BAR;
constexpr uint32_t BAR_RREADY = SM_BAR + 40;
constexpr uint32_t BAR_CLR = SM_BAR + 56;
constexpr uint32_t BAR_FULLX = SM_BAR + 72;
constexpr uint32_t BAR_EMPTYB = SM_BAR + 144;
constexpr uint32_t BAR_EMPTYX = SM_BAR + 184;
constexpr uint32_t BAR_REDDONE = SM_BAR + 248;
constexpr uint32_t BAR_DONE = SM_BAR + 264;
constexpr uint32_t SM_PROG = SM_BAR + 288;
constexpr uint32_t SMEM_BYTES = SM_BAR + 1024;

struct Maps { CUtensorMap x, qm, qc, o, oc, g, u, g3, u3, d, out, outc; };

constexpr int INBOX = 576;
struct Group {
  uint2 sum[4 * 8 * 8];
  uint4 m2[4 * 8 * 8];
  uint32_t flag[512];
  uint4 halo[8 * 160];
  uint4 obox[36 * 128];
  uint4 xbox[36 * 128];
  uint4 inbox[2][8 * INBOX];
};
__device__ __align__(1024) Group g_ws[32];
#define PROF(i)
#define PROFX(i)

#define PROF2(i) PROF(i)

template<int N> __device__ __forceinline__ void wgmma_ss(float (&d)[N / 2], uint64_t da, uint64_t db, int sc);
template<> __device__ __forceinline__ void wgmma_ss<192>(float (&d)[96], uint64_t da, uint64_t db, int sc) {
  asm volatile("{\n.reg .pred p;\nsetp.ne.b32 p, %98, 0;\n"
    "wgmma.mma_async.sync.aligned.m64n192k16.f32.bf16.bf16 {%0,%1,%2,%3,%4,%5,%6,%7,%8,%9,%10,%11,%12,%13,%14,%15,%16,%17,%18,%19,%20,%21,%22,%23,%24,%25,%26,%27,%28,%29,%30,%31,%32,%33,%34,%35,%36,%37,%38,%39,%40,%41,%42,%43,%44,%45,%46,%47,%48,%49,%50,%51,%52,%53,%54,%55,%56,%57,%58,%59,%60,%61,%62,%63,%64,%65,%66,%67,%68,%69,%70,%71,%72,%73,%74,%75,%76,%77,%78,%79,%80,%81,%82,%83,%84,%85,%86,%87,%88,%89,%90,%91,%92,%93,%94,%95}, %96, %97, p, 1, 1, 0, 1;\n}\n"
    : "+f"(d[0]),"+f"(d[1]),"+f"(d[2]),"+f"(d[3]),"+f"(d[4]),"+f"(d[5]),"+f"(d[6]),"+f"(d[7]),"+f"(d[8]),"+f"(d[9]),"+f"(d[10]),"+f"(d[11]),"+f"(d[12]),"+f"(d[13]),"+f"(d[14]),"+f"(d[15]),"+f"(d[16]),"+f"(d[17]),"+f"(d[18]),"+f"(d[19]),"+f"(d[20]),"+f"(d[21]),"+f"(d[22]),"+f"(d[23]),"+f"(d[24]),"+f"(d[25]),"+f"(d[26]),"+f"(d[27]),"+f"(d[28]),"+f"(d[29]),"+f"(d[30]),"+f"(d[31]),"+f"(d[32]),"+f"(d[33]),"+f"(d[34]),"+f"(d[35]),"+f"(d[36]),"+f"(d[37]),"+f"(d[38]),"+f"(d[39]),"+f"(d[40]),"+f"(d[41]),"+f"(d[42]),"+f"(d[43]),"+f"(d[44]),"+f"(d[45]),"+f"(d[46]),"+f"(d[47]),"+f"(d[48]),"+f"(d[49]),"+f"(d[50]),"+f"(d[51]),"+f"(d[52]),"+f"(d[53]),"+f"(d[54]),"+f"(d[55]),"+f"(d[56]),"+f"(d[57]),"+f"(d[58]),"+f"(d[59]),"+f"(d[60]),"+f"(d[61]),"+f"(d[62]),"+f"(d[63]),"+f"(d[64]),"+f"(d[65]),"+f"(d[66]),"+f"(d[67]),"+f"(d[68]),"+f"(d[69]),"+f"(d[70]),"+f"(d[71]),"+f"(d[72]),"+f"(d[73]),"+f"(d[74]),"+f"(d[75]),"+f"(d[76]),"+f"(d[77]),"+f"(d[78]),"+f"(d[79]),"+f"(d[80]),"+f"(d[81]),"+f"(d[82]),"+f"(d[83]),"+f"(d[84]),"+f"(d[85]),"+f"(d[86]),"+f"(d[87]),"+f"(d[88]),"+f"(d[89]),"+f"(d[90]),"+f"(d[91]),"+f"(d[92]),"+f"(d[93]),"+f"(d[94]),"+f"(d[95]) : "l"(da), "l"(db), "r"(sc));
}
template<> __device__ __forceinline__ void wgmma_ss<256>(float (&d)[128], uint64_t da, uint64_t db, int sc) {
  asm volatile("{\n.reg .pred p;\nsetp.ne.b32 p, %130, 0;\n"
    "wgmma.mma_async.sync.aligned.m64n256k16.f32.bf16.bf16 {%0,%1,%2,%3,%4,%5,%6,%7,%8,%9,%10,%11,%12,%13,%14,%15,%16,%17,%18,%19,%20,%21,%22,%23,%24,%25,%26,%27,%28,%29,%30,%31,%32,%33,%34,%35,%36,%37,%38,%39,%40,%41,%42,%43,%44,%45,%46,%47,%48,%49,%50,%51,%52,%53,%54,%55,%56,%57,%58,%59,%60,%61,%62,%63,%64,%65,%66,%67,%68,%69,%70,%71,%72,%73,%74,%75,%76,%77,%78,%79,%80,%81,%82,%83,%84,%85,%86,%87,%88,%89,%90,%91,%92,%93,%94,%95,%96,%97,%98,%99,%100,%101,%102,%103,%104,%105,%106,%107,%108,%109,%110,%111,%112,%113,%114,%115,%116,%117,%118,%119,%120,%121,%122,%123,%124,%125,%126,%127}, %128, %129, p, 1, 1, 0, 1;\n}\n"
    : "+f"(d[0]),"+f"(d[1]),"+f"(d[2]),"+f"(d[3]),"+f"(d[4]),"+f"(d[5]),"+f"(d[6]),"+f"(d[7]),"+f"(d[8]),"+f"(d[9]),"+f"(d[10]),"+f"(d[11]),"+f"(d[12]),"+f"(d[13]),"+f"(d[14]),"+f"(d[15]),"+f"(d[16]),"+f"(d[17]),"+f"(d[18]),"+f"(d[19]),"+f"(d[20]),"+f"(d[21]),"+f"(d[22]),"+f"(d[23]),"+f"(d[24]),"+f"(d[25]),"+f"(d[26]),"+f"(d[27]),"+f"(d[28]),"+f"(d[29]),"+f"(d[30]),"+f"(d[31]),"+f"(d[32]),"+f"(d[33]),"+f"(d[34]),"+f"(d[35]),"+f"(d[36]),"+f"(d[37]),"+f"(d[38]),"+f"(d[39]),"+f"(d[40]),"+f"(d[41]),"+f"(d[42]),"+f"(d[43]),"+f"(d[44]),"+f"(d[45]),"+f"(d[46]),"+f"(d[47]),"+f"(d[48]),"+f"(d[49]),"+f"(d[50]),"+f"(d[51]),"+f"(d[52]),"+f"(d[53]),"+f"(d[54]),"+f"(d[55]),"+f"(d[56]),"+f"(d[57]),"+f"(d[58]),"+f"(d[59]),"+f"(d[60]),"+f"(d[61]),"+f"(d[62]),"+f"(d[63]),"+f"(d[64]),"+f"(d[65]),"+f"(d[66]),"+f"(d[67]),"+f"(d[68]),"+f"(d[69]),"+f"(d[70]),"+f"(d[71]),"+f"(d[72]),"+f"(d[73]),"+f"(d[74]),"+f"(d[75]),"+f"(d[76]),"+f"(d[77]),"+f"(d[78]),"+f"(d[79]),"+f"(d[80]),"+f"(d[81]),"+f"(d[82]),"+f"(d[83]),"+f"(d[84]),"+f"(d[85]),"+f"(d[86]),"+f"(d[87]),"+f"(d[88]),"+f"(d[89]),"+f"(d[90]),"+f"(d[91]),"+f"(d[92]),"+f"(d[93]),"+f"(d[94]),"+f"(d[95]),"+f"(d[96]),"+f"(d[97]),"+f"(d[98]),"+f"(d[99]),"+f"(d[100]),"+f"(d[101]),"+f"(d[102]),"+f"(d[103]),"+f"(d[104]),"+f"(d[105]),"+f"(d[106]),"+f"(d[107]),"+f"(d[108]),"+f"(d[109]),"+f"(d[110]),"+f"(d[111]),"+f"(d[112]),"+f"(d[113]),"+f"(d[114]),"+f"(d[115]),"+f"(d[116]),"+f"(d[117]),"+f"(d[118]),"+f"(d[119]),"+f"(d[120]),"+f"(d[121]),"+f"(d[122]),"+f"(d[123]),"+f"(d[124]),"+f"(d[125]),"+f"(d[126]),"+f"(d[127]) : "l"(da), "l"(db), "r"(sc));
}
template<int N> __device__ __forceinline__ void wgmma_rs(float (&d)[N / 2], uint32_t a0, uint32_t a1, uint32_t a2, uint32_t a3, uint64_t db, int sc);
template<> __device__ __forceinline__ void wgmma_rs<8>(float (&d)[4], uint32_t a0, uint32_t a1, uint32_t a2, uint32_t a3, uint64_t db, int sc) {
  asm volatile("{\n.reg .pred p;\nsetp.ne.b32 p, %9, 0;\n"
    "wgmma.mma_async.sync.aligned.m64n8k16.f32.bf16.bf16 {%0,%1,%2,%3}, {%4,%5,%6,%7}, %8, p, 1, 1, 1;\n}\n"
    : "+f"(d[0]),"+f"(d[1]),"+f"(d[2]),"+f"(d[3]) : "r"(a0), "r"(a1), "r"(a2), "r"(a3), "l"(db), "r"(sc));
}
template<> __device__ __forceinline__ void wgmma_rs<24>(float (&d)[12], uint32_t a0, uint32_t a1, uint32_t a2, uint32_t a3, uint64_t db, int sc) {
  asm volatile("{\n.reg .pred p;\nsetp.ne.b32 p, %17, 0;\n"
    "wgmma.mma_async.sync.aligned.m64n24k16.f32.bf16.bf16 {%0,%1,%2,%3,%4,%5,%6,%7,%8,%9,%10,%11}, {%12,%13,%14,%15}, %16, p, 1, 1, 1;\n}\n"
    : "+f"(d[0]),"+f"(d[1]),"+f"(d[2]),"+f"(d[3]),"+f"(d[4]),"+f"(d[5]),"+f"(d[6]),"+f"(d[7]),"+f"(d[8]),"+f"(d[9]),"+f"(d[10]),"+f"(d[11]) : "r"(a0), "r"(a1), "r"(a2), "r"(a3), "l"(db), "r"(sc));
}
template<> __device__ __forceinline__ void wgmma_rs<64>(float (&d)[32], uint32_t a0, uint32_t a1, uint32_t a2, uint32_t a3, uint64_t db, int sc) {
  asm volatile("{\n.reg .pred p;\nsetp.ne.b32 p, %37, 0;\n"
    "wgmma.mma_async.sync.aligned.m64n64k16.f32.bf16.bf16 {%0,%1,%2,%3,%4,%5,%6,%7,%8,%9,%10,%11,%12,%13,%14,%15,%16,%17,%18,%19,%20,%21,%22,%23,%24,%25,%26,%27,%28,%29,%30,%31}, {%32,%33,%34,%35}, %36, p, 1, 1, 1;\n}\n"
    : "+f"(d[0]),"+f"(d[1]),"+f"(d[2]),"+f"(d[3]),"+f"(d[4]),"+f"(d[5]),"+f"(d[6]),"+f"(d[7]),"+f"(d[8]),"+f"(d[9]),"+f"(d[10]),"+f"(d[11]),"+f"(d[12]),"+f"(d[13]),"+f"(d[14]),"+f"(d[15]),"+f"(d[16]),"+f"(d[17]),"+f"(d[18]),"+f"(d[19]),"+f"(d[20]),"+f"(d[21]),"+f"(d[22]),"+f"(d[23]),"+f"(d[24]),"+f"(d[25]),"+f"(d[26]),"+f"(d[27]),"+f"(d[28]),"+f"(d[29]),"+f"(d[30]),"+f"(d[31]) : "r"(a0), "r"(a1), "r"(a2), "r"(a3), "l"(db), "r"(sc));
}
template<> __device__ __forceinline__ void wgmma_rs<192>(float (&d)[96], uint32_t a0, uint32_t a1, uint32_t a2, uint32_t a3, uint64_t db, int sc) {
  asm volatile("{\n.reg .pred p;\nsetp.ne.b32 p, %101, 0;\n"
    "wgmma.mma_async.sync.aligned.m64n192k16.f32.bf16.bf16 {%0,%1,%2,%3,%4,%5,%6,%7,%8,%9,%10,%11,%12,%13,%14,%15,%16,%17,%18,%19,%20,%21,%22,%23,%24,%25,%26,%27,%28,%29,%30,%31,%32,%33,%34,%35,%36,%37,%38,%39,%40,%41,%42,%43,%44,%45,%46,%47,%48,%49,%50,%51,%52,%53,%54,%55,%56,%57,%58,%59,%60,%61,%62,%63,%64,%65,%66,%67,%68,%69,%70,%71,%72,%73,%74,%75,%76,%77,%78,%79,%80,%81,%82,%83,%84,%85,%86,%87,%88,%89,%90,%91,%92,%93,%94,%95}, {%96,%97,%98,%99}, %100, p, 1, 1, 1;\n}\n"
    : "+f"(d[0]),"+f"(d[1]),"+f"(d[2]),"+f"(d[3]),"+f"(d[4]),"+f"(d[5]),"+f"(d[6]),"+f"(d[7]),"+f"(d[8]),"+f"(d[9]),"+f"(d[10]),"+f"(d[11]),"+f"(d[12]),"+f"(d[13]),"+f"(d[14]),"+f"(d[15]),"+f"(d[16]),"+f"(d[17]),"+f"(d[18]),"+f"(d[19]),"+f"(d[20]),"+f"(d[21]),"+f"(d[22]),"+f"(d[23]),"+f"(d[24]),"+f"(d[25]),"+f"(d[26]),"+f"(d[27]),"+f"(d[28]),"+f"(d[29]),"+f"(d[30]),"+f"(d[31]),"+f"(d[32]),"+f"(d[33]),"+f"(d[34]),"+f"(d[35]),"+f"(d[36]),"+f"(d[37]),"+f"(d[38]),"+f"(d[39]),"+f"(d[40]),"+f"(d[41]),"+f"(d[42]),"+f"(d[43]),"+f"(d[44]),"+f"(d[45]),"+f"(d[46]),"+f"(d[47]),"+f"(d[48]),"+f"(d[49]),"+f"(d[50]),"+f"(d[51]),"+f"(d[52]),"+f"(d[53]),"+f"(d[54]),"+f"(d[55]),"+f"(d[56]),"+f"(d[57]),"+f"(d[58]),"+f"(d[59]),"+f"(d[60]),"+f"(d[61]),"+f"(d[62]),"+f"(d[63]),"+f"(d[64]),"+f"(d[65]),"+f"(d[66]),"+f"(d[67]),"+f"(d[68]),"+f"(d[69]),"+f"(d[70]),"+f"(d[71]),"+f"(d[72]),"+f"(d[73]),"+f"(d[74]),"+f"(d[75]),"+f"(d[76]),"+f"(d[77]),"+f"(d[78]),"+f"(d[79]),"+f"(d[80]),"+f"(d[81]),"+f"(d[82]),"+f"(d[83]),"+f"(d[84]),"+f"(d[85]),"+f"(d[86]),"+f"(d[87]),"+f"(d[88]),"+f"(d[89]),"+f"(d[90]),"+f"(d[91]),"+f"(d[92]),"+f"(d[93]),"+f"(d[94]),"+f"(d[95]) : "r"(a0), "r"(a1), "r"(a2), "r"(a3), "l"(db), "r"(sc));
}
template<> __device__ __forceinline__ void wgmma_rs<256>(float (&d)[128], uint32_t a0, uint32_t a1, uint32_t a2, uint32_t a3, uint64_t db, int sc) {
  asm volatile("{\n.reg .pred p;\nsetp.ne.b32 p, %133, 0;\n"
    "wgmma.mma_async.sync.aligned.m64n256k16.f32.bf16.bf16 {%0,%1,%2,%3,%4,%5,%6,%7,%8,%9,%10,%11,%12,%13,%14,%15,%16,%17,%18,%19,%20,%21,%22,%23,%24,%25,%26,%27,%28,%29,%30,%31,%32,%33,%34,%35,%36,%37,%38,%39,%40,%41,%42,%43,%44,%45,%46,%47,%48,%49,%50,%51,%52,%53,%54,%55,%56,%57,%58,%59,%60,%61,%62,%63,%64,%65,%66,%67,%68,%69,%70,%71,%72,%73,%74,%75,%76,%77,%78,%79,%80,%81,%82,%83,%84,%85,%86,%87,%88,%89,%90,%91,%92,%93,%94,%95,%96,%97,%98,%99,%100,%101,%102,%103,%104,%105,%106,%107,%108,%109,%110,%111,%112,%113,%114,%115,%116,%117,%118,%119,%120,%121,%122,%123,%124,%125,%126,%127}, {%128,%129,%130,%131}, %132, p, 1, 1, 1;\n}\n"
    : "+f"(d[0]),"+f"(d[1]),"+f"(d[2]),"+f"(d[3]),"+f"(d[4]),"+f"(d[5]),"+f"(d[6]),"+f"(d[7]),"+f"(d[8]),"+f"(d[9]),"+f"(d[10]),"+f"(d[11]),"+f"(d[12]),"+f"(d[13]),"+f"(d[14]),"+f"(d[15]),"+f"(d[16]),"+f"(d[17]),"+f"(d[18]),"+f"(d[19]),"+f"(d[20]),"+f"(d[21]),"+f"(d[22]),"+f"(d[23]),"+f"(d[24]),"+f"(d[25]),"+f"(d[26]),"+f"(d[27]),"+f"(d[28]),"+f"(d[29]),"+f"(d[30]),"+f"(d[31]),"+f"(d[32]),"+f"(d[33]),"+f"(d[34]),"+f"(d[35]),"+f"(d[36]),"+f"(d[37]),"+f"(d[38]),"+f"(d[39]),"+f"(d[40]),"+f"(d[41]),"+f"(d[42]),"+f"(d[43]),"+f"(d[44]),"+f"(d[45]),"+f"(d[46]),"+f"(d[47]),"+f"(d[48]),"+f"(d[49]),"+f"(d[50]),"+f"(d[51]),"+f"(d[52]),"+f"(d[53]),"+f"(d[54]),"+f"(d[55]),"+f"(d[56]),"+f"(d[57]),"+f"(d[58]),"+f"(d[59]),"+f"(d[60]),"+f"(d[61]),"+f"(d[62]),"+f"(d[63]),"+f"(d[64]),"+f"(d[65]),"+f"(d[66]),"+f"(d[67]),"+f"(d[68]),"+f"(d[69]),"+f"(d[70]),"+f"(d[71]),"+f"(d[72]),"+f"(d[73]),"+f"(d[74]),"+f"(d[75]),"+f"(d[76]),"+f"(d[77]),"+f"(d[78]),"+f"(d[79]),"+f"(d[80]),"+f"(d[81]),"+f"(d[82]),"+f"(d[83]),"+f"(d[84]),"+f"(d[85]),"+f"(d[86]),"+f"(d[87]),"+f"(d[88]),"+f"(d[89]),"+f"(d[90]),"+f"(d[91]),"+f"(d[92]),"+f"(d[93]),"+f"(d[94]),"+f"(d[95]),"+f"(d[96]),"+f"(d[97]),"+f"(d[98]),"+f"(d[99]),"+f"(d[100]),"+f"(d[101]),"+f"(d[102]),"+f"(d[103]),"+f"(d[104]),"+f"(d[105]),"+f"(d[106]),"+f"(d[107]),"+f"(d[108]),"+f"(d[109]),"+f"(d[110]),"+f"(d[111]),"+f"(d[112]),"+f"(d[113]),"+f"(d[114]),"+f"(d[115]),"+f"(d[116]),"+f"(d[117]),"+f"(d[118]),"+f"(d[119]),"+f"(d[120]),"+f"(d[121]),"+f"(d[122]),"+f"(d[123]),"+f"(d[124]),"+f"(d[125]),"+f"(d[126]),"+f"(d[127]) : "r"(a0), "r"(a1), "r"(a2), "r"(a3), "l"(db), "r"(sc));
}
template<int N> __device__ __forceinline__ void wgmma_rsz(float (&d)[N / 2], uint32_t a0, uint32_t a1, uint32_t a2, uint32_t a3, uint64_t db);
template<> __device__ __forceinline__ void wgmma_rsz<8>(float (&d)[4], uint32_t a0, uint32_t a1, uint32_t a2, uint32_t a3, uint64_t db) {
  asm volatile("{\n.reg .pred p;\nsetp.ne.b32 p, 0, 0;\n"
    "wgmma.mma_async.sync.aligned.m64n8k16.f32.bf16.bf16 {%0,%1,%2,%3}, {%4,%5,%6,%7}, %8, p, 1, 1, 1;\n}\n"
    : "=f"(d[0]),"=f"(d[1]),"=f"(d[2]),"=f"(d[3]) : "r"(a0), "r"(a1), "r"(a2), "r"(a3), "l"(db));
}
template<> __device__ __forceinline__ void wgmma_rsz<24>(float (&d)[12], uint32_t a0, uint32_t a1, uint32_t a2, uint32_t a3, uint64_t db) {
  asm volatile("{\n.reg .pred p;\nsetp.ne.b32 p, 0, 0;\n"
    "wgmma.mma_async.sync.aligned.m64n24k16.f32.bf16.bf16 {%0,%1,%2,%3,%4,%5,%6,%7,%8,%9,%10,%11}, {%12,%13,%14,%15}, %16, p, 1, 1, 1;\n}\n"
    : "=f"(d[0]),"=f"(d[1]),"=f"(d[2]),"=f"(d[3]),"=f"(d[4]),"=f"(d[5]),"=f"(d[6]),"=f"(d[7]),"=f"(d[8]),"=f"(d[9]),"=f"(d[10]),"=f"(d[11]) : "r"(a0), "r"(a1), "r"(a2), "r"(a3), "l"(db));
}
template<> __device__ __forceinline__ void wgmma_rsz<64>(float (&d)[32], uint32_t a0, uint32_t a1, uint32_t a2, uint32_t a3, uint64_t db) {
  asm volatile("{\n.reg .pred p;\nsetp.ne.b32 p, 0, 0;\n"
    "wgmma.mma_async.sync.aligned.m64n64k16.f32.bf16.bf16 {%0,%1,%2,%3,%4,%5,%6,%7,%8,%9,%10,%11,%12,%13,%14,%15,%16,%17,%18,%19,%20,%21,%22,%23,%24,%25,%26,%27,%28,%29,%30,%31}, {%32,%33,%34,%35}, %36, p, 1, 1, 1;\n}\n"
    : "=f"(d[0]),"=f"(d[1]),"=f"(d[2]),"=f"(d[3]),"=f"(d[4]),"=f"(d[5]),"=f"(d[6]),"=f"(d[7]),"=f"(d[8]),"=f"(d[9]),"=f"(d[10]),"=f"(d[11]),"=f"(d[12]),"=f"(d[13]),"=f"(d[14]),"=f"(d[15]),"=f"(d[16]),"=f"(d[17]),"=f"(d[18]),"=f"(d[19]),"=f"(d[20]),"=f"(d[21]),"=f"(d[22]),"=f"(d[23]),"=f"(d[24]),"=f"(d[25]),"=f"(d[26]),"=f"(d[27]),"=f"(d[28]),"=f"(d[29]),"=f"(d[30]),"=f"(d[31]) : "r"(a0), "r"(a1), "r"(a2), "r"(a3), "l"(db));
}
template<> __device__ __forceinline__ void wgmma_rsz<192>(float (&d)[96], uint32_t a0, uint32_t a1, uint32_t a2, uint32_t a3, uint64_t db) {
  asm volatile("{\n.reg .pred p;\nsetp.ne.b32 p, 0, 0;\n"
    "wgmma.mma_async.sync.aligned.m64n192k16.f32.bf16.bf16 {%0,%1,%2,%3,%4,%5,%6,%7,%8,%9,%10,%11,%12,%13,%14,%15,%16,%17,%18,%19,%20,%21,%22,%23,%24,%25,%26,%27,%28,%29,%30,%31,%32,%33,%34,%35,%36,%37,%38,%39,%40,%41,%42,%43,%44,%45,%46,%47,%48,%49,%50,%51,%52,%53,%54,%55,%56,%57,%58,%59,%60,%61,%62,%63,%64,%65,%66,%67,%68,%69,%70,%71,%72,%73,%74,%75,%76,%77,%78,%79,%80,%81,%82,%83,%84,%85,%86,%87,%88,%89,%90,%91,%92,%93,%94,%95}, {%96,%97,%98,%99}, %100, p, 1, 1, 1;\n}\n"
    : "=f"(d[0]),"=f"(d[1]),"=f"(d[2]),"=f"(d[3]),"=f"(d[4]),"=f"(d[5]),"=f"(d[6]),"=f"(d[7]),"=f"(d[8]),"=f"(d[9]),"=f"(d[10]),"=f"(d[11]),"=f"(d[12]),"=f"(d[13]),"=f"(d[14]),"=f"(d[15]),"=f"(d[16]),"=f"(d[17]),"=f"(d[18]),"=f"(d[19]),"=f"(d[20]),"=f"(d[21]),"=f"(d[22]),"=f"(d[23]),"=f"(d[24]),"=f"(d[25]),"=f"(d[26]),"=f"(d[27]),"=f"(d[28]),"=f"(d[29]),"=f"(d[30]),"=f"(d[31]),"=f"(d[32]),"=f"(d[33]),"=f"(d[34]),"=f"(d[35]),"=f"(d[36]),"=f"(d[37]),"=f"(d[38]),"=f"(d[39]),"=f"(d[40]),"=f"(d[41]),"=f"(d[42]),"=f"(d[43]),"=f"(d[44]),"=f"(d[45]),"=f"(d[46]),"=f"(d[47]),"=f"(d[48]),"=f"(d[49]),"=f"(d[50]),"=f"(d[51]),"=f"(d[52]),"=f"(d[53]),"=f"(d[54]),"=f"(d[55]),"=f"(d[56]),"=f"(d[57]),"=f"(d[58]),"=f"(d[59]),"=f"(d[60]),"=f"(d[61]),"=f"(d[62]),"=f"(d[63]),"=f"(d[64]),"=f"(d[65]),"=f"(d[66]),"=f"(d[67]),"=f"(d[68]),"=f"(d[69]),"=f"(d[70]),"=f"(d[71]),"=f"(d[72]),"=f"(d[73]),"=f"(d[74]),"=f"(d[75]),"=f"(d[76]),"=f"(d[77]),"=f"(d[78]),"=f"(d[79]),"=f"(d[80]),"=f"(d[81]),"=f"(d[82]),"=f"(d[83]),"=f"(d[84]),"=f"(d[85]),"=f"(d[86]),"=f"(d[87]),"=f"(d[88]),"=f"(d[89]),"=f"(d[90]),"=f"(d[91]),"=f"(d[92]),"=f"(d[93]),"=f"(d[94]),"=f"(d[95]) : "r"(a0), "r"(a1), "r"(a2), "r"(a3), "l"(db));
}
template<> __device__ __forceinline__ void wgmma_rsz<256>(float (&d)[128], uint32_t a0, uint32_t a1, uint32_t a2, uint32_t a3, uint64_t db) {
  asm volatile("{\n.reg .pred p;\nsetp.ne.b32 p, 0, 0;\n"
    "wgmma.mma_async.sync.aligned.m64n256k16.f32.bf16.bf16 {%0,%1,%2,%3,%4,%5,%6,%7,%8,%9,%10,%11,%12,%13,%14,%15,%16,%17,%18,%19,%20,%21,%22,%23,%24,%25,%26,%27,%28,%29,%30,%31,%32,%33,%34,%35,%36,%37,%38,%39,%40,%41,%42,%43,%44,%45,%46,%47,%48,%49,%50,%51,%52,%53,%54,%55,%56,%57,%58,%59,%60,%61,%62,%63,%64,%65,%66,%67,%68,%69,%70,%71,%72,%73,%74,%75,%76,%77,%78,%79,%80,%81,%82,%83,%84,%85,%86,%87,%88,%89,%90,%91,%92,%93,%94,%95,%96,%97,%98,%99,%100,%101,%102,%103,%104,%105,%106,%107,%108,%109,%110,%111,%112,%113,%114,%115,%116,%117,%118,%119,%120,%121,%122,%123,%124,%125,%126,%127}, {%128,%129,%130,%131}, %132, p, 1, 1, 1;\n}\n"
    : "=f"(d[0]),"=f"(d[1]),"=f"(d[2]),"=f"(d[3]),"=f"(d[4]),"=f"(d[5]),"=f"(d[6]),"=f"(d[7]),"=f"(d[8]),"=f"(d[9]),"=f"(d[10]),"=f"(d[11]),"=f"(d[12]),"=f"(d[13]),"=f"(d[14]),"=f"(d[15]),"=f"(d[16]),"=f"(d[17]),"=f"(d[18]),"=f"(d[19]),"=f"(d[20]),"=f"(d[21]),"=f"(d[22]),"=f"(d[23]),"=f"(d[24]),"=f"(d[25]),"=f"(d[26]),"=f"(d[27]),"=f"(d[28]),"=f"(d[29]),"=f"(d[30]),"=f"(d[31]),"=f"(d[32]),"=f"(d[33]),"=f"(d[34]),"=f"(d[35]),"=f"(d[36]),"=f"(d[37]),"=f"(d[38]),"=f"(d[39]),"=f"(d[40]),"=f"(d[41]),"=f"(d[42]),"=f"(d[43]),"=f"(d[44]),"=f"(d[45]),"=f"(d[46]),"=f"(d[47]),"=f"(d[48]),"=f"(d[49]),"=f"(d[50]),"=f"(d[51]),"=f"(d[52]),"=f"(d[53]),"=f"(d[54]),"=f"(d[55]),"=f"(d[56]),"=f"(d[57]),"=f"(d[58]),"=f"(d[59]),"=f"(d[60]),"=f"(d[61]),"=f"(d[62]),"=f"(d[63]),"=f"(d[64]),"=f"(d[65]),"=f"(d[66]),"=f"(d[67]),"=f"(d[68]),"=f"(d[69]),"=f"(d[70]),"=f"(d[71]),"=f"(d[72]),"=f"(d[73]),"=f"(d[74]),"=f"(d[75]),"=f"(d[76]),"=f"(d[77]),"=f"(d[78]),"=f"(d[79]),"=f"(d[80]),"=f"(d[81]),"=f"(d[82]),"=f"(d[83]),"=f"(d[84]),"=f"(d[85]),"=f"(d[86]),"=f"(d[87]),"=f"(d[88]),"=f"(d[89]),"=f"(d[90]),"=f"(d[91]),"=f"(d[92]),"=f"(d[93]),"=f"(d[94]),"=f"(d[95]),"=f"(d[96]),"=f"(d[97]),"=f"(d[98]),"=f"(d[99]),"=f"(d[100]),"=f"(d[101]),"=f"(d[102]),"=f"(d[103]),"=f"(d[104]),"=f"(d[105]),"=f"(d[106]),"=f"(d[107]),"=f"(d[108]),"=f"(d[109]),"=f"(d[110]),"=f"(d[111]),"=f"(d[112]),"=f"(d[113]),"=f"(d[114]),"=f"(d[115]),"=f"(d[116]),"=f"(d[117]),"=f"(d[118]),"=f"(d[119]),"=f"(d[120]),"=f"(d[121]),"=f"(d[122]),"=f"(d[123]),"=f"(d[124]),"=f"(d[125]),"=f"(d[126]),"=f"(d[127]) : "r"(a0), "r"(a1), "r"(a2), "r"(a3), "l"(db));
}
template<int N> __device__ __forceinline__ void wgmma_ra(float (&d)[N / 2], const uint4& a, uint64_t db, bool acc) {
  if (acc) wgmma_rs<N>(d, a.x, a.y, a.z, a.w, db, 1); else wgmma_rsz<N>(d, a.x, a.y, a.z, a.w, db);
}

__device__ __forceinline__ uint32_t smem_u32(const void* p) { return (uint32_t)__cvta_generic_to_shared(p); }
__device__ __forceinline__ void mbar_init(uint32_t bar, uint32_t cnt) { asm volatile("mbarrier.init.shared::cta.b64 [%0], %1;" ::"r"(bar), "r"(cnt)); }
__device__ __forceinline__ void mbar_expect_tx(uint32_t bar, uint32_t bytes) { asm volatile("mbarrier.arrive.expect_tx.shared::cta.b64 _, [%0], %1;" ::"r"(bar), "r"(bytes) : "memory"); }
__device__ __forceinline__ void mbar_arrive(uint32_t bar) { asm volatile("mbarrier.arrive.shared::cta.b64 _, [%0];" ::"r"(bar) : "memory"); }
__device__ __forceinline__ void mbar_arrive_remote(uint32_t rbar) { asm volatile("mbarrier.arrive.shared::cluster.b64 _, [%0];" ::"r"(rbar) : "memory"); }
__device__ __forceinline__ void mbar_wait(uint32_t bar, uint32_t parity) {
  asm volatile(
      "{\n.reg .pred p;\n.reg .u32 c;\nmov.u32 c, 0;\nLAB_WAIT:\nmbarrier.try_wait.parity.shared::cta.b64 p, [%0], %1;\n@p bra DONE;\n"
      "add.u32 c, c, 1;\nsetp.lt.u32 p, c, 1000000;\n@p bra LAB_WAIT;\ntrap;\nDONE:\n}\n" ::"r"(bar), "r"(parity) : "memory");
}
__device__ __forceinline__ void mbar_wait_c(uint32_t bar, uint32_t parity) {
  asm volatile("{\n.reg .pred p;\nLAB_WAIT:\nmbarrier.try_wait.parity.shared::cta.b64 p, [%0], %1;\n@!p bra LAB_WAIT;\n}\n" ::"r"(bar), "r"(parity) : "memory");
}
__device__ __forceinline__ uint32_t late(uint32_t bar, uint32_t v) {
  uint32_t r;
  asm volatile("{\n.reg .pred p;\nmbarrier.test_wait.parity.shared::cta.b64 p, [%1], 0;\nselp.b32 %0, %2, %1, p;\n}\n" : "=r"(r) : "r"(bar), "r"(v) : "memory");
  return r;
}
__device__ __forceinline__ void wtma2d(uint32_t dst, const CUtensorMap* m, int c0, int c1, uint32_t bar, uint64_t pol) {
  asm volatile("cp.async.bulk.tensor.2d.shared::cluster.global.mbarrier::complete_tx::bytes.multicast::cluster.L2::cache_hint [%0], [%1, {%3, %4}], [%2], %5, %6;"
               ::"r"(dst), "l"(m), "r"(bar), "r"(c0), "r"(c1), "h"((uint16_t)3), "l"(pol) : "memory");
}
__device__ __forceinline__ void wtma3d(uint32_t dst, const CUtensorMap* m, int c0, int c1, int c2, uint32_t bar, uint64_t pol) {
  asm volatile("cp.async.bulk.tensor.3d.shared::cluster.global.mbarrier::complete_tx::bytes.multicast::cluster.L2::cache_hint [%0], [%1, {%3, %4, %5}], [%2], %6, %7;"
               ::"r"(dst), "l"(m), "r"(bar), "r"(c0), "r"(c1), "r"(c2), "h"((uint16_t)3), "l"(pol) : "memory");
}
__device__ __forceinline__ void tma3d(uint32_t dst, const CUtensorMap* m, int c0, int c1, int c2, uint32_t bar) {
  asm volatile("cp.async.bulk.tensor.3d.shared::cluster.global.mbarrier::complete_tx::bytes [%0], [%1, {%3, %4, %5}], [%2];"
               ::"r"(dst), "l"(m), "r"(bar), "r"(c0), "r"(c1), "r"(c2) : "memory");
}
__device__ __forceinline__ void tma_store3d(const CUtensorMap* m, uint32_t src, int c0, int c1, int c2) {
  asm volatile("cp.async.bulk.tensor.3d.global.shared::cta.bulk_group [%0, {%2, %3, %4}], [%1];" ::"l"(m), "r"(src), "r"(c0), "r"(c1), "r"(c2) : "memory");
}
__device__ __forceinline__ void prefetch_l2(const void* p, uint32_t bytes) { asm volatile("cp.async.bulk.prefetch.L2.global [%0], %1;" ::"l"(p), "r"(bytes) : "memory"); }
__device__ __forceinline__ uint64_t policy_evict_first() { uint64_t p; asm volatile("createpolicy.fractional.L2::evict_first.b64 %0, 1.0;" : "=l"(p)); return p; }
__device__ __forceinline__ uint64_t policy_evict_normal() { uint64_t p; asm volatile("createpolicy.fractional.L2::evict_normal.b64 %0, 1.0;" : "=l"(p)); return p; }
__device__ __forceinline__ void bulk_commit() { asm volatile("cp.async.bulk.commit_group;" ::: "memory"); }
__device__ __forceinline__ void bulk_wait_all() { asm volatile("cp.async.bulk.wait_group 0;" ::: "memory"); }
__device__ __forceinline__ void fence_async_smem() { asm volatile("fence.proxy.async.shared::cta;" ::: "memory"); }
__device__ __forceinline__ bool elect_one() {
  uint32_t p;
  asm volatile("{\n.reg .pred P;\nelect.sync _|P, 0xffffffff;\nselp.u32 %0, 1, 0, P;\n}\n" : "=r"(p));
  return p;
}
__device__ __forceinline__ void wg_fence() { asm volatile("wgmma.fence.sync.aligned;" ::: "memory"); }
__device__ __forceinline__ void wg_commit() { asm volatile("wgmma.commit_group.sync.aligned;" ::: "memory"); }
template <int n> __device__ __forceinline__ void wg_wait() { asm volatile("wgmma.wait_group.sync.aligned %0;" ::"n"(n) : "memory"); }
__device__ __forceinline__ void wg_bar(int w) { asm volatile("bar.sync %0, 128;" ::"r"(w + 1) : "memory"); }
__device__ __forceinline__ void cluster_sync() { asm volatile("barrier.cluster.arrive.relaxed.aligned;\nbarrier.cluster.wait.aligned;" ::: "memory"); }
__device__ __forceinline__ constexpr uint64_t desc_hi(uint32_t lbo, uint32_t sbo, int sw) {
  return ((uint64_t)(lbo >> 4) << 16) | ((uint64_t)(sbo >> 4) << 32) | ((uint64_t)sw << 62);
}
__device__ __forceinline__ void fence_gpu() { asm volatile("fence.acq_rel.gpu;" ::: "memory"); }
__device__ __forceinline__ uint32_t ld_relaxed(const uint32_t* p) { uint32_t v; asm volatile("ld.relaxed.gpu.global.u32 %0, [%1];" : "=r"(v) : "l"(p) : "memory"); return v; }
__device__ __forceinline__ uint4 ld_relaxed4(const uint4* p) {
  uint4 v; asm volatile("ld.relaxed.gpu.global.v4.u32 {%0,%1,%2,%3}, [%4];" : "=r"(v.x), "=r"(v.y), "=r"(v.z), "=r"(v.w) : "l"(p) : "memory"); return v;
}
__device__ __forceinline__ uint2 ld_relaxed2(const uint2* p) {
  uint2 v; asm volatile("ld.relaxed.gpu.global.v2.u32 {%0,%1}, [%2];" : "=r"(v.x), "=r"(v.y) : "l"(p) : "memory"); return v;
}
__device__ __forceinline__ void st_relaxed(uint32_t* p, uint32_t a) { asm volatile("st.relaxed.gpu.global.u32 [%0], %1;" ::"l"(p), "r"(a) : "memory"); }
__device__ __forceinline__ void st_relaxed4(uint4* p, uint32_t a, uint32_t b, uint32_t c, uint32_t d) {
  asm volatile("st.relaxed.gpu.global.v4.u32 [%0], {%1,%2,%3,%4};" ::"l"(p), "r"(a), "r"(b), "r"(c), "r"(d) : "memory");
}
__device__ __forceinline__ void st_relaxed2(uint2* p, uint32_t a, uint32_t b) {
  asm volatile("st.relaxed.gpu.global.v2.u32 [%0], {%1,%2};" ::"l"(p), "r"(a), "r"(b) : "memory");
}
__device__ __forceinline__ void red4(uint4* p, uint32_t a, uint32_t b, uint32_t c, uint32_t d) {
  asm volatile("red.relaxed.gpu.global.add.noftz.v4.bf16x2 [%0], {%1,%2,%3,%4};" ::"l"(p), "r"(a), "r"(b), "r"(c), "r"(d) : "memory");
}
__device__ __forceinline__ void red2(uint2* p, uint32_t a, uint32_t b) {
  asm volatile("red.relaxed.gpu.global.add.noftz.v2.bf16x2 [%0], {%1,%2};" ::"l"(p), "r"(a), "r"(b) : "memory");
}
constexpr int SPIN_MAX = 1 << 21;
__device__ __forceinline__ uint32_t pack_bf16(float lo, float hi) { uint32_t r; asm("cvt.rn.bf16x2.f32 %0, %1, %2;" : "=r"(r) : "f"(hi), "f"(lo)); return r; }
__device__ __forceinline__ float bf_lo(uint32_t v) { return __uint_as_float(v << 16); }
__device__ __forceinline__ float bf_hi(uint32_t v) { return __uint_as_float(v & 0xffff0000u); }
__device__ __forceinline__ float2 lds64(uint32_t a) { float2 v; asm volatile("ld.shared.v2.f32 {%0,%1}, [%2];" : "=f"(v.x), "=f"(v.y) : "r"(a)); return v; }
__device__ __forceinline__ void sts64f(uint32_t a, float x, float y) { asm volatile("st.shared.v2.f32 [%0], {%1,%2};" ::"r"(a), "f"(x), "f"(y) : "memory"); }
__device__ __forceinline__ void sts32(uint32_t a, uint32_t x) { asm volatile("st.volatile.shared.b32 [%0], %1;" ::"r"(a), "r"(x) : "memory"); }
__device__ __forceinline__ void gate(uint32_t a, int need) {
#pragma unroll 1
  for (int it = 0; it < SPIN_MAX; it++) {
    int v; asm volatile("ld.volatile.shared.b32 %0, [%1];" : "=r"(v) : "r"(a) : "memory");
    if (v >= need) break;
    if (GSLEEP) __nanosleep(GSLEEP);
  }
}
__device__ __forceinline__ void sts128(uint32_t a, uint32_t x, uint32_t y, uint32_t z, uint32_t u) { asm volatile("st.shared.v4.b32 [%0], {%1,%2,%3,%4};" ::"r"(a), "r"(x), "r"(y), "r"(z), "r"(u) : "memory"); }
__device__ __forceinline__ uint4 lds128(uint32_t a) { uint4 v; asm volatile("ld.shared.v4.u32 {%0,%1,%2,%3}, [%4];" : "=r"(v.x), "=r"(v.y), "=r"(v.z), "=r"(v.w) : "r"(a) : "memory"); return v; }
__device__ __forceinline__ uint32_t hmul2(uint32_t a, uint32_t b) { uint32_t r; asm("mul.rn.bf16x2 %0, %1, %2;" : "=r"(r) : "r"(a), "r"(b)); return r; }
__device__ __forceinline__ uint32_t hadd2(uint32_t a, uint32_t b) { uint32_t r; asm("add.rn.bf16x2 %0, %1, %2;" : "=r"(r) : "r"(a), "r"(b)); return r; }
__device__ __forceinline__ void stsm4(uint32_t a, uint32_t r0, uint32_t r1, uint32_t r2, uint32_t r3) {
  asm volatile("stmatrix.sync.aligned.m8n8.x4.shared.b16 [%0], {%1,%2,%3,%4};" ::"r"(a), "r"(r0), "r"(r1), "r"(r2), "r"(r3) : "memory");
}
__device__ __forceinline__ void stsm2(uint32_t a, uint32_t r0, uint32_t r1) {
  asm volatile("stmatrix.sync.aligned.m8n8.x2.shared.b16 [%0], {%1,%2};" ::"r"(a), "r"(r0), "r"(r1) : "memory");
}
__device__ __forceinline__ uint4 ldsm4(uint32_t a) {
  uint4 r; asm volatile("ldmatrix.sync.aligned.m8n8.x4.shared.b16 {%0,%1,%2,%3}, [%4];" : "=r"(r.x), "=r"(r.y), "=r"(r.z), "=r"(r.w) : "r"(a) : "memory"); return r;
}
__device__ __forceinline__ uint32_t movm(uint32_t a) { uint32_t r; asm("movmatrix.sync.aligned.m8n8.trans.b16 %0, %1;" : "=r"(r) : "r"(a)); return r; }
__device__ __forceinline__ void mma16816z(float (&d)[4], uint32_t a0, uint32_t a1, uint32_t a2, uint32_t a3, uint32_t b0, uint32_t b1) {
  asm("mma.sync.aligned.m16n8k16.row.col.f32.bf16.bf16.f32 {%0,%1,%2,%3}, {%4,%5,%6,%7}, {%8,%9}, {%10,%10,%10,%10};"
      : "=f"(d[0]), "=f"(d[1]), "=f"(d[2]), "=f"(d[3]) : "r"(a0), "r"(a1), "r"(a2), "r"(a3), "r"(b0), "r"(b1), "f"(0.f));
}
__device__ __forceinline__ void mma16816(float (&d)[4], const uint4& a, uint32_t b) {
  asm("mma.sync.aligned.m16n8k16.row.col.f32.bf16.bf16.f32 {%0,%1,%2,%3}, {%4,%5,%6,%7}, {%8,%8}, {%0,%1,%2,%3};"
      : "+f"(d[0]), "+f"(d[1]), "+f"(d[2]), "+f"(d[3]) : "r"(a.x), "r"(a.y), "r"(a.z), "r"(a.w), "r"(b));
}
__device__ __forceinline__ void mma1688(float (&d)[4], uint32_t a0, uint32_t a1, uint32_t b0) {
  asm("mma.sync.aligned.m16n8k8.row.col.f32.bf16.bf16.f32 {%0,%1,%2,%3}, {%4,%5}, {%6}, {%0,%1,%2,%3};"
      : "+f"(d[0]), "+f"(d[1]), "+f"(d[2]), "+f"(d[3]) : "r"(a0), "r"(a1), "r"(b0));
}
__device__ __forceinline__ float quad_sum(float v) { v += __shfl_xor_sync(0xffffffffu, v, 1); v += __shfl_xor_sync(0xffffffffu, v, 2); return v; }
__device__ __forceinline__ float quad_max(float v) { v = fmaxf(v, __shfl_xor_sync(0xffffffffu, v, 1)); v = fmaxf(v, __shfl_xor_sync(0xffffffffu, v, 2)); return v; }
__device__ __forceinline__ float rcp(float x) { float r; asm("rcp.approx.ftz.f32 %0, %1;" : "=f"(r) : "f"(x)); return r; }
__device__ __forceinline__ float rsq(float x) { float r; asm("rsqrt.approx.ftz.f32 %0, %1;" : "=f"(r) : "f"(x)); return r; }
__device__ __forceinline__ float ex2(float x) { float r; asm("ex2.approx.ftz.f32 %0, %1;" : "=f"(r) : "f"(x)); return r; }
__device__ __forceinline__ uint32_t chk(uint32_t acc, uint32_t v, uint32_t tag) { uint32_t r; asm("lop3.b32 %0, %1, %2, %3, 0xF6;" : "=r"(r) : "r"(acc), "r"(v), "r"(tag)); return r; }
__device__ __forceinline__ uint32_t chk2(uint32_t a, uint32_t b, uint32_t tag) { uint32_t r; asm("lop3.b32 %0, %1, %2, %3, 0x7E;" : "=r"(r) : "r"(a), "r"(b), "r"(tag)); return r; }
__device__ __forceinline__ uint32_t tagged(uint32_t v, uint32_t tag) { return (v & ~1u) | tag; }

__device__ __forceinline__ int group_k0(int g) { return g < 16 ? 64 * (g & 7) + 4 * (g & 8) : 32 * g; }
__device__ __forceinline__ uint32_t xin_off(int c, int w) { return SM_X + (2 * c + w + (2 * c + w < 9 ? 9 : -9)) * 8192; }
__device__ __forceinline__ uint32_t xin_bar(int c) { return BAR_FULLX + 8 * (c < 8 ? c ^ 4 : c); }
__device__ __forceinline__ int xin_order(int i, int j) { return i; }
__device__ __forceinline__ constexpr uint32_t qkv_xslot(int g) { return (0x5140762u >> (4 * (g - 5))) & 15; }

template <int N> struct IC { static constexpr int v = N; };

struct Cons {
  uint32_t sb;
  uint32_t rem;
  uint32_t sB, mB;
  uint32_t mX;
  bool elect;
  __device__ __forceinline__ void release2(uint32_t bar) const { if (elect) { mbar_arrive(sb + bar); mbar_arrive_remote(rem + bar); } }
  __device__ __forceinline__ uint32_t nextB(uint32_t& prev) {
    mbar_wait_c(sb + BAR_FULLB + sB, mB);
    const uint32_t a = (((sb & 0x3FFFF) + SM_B) >> 4) + sB * (BSLOT / 128);
    prev = sB == 0 ? 32 : sB - 8;
    sB += 8;
    if (sB == 40) { sB = 0; mB ^= 1; }
    return a;
  }
  __device__ __forceinline__ void progress(uint32_t v) const { if (elect) sts32(sb + SM_PROG + (threadIdx.x >> 5), v); }
  __device__ __forceinline__ void releaseLastB() const { release2(BAR_EMPTYB + (sB == 0 ? 32 : sB - 8)); }
};

template <bool QKV, class Pre, class Mma>
__device__ __forceinline__ float2 ln_gemm(Cons& c, Group* G, const float (&v)[36], uint32_t (&p)[18], int w, int st0, int j, int t,
                                          int layer, uint32_t tag, Pre&& pre, Mma&& mma) {
  const bool direct = QKV && layer == 0;
  const uint32_t stag = (2 * layer + (QKV ? 1 : 2)) & 3;
  constexpr int NBUF = 6;
  const uint32_t pbase = 32 * layer;
  uint4* const box = G->xbox;
  uint4 x[NBUF][2];
  const uint4* src = box + t;
  uint32_t xa = c.sb + w * 8192 + (t >> 5) * 2048 + (t & 7) * 128 + (((t >> 3) & 3) ^ (t & 7)) * 16;
  asm volatile("" : "+l"(src), "+r"(xa));
  auto load = [&](int g) { x[g % NBUF][0] = ld_relaxed4(src + 2 * g * 128); x[g % NBUF][1] = ld_relaxed4(src + (2 * g + 1) * 128); };
  auto load_in = [&](int g) {
    if (g == 8) xa -= w * 8 * XSLOT;
    if (g == 10) xa += w * 8 * XSLOT;
    if (g == 16) xa = c.sb + w * 8192 + (t >> 5) * 2048 + (t & 15) * 128 + (((t >> 4) & 1) ^ (t & 7)) * 16;
    const uint32_t a = xa ^ (64 * (g & 1));
    x[g % NBUF][0] = ldsm4(a + xin_off(g >> 1, 0));
    x[g % NBUF][1] = ldsm4((g < 16 ? a + 1024 : a ^ 32) + xin_off(g >> 1, 0));
  };
  float s0 = 0.f, s1 = 0.f, d0 = 0.f, d1 = 0.f;
  auto sums = [&](const float (&v)[36]) {
    s0 = v[0] + v[1]; s1 = v[2] + v[3];
#pragma unroll
    for (int i = 1; i < 9; i++) { s0 += v[4 * i] + v[4 * i + 1]; s1 += v[4 * i + 2] + v[4 * i + 3]; }
    s0 = __uint_as_float((__float_as_uint(quad_sum(s0)) & ~3u) | stag); s1 = quad_sum(s1);
  };
  auto squares = [&](const float (&v)[36]) {
    const float m0 = s0 * (1.f / 72), m1 = s1 * (1.f / 72);
    d0 = d1 = 0.f;
#pragma unroll
    for (int i = 0; i < 9; i++) {
      float a = v[4 * i] - m0, b = v[4 * i + 1] - m0; d0 = fmaf(a, a, fmaf(b, b, d0));
      a = v[4 * i + 2] - m1; b = v[4 * i + 3] - m1; d1 = fmaf(a, a, fmaf(b, b, d1));
    }
    d0 = quad_sum(d0); d1 = quad_sum(d1);
  };
  auto load3 = [&](int g) { load(g); load(g + 1); load(g + 2); };
  auto invalid = [&](int g, uint32_t tag) {
    const uint4 (&y)[2] = x[g % NBUF], (&y1)[2] = x[(g + 1) % NBUF], (&y2)[2] = x[(g + 2) % NBUF];
    uint32_t bad = chk2(y[0].x, y[1].x, tag) | chk2(y1[0].x, y1[1].x, tag) | chk2(y2[0].x, y2[1].x, tag);
    if (g == 15) bad |= chk2(y1[0].z, y1[1].z, tag) | chk2(y2[0].z, y2[1].z, tag);
    return __any_sync(0xffffffffu, bad & 1);
  };
  uint4* const d = box + 2 * j * 128 + t;
  const int sq = st0 + 16 * (t & 3);
#pragma unroll
  for (int g = 0; g < NBUF; g++) x[g][0] = x[g][1] = make_uint4(tag ^ 1, 0, 0, 0);
  float m0, m1;
  if (direct) {
    float ra[4] = {0.f, 0.f, 0.f, 0.f}, rb[4] = {0.f, 0.f, 0.f, 0.f};
#pragma unroll 1
    for (int cc = 0; cc < 9; cc++) {
      const uint32_t a = xa - w * 8192 + xin_off(cc, w);
      mbar_wait_c(c.sb + xin_bar(cc), 0);
      const uint4 u0 = ldsm4(a), u1 = ldsm4(a + 1024), u2 = ldsm4(a ^ 64), u3 = ldsm4((a ^ 64) + 1024);
      mma16816(ra, u0, 0x3f803f80u); mma16816(rb, u1, 0x3f803f80u); mma16816(ra, u2, 0x3f803f80u); mma16816(rb, u3, 0x3f803f80u);
    }
    m0 = ra[0] + ra[2]; m1 = rb[0] + rb[2];
#pragma unroll
    for (int i = 0; i < 5; i++) {
      const uint4 u = ldsm4(c.sb + (t >> 5) * 2048 + (t & 15) * 128 + xin_off(i < 4 ? j : 8, w) + (((i < 4 ? 2 * i + ((t >> 4) & 1) : j) ^ (t & 7)) << 4));
      p[4 * i] = u.x; p[4 * i + 1] = u.y;
      if (i < 4) { p[4 * i + 2] = u.z; p[4 * i + 3] = u.w; }
    }
    pre(0);
  } else {
    sums(v);
    if ((t & 3) == 0) st_relaxed2(G->sum + st0 + 8 * j, __float_as_uint(s0), __float_as_uint(s1));
#pragma unroll
    for (int i = 0; i < 18; i++) p[i] = pack_bf16(v[2 * i], v[2 * i + 1]);
#pragma unroll
    for (int i = 0; i < 2; i++) st_relaxed4(d + i * 128, tagged(p[i], tag), p[i + 2], p[i + 4], p[i + 6]);
    uint2 sa, sc;
    auto poll = [&] {
      if (SPEC && layer && invalid(0, tag)) load3(0);
      sa = ld_relaxed2(G->sum + sq); sc = ld_relaxed2(G->sum + sq + 8);
    };
    poll();
    squares(v);
    pre(0);
    while (__any_sync(0xffffffffu, ((sa.x ^ stag) | (sc.x ^ stag)) & 3)) poll();
    if (invalid(0, tag)) load3(0);
    m0 = quad_sum(__uint_as_float(sa.x) + __uint_as_float(sc.x)); m1 = quad_sum(__uint_as_float(sa.y) + __uint_as_float(sc.y));
  }
  m0 *= -1.f / 576; m1 *= -1.f / 576;
  const uint32_t nm0 = pack_bf16(m0, m0), nm1 = pack_bf16(m1, m1);
  pre(1);
  uint4 u0, u1;
#pragma unroll
  for (int g = 0; g < 18; g++) {
    uint4 &a = x[g % NBUF][0], &b = x[g % NBUF][1];
    if (direct) load_in(g);
    else if (g % 3 == 0) {
      const uint32_t lt = g ? late(c.sb + BAR_FULLX + 64, tag) : tag;
      while (invalid(g, lt)) load3(g);
      if (g > 0 && g < 15) load3(g + 3);
    }
    const bool rows = g < 16;
    const uint4 f0 = make_uint4(hadd2(a.x, nm0), hadd2(rows ? b.x : a.y, nm1), hadd2(rows ? a.y : a.z, nm0), hadd2(rows ? b.y : a.w, nm1));
    const uint4 f1 = make_uint4(hadd2(rows ? a.z : b.x, nm0), hadd2(rows ? b.z : b.y, nm1), hadd2(rows ? a.w : b.z, nm0), hadd2(b.w, nm1));
    if (g == 12) { u0 = ld_relaxed4(G->m2 + sq); u1 = ld_relaxed4(G->m2 + sq + 8); }
    uint32_t prev = c.sB == 0 ? 32 : c.sB - 8, bb;
    if (QKV && g >= 5 && g < 12 && !direct) {
      mbar_wait_c(c.sb + BAR_FULLX + 8 * qkv_xslot(g), (c.mX >> qkv_xslot(g)) & 1);
      bb = ((c.sb & 0x3FFFF) + SM_X + qkv_xslot(g) * XSLOT) >> 4;
    } else {
      bb = c.nextB(prev);
    }
    if (QKV && g == GL && w == 1) asm volatile("bar.sync 6, 256;" ::: "memory");
    mma(g, bb, f0, f1);
    if (QKV && g == 17 && w == 0) asm volatile("bar.arrive 6, 256;" ::: "memory");
    if (g == 0) {
      if (!direct) {
        load3(3);
#pragma unroll
        for (int i = 0; i < 2; i++) st_relaxed4(d + (16 + i) * 128, tagged(p[8 + i], tag), p[10 + i], p[12 + i], p[14 + i]);
        st_relaxed2((uint2*)(box + (32 + (j >> 1)) * 128 + t) + (j & 1), tagged(p[16], tag), p[17]);
      } else {
        float u[36];
#pragma unroll
        for (int i = 0; i < 18; i++) { u[2 * i] = bf_lo(p[i]); u[2 * i + 1] = bf_hi(p[i]); }
        sums(u);
        squares(u);
      }
      if ((t & 3) == 0) st_relaxed4(G->m2 + st0 + 8 * j, __float_as_uint(s0), __float_as_uint(s1), __float_as_uint(d0), __float_as_uint(d1));
      c.progress(pbase + (QKV ? 1 : 21));
    }
    wg_wait<1>();
    if (g > 0 && !(QKV && g > 5 && g <= 12 && !direct)) c.release2(BAR_EMPTYB + prev);
    if (QKV && g > 0 && g < 15) c.progress(pbase + 1 + g);
    if (QKV && g >= WOG && g < WOG + 4) c.release2(BAR_EMPTYX + 32 + 8 * (g - WOG));
  }
  if (QKV) c.mX ^= direct ? 0xff : 0xf7;
  while (__any_sync(0xffffffffu, chk2(u0.x, u1.x, stag) & 3)) { u0 = ld_relaxed4(G->m2 + sq); u1 = ld_relaxed4(G->m2 + sq + 8); }
  float e0 = fmaf(__uint_as_float(u0.x), 1.f / 72, m0), e1 = fmaf(__uint_as_float(u1.x), 1.f / 72, m0);
  const float v0 = quad_sum(fmaf(72.f, fmaf(e0, e0, e1 * e1), __uint_as_float(u0.z) + __uint_as_float(u1.z)));
  e0 = fmaf(__uint_as_float(u0.y), 1.f / 72, m1); e1 = fmaf(__uint_as_float(u1.y), 1.f / 72, m1);
  const float v1 = quad_sum(fmaf(72.f, fmaf(e0, e0, e1 * e1), __uint_as_float(u0.w) + __uint_as_float(u1.w)));
  float2 r = make_float2(rsq(fmaf(v0, 1.f / 576, 1e-5f)), rsq(fmaf(v1, 1.f / 576, 1e-5f)));
  asm volatile("" : "+f"(r.x), "+f"(r.y));
  if (QKV && GL == 18 && w == 1) asm volatile("bar.sync 6, 256;" ::: "memory");
  wg_wait<0>();
  if (QKV && ATTBAR && w == 1) asm volatile("bar.arrive 4, 256;" ::: "memory");
  c.releaseLastB();
  if (direct) c.release2(BAR_EMPTYX + 24);
  return r;
}

template <int NB, int OFF>
__device__ __forceinline__ void glu(const float (&a)[128], uint32_t (&h)[144]) {
#pragma unroll
  for (int b = 0; b < 2 * NB; b++) {
    if (HMUL) h[OFF + b] = hmul2(pack_bf16(a[2 * b], a[2 * b + 1]), pack_bf16(a[4 * NB + 2 * b], a[4 * NB + 2 * b + 1]));
    else h[OFF + b] = pack_bf16(a[2 * b] * a[4 * NB + 2 * b], a[2 * b + 1] * a[4 * NB + 2 * b + 1]);
  }
}

__global__ void __cluster_dims__(2, 1, 1) __launch_bounds__(384, 1)
fused_kernel(const __nv_bfloat16* __restrict__ x_in, Group* ws, const char* __restrict__ wqkv,
             const char* __restrict__ wg, const char* __restrict__ wu, const char* __restrict__ wd, const __grid_constant__ Maps maps,
             const char* __restrict__ wo) {
  extern __shared__ __align__(1024) uint8_t smem_raw[];
  const uint32_t sb = smem_u32(smem_raw);
  if (threadIdx.x == 0) asm volatile("prefetch.tensormap [%0];" ::"l"(&maps.x) : "memory");
  const int warp = __shfl_sync(0xffffffffu, threadIdx.x >> 5, 0);
  const int lane = threadIdx.x & 31;
  const int rank = blockIdx.x & 1;
  if (elect_one()) {
    if (warp >= 8) {
#pragma unroll
      for (int i = 0; i < 9; i++) mbar_init(sb + SM_BAR + 72 * (warp - 8) + 8 * i, warp < 10 ? 1 : 4);
      sts32(sb + SM_PROG + 4 * (warp - 8), 0);
      asm volatile("fence.mbarrier_init.release.cluster;" ::: "memory");
    } else if (warp == 1 || warp == 2) {
      asm volatile("prefetch.tensormap [%0];" ::"l"(&maps.x + warp) : "memory");
    } else if (warp == 3) {
      if (PFMODE & 1) prefetch_l2((const char*)x_in + blockIdx.x * 18432, 18432);
    } else if (warp == 4) {
      if (PFMODE & 2) prefetch_l2(wqkv + blockIdx.x * (15552 / PFQ), 15552 / PFQ);
    }
  }
  __syncwarp();
  asm volatile("barrier.cluster.arrive.relaxed.aligned;" ::: "memory");
  if (warp == 8) PROFX(53);
  int lb = blockIdx.x;
  if (GPCMAP) {
    const int cl = blockIdx.x >> 1, u = cl - 36;
    lb = (cl < 4 ? cl : cl < 36 ? 8 * ((cl - 4) & 7) + ((cl - 4) >> 3) + (((cl - 4) & 7) ? 0 : 4) : 8 * (1 + u % 7) + 4 + u / 7) * 2 + rank;
  }
#define CTA_J(b) (((b) >> 1) & 7)
#define CTA_RB(b) ((((b) >> 4) << 1) | ((b) & 1))
  const int j = CTA_J(lb), rb = CTA_RB(lb);

  PROF(23);
  if (warp >= 8) {
    asm volatile("setmaxnreg.dec.sync.aligned.u32 " STR(REGS_P) ";");
    auto x_chunk = [&](int cc) {
      mbar_expect_tx(sb + xin_bar(cc), 16384);
      tma3d(sb + xin_off(cc, 0), &maps.x, 64 * cc, 0, 64 * rb, sb + xin_bar(cc));
      tma3d(sb + xin_off(cc, 1), &maps.x, 64 * cc, 1, 64 * rb, sb + xin_bar(cc));
    };
    if (warp == 9 && elect_one()) {
      fence_async_smem();
#pragma unroll 1
      for (int i = 0; i < 9; i++) x_chunk(xin_order(i, j));
    }
    __syncwarp();
    if (warp == 9) PROFX(54);
    asm volatile("barrier.cluster.wait.aligned;" ::: "memory");
    if (warp == 8) PROFX(56);
    const uint64_t pol = W_POLICY(), pola = A_POLICY();
    auto qkv_group = [&](int k, uint32_t dst, uint32_t bar) {
      wtma3d(dst + rank * 8192, &maps.qm, 72 * j, k + 16 * rank, 0, bar, pola);
      wtma3d(dst + rank * 8192 + 6144, &maps.qc, 72 * j + 64, k + 16 * rank, 0, bar, pola);
    };
    auto qkv_gate = [&](int g) { if (g >= 8) gate(sb + SM_PROG, 33 + ((g - 8) * 23 >> 4)); };
    if (warp == 8) {
      uint32_t s = 0, ph = 1;
      auto slot = [&](uint32_t bytes, auto&& issue) {
        const uint32_t bar = sb + BAR_FULLB + 8 * s;
        mbar_wait(sb + BAR_EMPTYB + 8 * s, ph);
        if (elect_one()) {
          mbar_expect_tx(bar, bytes);
          issue(sb + SM_B + s * BSLOT, bar);
        }
        if (++s == 5) { s = 0; ph ^= 1; }
      };
#pragma unroll 1
      for (int layer = 0; layer < NLAYERS; layer++) {
#pragma unroll 1
        for (int g = 0; g < 18; g += layer && g == 4 ? 8 : 1) {
          if (layer) qkv_gate(g);
          else if (g == QD) mbar_wait(sb + xin_bar(xin_order(XH, j)), 0);
          slot(2 * 6912, [&](uint32_t dst, uint32_t bar) { qkv_group(layer ? group_k0(g) : 32 * g, dst, bar); });
        }
        if (!FCH) {
          gate(sb + SM_PROG, 32 * layer + 20);
          gate(sb + SM_PROG + 4, 32 * layer + 20);
        }
#pragma unroll 1
        for (int t = 0; t < 5; t++) {
          const CUtensorMap* m = &maps.g + (t < 3 ? rank : 2 + rank);
          const int c2 = t < 3 ? 9 * j + 2 * t : 18 * j + 3 + 3 * t;
          const uint32_t half = t < 3 ? 8192 : 6144;
#pragma unroll 1
          for (int g = 0; g < 18; g++) {
            if (FCH && t == 0 && g < 5) mbar_wait(sb + BAR_FULLB + 8 * (s < FCH ? s + 5 - FCH : s - FCH), s < FCH ? ph : ph ^ 1);
            slot(2 * half, [&](uint32_t dst, uint32_t bar) { wtma3d(dst + rank * half, m, 0, group_k0(g), c2, bar, pol); });
          }
        }
      }
    } else if (warp == 9) {
      uint32_t mE = 0;
      auto acquire = [&](uint32_t s) { mbar_wait(sb + BAR_EMPTYX + 8 * s, (mE >> s) & 1); mE ^= 1u << s; };
      auto landed = [&](uint32_t s) { mbar_wait(sb + BAR_FULLX + 8 * s, (mE >> s) & 1); };
      auto slot = [&](uint32_t s, const CUtensorMap* m, int col, int row, uint64_t pol) {
        acquire(s);
        if (elect_one()) {
          mbar_expect_tx(sb + BAR_FULLX + 8 * s, XSLOT);
          wtma2d(sb + SM_X + s * XSLOT + rank * 9216, m, col, row + 72 * rank, sb + BAR_FULLX + 8 * s, pol);
        }
      };
#pragma unroll 1
      for (int layer = 0; layer < NLAYERS; layer++) {
#pragma unroll 1
        for (int g = 5; g < 12 * layer; g++) {
          const uint32_t s = qkv_xslot(g);
          qkv_gate(g);
          acquire(s);
          if (elect_one()) {
            mbar_expect_tx(sb + BAR_FULLX + 8 * s, 2 * 6912);
            qkv_group(group_k0(g), sb + SM_X + s * XSLOT, sb + BAR_FULLX + 8 * s);
          }
          if (XCH & 1) landed(s);
        }
#pragma unroll 1
        for (int i = 0; i < 4; i++) { slot(4 + i, &maps.o, 64 * j, 144 * i, pola); if (XCH & 2) landed(4 + i); }
        acquire(3);
        if (elect_one()) {
          mbar_expect_tx(sb + BAR_FULLX + 24, 9216);
          wtma2d(sb + SM_WOC + rank * 4608, &maps.oc, 512 + 8 * j, 288 * rank, sb + BAR_FULLX + 24, pola);
          wtma2d(sb + SM_WOC + rank * 4608 + 2304, &maps.oc, 512 + 8 * j, 288 * rank + 144, sb + BAR_FULLX + 24, pola);
        }
#pragma unroll 1
        for (int u = 0; u < 36; u++) {
          const uint32_t s = 4 * (u & 1) + ((u >> 1) & 3);
          slot(s, &maps.d, u < 4 ? 512 : 64 * ((j + (u >> 2)) & 7), 576 * j + 144 * (u & 3), pol);
          if ((XCH & 4) && u < 3) landed(s);
        }
      }
    } else {
      const int w = warp - 10, grp = 2 * rb + w;
      if (PFMODE & 4) {
        mbar_wait(sb + xin_bar(xin_order(XP, j)), 0);
        if (lane == 0) prefetch_l2(wqkv + (2 * blockIdx.x + w) * 7776, 7776);
      }
      gate(sb + SM_PROG, 3);
      if (w == 0) PROFX(58);
      auto prefetch_gu = [&](int l0, int n) {
#pragma unroll 1
        for (int i = lane; i < 36 * n; i += 32) {
          asm volatile("prefetch.global.L2 [%0];" ::"l"((w ? wu : wg) + (size_t)(36 * rb + i / n) * 9216 + 1152 * j + 128 * (l0 + i % n)));
          __nanosleep(PFSLEEP);
        }
      };
      auto clear = [&](uint4* p, int n) {
#pragma unroll 1
        for (int i = lane; i < n; i += 64) { st_relaxed4(p + i, 0, 0, 0, 0); st_relaxed4(p + i + 32, 0, 0, 0, 0); __nanosleep(CLRSLEEP); }
      };
      auto exchange = [&](uint32_t v, uint32_t bar) {
        fence_gpu();
        __syncwarp();
        if (lane == 0) st_relaxed(ws[grp].flag + j, v);
#pragma unroll 1
        for (int it = 0; it < SPIN_MAX; it++) {
          const uint32_t f = ld_relaxed(ws[grp].flag + (lane & 7));
          if (__all_sync(0xffffffffu, v ? f >= v : f == 0)) break;
        }
        if (lane == 0) mbar_arrive(sb + bar + 8 * w);
      };
      if (lane == 0) prefetch_l2(wo + (2 * blockIdx.x + w) * 2592, 2592);
      if (MAPPF && w == 0 && lane < 9) asm volatile("prefetch.tensormap [%0];" ::"l"(&maps.o + lane) : "memory");
#pragma unroll 1
      for (int layer = 0; layer < NLAYERS; layer++) {
        gate(sb + SM_PROG, 32 * layer + 3);
        if (PFF & 1) prefetch_gu(0, 2);
        gate(sb + SM_PROG, 32 * layer + 22);
        if (PFF & 2) prefetch_gu(2, 2);
        if (layer == 0) {
          clear(ws[grp].inbox[0] + 2 * j * INBOX, 2 * INBOX);
          exchange(1, BAR_CLR);
          if (w == 0) PROFX(59);
        }
        if (PFF & 2) prefetch_gu(4, 2);
        if (PFF & 4) prefetch_gu(6, 3);
#pragma unroll 1
        for (int i = lane; i < ((PFF & 8) ? 162 : 0); i += 32) {
          asm volatile("prefetch.global.L2 [%0];" ::"l"(wd + (size_t)(576 * j + 36 * rb + 18 * w) * 1152 + 128 * i));
          __nanosleep(PFSLEEP);
        }
        if (w == 0 && layer == 0) PROFX(60);
        mbar_wait(sb + BAR_REDDONE + 8 * w, layer);
        if (w == 0) PROFX(64 + 53 + 4 * layer);
        exchange(2 - 2 * layer, BAR_RREADY);
        if (w == 0) PROFX(64 + 56 + 4 * layer);
      }
      mbar_wait(sb + BAR_DONE + 8 * w, 0);
    }
    __syncwarp();
    cluster_sync();
  } else {
    asm volatile("setmaxnreg.inc.sync.aligned.u32 " STR(REGS_C) ";");
#define THREAD_IDS()                                                                   \
    int tid_ = threadIdx.x, bid_ = lb;                                                  \
    asm volatile("" : "+r"(tid_), "+r"(bid_));                                          \
    const int w = warp >> 2, wp = warp & 3;                                             \
    const int lane = tid_ & 31, t = tid_ & 127, g = lane >> 2, q = lane & 3;           \
    const int j = CTA_J(bid_), rb = CTA_RB(bid_), grp = 2 * rb + w;                    \
    const int st0 = wp * 64 + g;                         \
    Group* const G = ws + grp;                                                         \
    const uint32_t dsb = (sb & 0x3FFFF) >> 4;                                          \
    (void)t; (void)g; (void)q; (void)grp; (void)j; (void)st0; (void)dsb; (void)G
    Cons c;
    c.sb = sb; c.sB = 0; c.mB = 0; c.mX = 0; c.elect = (threadIdx.x & 127) == 0;
    asm volatile("mapa.shared::cluster.u32 %0, %1, %2;" : "=r"(c.rem) : "r"(sb), "r"(rank ^ 1));
    float v[36];
    uint32_t xtag;
    {
      THREAD_IDS();
      if (OPEN) {
        if (q == 0) { st_relaxed2(G->sum + st0 + 8 * j, 0, 0); st_relaxed4(G->m2 + st0 + 8 * j, 0, 0, 0, 0); }
        if (wp == 3) {
#pragma unroll
          for (int i = 0; i < 5; i++) st_relaxed4(G->halo + j * 160 + lane + i * 32, 0, 0, 0, 0);
        }
        if (lane >= OPENL) st_relaxed4(G->obox + (8 * WPROBE + j) * 128 + t, 0, 0, 0, 0);
      }
      xtag = __shfl_sync(0xffffffffu, ~ld_relaxed(G->flag + 32 + 32 * j) & 1, 0);
      asm volatile("barrier.cluster.wait.aligned;" ::: "memory");
      PROF(0);
#pragma unroll
      for (int i = 0; i < 36; i++) v[i] = 0.f;
    }
#pragma unroll 1
    for (int layer = 0;; layer++) {
      const uint32_t tag = layer ^ 1;
      const int pb = 1 + layer * 30;
      uint32_t res[18];
      {
        THREAD_IDS();
        PROF(pb + 0);
        float a1[96], a2[12];
        const float2 rs = ln_gemm<true>(c, G, v, res, w, st0, j, t, layer, xtag ^ 1,
          [&](int i) { PROF(pb + 1 + i); },
          [&](int gi, uint32_t bb, const uint4& f0, const uint4& f1) {
            if (gi == 0) PROF(pb + 3);
            wg_fence();
            wgmma_ra<192>(a1, f0, desc_hi(2048, 1024, 1) + bb, gi > 0);
            wgmma_ra<24>(a2, f0, desc_hi(128, 256, 0) + (bb + 384), gi > 0);
            wgmma_ra<192>(a1, f1, desc_hi(2048, 1024, 1) + (bb + 512), true);
            wgmma_ra<24>(a2, f1, desc_hi(128, 256, 0) + (bb + 896), true);
            wg_commit();
          });
        PROF(pb + 4);
        uint32_t kv[3][18];
        auto cvt = [&](int b, float r) {
#pragma unroll
          for (int cc = 0; cc < 18; cc++) {
            const float* a = (cc == 8 ? a2 + 4 : cc == 17 ? a2 + 8 : cc < 8 ? a1 + 32 + 4 * cc : a1 + 28 + 4 * cc) + 2 * (b - 1);
            const uint32_t u = pack_bf16(a[0] * r, a[1] * r);
            kv[b][cc] = cc < 9 ? u : movm(u);
          }
        };
        cvt(2, rs.y);
        const uint32_t msg = sb + SM_X + (w ? 3 * XSLOT : 24576) + wp * 2304 + lane * 16;
        if (wp == 3) {
          uint4* hp = G->halo + j * 160 + lane;
#pragma unroll
          for (int i = 0; i < 4; i++) st_relaxed4(hp + i * 32, tagged(kv[2][4 * i], tag), kv[2][4 * i + 1], kv[2][4 * i + 2], kv[2][4 * i + 3]);
          st_relaxed2((uint2*)(hp + 128), tagged(kv[2][16], tag), kv[2][17]);
        } else {
#pragma unroll
          for (int i = 0; i < 4; i++) sts128(msg + i * 512, kv[2][4 * i], kv[2][4 * i + 1], kv[2][4 * i + 2], kv[2][4 * i + 3]);
          sts64f(msg + 2048 - lane * 8, __uint_as_float(kv[2][16]), __uint_as_float(kv[2][17]));
        }
        cvt(1, rs.x);
        uint32_t Q[4][6];
#pragma unroll
        for (int h = 0; h < 4; h++)
#pragma unroll
          for (int i = 0; i < 6; i++) {
            const float* a = 4 * h + i < 16 ? a1 + 8 * h + 2 * i : a2 + 8 * h + 2 * i - 32;
            const uint32_t u = pack_bf16(a[0], a[1]);
            Q[h][i] = i < 2 ? (q >= h ? u : 0) : i < 4 ? u : (q <= h ? u : 0);
          }
        const bool lo0 = 2 * q > g, lo1 = 2 * q + 1 > g;
        const uint32_t M = (lo0 ? 0xffffu : 0u) | (lo1 ? 0xffff0000u : 0u);
        auto scores = [&](int h, int b, float (&s)[4]) {
          mma16816z(s, Q[h][0], Q[h][1], Q[h][2], Q[h][3], kv[b][2 * h], kv[b][2 * h + 1]);
          mma1688(s, Q[h][4], Q[h][5], kv[b][2 * h + 2]);
        };
        auto softmax = [&](float (&l)[4][2], float r, uint32_t (&P)[4]) {
          const float sl = r * (0.23570226039551584f * 1.4426950408889634f);
          float m[4];
#pragma unroll
          for (int h = 0; h < 4; h++) { m[h] = fmaxf(l[h][0], l[h][1]); m[h] = fmaxf(m[h], __shfl_xor_sync(0xffffffffu, m[h], 1)); }
#pragma unroll
          for (int h = 0; h < 4; h++) m[h] = fmaxf(m[h], __shfl_xor_sync(0xffffffffu, m[h], 2)) * sl;
#pragma unroll
          for (int h = 0; h < 4; h++) {
            l[h][0] = ex2(fmaf(l[h][0], sl, -m[h])); l[h][1] = ex2(fmaf(l[h][1], sl, -m[h]));
            m[h] = l[h][0] + l[h][1]; m[h] += __shfl_xor_sync(0xffffffffu, m[h], 1);
          }
#pragma unroll
          for (int h = 0; h < 4; h++) { m[h] = rcp(m[h] + __shfl_xor_sync(0xffffffffu, m[h], 2)); P[h] = pack_bf16(l[h][0] * m[h], l[h][1] * m[h]); }
        };
        const bool remote = wp == 0 && rb > 0;
        const uint4* hp = (G - 2)->halo + j * 160 + lane;
        auto halo = [&] {
#pragma unroll
          for (int i = 0; i < 4; i++) { const uint4 u = ld_relaxed4(hp + i * 32); kv[0][4 * i] = u.x; kv[0][4 * i + 1] = u.y; kv[0][4 * i + 2] = u.z; kv[0][4 * i + 3] = u.w; }
          const uint2 u = ld_relaxed2((const uint2*)(hp + 128));
          kv[0][16] = u.x; kv[0][17] = u.y;
        };
#pragma unroll
        for (int i = 0; i < 18; i++) kv[0][i] = 0;
        if (remote) halo();
        if (ATTBAR && w == 0) asm volatile("bar.sync 4, 256;" : "+r"(Q[0][2]), "+r"(Q[1][2]), "+r"(Q[2][2]), "+r"(Q[3][2]) :: "memory");
        float l0[4][2], l1[4][2];
#pragma unroll
        for (int h = 0; h < 4; h++) {
          float s1[4], s2[4];
          scores(h, 1, s1); scores(h, 2, s2);
          l0[h][0] = s1[0]; l0[h][1] = s1[1];
          l1[h][0] = lo0 ? s1[2] : s2[2]; l1[h][1] = lo1 ? s1[3] : s2[3];
        }
        uint32_t P0[4], P1[4];
        softmax(l1, rs.y, P1);
        if (remote) {
          while (__any_sync(0xffffffffu, chk(chk2(kv[0][0], kv[0][4], tag) | chk2(kv[0][8], kv[0][12], tag), kv[0][16], tag) & 1)) halo();
        }
        if (FG < 0) c.progress(32 * layer + 20);
        wg_bar(w);
        if (wp > 0) {
          const uint32_t from = msg - 2304;
#pragma unroll
          for (int i = 0; i < 4; i++) { const uint4 u = lds128(from + i * 512); kv[0][4 * i] = u.x; kv[0][4 * i + 1] = u.y; kv[0][4 * i + 2] = u.z; kv[0][4 * i + 3] = u.w; }
          const float2 u = lds64(from + 2048 - lane * 8);
          kv[0][16] = __float_as_uint(u.x); kv[0][17] = __float_as_uint(u.y);
        }
        PROF(pb + 5);
        const bool first = (rb == 0 && wp == 0);
#pragma unroll
        for (int h = 0; h < 4; h++) {
          float s0[4];
          scores(h, 0, s0);
          if (first) s0[0] = s0[1] = -INFINITY;
          l0[h][0] = lo0 ? s0[0] : l0[h][0]; l0[h][1] = lo1 ? s0[1] : l0[h][1];
        }
        softmax(l0, rs.x, P0);
        uint4* ob = G->obox + t;
        uint32_t car0 = 0, car1 = 0;
#pragma unroll
        for (int h = 0; h < 4; h++) {
          float o[3][4];
#pragma unroll
          for (int i = 0; i < 3; i++) {
            mma16816z(o[i], P0[h] & ~M, P1[h] & M, 0u, P1[h] & ~M, kv[1][9 + 2 * h + i], kv[2][9 + 2 * h + i]);
            mma1688(o[i], P0[h] & M, 0u, kv[0][9 + 2 * h + i]);
          }
          const uint32_t o0 = q < h ? car0 : pack_bf16(o[0][0], o[0][1]), o1 = q < h ? car1 : pack_bf16(o[0][2], o[0][3]);
          st_relaxed4(ob + (8 * h + j) * 128, o0 | 1, o1, pack_bf16(o[1][0], o[1][1]), pack_bf16(o[1][2], o[1][3]));
          car0 = pack_bf16(o[2][0], o[2][1]); car1 = pack_bf16(o[2][2], o[2][3]);
        }
        st_relaxed2((uint2*)(ob + (32 + (j >> 1)) * 128) + (j & 1), tagged(car0, tag), car1);
        PROF(pb + 6);
      }
      {
        THREAD_IDS();
        const uint4* src = G->obox + t;
        float a[32], a8[4];
#pragma unroll
        for (int i = 3; i < 8; i++) mbar_wait_c(sb + BAR_FULLX + 8 * i, (c.mX >> i) & 1);
        c.mX ^= 0xf8;
        const uint32_t* probe = &(G->obox + (8 * WPROBE + (lane & 7)) * 128 + (t | 31))->x;
        while (__any_sync(0xffffffffu, ~ld_relaxed(probe) & 1)) {}
        if (w == 1) asm volatile("bar.sync 7, 256;" ::: "memory");
        uint4 x[36];
        auto batch = [&](auto e0, auto e1, auto e2, int b) {
          constexpr int E0 = decltype(e0)::v, E1 = decltype(e1)::v, E2 = decltype(e2)::v;
          const uint32_t one = E0 > 0 && E1 > E0 ? late(sb + BAR_FULLX + 64, 1) : 1;
          while (E1 > E0) {
            uint32_t bad = 0;
#pragma unroll
            for (int i = E0; i < E1; i++) bad = i < 32 ? chk(bad, x[i].x, one) : chk(chk(bad, x[i].x, tag), x[i].z, tag);
            if (!__any_sync(0xffffffffu, bad & 1)) break;
#pragma unroll
            for (int i = E0; i < E1; i++) x[i] = ld_relaxed4(src + i * 128);
          }
          if (b == 0) PROF(pb + 7);
#pragma unroll
          for (int i = E1; i < E2; i++) x[i] = ld_relaxed4(src + i * 128);
          if (b == WOREL && w == 0) asm volatile("bar.arrive 7, 256;" ::: "memory");
          if (E1 > E0) {
            wg_fence();
#pragma unroll
            for (int i = E0; i < E1; i++) {
              const int r0 = i < 32 ? 72 * (i & 7) + 16 * (i >> 3) : 144 * (i - 32) + 64, rs = i < 32 ? 8 : 72;
              wgmma_ra<64>(a, x[i], desc_hi(0, rs * 128, 1) + (dsb + ((SM_X + 4 * XSLOT) >> 4) + r0 * 8), i > 0);
              wgmma_ra<8>(a8, x[i], desc_hi(rs * 16, 0, 0) + (dsb + (SM_WOC >> 4) + r0), i > 0);
            }
            wg_commit();
          }
        };
        batch(IC<0>(), IC<0>(), IC<WB1>(), -1);
        batch(IC<0>(), IC<WB1>(), IC<WB2>(), 0);
        batch(IC<WB1>(), IC<WB2>(), IC<WB3>(), 1);
        batch(IC<WB2>(), IC<WB3>(), IC<WB4>(), 2);
        batch(IC<WB3>(), IC<WB4>(), IC<36>(), 3);
        batch(IC<WB4>(), IC<36>(), IC<36>(), 4);
        wg_wait<0>();
        if (w == 0) asm volatile("bar.arrive 3, 256;" ::: "memory");
        PROF(pb + 8);
#pragma unroll
        for (int i = 0; i < 18; i++) {
          v[2 * i] = bf_lo(res[i]) + (i < 16 ? a[2 * i] : a8[2 * i - 32]);
          v[2 * i + 1] = bf_hi(res[i]) + (i < 16 ? a[2 * i + 1] : a8[2 * i - 31]);
        }
      }
      uint32_t lsb;
      uint32_t h[144];
      {
        THREAD_IDS();
        float a[128];
        const uint32_t xd = sb + SM_X + w * 4 * XSLOT + (lane >> 4) * 1024 + (16 * wp + (lane & 15)) * 16;
        const float2 rs = ln_gemm<false>(c, G, v, res, w, st0, j, t, layer, xtag,
          [&](int i) {
            if (i == 0) {
              lsb = ((res[0] & 1) | (res[1] & 1) << 1 | (res[8] & 1) << 2 | (res[9] & 1) << 3 | (res[16] & 1) << 4) ^ (xtag * 31);
              if (w == 1) asm volatile("bar.sync 3, 256;" ::: "memory");
            }
            PROF(pb + 9 + i);
          },
          [&](int gi, uint32_t bb, const uint4& f0, const uint4& f1) {
            if (gi == 0) PROF(pb + 11);
            wg_fence();
            wgmma_ra<256>(a, f0, desc_hi(4096, 1024, 1) + bb, gi > 0);
            wgmma_ra<256>(a, f1, desc_hi(4096, 1024, 1) + (bb + 128), true);
            wg_commit();
            stsm4(xd + gi * 4096, f0.x, f0.y, f0.z, f0.w);
            stsm4(xd + gi * 4096 + 2048, f1.x, f1.y, f1.z, f1.w);
            if (gi == 17) { fence_async_smem(); wg_bar(w); }
          });
        sts64f(sb + SM_KEEP + tid_ * 8, rs.x * rs.x, rs.y * rs.y);
        c.progress(32 * layer + 22);
        PROF2(pb + 12);
        glu<16, 0>(a, h);
        const uint64_t da0 = desc_hi(1024, 128, 0) + (dsb + ((SM_X + w * 4 * XSLOT) >> 4));
        auto tile = [&](auto wide, auto last) {
          const uint32_t xe = BAR_EMPTYX + 32 * (t & 1) + 4 * (t & 6);
#pragma unroll 1
          for (int gi = 0; gi < 18; gi++) {
            uint32_t prev;
            const uint32_t bb = c.nextB(prev);
            const uint64_t da = da0 + gi * 256;
            wg_fence();
            if (wide()) {
              wgmma_ss<256>(a, da, desc_hi(4096, 1024, 1) + bb, gi);
              wgmma_ss<256>(a, da + 128, desc_hi(4096, 1024, 1) + (bb + 128), 1);
            } else {
              wgmma_ss<192>(*(float(*)[96])a, da, desc_hi(2048, 512, 2) + bb, gi);
              wgmma_ss<192>(*(float(*)[96])a, da + 128, desc_hi(2048, 512, 2) + (bb + 64), 1);
            }
            wg_commit();
            wg_wait<1>();
            if (gi > 0 && !(last() && gi > 13)) c.release2(BAR_EMPTYB + prev);
            if (last() && gi >= XREL && !((gi ^ XREL) & 1)) c.release2(BAR_EMPTYX + 16 * ((gi - XREL) & 2) + 2 * ((gi - XREL) & 12));
          }
          wg_wait<0>();
          if (!last()) c.releaseLastB();
          if (last() && t >= (19 - XREL) / 2 && t < 8) { mbar_arrive(sb + xe); mbar_arrive_remote(c.rem + xe); }
        };
        auto yes = [] { return true; };
        auto no = [] { return false; };
        tile(yes, no); PROF2(pb + 13); glu<16, 32>(a, h);
        tile(yes, no); PROF2(pb + 14); glu<16, 64>(a, h);
        tile(no, no); PROF2(pb + 15); glu<12, 96>(a, h);
        const uint32_t hole = sb + SM_B + 12288 + tid_ * 16;
#pragma unroll
        for (int i = 0; i < NSPILL; i++) sts128(hole + i * BSLOT, h[96 + 4 * i], h[97 + 4 * i], h[98 + 4 * i], h[99 + 4 * i]);
        if (w == 1) asm volatile("bar.arrive 8, 256;" ::: "memory");
        tile(no, yes); PROF2(pb + 16); glu<12, 120>(a, h);
#pragma unroll
        for (int i = 0; i < NSPILL; i++) { const uint4 u = lds128(hole + i * BSLOT); h[96 + 4 * i] = u.x; h[97 + 4 * i] = u.y; h[98 + 4 * i] = u.z; h[99 + 4 * i] = u.w; }
      }
      {
        THREAD_IDS();
        float d[32];
        uint4* gt = G->obox + t;
        asm volatile("" : "+l"(gt));
        uint4* const ib = gt + 2 * 4608 + layer * 8 * INBOX;
        auto pass = [&](uint32_t s0, bool last, auto&& hook) {
          const uint64_t db = desc_hi(0, 1024, 1) + (dsb + (SM_X >> 4) + s0 * (XSLOT >> 4));
          mbar_wait_c(sb + BAR_FULLX + 8 * s0, (c.mX >> s0) & 1);
          asm volatile("bar.sync %0, 256;" ::"r"(8 + w) : "memory");
#pragma unroll
          for (int i = 0; i < 4; i++) {
            const int si = 4 * (i & 1) + (i >> 1);
            if (i > 0) mbar_wait_c(sb + BAR_FULLX + 8 * (s0 + si), (c.mX >> (s0 + si)) & 1);
            wg_fence();
#pragma unroll
            for (int k = 0; k < 9; k++) {
              const uint32_t* hk = h + 36 * i + 4 * k;
              wgmma_ra<64>(d, make_uint4(hk[0], hk[1], hk[2], hk[3]), db + (si * (XSLOT >> 4) + k * 128), last || i + k > 0);
              if (9 * i + k == PPK && !(last && w == 1)) asm volatile("bar.arrive %0, 256;" ::"r"(9 - w) : "memory");
            }
            wg_commit();
            if (i > 0) { wg_wait<1>(); c.release2(BAR_EMPTYX + 8 * (s0 + 4 * ((i - 1) & 1) + ((i - 1) >> 1))); }
            if (i == RHOOK) hook();
          }
          c.mX ^= 0x33u << s0;
        };
        PROF2(pb + 17);
#pragma unroll 1
        for (int p = 0; p < 8; p++) {
          const uint32_t s0 = 2 * (p & 1);
          pass(s0, false, [] {});
          wg_wait<0>();
          c.release2(BAR_EMPTYX + 8 * (s0 + 5));
          uint32_t pk[16];
#pragma unroll
          for (int i = 0; i < 16; i++) pk[i] = pack_bf16(d[2 * i], d[2 * i + 1]);
          if (p >= BREL && p < BREL + 5) {
            const uint32_t o = c.sB + 8 * (p - BREL);
            c.release2(BAR_EMPTYB + (o < 40 ? o : o - 40));
          }
          uint4* const dst = ib + ((j + p) & 7) * INBOX;
          if (p == 0) {
            mbar_wait_c(sb + BAR_CLR + 8 * w, 0);
#pragma unroll
            for (int k = 0; k < 8; k++) red2((uint2*)(ib + k * INBOX + 512) - t, pk[2 * k], pk[2 * k + 1]);
          } else if (p < 7) {
#pragma unroll
            for (int k = 0; k < 4; k++) red4(dst + k * 128, pk[4 * k], pk[4 * k + 1], pk[4 * k + 2], pk[4 * k + 3]);
            if (p == 6) { __syncwarp(); if (lane == 0) mbar_arrive(sb + BAR_REDDONE + 8 * w); }
          } else {
#pragma unroll
            for (int k = 0; k < 4; k++) st_relaxed4(gt + ((j + 7) & 7) * 128 + k * 1024, pk[4 * k] & ~1u, pk[4 * k + 1], pk[4 * k + 2], pk[4 * k + 3]);
          }
        }
        PROF2(pb + 18);
        const uint4 *in = ib + j * INBOX, *pin = gt + j * 128;
        const uint2* in9 = (const uint2*)(in + 512) - t;
        asm volatile("" : "+l"(in), "+l"(pin), "+l"(in9));
        const float2 r2 = lds64(sb + SM_KEEP + tid_ * 8);
        uint2 X9;
        {
          uint4 X[4];
          const uint4* box = gt + 4608;
#pragma unroll
          for (int k = 0; k < 4; k++) X[k] = ld_relaxed4(box + 256 * j + ((k & 1) + 8 * (k & 2)) * 128);
          X9 = ld_relaxed2((const uint2*)(box + (32 + (j >> 1)) * 128) + (j & 1));
          const float i0 = rcp(r2.x), i1 = rcp(r2.y);
#pragma unroll
          for (int k = 0; k < 4; k++) {
            const float f = k & 1 ? i1 : i0;
            float* e = d + 8 * (k & 2) + 2 * (k & 1);
            X[k].x ^= (lsb >> k) & 1;
            e[0] = bf_lo(X[k].x) * f; e[1] = bf_hi(X[k].x) * f; e[4] = bf_lo(X[k].y) * f; e[5] = bf_hi(X[k].y) * f;
            e[8] = bf_lo(X[k].z) * f; e[9] = bf_hi(X[k].z) * f; e[12] = bf_lo(X[k].w) * f; e[13] = bf_hi(X[k].w) * f;
          }
        }
        uint4 R[4], P[4];
        uint2 R9;
        PROF2(pb + 19);
        pass(0, true, [&] {
          mbar_wait_c(sb + BAR_RREADY + 8 * w, layer);
#pragma unroll
          for (int k = 0; k < 4; k++) R[k] = ld_relaxed4(in + k * 128);
          R9 = ld_relaxed2(in9);
#pragma unroll
          for (int k = 0; k < 4; k++) P[k] = ld_relaxed4(pin + k * 1024);
        });
        const uint32_t zero = late(sb + BAR_FULLX + 64, 0);
        while (__any_sync(0xffffffffu, (chk2(P[0].x, P[1].x, zero) | chk2(P[2].x, P[3].x, zero)) & 1)) {
#pragma unroll
          for (int k = 0; k < 4; k++) P[k] = ld_relaxed4(pin + k * 1024);
        }
#pragma unroll
        for (int k = 0; k < 4; k++) {
          const uint32_t u[4] = {hadd2(R[k].x, P[k].x), hadd2(R[k].y, P[k].y), hadd2(R[k].z, P[k].z), hadd2(R[k].w, P[k].w)};
#pragma unroll
          for (int i = 0; i < 4; i++) { v[8 * k + 2 * i] = bf_lo(u[i]); v[8 * k + 2 * i + 1] = bf_hi(u[i]); }
        }
        X9.x = chk(zero, X9.x, lsb >> 4);
        v[32] = fmaf(bf_lo(R9.x), r2.x, bf_lo(X9.x)); v[33] = fmaf(bf_hi(R9.x), r2.x, bf_hi(X9.x));
        v[34] = fmaf(bf_lo(R9.y), r2.y, bf_lo(X9.y)); v[35] = fmaf(bf_hi(R9.y), r2.y, bf_hi(X9.y));
        PROF2(pb + 20);
        wg_wait<0>();
        c.release2(BAR_EMPTYX + 40);
        PROF2(pb + 21);
#pragma unroll
        for (int i = 0; i < 32; i++) v[i] = (v[i] + d[i]) * (i & 2 ? r2.y : r2.x);
      }
      if (layer == NLAYERS - 1) break;
    }
    {
      THREAD_IDS();
      const uint32_t stg = sb + SM_B + warp * 4096;
      const uint32_t sd = stg + (lane & 15) * 128;
#pragma unroll
      for (int i = 0; i < 4; i++)
        stsm4(sd + (((2 * i + (lane >> 4)) ^ (lane & 7)) << 4), pack_bf16(v[8 * i], v[8 * i + 1]), pack_bf16(v[8 * i + 2], v[8 * i + 3]),
              pack_bf16(v[8 * i + 4], v[8 * i + 5]), pack_bf16(v[8 * i + 6], v[8 * i + 7]));
      stsm2(stg + 2048 + (lane & 15) * 16, pack_bf16(v[32], v[33]), pack_bf16(v[34], v[35]));
      fence_async_smem();
      __syncwarp();
      if (lane == 0) {
        tma_store3d(&maps.out, stg, 64 * j, w, 64 * rb + 16 * wp);
        tma_store3d(&maps.outc, stg + 2048, 512 + 8 * j, w, 64 * rb + 16 * wp);
        bulk_commit();
        if (wp == 0) st_relaxed(G->flag + 32 + 32 * j, xtag);
        bulk_wait_all();
        mbar_arrive(sb + BAR_DONE + 8 * w);
      }
      PROF(61);
    }
    __syncwarp();
    cluster_sync();
  }
}

typedef CUresult (*EncFn)(CUtensorMap*, CUtensorMapDataType, cuuint32_t, void*, const cuuint64_t*, const cuuint64_t*, const cuuint32_t*,
                          const cuuint32_t*, CUtensorMapInterleave, CUtensorMapSwizzle, CUtensorMapL2promotion, CUtensorMapFloatOOBfill);

void make_map(EncFn enc, CUtensorMap* m, const void* p, int rank, uint64_t d0, uint64_t d1, uint64_t d2, uint64_t s1, uint64_t s2, uint32_t b0,
              uint32_t b1, uint32_t b2, CUtensorMapSwizzle sw) {
  cuuint64_t gd[3] = {d0, d1, d2};
  cuuint64_t gs[2] = {s1, s2};
  cuuint32_t bd[3] = {b0, b1, b2};
  cuuint32_t es[3] = {1, 1, 1};
  enc(m, CU_TENSOR_MAP_DATA_TYPE_BFLOAT16, rank, const_cast<void*>(p), gd, gs, bd, es, CU_TENSOR_MAP_INTERLEAVE_NONE, sw,
      CU_TENSOR_MAP_L2_PROMOTION_L2_128B, CU_TENSOR_MAP_FLOAT_OOB_FILL_NONE);
}

}

extern "C" void kernel_launch(void* const* d_in, const int* in_sizes, int n_in, void* d_out, int out_size) {
  const __nv_bfloat16* x = (const __nv_bfloat16*)d_in[0];
  const char *wqkv = (const char*)d_in[1], *wo = (const char*)d_in[2], *wg = (const char*)d_in[4], *wu = (const char*)d_in[5], *wd = (const char*)d_in[6];
  static EncFn enc = nullptr;
  static Group* ws = nullptr;
  if (!enc) {
    cudaDriverEntryPointQueryResult qr;
    cudaGetDriverEntryPoint("cuTensorMapEncodeTiled", (void**)&enc, cudaEnableDefault, &qr);
    cudaGetSymbolAddress((void**)&ws, g_ws);
    cudaFuncSetAttribute(fused_kernel, cudaFuncAttributeMaxDynamicSharedMemorySize, SMEM_BYTES);
  }
  const CUtensorMapSwizzle S0 = CU_TENSOR_MAP_SWIZZLE_NONE, S64 = CU_TENSOR_MAP_SWIZZLE_64B, S128 = CU_TENSOR_MAP_SWIZZLE_128B;
  Maps m;
  make_map(enc, &m.x, x, 3, 576, 2, 1024, 1152, 2304, 64, 1, 64, S128);
  make_map(enc, &m.qm, wqkv, 3, 576, 576, 3, 3456, 1152, 64, 16, 3, S128);
  make_map(enc, &m.qc, wqkv, 3, 576, 576, 3, 3456, 1152, 8, 16, 3, S0);
  make_map(enc, &m.o, wo, 2, 576, 576, 1, 1152, 0, 64, 72, 1, S128);
  make_map(enc, &m.oc, wo, 2, 576, 576, 1, 1152, 0, 8, 144, 1, S0);
  make_map(enc, &m.g, wg, 3, 64, 576, 72, 9216, 128, 64, 32, 2, S128);
  make_map(enc, &m.u, wu, 3, 64, 576, 72, 9216, 128, 64, 32, 2, S128);
  make_map(enc, &m.g3, wg, 3, 32, 576, 144, 9216, 64, 32, 32, 3, S64);
  make_map(enc, &m.u3, wu, 3, 32, 576, 144, 9216, 64, 32, 32, 3, S64);
  make_map(enc, &m.d, wd, 2, 576, 4608, 1, 1152, 0, 64, 72, 1, S128);
  make_map(enc, &m.out, d_out, 3, 576, 2, 1024, 1152, 2304, 64, 1, 16, S128);
  make_map(enc, &m.outc, d_out, 3, 576, 2, 1024, 1152, 2304, 8, 1, 16, S0);
  fused_kernel<<<NCTA, 384, SMEM_BYTES>>>(x, ws, wqkv, wg, wu, wd, m, wo);
}
```

```cpp
#include <cuda_runtime.h>
#include <cuda_bf16.h>
#include <cuda.h>
#include <stdint.h>
#include <stddef.h>

namespace {

constexpr int D_ = 576;
constexpr int NCTA = 128;
#define NLAYERS 2
#define W_POLICY policy_evict_first
#define A_POLICY policy_evict_normal
#define OPEN 1
#define PFMODE 5
#define WWIN 4
#define WOREL -1
#define WB1 11
#define WB2 21
#define WB3 32
#define WPROBE 1
#define WPROBE2 0
#define SPEC 2
#define POLLFIRST 0
#define SUMFIRST 1
#define EARLYPOLL 1
#define LEAD 0
#define ATTBAR 0
#define GL 18
#define WOBAR 0
#define QD 0
#define QG 4
#define PFQ 1
#define XDELAY 0
#define WOH 1
#define PFSLEEP 700
#define GPCMAP 1
#define PFF 1
#define REDN 1
#define CLRSLEEP 300
#define OPENL 24
#define FG -1
#define NON8 0
#define HMUL 1
#define FCH 1
#define PPK 34
#define RHOOK 0
#define SCHEDBAR 1
#define QH 5
#define XH 3
#define XP 2
#define GSLEEP 32
#define XCH 1
#define MAPPF 1
#define XREL 8
#define WOG 13
#define BREL 1
#define FENCE1 0
#define OWNX 0
#define OWNBAR 1
#define NSPILL 4
#define REGS_C 232
#define REGS_P 40
#define STR2(x) #x
#define STR(x) STR2(x)
constexpr uint32_t SM_X = 0;
constexpr uint32_t XSLOT = 18432;
constexpr uint32_t SM_WOC = SM_X + 3 * XSLOT + 9216;
constexpr uint32_t SM_B = 147456;
constexpr uint32_t BSLOT = 16384;
constexpr uint32_t SM_KEEP = 229376;
constexpr uint32_t SM_BAR = SM_KEEP + 2048;
constexpr uint32_t BAR_FULLB = SM_BAR;
constexpr uint32_t BAR_RREADY = SM_BAR + 40;
constexpr uint32_t BAR_CLR = SM_BAR + 56;
constexpr uint32_t BAR_FULLX = SM_BAR + 72;
constexpr uint32_t BAR_EMPTYB = SM_BAR + 144;
constexpr uint32_t BAR_EMPTYX = SM_BAR + 184;
constexpr uint32_t BAR_REDDONE = SM_BAR + 248;
constexpr uint32_t BAR_DONE = SM_BAR + 264;
constexpr uint32_t SM_PROG = SM_BAR + 288;
constexpr uint32_t SMEM_BYTES = SM_BAR + 1024;

struct Maps { CUtensorMap x, qm, qc, o, oc, g, u, g3, u3, d, out, outc; };

constexpr int INBOX = 576;
struct Group {
  uint2 sum[4 * 8 * 8];
  uint4 m2[4 * 8 * 8];
  uint32_t flag[512];
  uint4 halo[8 * 160];
  uint4 obox[36 * 128];
  uint4 xbox[36 * 128];
  uint4 inbox[2][8 * INBOX];
};
__device__ __align__(1024) Group g_ws[32];
#define PROF(i)
#define PROFX(i)

#define PROF2(i) PROF(i)

template<int N> __device__ __forceinline__ void wgmma_ss(float (&d)[N / 2], uint64_t da, uint64_t db, int sc);
template<> __device__ __forceinline__ void wgmma_ss<192>(float (&d)[96], uint64_t da, uint64_t db, int sc) {
  asm volatile("{\n.reg .pred p;\nsetp.ne.b32 p, %98, 0;\n"
    "wgmma.mma_async.sync.aligned.m64n192k16.f32.bf16.bf16 {%0,%1,%2,%3,%4,%5,%6,%7,%8,%9,%10,%11,%12,%13,%14,%15,%16,%17,%18,%19,%20,%21,%22,%23,%24,%25,%26,%27,%28,%29,%30,%31,%32,%33,%34,%35,%36,%37,%38,%39,%40,%41,%42,%43,%44,%45,%46,%47,%48,%49,%50,%51,%52,%53,%54,%55,%56,%57,%58,%59,%60,%61,%62,%63,%64,%65,%66,%67,%68,%69,%70,%71,%72,%73,%74,%75,%76,%77,%78,%79,%80,%81,%82,%83,%84,%85,%86,%87,%88,%89,%90,%91,%92,%93,%94,%95}, %96, %97, p, 1, 1, 0, 1;\n}\n"
    : "+f"(d[0]),"+f"(d[1]),"+f"(d[2]),"+f"(d[3]),"+f"(d[4]),"+f"(d[5]),"+f"(d[6]),"+f"(d[7]),"+f"(d[8]),"+f"(d[9]),"+f"(d[10]),"+f"(d[11]),"+f"(d[12]),"+f"(d[13]),"+f"(d[14]),"+f"(d[15]),"+f"(d[16]),"+f"(d[17]),"+f"(d[18]),"+f"(d[19]),"+f"(d[20]),"+f"(d[21]),"+f"(d[22]),"+f"(d[23]),"+f"(d[24]),"+f"(d[25]),"+f"(d[26]),"+f"(d[27]),"+f"(d[28]),"+f"(d[29]),"+f"(d[30]),"+f"(d[31]),"+f"(d[32]),"+f"(d[33]),"+f"(d[34]),"+f"(d[35]),"+f"(d[36]),"+f"(d[37]),"+f"(d[38]),"+f"(d[39]),"+f"(d[40]),"+f"(d[41]),"+f"(d[42]),"+f"(d[43]),"+f"(d[44]),"+f"(d[45]),"+f"(d[46]),"+f"(d[47]),"+f"(d[48]),"+f"(d[49]),"+f"(d[50]),"+f"(d[51]),"+f"(d[52]),"+f"(d[53]),"+f"(d[54]),"+f"(d[55]),"+f"(d[56]),"+f"(d[57]),"+f"(d[58]),"+f"(d[59]),"+f"(d[60]),"+f"(d[61]),"+f"(d[62]),"+f"(d[63]),"+f"(d[64]),"+f"(d[65]),"+f"(d[66]),"+f"(d[67]),"+f"(d[68]),"+f"(d[69]),"+f"(d[70]),"+f"(d[71]),"+f"(d[72]),"+f"(d[73]),"+f"(d[74]),"+f"(d[75]),"+f"(d[76]),"+f"(d[77]),"+f"(d[78]),"+f"(d[79]),"+f"(d[80]),"+f"(d[81]),"+f"(d[82]),"+f"(d[83]),"+f"(d[84]),"+f"(d[85]),"+f"(d[86]),"+f"(d[87]),"+f"(d[88]),"+f"(d[89]),"+f"(d[90]),"+f"(d[91]),"+f"(d[92]),"+f"(d[93]),"+f"(d[94]),"+f"(d[95]) : "l"(da), "l"(db), "r"(sc));
}
template<> __device__ __forceinline__ void wgmma_ss<256>(float (&d)[128], uint64_t da, uint64_t db, int sc) {
  asm volatile("{\n.reg .pred p;\nsetp.ne.b32 p, %130, 0;\n"
    "wgmma.mma_async.sync.aligned.m64n256k16.f32.bf16.bf16 {%0,%1,%2,%3,%4,%5,%6,%7,%8,%9,%10,%11,%12,%13,%14,%15,%16,%17,%18,%19,%20,%21,%22,%23,%24,%25,%26,%27,%28,%29,%30,%31,%32,%33,%34,%35,%36,%37,%38,%39,%40,%41,%42,%43,%44,%45,%46,%47,%48,%49,%50,%51,%52,%53,%54,%55,%56,%57,%58,%59,%60,%61,%62,%63,%64,%65,%66,%67,%68,%69,%70,%71,%72,%73,%74,%75,%76,%77,%78,%79,%80,%81,%82,%83,%84,%85,%86,%87,%88,%89,%90,%91,%92,%93,%94,%95,%96,%97,%98,%99,%100,%101,%102,%103,%104,%105,%106,%107,%108,%109,%110,%111,%112,%113,%114,%115,%116,%117,%118,%119,%120,%121,%122,%123,%124,%125,%126,%127}, %128, %129, p, 1, 1, 0, 1;\n}\n"
    : "+f"(d[0]),"+f"(d[1]),"+f"(d[2]),"+f"(d[3]),"+f"(d[4]),"+f"(d[5]),"+f"(d[6]),"+f"(d[7]),"+f"(d[8]),"+f"(d[9]),"+f"(d[10]),"+f"(d[11]),"+f"(d[12]),"+f"(d[13]),"+f"(d[14]),"+f"(d[15]),"+f"(d[16]),"+f"(d[17]),"+f"(d[18]),"+f"(d[19]),"+f"(d[20]),"+f"(d[21]),"+f"(d[22]),"+f"(d[23]),"+f"(d[24]),"+f"(d[25]),"+f"(d[26]),"+f"(d[27]),"+f"(d[28]),"+f"(d[29]),"+f"(d[30]),"+f"(d[31]),"+f"(d[32]),"+f"(d[33]),"+f"(d[34]),"+f"(d[35]),"+f"(d[36]),"+f"(d[37]),"+f"(d[38]),"+f"(d[39]),"+f"(d[40]),"+f"(d[41]),"+f"(d[42]),"+f"(d[43]),"+f"(d[44]),"+f"(d[45]),"+f"(d[46]),"+f"(d[47]),"+f"(d[48]),"+f"(d[49]),"+f"(d[50]),"+f"(d[51]),"+f"(d[52]),"+f"(d[53]),"+f"(d[54]),"+f"(d[55]),"+f"(d[56]),"+f"(d[57]),"+f"(d[58]),"+f"(d[59]),"+f"(d[60]),"+f"(d[61]),"+f"(d[62]),"+f"(d[63]),"+f"(d[64]),"+f"(d[65]),"+f"(d[66]),"+f"(d[67]),"+f"(d[68]),"+f"(d[69]),"+f"(d[70]),"+f"(d[71]),"+f"(d[72]),"+f"(d[73]),"+f"(d[74]),"+f"(d[75]),"+f"(d[76]),"+f"(d[77]),"+f"(d[78]),"+f"(d[79]),"+f"(d[80]),"+f"(d[81]),"+f"(d[82]),"+f"(d[83]),"+f"(d[84]),"+f"(d[85]),"+f"(d[86]),"+f"(d[87]),"+f"(d[88]),"+f"(d[89]),"+f"(d[90]),"+f"(d[91]),"+f"(d[92]),"+f"(d[93]),"+f"(d[94]),"+f"(d[95]),"+f"(d[96]),"+f"(d[97]),"+f"(d[98]),"+f"(d[99]),"+f"(d[100]),"+f"(d[101]),"+f"(d[102]),"+f"(d[103]),"+f"(d[104]),"+f"(d[105]),"+f"(d[106]),"+f"(d[107]),"+f"(d[108]),"+f"(d[109]),"+f"(d[110]),"+f"(d[111]),"+f"(d[112]),"+f"(d[113]),"+f"(d[114]),"+f"(d[115]),"+f"(d[116]),"+f"(d[117]),"+f"(d[118]),"+f"(d[119]),"+f"(d[120]),"+f"(d[121]),"+f"(d[122]),"+f"(d[123]),"+f"(d[124]),"+f"(d[125]),"+f"(d[126]),"+f"(d[127]) : "l"(da), "l"(db), "r"(sc));
}
template<int N> __device__ __forceinline__ void wgmma_rs(float (&d)[N / 2], uint32_t a0, uint32_t a1, uint32_t a2, uint32_t a3, uint64_t db, int sc);
template<> __device__ __forceinline__ void wgmma_rs<8>(float (&d)[4], uint32_t a0, uint32_t a1, uint32_t a2, uint32_t a3, uint64_t db, int sc) {
  asm volatile("{\n.reg .pred p;\nsetp.ne.b32 p, %9, 0;\n"
    "wgmma.mma_async.sync.aligned.m64n8k16.f32.bf16.bf16 {%0,%1,%2,%3}, {%4,%5,%6,%7}, %8, p, 1, 1, 1;\n}\n"
    : "+f"(d[0]),"+f"(d[1]),"+f"(d[2]),"+f"(d[3]) : "r"(a0), "r"(a1), "r"(a2), "r"(a3), "l"(db), "r"(sc));
}
template<> __device__ __forceinline__ void wgmma_rs<24>(float (&d)[12], uint32_t a0, uint32_t a1, uint32_t a2, uint32_t a3, uint64_t db, int sc) {
  asm volatile("{\n.reg .pred p;\nsetp.ne.b32 p, %17, 0;\n"
    "wgmma.mma_async.sync.aligned.m64n24k16.f32.bf16.bf16 {%0,%1,%2,%3,%4,%5,%6,%7,%8,%9,%10,%11}, {%12,%13,%14,%15}, %16, p, 1, 1, 1;\n}\n"
    : "+f"(d[0]),"+f"(d[1]),"+f"(d[2]),"+f"(d[3]),"+f"(d[4]),"+f"(d[5]),"+f"(d[6]),"+f"(d[7]),"+f"(d[8]),"+f"(d[9]),"+f"(d[10]),"+f"(d[11]) : "r"(a0), "r"(a1), "r"(a2), "r"(a3), "l"(db), "r"(sc));
}
template<> __device__ __forceinline__ void wgmma_rs<64>(float (&d)[32], uint32_t a0, uint32_t a1, uint32_t a2, uint32_t a3, uint64_t db, int sc) {
  asm volatile("{\n.reg .pred p;\nsetp.ne.b32 p, %37, 0;\n"
    "wgmma.mma_async.sync.aligned.m64n64k16.f32.bf16.bf16 {%0,%1,%2,%3,%4,%5,%6,%7,%8,%9,%10,%11,%12,%13,%14,%15,%16,%17,%18,%19,%20,%21,%22,%23,%24,%25,%26,%27,%28,%29,%30,%31}, {%32,%33,%34,%35}, %36, p, 1, 1, 1;\n}\n"
    : "+f"(d[0]),"+f"(d[1]),"+f"(d[2]),"+f"(d[3]),"+f"(d[4]),"+f"(d[5]),"+f"(d[6]),"+f"(d[7]),"+f"(d[8]),"+f"(d[9]),"+f"(d[10]),"+f"(d[11]),"+f"(d[12]),"+f"(d[13]),"+f"(d[14]),"+f"(d[15]),"+f"(d[16]),"+f"(d[17]),"+f"(d[18]),"+f"(d[19]),"+f"(d[20]),"+f"(d[21]),"+f"(d[22]),"+f"(d[23]),"+f"(d[24]),"+f"(d[25]),"+f"(d[26]),"+f"(d[27]),"+f"(d[28]),"+f"(d[29]),"+f"(d[30]),"+f"(d[31]) : "r"(a0), "r"(a1), "r"(a2), "r"(a3), "l"(db), "r"(sc));
}
template<> __device__ __forceinline__ void wgmma_rs<192>(float (&d)[96], uint32_t a0, uint32_t a1, uint32_t a2, uint32_t a3, uint64_t db, int sc) {
  asm volatile("{\n.reg .pred p;\nsetp.ne.b32 p, %101, 0;\n"
    "wgmma.mma_async.sync.aligned.m64n192k16.f32.bf16.bf16 {%0,%1,%2,%3,%4,%5,%6,%7,%8,%9,%10,%11,%12,%13,%14,%15,%16,%17,%18,%19,%20,%21,%22,%23,%24,%25,%26,%27,%28,%29,%30,%31,%32,%33,%34,%35,%36,%37,%38,%39,%40,%41,%42,%43,%44,%45,%46,%47,%48,%49,%50,%51,%52,%53,%54,%55,%56,%57,%58,%59,%60,%61,%62,%63,%64,%65,%66,%67,%68,%69,%70,%71,%72,%73,%74,%75,%76,%77,%78,%79,%80,%81,%82,%83,%84,%85,%86,%87,%88,%89,%90,%91,%92,%93,%94,%95}, {%96,%97,%98,%99}, %100, p, 1, 1, 1;\n}\n"
    : "+f"(d[0]),"+f"(d[1]),"+f"(d[2]),"+f"(d[3]),"+f"(d[4]),"+f"(d[5]),"+f"(d[6]),"+f"(d[7]),"+f"(d[8]),"+f"(d[9]),"+f"(d[10]),"+f"(d[11]),"+f"(d[12]),"+f"(d[13]),"+f"(d[14]),"+f"(d[15]),"+f"(d[16]),"+f"(d[17]),"+f"(d[18]),"+f"(d[19]),"+f"(d[20]),"+f"(d[21]),"+f"(d[22]),"+f"(d[23]),"+f"(d[24]),"+f"(d[25]),"+f"(d[26]),"+f"(d[27]),"+f"(d[28]),"+f"(d[29]),"+f"(d[30]),"+f"(d[31]),"+f"(d[32]),"+f"(d[33]),"+f"(d[34]),"+f"(d[35]),"+f"(d[36]),"+f"(d[37]),"+f"(d[38]),"+f"(d[39]),"+f"(d[40]),"+f"(d[41]),"+f"(d[42]),"+f"(d[43]),"+f"(d[44]),"+f"(d[45]),"+f"(d[46]),"+f"(d[47]),"+f"(d[48]),"+f"(d[49]),"+f"(d[50]),"+f"(d[51]),"+f"(d[52]),"+f"(d[53]),"+f"(d[54]),"+f"(d[55]),"+f"(d[56]),"+f"(d[57]),"+f"(d[58]),"+f"(d[59]),"+f"(d[60]),"+f"(d[61]),"+f"(d[62]),"+f"(d[63]),"+f"(d[64]),"+f"(d[65]),"+f"(d[66]),"+f"(d[67]),"+f"(d[68]),"+f"(d[69]),"+f"(d[70]),"+f"(d[71]),"+f"(d[72]),"+f"(d[73]),"+f"(d[74]),"+f"(d[75]),"+f"(d[76]),"+f"(d[77]),"+f"(d[78]),"+f"(d[79]),"+f"(d[80]),"+f"(d[81]),"+f"(d[82]),"+f"(d[83]),"+f"(d[84]),"+f"(d[85]),"+f"(d[86]),"+f"(d[87]),"+f"(d[88]),"+f"(d[89]),"+f"(d[90]),"+f"(d[91]),"+f"(d[92]),"+f"(d[93]),"+f"(d[94]),"+f"(d[95]) : "r"(a0), "r"(a1), "r"(a2), "r"(a3), "l"(db), "r"(sc));
}
template<> __device__ __forceinline__ void wgmma_rs<256>(float (&d)[128], uint32_t a0, uint32_t a1, uint32_t a2, uint32_t a3, uint64_t db, int sc) {
  asm volatile("{\n.reg .pred p;\nsetp.ne.b32 p, %133, 0;\n"
    "wgmma.mma_async.sync.aligned.m64n256k16.f32.bf16.bf16 {%0,%1,%2,%3,%4,%5,%6,%7,%8,%9,%10,%11,%12,%13,%14,%15,%16,%17,%18,%19,%20,%21,%22,%23,%24,%25,%26,%27,%28,%29,%30,%31,%32,%33,%34,%35,%36,%37,%38,%39,%40,%41,%42,%43,%44,%45,%46,%47,%48,%49,%50,%51,%52,%53,%54,%55,%56,%57,%58,%59,%60,%61,%62,%63,%64,%65,%66,%67,%68,%69,%70,%71,%72,%73,%74,%75,%76,%77,%78,%79,%80,%81,%82,%83,%84,%85,%86,%87,%88,%89,%90,%91,%92,%93,%94,%95,%96,%97,%98,%99,%100,%101,%102,%103,%104,%105,%106,%107,%108,%109,%110,%111,%112,%113,%114,%115,%116,%117,%118,%119,%120,%121,%122,%123,%124,%125,%126,%127}, {%128,%129,%130,%131}, %132, p, 1, 1, 1;\n}\n"
    : "+f"(d[0]),"+f"(d[1]),"+f"(d[2]),"+f"(d[3]),"+f"(d[4]),"+f"(d[5]),"+f"(d[6]),"+f"(d[7]),"+f"(d[8]),"+f"(d[9]),"+f"(d[10]),"+f"(d[11]),"+f"(d[12]),"+f"(d[13]),"+f"(d[14]),"+f"(d[15]),"+f"(d[16]),"+f"(d[17]),"+f"(d[18]),"+f"(d[19]),"+f"(d[20]),"+f"(d[21]),"+f"(d[22]),"+f"(d[23]),"+f"(d[24]),"+f"(d[25]),"+f"(d[26]),"+f"(d[27]),"+f"(d[28]),"+f"(d[29]),"+f"(d[30]),"+f"(d[31]),"+f"(d[32]),"+f"(d[33]),"+f"(d[34]),"+f"(d[35]),"+f"(d[36]),"+f"(d[37]),"+f"(d[38]),"+f"(d[39]),"+f"(d[40]),"+f"(d[41]),"+f"(d[42]),"+f"(d[43]),"+f"(d[44]),"+f"(d[45]),"+f"(d[46]),"+f"(d[47]),"+f"(d[48]),"+f"(d[49]),"+f"(d[50]),"+f"(d[51]),"+f"(d[52]),"+f"(d[53]),"+f"(d[54]),"+f"(d[55]),"+f"(d[56]),"+f"(d[57]),"+f"(d[58]),"+f"(d[59]),"+f"(d[60]),"+f"(d[61]),"+f"(d[62]),"+f"(d[63]),"+f"(d[64]),"+f"(d[65]),"+f"(d[66]),"+f"(d[67]),"+f"(d[68]),"+f"(d[69]),"+f"(d[70]),"+f"(d[71]),"+f"(d[72]),"+f"(d[73]),"+f"(d[74]),"+f"(d[75]),"+f"(d[76]),"+f"(d[77]),"+f"(d[78]),"+f"(d[79]),"+f"(d[80]),"+f"(d[81]),"+f"(d[82]),"+f"(d[83]),"+f"(d[84]),"+f"(d[85]),"+f"(d[86]),"+f"(d[87]),"+f"(d[88]),"+f"(d[89]),"+f"(d[90]),"+f"(d[91]),"+f"(d[92]),"+f"(d[93]),"+f"(d[94]),"+f"(d[95]),"+f"(d[96]),"+f"(d[97]),"+f"(d[98]),"+f"(d[99]),"+f"(d[100]),"+f"(d[101]),"+f"(d[102]),"+f"(d[103]),"+f"(d[104]),"+f"(d[105]),"+f"(d[106]),"+f"(d[107]),"+f"(d[108]),"+f"(d[109]),"+f"(d[110]),"+f"(d[111]),"+f"(d[112]),"+f"(d[113]),"+f"(d[114]),"+f"(d[115]),"+f"(d[116]),"+f"(d[117]),"+f"(d[118]),"+f"(d[119]),"+f"(d[120]),"+f"(d[121]),"+f"(d[122]),"+f"(d[123]),"+f"(d[124]),"+f"(d[125]),"+f"(d[126]),"+f"(d[127]) : "r"(a0), "r"(a1), "r"(a2), "r"(a3), "l"(db), "r"(sc));
}
template<int N> __device__ __forceinline__ void wgmma_rsz(float (&d)[N / 2], uint32_t a0, uint32_t a1, uint32_t a2, uint32_t a3, uint64_t db);
template<> __device__ __forceinline__ void wgmma_rsz<8>(float (&d)[4], uint32_t a0, uint32_t a1, uint32_t a2, uint32_t a3, uint64_t db) {
  asm volatile("{\n.reg .pred p;\nsetp.ne.b32 p, 0, 0;\n"
    "wgmma.mma_async.sync.aligned.m64n8k16.f32.bf16.bf16 {%0,%1,%2,%3}, {%4,%5,%6,%7}, %8, p, 1, 1, 1;\n}\n"
    : "=f"(d[0]),"=f"(d[1]),"=f"(d[2]),"=f"(d[3]) : "r"(a0), "r"(a1), "r"(a2), "r"(a3), "l"(db));
}
template<> __device__ __forceinline__ void wgmma_rsz<24>(float (&d)[12], uint32_t a0, uint32_t a1, uint32_t a2, uint32_t a3, uint64_t db) {
  asm volatile("{\n.reg .pred p;\nsetp.ne.b32 p, 0, 0;\n"
    "wgmma.mma_async.sync.aligned.m64n24k16.f32.bf16.bf16 {%0,%1,%2,%3,%4,%5,%6,%7,%8,%9,%10,%11}, {%12,%13,%14,%15}, %16, p, 1, 1, 1;\n}\n"
    : "=f"(d[0]),"=f"(d[1]),"=f"(d[2]),"=f"(d[3]),"=f"(d[4]),"=f"(d[5]),"=f"(d[6]),"=f"(d[7]),"=f"(d[8]),"=f"(d[9]),"=f"(d[10]),"=f"(d[11]) : "r"(a0), "r"(a1), "r"(a2), "r"(a3), "l"(db));
}
template<> __device__ __forceinline__ void wgmma_rsz<64>(float (&d)[32], uint32_t a0, uint32_t a1, uint32_t a2, uint32_t a3, uint64_t db) {
  asm volatile("{\n.reg .pred p;\nsetp.ne.b32 p, 0, 0;\n"
    "wgmma.mma_async.sync.aligned.m64n64k16.f32.bf16.bf16 {%0,%1,%2,%3,%4,%5,%6,%7,%8,%9,%10,%11,%12,%13,%14,%15,%16,%17,%18,%19,%20,%21,%22,%23,%24,%25,%26,%27,%28,%29,%30,%31}, {%32,%33,%34,%35}, %36, p, 1, 1, 1;\n}\n"
    : "=f"(d[0]),"=f"(d[1]),"=f"(d[2]),"=f"(d[3]),"=f"(d[4]),"=f"(d[5]),"=f"(d[6]),"=f"(d[7]),"=f"(d[8]),"=f"(d[9]),"=f"(d[10]),"=f"(d[11]),"=f"(d[12]),"=f"(d[13]),"=f"(d[14]),"=f"(d[15]),"=f"(d[16]),"=f"(d[17]),"=f"(d[18]),"=f"(d[19]),"=f"(d[20]),"=f"(d[21]),"=f"(d[22]),"=f"(d[23]),"=f"(d[24]),"=f"(d[25]),"=f"(d[26]),"=f"(d[27]),"=f"(d[28]),"=f"(d[29]),"=f"(d[30]),"=f"(d[31]) : "r"(a0), "r"(a1), "r"(a2), "r"(a3), "l"(db));
}
template<> __device__ __forceinline__ void wgmma_rsz<192>(float (&d)[96], uint32_t a0, uint32_t a1, uint32_t a2, uint32_t a3, uint64_t db) {
  asm volatile("{\n.reg .pred p;\nsetp.ne.b32 p, 0, 0;\n"
    "wgmma.mma_async.sync.aligned.m64n192k16.f32.bf16.bf16 {%0,%1,%2,%3,%4,%5,%6,%7,%8,%9,%10,%11,%12,%13,%14,%15,%16,%17,%18,%19,%20,%21,%22,%23,%24,%25,%26,%27,%28,%29,%30,%31,%32,%33,%34,%35,%36,%37,%38,%39,%40,%41,%42,%43,%44,%45,%46,%47,%48,%49,%50,%51,%52,%53,%54,%55,%56,%57,%58,%59,%60,%61,%62,%63,%64,%65,%66,%67,%68,%69,%70,%71,%72,%73,%74,%75,%76,%77,%78,%79,%80,%81,%82,%83,%84,%85,%86,%87,%88,%89,%90,%91,%92,%93,%94,%95}, {%96,%97,%98,%99}, %100, p, 1, 1, 1;\n}\n"
    : "=f"(d[0]),"=f"(d[1]),"=f"(d[2]),"=f"(d[3]),"=f"(d[4]),"=f"(d[5]),"=f"(d[6]),"=f"(d[7]),"=f"(d[8]),"=f"(d[9]),"=f"(d[10]),"=f"(d[11]),"=f"(d[12]),"=f"(d[13]),"=f"(d[14]),"=f"(d[15]),"=f"(d[16]),"=f"(d[17]),"=f"(d[18]),"=f"(d[19]),"=f"(d[20]),"=f"(d[21]),"=f"(d[22]),"=f"(d[23]),"=f"(d[24]),"=f"(d[25]),"=f"(d[26]),"=f"(d[27]),"=f"(d[28]),"=f"(d[29]),"=f"(d[30]),"=f"(d[31]),"=f"(d[32]),"=f"(d[33]),"=f"(d[34]),"=f"(d[35]),"=f"(d[36]),"=f"(d[37]),"=f"(d[38]),"=f"(d[39]),"=f"(d[40]),"=f"(d[41]),"=f"(d[42]),"=f"(d[43]),"=f"(d[44]),"=f"(d[45]),"=f"(d[46]),"=f"(d[47]),"=f"(d[48]),"=f"(d[49]),"=f"(d[50]),"=f"(d[51]),"=f"(d[52]),"=f"(d[53]),"=f"(d[54]),"=f"(d[55]),"=f"(d[56]),"=f"(d[57]),"=f"(d[58]),"=f"(d[59]),"=f"(d[60]),"=f"(d[61]),"=f"(d[62]),"=f"(d[63]),"=f"(d[64]),"=f"(d[65]),"=f"(d[66]),"=f"(d[67]),"=f"(d[68]),"=f"(d[69]),"=f"(d[70]),"=f"(d[71]),"=f"(d[72]),"=f"(d[73]),"=f"(d[74]),"=f"(d[75]),"=f"(d[76]),"=f"(d[77]),"=f"(d[78]),"=f"(d[79]),"=f"(d[80]),"=f"(d[81]),"=f"(d[82]),"=f"(d[83]),"=f"(d[84]),"=f"(d[85]),"=f"(d[86]),"=f"(d[87]),"=f"(d[88]),"=f"(d[89]),"=f"(d[90]),"=f"(d[91]),"=f"(d[92]),"=f"(d[93]),"=f"(d[94]),"=f"(d[95]) : "r"(a0), "r"(a1), "r"(a2), "r"(a3), "l"(db));
}
template<> __device__ __forceinline__ void wgmma_rsz<256>(float (&d)[128], uint32_t a0, uint32_t a1, uint32_t a2, uint32_t a3, uint64_t db) {
  asm volatile("{\n.reg .pred p;\nsetp.ne.b32 p, 0, 0;\n"
    "wgmma.mma_async.sync.aligned.m64n256k16.f32.bf16.bf16 {%0,%1,%2,%3,%4,%5,%6,%7,%8,%9,%10,%11,%12,%13,%14,%15,%16,%17,%18,%19,%20,%21,%22,%23,%24,%25,%26,%27,%28,%29,%30,%31,%32,%33,%34,%35,%36,%37,%38,%39,%40,%41,%42,%43,%44,%45,%46,%47,%48,%49,%50,%51,%52,%53,%54,%55,%56,%57,%58,%59,%60,%61,%62,%63,%64,%65,%66,%67,%68,%69,%70,%71,%72,%73,%74,%75,%76,%77,%78,%79,%80,%81,%82,%83,%84,%85,%86,%87,%88,%89,%90,%91,%92,%93,%94,%95,%96,%97,%98,%99,%100,%101,%102,%103,%104,%105,%106,%107,%108,%109,%110,%111,%112,%113,%114,%115,%116,%117,%118,%119,%120,%121,%122,%123,%124,%125,%126,%127}, {%128,%129,%130,%131}, %132, p, 1, 1, 1;\n}\n"
    : "=f"(d[0]),"=f"(d[1]),"=f"(d[2]),"=f"(d[3]),"=f"(d[4]),"=f"(d[5]),"=f"(d[6]),"=f"(d[7]),"=f"(d[8]),"=f"(d[9]),"=f"(d[10]),"=f"(d[11]),"=f"(d[12]),"=f"(d[13]),"=f"(d[14]),"=f"(d[15]),"=f"(d[16]),"=f"(d[17]),"=f"(d[18]),"=f"(d[19]),"=f"(d[20]),"=f"(d[21]),"=f"(d[22]),"=f"(d[23]),"=f"(d[24]),"=f"(d[25]),"=f"(d[26]),"=f"(d[27]),"=f"(d[28]),"=f"(d[29]),"=f"(d[30]),"=f"(d[31]),"=f"(d[32]),"=f"(d[33]),"=f"(d[34]),"=f"(d[35]),"=f"(d[36]),"=f"(d[37]),"=f"(d[38]),"=f"(d[39]),"=f"(d[40]),"=f"(d[41]),"=f"(d[42]),"=f"(d[43]),"=f"(d[44]),"=f"(d[45]),"=f"(d[46]),"=f"(d[47]),"=f"(d[48]),"=f"(d[49]),"=f"(d[50]),"=f"(d[51]),"=f"(d[52]),"=f"(d[53]),"=f"(d[54]),"=f"(d[55]),"=f"(d[56]),"=f"(d[57]),"=f"(d[58]),"=f"(d[59]),"=f"(d[60]),"=f"(d[61]),"=f"(d[62]),"=f"(d[63]),"=f"(d[64]),"=f"(d[65]),"=f"(d[66]),"=f"(d[67]),"=f"(d[68]),"=f"(d[69]),"=f"(d[70]),"=f"(d[71]),"=f"(d[72]),"=f"(d[73]),"=f"(d[74]),"=f"(d[75]),"=f"(d[76]),"=f"(d[77]),"=f"(d[78]),"=f"(d[79]),"=f"(d[80]),"=f"(d[81]),"=f"(d[82]),"=f"(d[83]),"=f"(d[84]),"=f"(d[85]),"=f"(d[86]),"=f"(d[87]),"=f"(d[88]),"=f"(d[89]),"=f"(d[90]),"=f"(d[91]),"=f"(d[92]),"=f"(d[93]),"=f"(d[94]),"=f"(d[95]),"=f"(d[96]),"=f"(d[97]),"=f"(d[98]),"=f"(d[99]),"=f"(d[100]),"=f"(d[101]),"=f"(d[102]),"=f"(d[103]),"=f"(d[104]),"=f"(d[105]),"=f"(d[106]),"=f"(d[107]),"=f"(d[108]),"=f"(d[109]),"=f"(d[110]),"=f"(d[111]),"=f"(d[112]),"=f"(d[113]),"=f"(d[114]),"=f"(d[115]),"=f"(d[116]),"=f"(d[117]),"=f"(d[118]),"=f"(d[119]),"=f"(d[120]),"=f"(d[121]),"=f"(d[122]),"=f"(d[123]),"=f"(d[124]),"=f"(d[125]),"=f"(d[126]),"=f"(d[127]) : "r"(a0), "r"(a1), "r"(a2), "r"(a3), "l"(db));
}
template<int N> __device__ __forceinline__ void wgmma_ra(float (&d)[N / 2], const uint4& a, uint64_t db, bool acc) {
  if (acc) wgmma_rs<N>(d, a.x, a.y, a.z, a.w, db, 1); else wgmma_rsz<N>(d, a.x, a.y, a.z, a.w, db);
}

__device__ __forceinline__ uint32_t smem_u32(const void* p) { return (uint32_t)__cvta_generic_to_shared(p); }
__device__ __forceinline__ void mbar_init(uint32_t bar, uint32_t cnt) { asm volatile("mbarrier.init.shared::cta.b64 [%0], %1;" ::"r"(bar), "r"(cnt)); }
__device__ __forceinline__ void mbar_expect_tx(uint32_t bar, uint32_t bytes) { asm volatile("mbarrier.arrive.expect_tx.shared::cta.b64 _, [%0], %1;" ::"r"(bar), "r"(bytes) : "memory"); }
__device__ __forceinline__ void mbar_arrive(uint32_t bar) { asm volatile("mbarrier.arrive.shared::cta.b64 _, [%0];" ::"r"(bar) : "memory"); }
__device__ __forceinline__ void mbar_arrive_remote(uint32_t rbar) { asm volatile("mbarrier.arrive.shared::cluster.b64 _, [%0];" ::"r"(rbar) : "memory"); }
__device__ __forceinline__ void mbar_wait(uint32_t bar, uint32_t parity) {
  asm volatile(
      "{\n.reg .pred p;\n.reg .u32 c;\nmov.u32 c, 0;\nLAB_WAIT:\nmbarrier.try_wait.parity.shared::cta.b64 p, [%0], %1;\n@p bra DONE;\n"
      "add.u32 c, c, 1;\nsetp.lt.u32 p, c, 1000000;\n@p bra LAB_WAIT;\ntrap;\nDONE:\n}\n" ::"r"(bar), "r"(parity) : "memory");
}
__device__ __forceinline__ void mbar_wait_c(uint32_t bar, uint32_t parity) {
  asm volatile("{\n.reg .pred p;\nLAB_WAIT:\nmbarrier.try_wait.parity.shared::cta.b64 p, [%0], %1;\n@!p bra LAB_WAIT;\n}\n" ::"r"(bar), "r"(parity) : "memory");
}
__device__ __forceinline__ uint32_t late(uint32_t bar, uint32_t v) {
  uint32_t r;
  asm volatile("{\n.reg .pred p;\nmbarrier.test_wait.parity.shared::cta.b64 p, [%1], 0;\nselp.b32 %0, %2, %1, p;\n}\n" : "=r"(r) : "r"(bar), "r"(v) : "memory");
  return r;
}
__device__ __forceinline__ void wtma2d(uint32_t dst, const CUtensorMap* m, int c0, int c1, uint32_t bar, uint64_t pol) {
  asm volatile("cp.async.bulk.tensor.2d.shared::cluster.global.mbarrier::complete_tx::bytes.multicast::cluster.L2::cache_hint [%0], [%1, {%3, %4}], [%2], %5, %6;"
               ::"r"(dst), "l"(m), "r"(bar), "r"(c0), "r"(c1), "h"((uint16_t)3), "l"(pol) : "memory");
}
__device__ __forceinline__ void wtma3d(uint32_t dst, const CUtensorMap* m, int c0, int c1, int c2, uint32_t bar, uint64_t pol) {
  asm volatile("cp.async.bulk.tensor.3d.shared::cluster.global.mbarrier::complete_tx::bytes.multicast::cluster.L2::cache_hint [%0], [%1, {%3, %4, %5}], [%2], %6, %7;"
               ::"r"(dst), "l"(m), "r"(bar), "r"(c0), "r"(c1), "r"(c2), "h"((uint16_t)3), "l"(pol) : "memory");
}
__device__ __forceinline__ void tma3d(uint32_t dst, const CUtensorMap* m, int c0, int c1, int c2, uint32_t bar) {
  asm volatile("cp.async.bulk.tensor.3d.shared::cluster.global.mbarrier::complete_tx::bytes [%0], [%1, {%3, %4, %5}], [%2];"
               ::"r"(dst), "l"(m), "r"(bar), "r"(c0), "r"(c1), "r"(c2) : "memory");
}
__device__ __forceinline__ void tma_store3d(const CUtensorMap* m, uint32_t src, int c0, int c1, int c2) {
  asm volatile("cp.async.bulk.tensor.3d.global.shared::cta.bulk_group [%0, {%2, %3, %4}], [%1];" ::"l"(m), "r"(src), "r"(c0), "r"(c1), "r"(c2) : "memory");
}
__device__ __forceinline__ void prefetch_l2(const void* p, uint32_t bytes) { asm volatile("cp.async.bulk.prefetch.L2.global [%0], %1;" ::"l"(p), "r"(bytes) : "memory"); }
__device__ __forceinline__ uint64_t policy_evict_first() { uint64_t p; asm volatile("createpolicy.fractional.L2::evict_first.b64 %0, 1.0;" : "=l"(p)); return p; }
__device__ __forceinline__ uint64_t policy_evict_normal() { uint64_t p; asm volatile("createpolicy.fractional.L2::evict_normal.b64 %0, 1.0;" : "=l"(p)); return p; }
__device__ __forceinline__ void bulk_commit() { asm volatile("cp.async.bulk.commit_group;" ::: "memory"); }
__device__ __forceinline__ void bulk_wait_all() { asm volatile("cp.async.bulk.wait_group 0;" ::: "memory"); }
__device__ __forceinline__ void fence_async_smem() { asm volatile("fence.proxy.async.shared::cta;" ::: "memory"); }
__device__ __forceinline__ bool elect_one() {
  uint32_t p;
  asm volatile("{\n.reg .pred P;\nelect.sync _|P, 0xffffffff;\nselp.u32 %0, 1, 0, P;\n}\n" : "=r"(p));
  return p;
}
__device__ __forceinline__ void wg_fence() { asm volatile("wgmma.fence.sync.aligned;" ::: "memory"); }
__device__ __forceinline__ void wg_commit() { asm volatile("wgmma.commit_group.sync.aligned;" ::: "memory"); }
template <int n> __device__ __forceinline__ void wg_wait() { asm volatile("wgmma.wait_group.sync.aligned %0;" ::"n"(n) : "memory"); }
__device__ __forceinline__ void wg_bar(int w) { asm volatile("bar.sync %0, 128;" ::"r"(w + 1) : "memory"); }
__device__ __forceinline__ void cluster_sync() { asm volatile("barrier.cluster.arrive.relaxed.aligned;\nbarrier.cluster.wait.aligned;" ::: "memory"); }
__device__ __forceinline__ constexpr uint64_t desc_hi(uint32_t lbo, uint32_t sbo, int sw) {
  return ((uint64_t)(lbo >> 4) << 16) | ((uint64_t)(sbo >> 4) << 32) | ((uint64_t)sw << 62);
}
__device__ __forceinline__ void fence_gpu() { asm volatile("fence.acq_rel.gpu;" ::: "memory"); }
__device__ __forceinline__ uint32_t ld_relaxed(const uint32_t* p) { uint32_t v; asm volatile("ld.relaxed.gpu.global.u32 %0, [%1];" : "=r"(v) : "l"(p) : "memory"); return v; }
__device__ __forceinline__ uint4 ld_relaxed4(const uint4* p) {
  uint4 v; asm volatile("ld.relaxed.gpu.global.v4.u32 {%0,%1,%2,%3}, [%4];" : "=r"(v.x), "=r"(v.y), "=r"(v.z), "=r"(v.w) : "l"(p) : "memory"); return v;
}
__device__ __forceinline__ uint2 ld_relaxed2(const uint2* p) {
  uint2 v; asm volatile("ld.relaxed.gpu.global.v2.u32 {%0,%1}, [%2];" : "=r"(v.x), "=r"(v.y) : "l"(p) : "memory"); return v;
}
__device__ __forceinline__ void st_relaxed(uint32_t* p, uint32_t a) { asm volatile("st.relaxed.gpu.global.u32 [%0], %1;" ::"l"(p), "r"(a) : "memory"); }
__device__ __forceinline__ void st_relaxed4(uint4* p, uint32_t a, uint32_t b, uint32_t c, uint32_t d) {
  asm volatile("st.relaxed.gpu.global.v4.u32 [%0], {%1,%2,%3,%4};" ::"l"(p), "r"(a), "r"(b), "r"(c), "r"(d) : "memory");
}
__device__ __forceinline__ void st_relaxed2(uint2* p, uint32_t a, uint32_t b) {
  asm volatile("st.relaxed.gpu.global.v2.u32 [%0], {%1,%2};" ::"l"(p), "r"(a), "r"(b) : "memory");
}
__device__ __forceinline__ void red4(uint4* p, uint32_t a, uint32_t b, uint32_t c, uint32_t d) {
  asm volatile("red.relaxed.gpu.global.add.noftz.v4.bf16x2 [%0], {%1,%2,%3,%4};" ::"l"(p), "r"(a), "r"(b), "r"(c), "r"(d) : "memory");
}
__device__ __forceinline__ void red2(uint2* p, uint32_t a, uint32_t b) {
  asm volatile("red.relaxed.gpu.global.add.noftz.v2.bf16x2 [%0], {%1,%2};" ::"l"(p), "r"(a), "r"(b) : "memory");
}
constexpr int SPIN_MAX = 1 << 21;
__device__ __forceinline__ uint32_t pack_bf16(float lo, float hi) { uint32_t r; asm("cvt.rn.bf16x2.f32 %0, %1, %2;" : "=r"(r) : "f"(hi), "f"(lo)); return r; }
__device__ __forceinline__ float bf_lo(uint32_t v) { return __uint_as_float(v << 16); }
__device__ __forceinline__ float bf_hi(uint32_t v) { return __uint_as_float(v & 0xffff0000u); }
__device__ __forceinline__ float2 lds64(uint32_t a) { float2 v; asm volatile("ld.shared.v2.f32 {%0,%1}, [%2];" : "=f"(v.x), "=f"(v.y) : "r"(a)); return v; }
__device__ __forceinline__ void sts64f(uint32_t a, float x, float y) { asm volatile("st.shared.v2.f32 [%0], {%1,%2};" ::"r"(a), "f"(x), "f"(y) : "memory"); }
__device__ __forceinline__ void sts32(uint32_t a, uint32_t x) { asm volatile("st.volatile.shared.b32 [%0], %1;" ::"r"(a), "r"(x) : "memory"); }
__device__ __forceinline__ void gate(uint32_t a, int need) {
#pragma unroll 1
  for (int it = 0; it < SPIN_MAX; it++) {
    int v; asm volatile("ld.volatile.shared.b32 %0, [%1];" : "=r"(v) : "r"(a) : "memory");
    if (v >= need) break;
    if (GSLEEP) __nanosleep(GSLEEP);
  }
}
__device__ __forceinline__ void sts128(uint32_t a, uint32_t x, uint32_t y, uint32_t z, uint32_t u) { asm volatile("st.shared.v4.b32 [%0], {%1,%2,%3,%4};" ::"r"(a), "r"(x), "r"(y), "r"(z), "r"(u) : "memory"); }
__device__ __forceinline__ uint4 lds128(uint32_t a) { uint4 v; asm volatile("ld.shared.v4.u32 {%0,%1,%2,%3}, [%4];" : "=r"(v.x), "=r"(v.y), "=r"(v.z), "=r"(v.w) : "r"(a) : "memory"); return v; }
__device__ __forceinline__ uint32_t hmul2(uint32_t a, uint32_t b) { uint32_t r; asm("mul.rn.bf16x2 %0, %1, %2;" : "=r"(r) : "r"(a), "r"(b)); return r; }
__device__ __forceinline__ uint32_t hadd2(uint32_t a, uint32_t b) { uint32_t r; asm("add.rn.bf16x2 %0, %1, %2;" : "=r"(r) : "r"(a), "r"(b)); return r; }
__device__ __forceinline__ void stsm4(uint32_t a, uint32_t r0, uint32_t r1, uint32_t r2, uint32_t r3) {
  asm volatile("stmatrix.sync.aligned.m8n8.x4.shared.b16 [%0], {%1,%2,%3,%4};" ::"r"(a), "r"(r0), "r"(r1), "r"(r2), "r"(r3) : "memory");
}
__device__ __forceinline__ void stsm2(uint32_t a, uint32_t r0, uint32_t r1) {
  asm volatile("stmatrix.sync.aligned.m8n8.x2.shared.b16 [%0], {%1,%2};" ::"r"(a), "r"(r0), "r"(r1) : "memory");
}
__device__ __forceinline__ uint4 ldsm4(uint32_t a) {
  uint4 r; asm volatile("ldmatrix.sync.aligned.m8n8.x4.shared.b16 {%0,%1,%2,%3}, [%4];" : "=r"(r.x), "=r"(r.y), "=r"(r.z), "=r"(r.w) : "r"(a) : "memory"); return r;
}
__device__ __forceinline__ uint32_t movm(uint32_t a) { uint32_t r; asm("movmatrix.sync.aligned.m8n8.trans.b16 %0, %1;" : "=r"(r) : "r"(a)); return r; }
__device__ __forceinline__ void mma16816z(float (&d)[4], uint32_t a0, uint32_t a1, uint32_t a2, uint32_t a3, uint32_t b0, uint32_t b1) {
  asm("mma.sync.aligned.m16n8k16.row.col.f32.bf16.bf16.f32 {%0,%1,%2,%3}, {%4,%5,%6,%7}, {%8,%9}, {%10,%10,%10,%10};"
      : "=f"(d[0]), "=f"(d[1]), "=f"(d[2]), "=f"(d[3]) : "r"(a0), "r"(a1), "r"(a2), "r"(a3), "r"(b0), "r"(b1), "f"(0.f));
}
__device__ __forceinline__ void mma16816(float (&d)[4], const uint4& a, uint32_t b) {
  asm("mma.sync.aligned.m16n8k16.row.col.f32.bf16.bf16.f32 {%0,%1,%2,%3}, {%4,%5,%6,%7}, {%8,%8}, {%0,%1,%2,%3};"
      : "+f"(d[0]), "+f"(d[1]), "+f"(d[2]), "+f"(d[3]) : "r"(a.x), "r"(a.y), "r"(a.z), "r"(a.w), "r"(b));
}
__device__ __forceinline__ void mma1688(float (&d)[4], uint32_t a0, uint32_t a1, uint32_t b0) {
  asm("mma.sync.aligned.m16n8k8.row.col.f32.bf16.bf16.f32 {%0,%1,%2,%3}, {%4,%5}, {%6}, {%0,%1,%2,%3};"
      : "+f"(d[0]), "+f"(d[1]), "+f"(d[2]), "+f"(d[3]) : "r"(a0), "r"(a1), "r"(b0));
}
__device__ __forceinline__ float quad_sum(float v) { v += __shfl_xor_sync(0xffffffffu, v, 1); v += __shfl_xor_sync(0xffffffffu, v, 2); return v; }
__device__ __forceinline__ float quad_max(float v) { v = fmaxf(v, __shfl_xor_sync(0xffffffffu, v, 1)); v = fmaxf(v, __shfl_xor_sync(0xffffffffu, v, 2)); return v; }
__device__ __forceinline__ float rcp(float x) { float r; asm("rcp.approx.ftz.f32 %0, %1;" : "=f"(r) : "f"(x)); return r; }
__device__ __forceinline__ float rsq(float x) { float r; asm("rsqrt.approx.ftz.f32 %0, %1;" : "=f"(r) : "f"(x)); return r; }
__device__ __forceinline__ float ex2(float x) { float r; asm("ex2.approx.ftz.f32 %0, %1;" : "=f"(r) : "f"(x)); return r; }
__device__ __forceinline__ uint32_t chk(uint32_t acc, uint32_t v, uint32_t tag) { uint32_t r; asm("lop3.b32 %0, %1, %2, %3, 0xF6;" : "=r"(r) : "r"(acc), "r"(v), "r"(tag)); return r; }
__device__ __forceinline__ uint32_t chk2(uint32_t a, uint32_t b, uint32_t tag) { uint32_t r; asm("lop3.b32 %0, %1, %2, %3, 0x7E;" : "=r"(r) : "r"(a), "r"(b), "r"(tag)); return r; }
__device__ __forceinline__ uint32_t tagged(uint32_t v, uint32_t tag) { return (v & ~1u) | tag; }

__device__ __forceinline__ int group_k0(int g) { return g < 16 ? 64 * (g & 7) + 4 * (g & 8) : 32 * g; }
__device__ __forceinline__ uint32_t xin_off(int c, int w) { return SM_X + (2 * c + w + (2 * c + w < 9 ? 9 : -9)) * 8192; }
__device__ __forceinline__ uint32_t xin_bar(int c) { return BAR_FULLX + 8 * (c < 8 ? c ^ 4 : c); }
__device__ __forceinline__ int xin_order(int i, int j) { return i; }
__device__ __forceinline__ constexpr uint32_t qkv_xslot(int g) { return (0x5140762u >> (4 * (g - 5))) & 15; }

template <int N> struct IC { static constexpr int v = N; };

struct Cons {
  uint32_t sb;
  uint32_t rem;
  uint32_t sB, mB;
  uint32_t mX;
  bool elect;
  __device__ __forceinline__ void release2(uint32_t bar) const { if (elect) { mbar_arrive(sb + bar); mbar_arrive_remote(rem + bar); } }
  __device__ __forceinline__ uint32_t nextB(uint32_t& prev) {
    mbar_wait_c(sb + BAR_FULLB + sB, mB);
    const uint32_t a = (((sb & 0x3FFFF) + SM_B) >> 4) + sB * (BSLOT / 128);
    prev = sB == 0 ? 32 : sB - 8;
    sB += 8;
    if (sB == 40) { sB = 0; mB ^= 1; }
    return a;
  }
  __device__ __forceinline__ void progress(uint32_t v) const { if (elect) sts32(sb + SM_PROG + (threadIdx.x >> 5), v); }
  __device__ __forceinline__ void releaseLastB() const { release2(BAR_EMPTYB + (sB == 0 ? 32 : sB - 8)); }
};

template <bool QKV, class Pre, class Mma>
__device__ __forceinline__ float2 ln_gemm(Cons& c, Group* G, const float (&v)[36], uint32_t (&p)[18], int w, int st0, int j, int t,
                                          int layer, uint32_t tag, Pre&& pre, Mma&& mma) {
  const bool direct = QKV && layer == 0;
  const uint32_t stag = (2 * layer + (QKV ? 1 : 2)) & 3;
  constexpr int NBUF = 6;
  const uint32_t pbase = 32 * layer;
  uint4* const box = G->xbox;
  uint4 x[NBUF][2];
  const uint4* src = box + t;
  uint32_t xa = c.sb + w * 8192 + (t >> 5) * 2048 + (t & 7) * 128 + (((t >> 3) & 3) ^ (t & 7)) * 16;
  asm volatile("" : "+l"(src), "+r"(xa));
  auto load = [&](int g) { x[g % NBUF][0] = ld_relaxed4(src + 2 * g * 128); x[g % NBUF][1] = ld_relaxed4(src + (2 * g + 1) * 128); };
  auto load_in = [&](int g) {
    if (g == 8) xa -= w * 8 * XSLOT;
    if (g == 10) xa += w * 8 * XSLOT;
    if (g == 16) xa = c.sb + w * 8192 + (t >> 5) * 2048 + (t & 15) * 128 + (((t >> 4) & 1) ^ (t & 7)) * 16;
    const uint32_t a = xa ^ (64 * (g & 1));
    x[g % NBUF][0] = ldsm4(a + xin_off(g >> 1, 0));
    x[g % NBUF][1] = ldsm4((g < 16 ? a + 1024 : a ^ 32) + xin_off(g >> 1, 0));
  };
  float s0 = 0.f, s1 = 0.f, d0 = 0.f, d1 = 0.f;
  auto sums = [&](const float (&v)[36]) {
    s0 = v[0] + v[1]; s1 = v[2] + v[3];
#pragma unroll
    for (int i = 1; i < 9; i++) { s0 += v[4 * i] + v[4 * i + 1]; s1 += v[4 * i + 2] + v[4 * i + 3]; }
    s0 = __uint_as_float((__float_as_uint(quad_sum(s0)) & ~3u) | stag); s1 = quad_sum(s1);
  };
  auto squares = [&](const float (&v)[36]) {
    const float m0 = s0 * (1.f / 72), m1 = s1 * (1.f / 72);
    d0 = d1 = 0.f;
#pragma unroll
    for (int i = 0; i < 9; i++) {
      float a = v[4 * i] - m0, b = v[4 * i + 1] - m0; d0 = fmaf(a, a, fmaf(b, b, d0));
      a = v[4 * i + 2] - m1; b = v[4 * i + 3] - m1; d1 = fmaf(a, a, fmaf(b, b, d1));
    }
    d0 = quad_sum(d0); d1 = quad_sum(d1);
  };
  auto load3 = [&](int g) { load(g); load(g + 1); load(g + 2); };
  auto fetch3 = [&](int g0) {
#pragma unroll
    for (int g = g0; g < g0 + 3; g++) {
      if (OWNX && g < 16 && (g & 7) == j) {
        const uint32_t* o = p + (g & 8);
        x[g % NBUF][0] = make_uint4(tagged(o[0], tag), o[2], o[4], o[6]); x[g % NBUF][1] = make_uint4(tagged(o[1], tag), o[3], o[5], o[7]);
      } else {
        load(g);
      }
    }
  };
  auto invalid = [&](int g, uint32_t tag) {
    const uint4 (&y)[2] = x[g % NBUF], (&y1)[2] = x[(g + 1) % NBUF], (&y2)[2] = x[(g + 2) % NBUF];
    uint32_t bad = chk2(y[0].x, y[1].x, tag) | chk2(y1[0].x, y1[1].x, tag) | chk2(y2[0].x, y2[1].x, tag);
    if (g == 15) bad |= chk2(y1[0].z, y1[1].z, tag) | chk2(y2[0].z, y2[1].z, tag);
    return __any_sync(0xffffffffu, bad & 1);
  };
  uint4* const d = box + 2 * j * 128 + t;
  const int sq = st0 + 16 * (t & 3);
#pragma unroll
  for (int g = 0; g < NBUF; g++) x[g][0] = x[g][1] = make_uint4(tag ^ 1, 0, 0, 0);
  float m0, m1;
  if (direct) {
    float ra[4] = {0.f, 0.f, 0.f, 0.f}, rb[4] = {0.f, 0.f, 0.f, 0.f};
#pragma unroll 1
    for (int cc = 0; cc < 9; cc++) {
      const uint32_t a = xa - w * 8192 + xin_off(cc, w);
      mbar_wait_c(c.sb + xin_bar(cc), 0);
      const uint4 u0 = ldsm4(a), u1 = ldsm4(a + 1024), u2 = ldsm4(a ^ 64), u3 = ldsm4((a ^ 64) + 1024);
      mma16816(ra, u0, 0x3f803f80u); mma16816(rb, u1, 0x3f803f80u); mma16816(ra, u2, 0x3f803f80u); mma16816(rb, u3, 0x3f803f80u);
    }
    m0 = ra[0] + ra[2]; m1 = rb[0] + rb[2];
#pragma unroll
    for (int i = 0; i < 5; i++) {
      const uint4 u = ldsm4(c.sb + (t >> 5) * 2048 + (t & 15) * 128 + xin_off(i < 4 ? j : 8, w) + (((i < 4 ? 2 * i + ((t >> 4) & 1) : j) ^ (t & 7)) << 4));
      p[4 * i] = u.x; p[4 * i + 1] = u.y;
      if (i < 4) { p[4 * i + 2] = u.z; p[4 * i + 3] = u.w; }
    }
    pre(0);
  } else {
    sums(v);
    if ((t & 3) == 0) st_relaxed2(G->sum + st0 + 8 * j, __float_as_uint(s0), __float_as_uint(s1));
#pragma unroll
    for (int i = 0; i < 18; i++) p[i] = pack_bf16(v[2 * i], v[2 * i + 1]);
#pragma unroll
    for (int i = 0; i < 2; i++) st_relaxed4(d + i * 128, tagged(p[i], tag), p[i + 2], p[i + 4], p[i + 6]);
    uint2 sa, sc;
    auto poll = [&] {
      if (SPEC && layer && invalid(0, tag)) fetch3(0);
      sa = ld_relaxed2(G->sum + sq); sc = ld_relaxed2(G->sum + sq + 8);
    };
    poll();
    squares(v);
    pre(0);
    while (__any_sync(0xffffffffu, ((sa.x ^ stag) | (sc.x ^ stag)) & 3)) poll();
    if (invalid(0, tag)) fetch3(0);
    m0 = quad_sum(__uint_as_float(sa.x) + __uint_as_float(sc.x)); m1 = quad_sum(__uint_as_float(sa.y) + __uint_as_float(sc.y));
  }
  m0 *= -1.f / 576; m1 *= -1.f / 576;
  const uint32_t nm0 = pack_bf16(m0, m0), nm1 = pack_bf16(m1, m1);
  pre(1);
  uint4 u0, u1;
#pragma unroll
  for (int g = 0; g < 18; g++) {
    uint4 &a = x[g % NBUF][0], &b = x[g % NBUF][1];
    if (direct) load_in(g);
    else if (g % 3 == 0) {
      const uint32_t lt = g ? late(c.sb + BAR_FULLX + 64, tag) : tag;
      while (invalid(g, lt)) load3(g);
      if (g > 0 && g < 15) fetch3(g + 3);
    }
    const bool rows = g < 16;
    const uint4 f0 = make_uint4(hadd2(a.x, nm0), hadd2(rows ? b.x : a.y, nm1), hadd2(rows ? a.y : a.z, nm0), hadd2(rows ? b.y : a.w, nm1));
    const uint4 f1 = make_uint4(hadd2(rows ? a.z : b.x, nm0), hadd2(rows ? b.z : b.y, nm1), hadd2(rows ? a.w : b.z, nm0), hadd2(b.w, nm1));
    if (g == 12) { u0 = ld_relaxed4(G->m2 + sq); u1 = ld_relaxed4(G->m2 + sq + 8); }
    uint32_t prev = c.sB == 0 ? 32 : c.sB - 8, bb;
    if (QKV && g >= 5 && g < 12 && !direct) {
      mbar_wait_c(c.sb + BAR_FULLX + 8 * qkv_xslot(g), (c.mX >> qkv_xslot(g)) & 1);
      bb = ((c.sb & 0x3FFFF) + SM_X + qkv_xslot(g) * XSLOT) >> 4;
    } else {
      bb = c.nextB(prev);
    }
    if (QKV && g == GL && w == 1) asm volatile("bar.sync 6, 256;" ::: "memory");
    mma(g, bb, f0, f1);
    if (QKV && g == 17 && w == 0) asm volatile("bar.arrive 6, 256;" ::: "memory");
    if (g == 0) {
      if (!direct) {
        fetch3(3);
#pragma unroll
        for (int i = 0; i < 2; i++) st_relaxed4(d + (16 + i) * 128, tagged(p[8 + i], tag), p[10 + i], p[12 + i], p[14 + i]);
        st_relaxed2((uint2*)(box + (32 + (j >> 1)) * 128 + t) + (j & 1), tagged(p[16], tag), p[17]);
      } else {
        float u[36];
#pragma unroll
        for (int i = 0; i < 18; i++) { u[2 * i] = bf_lo(p[i]); u[2 * i + 1] = bf_hi(p[i]); }
        sums(u);
        squares(u);
      }
      if ((t & 3) == 0) st_relaxed4(G->m2 + st0 + 8 * j, __float_as_uint(s0), __float_as_uint(s1), __float_as_uint(d0), __float_as_uint(d1));
      c.progress(pbase + (QKV ? 1 : 21));
    }
    wg_wait<1>();
    if (g > 0 && !(QKV && g > 5 && g <= 12 && !direct)) c.release2(BAR_EMPTYB + prev);
    if (QKV && g > 0 && g < 15) c.progress(pbase + 1 + g);
    if (QKV && g >= WOG && g < WOG + 4) c.release2(BAR_EMPTYX + 32 + 8 * (g - WOG));
  }
  if (QKV) c.mX ^= direct ? 0xff : 0xf7;
  while (__any_sync(0xffffffffu, chk2(u0.x, u1.x, stag) & 3)) { u0 = ld_relaxed4(G->m2 + sq); u1 = ld_relaxed4(G->m2 + sq + 8); }
  float e0 = fmaf(__uint_as_float(u0.x), 1.f / 72, m0), e1 = fmaf(__uint_as_float(u1.x), 1.f / 72, m0);
  const float v0 = quad_sum(fmaf(72.f, fmaf(e0, e0, e1 * e1), __uint_as_float(u0.z) + __uint_as_float(u1.z)));
  e0 = fmaf(__uint_as_float(u0.y), 1.f / 72, m1); e1 = fmaf(__uint_as_float(u1.y), 1.f / 72, m1);
  const float v1 = quad_sum(fmaf(72.f, fmaf(e0, e0, e1 * e1), __uint_as_float(u0.w) + __uint_as_float(u1.w)));
  float2 r = make_float2(rsq(fmaf(v0, 1.f / 576, 1e-5f)), rsq(fmaf(v1, 1.f / 576, 1e-5f)));
  asm volatile("" : "+f"(r.x), "+f"(r.y));
  if (QKV && GL == 18 && w == 1) asm volatile("bar.sync 6, 256;" ::: "memory");
  wg_wait<0>();
  if (QKV && ATTBAR && w == 1) asm volatile("bar.arrive 4, 256;" ::: "memory");
  c.releaseLastB();
  if (direct) c.release2(BAR_EMPTYX + 24);
  return r;
}

template <int NB, int OFF>
__device__ __forceinline__ void glu(const float (&a)[128], uint32_t (&h)[144]) {
#pragma unroll
  for (int b = 0; b < 2 * NB; b++) {
    if (HMUL) h[OFF + b] = hmul2(pack_bf16(a[2 * b], a[2 * b + 1]), pack_bf16(a[4 * NB + 2 * b], a[4 * NB + 2 * b + 1]));
    else h[OFF + b] = pack_bf16(a[2 * b] * a[4 * NB + 2 * b], a[2 * b + 1] * a[4 * NB + 2 * b + 1]);
  }
}

__global__ void __cluster_dims__(2, 1, 1) __launch_bounds__(384, 1)
fused_kernel(const __nv_bfloat16* __restrict__ x_in, Group* ws, const char* __restrict__ wqkv,
             const char* __restrict__ wg, const char* __restrict__ wu, const char* __restrict__ wd, const __grid_constant__ Maps maps,
             const char* __restrict__ wo) {
  extern __shared__ __align__(1024) uint8_t smem_raw[];
  const uint32_t sb = smem_u32(smem_raw);
  if (threadIdx.x == 0) asm volatile("prefetch.tensormap [%0];" ::"l"(&maps.x) : "memory");
  const int warp = __shfl_sync(0xffffffffu, threadIdx.x >> 5, 0);
  const int lane = threadIdx.x & 31;
  const int rank = blockIdx.x & 1;
  if (elect_one()) {
    if (warp >= 8) {
#pragma unroll
      for (int i = 0; i < 9; i++) mbar_init(sb + SM_BAR + 72 * (warp - 8) + 8 * i, warp < 10 ? 1 : 4);
      sts32(sb + SM_PROG + 4 * (warp - 8), 0);
      asm volatile("fence.mbarrier_init.release.cluster;" ::: "memory");
    } else if (warp == 1 || warp == 2) {
      asm volatile("prefetch.tensormap [%0];" ::"l"(&maps.x + warp) : "memory");
    } else if (warp == 3) {
      if (PFMODE & 1) prefetch_l2((const char*)x_in + blockIdx.x * 18432, 18432);
    } else if (warp == 4) {
      if (PFMODE & 2) prefetch_l2(wqkv + blockIdx.x * (15552 / PFQ), 15552 / PFQ);
    }
  }
  __syncwarp();
  asm volatile("barrier.cluster.arrive.relaxed.aligned;" ::: "memory");
  if (warp == 8) PROFX(53);
  int lb = blockIdx.x;
  if (GPCMAP) {
    const int cl = blockIdx.x >> 1, u = cl - 36;
    lb = (cl < 4 ? cl : cl < 36 ? 8 * ((cl - 4) & 7) + ((cl - 4) >> 3) + (((cl - 4) & 7) ? 0 : 4) : 8 * (1 + u % 7) + 4 + u / 7) * 2 + rank;
  }
#define CTA_J(b) (((b) >> 1) & 7)
#define CTA_RB(b) ((((b) >> 4) << 1) | ((b) & 1))
  const int j = CTA_J(lb), rb = CTA_RB(lb);

  PROF(23);
  if (warp >= 8) {
    asm volatile("setmaxnreg.dec.sync.aligned.u32 " STR(REGS_P) ";");
    auto x_chunk = [&](int cc) {
      mbar_expect_tx(sb + xin_bar(cc), 16384);
      tma3d(sb + xin_off(cc, 0), &maps.x, 64 * cc, 0, 64 * rb, sb + xin_bar(cc));
      tma3d(sb + xin_off(cc, 1), &maps.x, 64 * cc, 1, 64 * rb, sb + xin_bar(cc));
    };
    if (warp == 9 && elect_one()) {
      fence_async_smem();
#pragma unroll 1
      for (int i = 0; i < 9; i++) x_chunk(xin_order(i, j));
    }
    __syncwarp();
    if (warp == 9) PROFX(54);
    asm volatile("barrier.cluster.wait.aligned;" ::: "memory");
    if (warp == 8) PROFX(56);
    const uint64_t pol = W_POLICY(), pola = A_POLICY();
    auto qkv_group = [&](int k, uint32_t dst, uint32_t bar) {
      wtma3d(dst + rank * 8192, &maps.qm, 72 * j, k + 16 * rank, 0, bar, pola);
      wtma3d(dst + rank * 8192 + 6144, &maps.qc, 72 * j + 64, k + 16 * rank, 0, bar, pola);
    };
    auto qkv_gate = [&](int g) { if (g >= 8) gate(sb + SM_PROG, 33 + ((g - 8) * 23 >> 4)); };
    if (warp == 8) {
      uint32_t s = 0, ph = 1;
      auto slot = [&](uint32_t bytes, auto&& issue) {
        const uint32_t bar = sb + BAR_FULLB + 8 * s;
        mbar_wait(sb + BAR_EMPTYB + 8 * s, ph);
        if (elect_one()) {
          mbar_expect_tx(bar, bytes);
          issue(sb + SM_B + s * BSLOT, bar);
        }
        if (++s == 5) { s = 0; ph ^= 1; }
      };
#pragma unroll 1
      for (int layer = 0; layer < NLAYERS; layer++) {
#pragma unroll 1
        for (int g = 0; g < 18; g += layer && g == 4 ? 8 : 1) {
          if (layer) qkv_gate(g);
          else if (g == QD) mbar_wait(sb + xin_bar(xin_order(XH, j)), 0);
          slot(2 * 6912, [&](uint32_t dst, uint32_t bar) { qkv_group(layer ? group_k0(g) : 32 * g, dst, bar); });
        }
        if (!FCH) {
          gate(sb + SM_PROG, 32 * layer + 20);
          gate(sb + SM_PROG + 4, 32 * layer + 20);
        }
#pragma unroll 1
        for (int t = 0; t < 5; t++) {
          const CUtensorMap* m = &maps.g + (t < 3 ? rank : 2 + rank);
          const int c2 = t < 3 ? 9 * j + 2 * t : 18 * j + 3 + 3 * t;
          const uint32_t half = t < 3 ? 8192 : 6144;
#pragma unroll 1
          for (int g = 0; g < 18; g++) {
            if (FCH && t == 0 && g < 5) mbar_wait(sb + BAR_FULLB + 8 * (s < FCH ? s + 5 - FCH : s - FCH), s < FCH ? ph : ph ^ 1);
            slot(2 * half, [&](uint32_t dst, uint32_t bar) { wtma3d(dst + rank * half, m, 0, group_k0(g), c2, bar, pol); });
          }
        }
      }
    } else if (warp == 9) {
      uint32_t mE = 0;
      auto acquire = [&](uint32_t s) { mbar_wait(sb + BAR_EMPTYX + 8 * s, (mE >> s) & 1); mE ^= 1u << s; };
      auto landed = [&](uint32_t s) { mbar_wait(sb + BAR_FULLX + 8 * s, (mE >> s) & 1); };
      auto slot = [&](uint32_t s, const CUtensorMap* m, int col, int row, uint64_t pol) {
        acquire(s);
        if (elect_one()) {
          mbar_expect_tx(sb + BAR_FULLX + 8 * s, XSLOT);
          wtma2d(sb + SM_X + s * XSLOT + rank * 9216, m, col, row + 72 * rank, sb + BAR_FULLX + 8 * s, pol);
        }
      };
#pragma unroll 1
      for (int layer = 0; layer < NLAYERS; layer++) {
#pragma unroll 1
        for (int g = 5; g < 12 * layer; g++) {
          const uint32_t s = qkv_xslot(g);
          qkv_gate(g);
          acquire(s);
          if (elect_one()) {
            mbar_expect_tx(sb + BAR_FULLX + 8 * s, 2 * 6912);
            qkv_group(group_k0(g), sb + SM_X + s * XSLOT, sb + BAR_FULLX + 8 * s);
          }
          if (XCH & 1) landed(s);
        }
#pragma unroll 1
        for (int i = 0; i < 4; i++) { slot(4 + i, &maps.o, 64 * j, 144 * i, pola); if (XCH & 2) landed(4 + i); }
        acquire(3);
        if (elect_one()) {
          mbar_expect_tx(sb + BAR_FULLX + 24, 9216);
          wtma2d(sb + SM_WOC + rank * 4608, &maps.oc, 512 + 8 * j, 288 * rank, sb + BAR_FULLX + 24, pola);
          wtma2d(sb + SM_WOC + rank * 4608 + 2304, &maps.oc, 512 + 8 * j, 288 * rank + 144, sb + BAR_FULLX + 24, pola);
        }
#pragma unroll 1
        for (int u = 0; u < 36; u++) {
          const uint32_t s = 4 * (u & 1) + ((u >> 1) & 3);
          slot(s, &maps.d, u < 4 ? 512 : 64 * ((j + (u >> 2)) & 7), 576 * j + 144 * (u & 3), pol);
          if ((XCH & 4) && u < 3) landed(s);
        }
      }
    } else {
      const int w = warp - 10, grp = 2 * rb + w;
      if (PFMODE & 4) {
        mbar_wait(sb + xin_bar(xin_order(XP, j)), 0);
        if (lane == 0) prefetch_l2(wqkv + (2 * blockIdx.x + w) * 7776, 7776);
      }
      gate(sb + SM_PROG, 3);
      if (w == 0) PROFX(58);
      auto prefetch_gu = [&](int l0, int n) {
#pragma unroll 1
        for (int i = lane; i < 36 * n; i += 32) {
          asm volatile("prefetch.global.L2 [%0];" ::"l"((w ? wu : wg) + (size_t)(36 * rb + i / n) * 9216 + 1152 * j + 128 * (l0 + i % n)));
          __nanosleep(PFSLEEP);
        }
      };
      auto clear = [&](uint4* p, int n) {
#pragma unroll 1
        for (int i = lane; i < n; i += 64) { st_relaxed4(p + i, 0, 0, 0, 0); st_relaxed4(p + i + 32, 0, 0, 0, 0); __nanosleep(CLRSLEEP); }
      };
      auto exchange = [&](uint32_t v, uint32_t bar) {
        if (FENCE1) { if (lane == 0) fence_gpu(); } else fence_gpu();
        __syncwarp();
        if (w == 0 && v != 1) PROFX(64 + 58 - 2 * v);
        if (lane == 0) st_relaxed(ws[grp].flag + j, v);
#pragma unroll 1
        for (int it = 0; it < SPIN_MAX; it++) {
          const uint32_t f = ld_relaxed(ws[grp].flag + (lane & 7));
          if (__all_sync(0xffffffffu, v ? f >= v : f == 0)) break;
        }
        if (lane == 0) mbar_arrive(sb + bar + 8 * w);
      };
      if (lane == 0) prefetch_l2(wo + (2 * blockIdx.x + w) * 2592, 2592);
      if (MAPPF && w == 0 && lane < 9) asm volatile("prefetch.tensormap [%0];" ::"l"(&maps.o + lane) : "memory");
#pragma unroll 1
      for (int layer = 0; layer < NLAYERS; layer++) {
        gate(sb + SM_PROG, 32 * layer + 3);
        if (PFF & 1) prefetch_gu(0, 2);
        gate(sb + SM_PROG, 32 * layer + 22);
        if (PFF & 2) prefetch_gu(2, 2);
        if (layer == 0) {
          clear(ws[grp].inbox[0] + 2 * j * INBOX, 2 * INBOX);
          exchange(1, BAR_CLR);
          if (w == 0) PROFX(59);
        }
        if (PFF & 2) prefetch_gu(4, 2);
        if (PFF & 4) prefetch_gu(6, 3);
#pragma unroll 1
        for (int i = lane; i < ((PFF & 8) ? 162 : 0); i += 32) {
          asm volatile("prefetch.global.L2 [%0];" ::"l"(wd + (size_t)(576 * j + 36 * rb + 18 * w) * 1152 + 128 * i));
          __nanosleep(PFSLEEP);
        }
        if (w == 0 && layer == 0) PROFX(60);
        mbar_wait(sb + BAR_REDDONE + 8 * w, layer);
        if (w == 0) PROFX(64 + 53 + 4 * layer);
        exchange(2 - 2 * layer, BAR_RREADY);
        if (w == 0) PROFX(64 + 56 + 4 * layer);
      }
      mbar_wait(sb + BAR_DONE + 8 * w, 0);
    }
    __syncwarp();
    cluster_sync();
  } else {
    asm volatile("setmaxnreg.inc.sync.aligned.u32 " STR(REGS_C) ";");
#define THREAD_IDS()                                                                   \
    int tid_ = threadIdx.x, bid_ = lb;                                                  \
    asm volatile("" : "+r"(tid_), "+r"(bid_));                                          \
    const int w = warp >> 2, wp = warp & 3;                                             \
    const int lane = tid_ & 31, t = tid_ & 127, g = lane >> 2, q = lane & 3;           \
    const int j = CTA_J(bid_), rb = CTA_RB(bid_), grp = 2 * rb + w;                    \
    const int st0 = wp * 64 + g;                         \
    Group* const G = ws + grp;                                                         \
    const uint32_t dsb = (sb & 0x3FFFF) >> 4;                                          \
    (void)t; (void)g; (void)q; (void)grp; (void)j; (void)st0; (void)dsb; (void)G
    Cons c;
    c.sb = sb; c.sB = 0; c.mB = 0; c.mX = 0; c.elect = (threadIdx.x & 127) == 0;
    asm volatile("mapa.shared::cluster.u32 %0, %1, %2;" : "=r"(c.rem) : "r"(sb), "r"(rank ^ 1));
    float v[36];
    uint32_t xtag;
    {
      THREAD_IDS();
      if (OPEN) {
        if (q == 0) { st_relaxed2(G->sum + st0 + 8 * j, 0, 0); st_relaxed4(G->m2 + st0 + 8 * j, 0, 0, 0, 0); }
        if (wp == 3) {
#pragma unroll
          for (int i = 0; i < 5; i++) st_relaxed4(G->halo + j * 160 + lane + i * 32, 0, 0, 0, 0);
        }
        if (lane >= OPENL) st_relaxed4(G->obox + (8 * WPROBE + j) * 128 + t, 0, 0, 0, 0);
      }
      xtag = __shfl_sync(0xffffffffu, ~ld_relaxed(G->flag + 32 + 32 * j) & 1, 0);
      asm volatile("barrier.cluster.wait.aligned;" ::: "memory");
      PROF(0);
#pragma unroll
      for (int i = 0; i < 36; i++) v[i] = 0.f;
    }
#pragma unroll 1
    for (int layer = 0;; layer++) {
      const uint32_t tag = layer ^ 1;
      const int pb = 1 + layer * 30;
      uint32_t res[18];
      uint4 own[4];
      {
        THREAD_IDS();
        PROF(pb + 0);
        float a1[96], a2[12];
        const float2 rs = ln_gemm<true>(c, G, v, res, w, st0, j, t, layer, xtag ^ 1,
          [&](int i) { PROF(pb + 1 + i); },
          [&](int gi, uint32_t bb, const uint4& f0, const uint4& f1) {
            if (gi == 0) PROF(pb + 3);
            wg_fence();
            wgmma_ra<192>(a1, f0, desc_hi(2048, 1024, 1) + bb, gi > 0);
            wgmma_ra<24>(a2, f0, desc_hi(128, 256, 0) + (bb + 384), gi > 0);
            wgmma_ra<192>(a1, f1, desc_hi(2048, 1024, 1) + (bb + 512), true);
            wgmma_ra<24>(a2, f1, desc_hi(128, 256, 0) + (bb + 896), true);
            wg_commit();
          });
        PROF(pb + 4);
        uint32_t kv[3][18];
        auto cvt = [&](int b, float r) {
#pragma unroll
          for (int cc = 0; cc < 18; cc++) {
            const float* a = (cc == 8 ? a2 + 4 : cc == 17 ? a2 + 8 : cc < 8 ? a1 + 32 + 4 * cc : a1 + 28 + 4 * cc) + 2 * (b - 1);
            const uint32_t u = pack_bf16(a[0] * r, a[1] * r);
            kv[b][cc] = cc < 9 ? u : movm(u);
          }
        };
        cvt(2, rs.y);
        const uint32_t msg = sb + SM_X + (w ? 3 * XSLOT : 24576) + wp * 2304 + lane * 16;
        if (wp == 3) {
          uint4* hp = G->halo + j * 160 + lane;
#pragma unroll
          for (int i = 0; i < 4; i++) st_relaxed4(hp + i * 32, tagged(kv[2][4 * i], tag), kv[2][4 * i + 1], kv[2][4 * i + 2], kv[2][4 * i + 3]);
          st_relaxed2((uint2*)(hp + 128), tagged(kv[2][16], tag), kv[2][17]);
        } else {
#pragma unroll
          for (int i = 0; i < 4; i++) sts128(msg + i * 512, kv[2][4 * i], kv[2][4 * i + 1], kv[2][4 * i + 2], kv[2][4 * i + 3]);
          sts64f(msg + 2048 - lane * 8, __uint_as_float(kv[2][16]), __uint_as_float(kv[2][17]));
        }
        cvt(1, rs.x);
        uint32_t Q[4][6];
#pragma unroll
        for (int h = 0; h < 4; h++)
#pragma unroll
          for (int i = 0; i < 6; i++) {
            const float* a = 4 * h + i < 16 ? a1 + 8 * h + 2 * i : a2 + 8 * h + 2 * i - 32;
            const uint32_t u = pack_bf16(a[0], a[1]);
            Q[h][i] = i < 2 ? (q >= h ? u : 0) : i < 4 ? u : (q <= h ? u : 0);
          }
        const bool lo0 = 2 * q > g, lo1 = 2 * q + 1 > g;
        const uint32_t M = (lo0 ? 0xffffu : 0u) | (lo1 ? 0xffff0000u : 0u);
        auto scores = [&](int h, int b, float (&s)[4]) {
          mma16816z(s, Q[h][0], Q[h][1], Q[h][2], Q[h][3], kv[b][2 * h], kv[b][2 * h + 1]);
          mma1688(s, Q[h][4], Q[h][5], kv[b][2 * h + 2]);
        };
        auto softmax = [&](float (&l)[4][2], float r, uint32_t (&P)[4]) {
          const float sl = r * (0.23570226039551584f * 1.4426950408889634f);
          float m[4];
#pragma unroll
          for (int h = 0; h < 4; h++) { m[h] = fmaxf(l[h][0], l[h][1]); m[h] = fmaxf(m[h], __shfl_xor_sync(0xffffffffu, m[h], 1)); }
#pragma unroll
          for (int h = 0; h < 4; h++) m[h] = fmaxf(m[h], __shfl_xor_sync(0xffffffffu, m[h], 2)) * sl;
#pragma unroll
          for (int h = 0; h < 4; h++) {
            l[h][0] = ex2(fmaf(l[h][0], sl, -m[h])); l[h][1] = ex2(fmaf(l[h][1], sl, -m[h]));
            m[h] = l[h][0] + l[h][1]; m[h] += __shfl_xor_sync(0xffffffffu, m[h], 1);
          }
#pragma unroll
          for (int h = 0; h < 4; h++) { m[h] = rcp(m[h] + __shfl_xor_sync(0xffffffffu, m[h], 2)); P[h] = pack_bf16(l[h][0] * m[h], l[h][1] * m[h]); }
        };
        const bool remote = wp == 0 && rb > 0;
        const uint4* hp = (G - 2)->halo + j * 160 + lane;
        auto halo = [&] {
#pragma unroll
          for (int i = 0; i < 4; i++) { const uint4 u = ld_relaxed4(hp + i * 32); kv[0][4 * i] = u.x; kv[0][4 * i + 1] = u.y; kv[0][4 * i + 2] = u.z; kv[0][4 * i + 3] = u.w; }
          const uint2 u = ld_relaxed2((const uint2*)(hp + 128));
          kv[0][16] = u.x; kv[0][17] = u.y;
        };
#pragma unroll
        for (int i = 0; i < 18; i++) kv[0][i] = 0;
        if (remote) halo();
        if (ATTBAR && w == 0) asm volatile("bar.sync 4, 256;" : "+r"(Q[0][2]), "+r"(Q[1][2]), "+r"(Q[2][2]), "+r"(Q[3][2]) :: "memory");
        float l0[4][2], l1[4][2];
#pragma unroll
        for (int h = 0; h < 4; h++) {
          float s1[4], s2[4];
          scores(h, 1, s1); scores(h, 2, s2);
          l0[h][0] = s1[0]; l0[h][1] = s1[1];
          l1[h][0] = lo0 ? s1[2] : s2[2]; l1[h][1] = lo1 ? s1[3] : s2[3];
        }
        uint32_t P0[4], P1[4];
        softmax(l1, rs.y, P1);
        if (remote) {
          while (__any_sync(0xffffffffu, chk(chk2(kv[0][0], kv[0][4], tag) | chk2(kv[0][8], kv[0][12], tag), kv[0][16], tag) & 1)) halo();
        }
        if (FG < 0) c.progress(32 * layer + 20);
        wg_bar(w);
        if (wp > 0) {
          const uint32_t from = msg - 2304;
#pragma unroll
          for (int i = 0; i < 4; i++) { const uint4 u = lds128(from + i * 512); kv[0][4 * i] = u.x; kv[0][4 * i + 1] = u.y; kv[0][4 * i + 2] = u.z; kv[0][4 * i + 3] = u.w; }
          const float2 u = lds64(from + 2048 - lane * 8);
          kv[0][16] = __float_as_uint(u.x); kv[0][17] = __float_as_uint(u.y);
        }
        PROF(pb + 5);
        const bool first = (rb == 0 && wp == 0);
#pragma unroll
        for (int h = 0; h < 4; h++) {
          float s0[4];
          scores(h, 0, s0);
          if (first) s0[0] = s0[1] = -INFINITY;
          l0[h][0] = lo0 ? s0[0] : l0[h][0]; l0[h][1] = lo1 ? s0[1] : l0[h][1];
        }
        softmax(l0, rs.x, P0);
        uint4* ob = G->obox + t;
        uint32_t car0 = 0, car1 = 0;
#pragma unroll
        for (int h = 0; h < 4; h++) {
          float o[3][4];
#pragma unroll
          for (int i = 0; i < 3; i++) {
            mma16816z(o[i], P0[h] & ~M, P1[h] & M, 0u, P1[h] & ~M, kv[1][9 + 2 * h + i], kv[2][9 + 2 * h + i]);
            mma1688(o[i], P0[h] & M, 0u, kv[0][9 + 2 * h + i]);
          }
          const uint32_t o0 = q < h ? car0 : pack_bf16(o[0][0], o[0][1]), o1 = q < h ? car1 : pack_bf16(o[0][2], o[0][3]);
          own[h] = make_uint4(o0 | 1, o1, pack_bf16(o[1][0], o[1][1]), pack_bf16(o[1][2], o[1][3]));
          st_relaxed4(ob + (8 * h + j) * 128, own[h].x, own[h].y, own[h].z, own[h].w);
          car0 = pack_bf16(o[2][0], o[2][1]); car1 = pack_bf16(o[2][2], o[2][3]);
        }
        st_relaxed2((uint2*)(ob + (32 + (j >> 1)) * 128) + (j & 1), tagged(car0, tag), car1);
        PROF(pb + 6);
      }
      {
        THREAD_IDS();
        const uint4* src = G->obox + t;
        asm volatile("" : "+l"(src));
        float a[32], a8[4];
#pragma unroll
        for (int i = 3; i < 8; i++) mbar_wait_c(sb + BAR_FULLX + 8 * i, (c.mX >> i) & 1);
        c.mX ^= 0xf8;
        auto step = [&](const uint4& f, uint32_t r0, int rs, bool acc) {
          wgmma_ra<64>(a, f, desc_hi(0, rs * 128, 1) + (dsb + ((SM_X + 4 * XSLOT) >> 4) + r0 * 8), acc);
          wgmma_ra<8>(a8, f, desc_hi(rs * 16, 0, 0) + (dsb + (SM_WOC >> 4) + r0), acc);
        };
        const uint32_t* probe = &(G->obox + (8 * WPROBE + (lane & 7)) * 128 + (t | 31))->x;
        uint32_t pv = ld_relaxed(probe);
        if (OWNBAR) asm volatile("bar.sync 4, 256;" ::: "memory");
        wg_fence();
#pragma unroll
        for (int i = 0; i < 4; i++) step(own[i], 72 * j + 16 * i, 8, i > 0);
        wg_commit();
        pv &= late(sb + BAR_FULLX + 64, 1);
        while (__any_sync(0xffffffffu, ~pv & 1)) pv = ld_relaxed(probe);
        if (w == 1) asm volatile("bar.sync 7, 256;" ::: "memory");
        uint4 x[32];
        auto load = [&](int i) { x[i] = ld_relaxed4(i < 28 ? src + (i % 7 >= j ? 128 : 0) + (8 * (i / 7) + i % 7) * 128 : src + (i + 4) * 128); };
        auto batch = [&](auto e0, auto e1, auto e2, int b) {
          constexpr int E0 = decltype(e0)::v, E1 = decltype(e1)::v, E2 = decltype(e2)::v;
          const uint32_t one = E0 > 0 && E1 > E0 ? late(sb + BAR_FULLX + 64, 1) : 1;
          while (E1 > E0) {
            uint32_t bad = 0;
#pragma unroll
            for (int i = E0; i < E1; i++) bad = i < 28 ? chk(bad, x[i].x, one) : chk(chk(bad, x[i].x, tag), x[i].z, tag);
            if (!__any_sync(0xffffffffu, bad & 1)) break;
#pragma unroll
            for (int i = E0; i < E1; i++) load(i);
          }
          if (b == 0) PROF(pb + 7);
#pragma unroll
          for (int i = E1; i < E2; i++) load(i);
          if (b == WOREL && w == 0) asm volatile("bar.arrive 7, 256;" ::: "memory");
          if (E1 > E0) {
            wg_fence();
#pragma unroll
            for (int i = E0; i < E1; i++) {
              if (i < 28) step(x[i], 72 * (i % 7) + (i % 7 >= j ? 72 : 0) + 16 * (i / 7), 8, true);
              else step(x[i], 144 * (i - 28) + 64, 72, true);
            }
            wg_commit();
          }
        };
        batch(IC<0>(), IC<0>(), IC<WB1>(), -1);
        batch(IC<0>(), IC<WB1>(), IC<WB2>(), 0);
        batch(IC<WB1>(), IC<WB2>(), IC<WB3>(), 1);
        batch(IC<WB2>(), IC<WB3>(), IC<32>(), 2);
        batch(IC<WB3>(), IC<32>(), IC<32>(), 3);
        wg_wait<0>();
        if (w == 0) asm volatile("bar.arrive 3, 256;" ::: "memory");
        PROF(pb + 8);
#pragma unroll
        for (int i = 0; i < 18; i++) {
          v[2 * i] = bf_lo(res[i]) + (i < 16 ? a[2 * i] : a8[2 * i - 32]);
          v[2 * i + 1] = bf_hi(res[i]) + (i < 16 ? a[2 * i + 1] : a8[2 * i - 31]);
        }
      }
      uint32_t lsb;
      uint32_t h[144];
      {
        THREAD_IDS();
        float a[128];
        const uint32_t xd = sb + SM_X + w * 4 * XSLOT + (lane >> 4) * 1024 + (16 * wp + (lane & 15)) * 16;
        const float2 rs = ln_gemm<false>(c, G, v, res, w, st0, j, t, layer, xtag,
          [&](int i) {
            if (i == 0) {
              lsb = ((res[0] & 1) | (res[1] & 1) << 1 | (res[8] & 1) << 2 | (res[9] & 1) << 3 | (res[16] & 1) << 4) ^ (xtag * 31);
              if (w == 1) asm volatile("bar.sync 3, 256;" ::: "memory");
            }
            PROF(pb + 9 + i);
          },
          [&](int gi, uint32_t bb, const uint4& f0, const uint4& f1) {
            if (gi == 0) PROF(pb + 11);
            wg_fence();
            wgmma_ra<256>(a, f0, desc_hi(4096, 1024, 1) + bb, gi > 0);
            wgmma_ra<256>(a, f1, desc_hi(4096, 1024, 1) + (bb + 128), true);
            wg_commit();
            stsm4(xd + gi * 4096, f0.x, f0.y, f0.z, f0.w);
            stsm4(xd + gi * 4096 + 2048, f1.x, f1.y, f1.z, f1.w);
            if (gi == 17) { fence_async_smem(); wg_bar(w); }
          });
        sts64f(sb + SM_KEEP + tid_ * 8, rs.x * rs.x, rs.y * rs.y);
        c.progress(32 * layer + 22);
        PROF2(pb + 12);
        glu<16, 0>(a, h);
        const uint64_t da0 = desc_hi(1024, 128, 0) + (dsb + ((SM_X + w * 4 * XSLOT) >> 4));
        auto tile = [&](auto wide, auto last) {
          const uint32_t xe = BAR_EMPTYX + 32 * (t & 1) + 4 * (t & 6);
#pragma unroll 1
          for (int gi = 0; gi < 18; gi++) {
            uint32_t prev;
            const uint32_t bb = c.nextB(prev);
            const uint64_t da = da0 + gi * 256;
            wg_fence();
            if (wide()) {
              wgmma_ss<256>(a, da, desc_hi(4096, 1024, 1) + bb, gi);
              wgmma_ss<256>(a, da + 128, desc_hi(4096, 1024, 1) + (bb + 128), 1);
            } else {
              wgmma_ss<192>(*(float(*)[96])a, da, desc_hi(2048, 512, 2) + bb, gi);
              wgmma_ss<192>(*(float(*)[96])a, da + 128, desc_hi(2048, 512, 2) + (bb + 64), 1);
            }
            wg_commit();
            wg_wait<1>();
            if (gi > 0 && !(last() && gi > 13)) c.release2(BAR_EMPTYB + prev);
            if (last() && gi >= XREL && !((gi ^ XREL) & 1)) c.release2(BAR_EMPTYX + 16 * ((gi - XREL) & 2) + 2 * ((gi - XREL) & 12));
          }
          wg_wait<0>();
          if (!last()) c.releaseLastB();
          if (last() && t >= (19 - XREL) / 2 && t < 8) { mbar_arrive(sb + xe); mbar_arrive_remote(c.rem + xe); }
        };
        auto yes = [] { return true; };
        auto no = [] { return false; };
        tile(yes, no); PROF2(pb + 13); glu<16, 32>(a, h);
        tile(yes, no); PROF2(pb + 14); glu<16, 64>(a, h);
        tile(no, no); PROF2(pb + 15); glu<12, 96>(a, h);
        const uint32_t hole = sb + SM_B + 12288 + tid_ * 16;
#pragma unroll
        for (int i = 0; i < NSPILL; i++) sts128(hole + i * BSLOT, h[96 + 4 * i], h[97 + 4 * i], h[98 + 4 * i], h[99 + 4 * i]);
        if (w == 1) asm volatile("bar.arrive 8, 256;" ::: "memory");
        tile(no, yes); PROF2(pb + 16); glu<12, 120>(a, h);
#pragma unroll
        for (int i = 0; i < NSPILL; i++) { const uint4 u = lds128(hole + i * BSLOT); h[96 + 4 * i] = u.x; h[97 + 4 * i] = u.y; h[98 + 4 * i] = u.z; h[99 + 4 * i] = u.w; }
      }
      {
        THREAD_IDS();
        float d[32];
        uint4* gt = G->obox + t;
        asm volatile("" : "+l"(gt));
        uint4* const ib = gt + 2 * 4608 + layer * 8 * INBOX;
        auto pass = [&](uint32_t s0, bool last, auto&& hook) {
          const uint64_t db = desc_hi(0, 1024, 1) + (dsb + (SM_X >> 4) + s0 * (XSLOT >> 4));
          mbar_wait_c(sb + BAR_FULLX + 8 * s0, (c.mX >> s0) & 1);
          asm volatile("bar.sync %0, 256;" ::"r"(8 + w) : "memory");
#pragma unroll
          for (int i = 0; i < 4; i++) {
            const int si = 4 * (i & 1) + (i >> 1);
            if (i > 0) mbar_wait_c(sb + BAR_FULLX + 8 * (s0 + si), (c.mX >> (s0 + si)) & 1);
            wg_fence();
#pragma unroll
            for (int k = 0; k < 9; k++) {
              const uint32_t* hk = h + 36 * i + 4 * k;
              wgmma_ra<64>(d, make_uint4(hk[0], hk[1], hk[2], hk[3]), db + (si * (XSLOT >> 4) + k * 128), last || i + k > 0);
              if (9 * i + k == PPK && !(last && w == 1)) asm volatile("bar.arrive %0, 256;" ::"r"(9 - w) : "memory");
            }
            wg_commit();
            if (i > 0) { wg_wait<1>(); c.release2(BAR_EMPTYX + 8 * (s0 + 4 * ((i - 1) & 1) + ((i - 1) >> 1))); }
            if (i == RHOOK) hook();
          }
          c.mX ^= 0x33u << s0;
        };
        PROF2(pb + 17);
#pragma unroll 1
        for (int p = 0; p < 8; p++) {
          const uint32_t s0 = 2 * (p & 1);
          pass(s0, false, [] {});
          wg_wait<0>();
          c.release2(BAR_EMPTYX + 8 * (s0 + 5));
          uint32_t pk[16];
#pragma unroll
          for (int i = 0; i < 16; i++) pk[i] = pack_bf16(d[2 * i], d[2 * i + 1]);
          if (p >= BREL && p < BREL + 5) {
            const uint32_t o = c.sB + 8 * (p - BREL);
            c.release2(BAR_EMPTYB + (o < 40 ? o : o - 40));
          }
          uint4* const dst = ib + ((j + p) & 7) * INBOX;
          if (p == 0) {
            mbar_wait_c(sb + BAR_CLR + 8 * w, 0);
#pragma unroll
            for (int k = 0; k < 8; k++) red2((uint2*)(ib + k * INBOX + 512) - t, pk[2 * k], pk[2 * k + 1]);
          } else if (p < 7) {
#pragma unroll
            for (int k = 0; k < 4; k++) red4(dst + k * 128, pk[4 * k], pk[4 * k + 1], pk[4 * k + 2], pk[4 * k + 3]);
            if (p == 6) { __syncwarp(); if (lane == 0) mbar_arrive(sb + BAR_REDDONE + 8 * w); }
          } else {
#pragma unroll
            for (int k = 0; k < 4; k++) st_relaxed4(gt + ((j + 7) & 7) * 128 + k * 1024, pk[4 * k] & ~1u, pk[4 * k + 1], pk[4 * k + 2], pk[4 * k + 3]);
          }
        }
        PROF2(pb + 18);
        const uint4 *in = ib + j * INBOX, *pin = gt + j * 128;
        const uint2* in9 = (const uint2*)(in + 512) - t;
        asm volatile("" : "+l"(in), "+l"(pin), "+l"(in9));
        const float2 r2 = lds64(sb + SM_KEEP + tid_ * 8);
        uint2 X9;
        {
          uint4 X[4];
          const uint4* box = gt + 4608;
#pragma unroll
          for (int k = 0; k < 4; k++) X[k] = ld_relaxed4(box + 256 * j + ((k & 1) + 8 * (k & 2)) * 128);
          X9 = ld_relaxed2((const uint2*)(box + (32 + (j >> 1)) * 128) + (j & 1));
          const float i0 = rcp(r2.x), i1 = rcp(r2.y);
#pragma unroll
          for (int k = 0; k < 4; k++) {
            const float f = k & 1 ? i1 : i0;
            float* e = d + 8 * (k & 2) + 2 * (k & 1);
            X[k].x ^= (lsb >> k) & 1;
            e[0] = bf_lo(X[k].x) * f; e[1] = bf_hi(X[k].x) * f; e[4] = bf_lo(X[k].y) * f; e[5] = bf_hi(X[k].y) * f;
            e[8] = bf_lo(X[k].z) * f; e[9] = bf_hi(X[k].z) * f; e[12] = bf_lo(X[k].w) * f; e[13] = bf_hi(X[k].w) * f;
          }
        }
        uint4 R[4], P[4];
        uint2 R9;
        PROF2(pb + 19);
        pass(0, true, [&] {
          mbar_wait_c(sb + BAR_RREADY + 8 * w, layer);
#pragma unroll
          for (int k = 0; k < 4; k++) R[k] = ld_relaxed4(in + k * 128);
          R9 = ld_relaxed2(in9);
#pragma unroll
          for (int k = 0; k < 4; k++) P[k] = ld_relaxed4(pin + k * 1024);
        });
        const uint32_t zero = late(sb + BAR_FULLX + 64, 0);
        while (__any_sync(0xffffffffu, (chk2(P[0].x, P[1].x, zero) | chk2(P[2].x, P[3].x, zero)) & 1)) {
#pragma unroll
          for (int k = 0; k < 4; k++) P[k] = ld_relaxed4(pin + k * 1024);
        }
#pragma unroll
        for (int k = 0; k < 4; k++) {
          const uint32_t u[4] = {hadd2(R[k].x, P[k].x), hadd2(R[k].y, P[k].y), hadd2(R[k].z, P[k].z), hadd2(R[k].w, P[k].w)};
#pragma unroll
          for (int i = 0; i < 4; i++) { v[8 * k + 2 * i] = bf_lo(u[i]); v[8 * k + 2 * i + 1] = bf_hi(u[i]); }
        }
        X9.x = chk(zero, X9.x, lsb >> 4);
        v[32] = fmaf(bf_lo(R9.x), r2.x, bf_lo(X9.x)); v[33] = fmaf(bf_hi(R9.x), r2.x, bf_hi(X9.x));
        v[34] = fmaf(bf_lo(R9.y), r2.y, bf_lo(X9.y)); v[35] = fmaf(bf_hi(R9.y), r2.y, bf_hi(X9.y));
        PROF2(pb + 20);
        wg_wait<0>();
        c.release2(BAR_EMPTYX + 40);
        PROF2(pb + 21);
#pragma unroll
        for (int i = 0; i < 32; i++) v[i] = (v[i] + d[i]) * (i & 2 ? r2.y : r2.x);
      }
      if (layer == NLAYERS - 1) break;
    }
    {
      THREAD_IDS();
      const uint32_t stg = sb + SM_B + warp * 4096;
      const uint32_t sd = stg + (lane & 15) * 128;
#pragma unroll
      for (int i = 0; i < 4; i++)
        stsm4(sd + (((2 * i + (lane >> 4)) ^ (lane & 7)) << 4), pack_bf16(v[8 * i], v[8 * i + 1]), pack_bf16(v[8 * i + 2], v[8 * i + 3]),
              pack_bf16(v[8 * i + 4], v[8 * i + 5]), pack_bf16(v[8 * i + 6], v[8 * i + 7]));
      stsm2(stg + 2048 + (lane & 15) * 16, pack_bf16(v[32], v[33]), pack_bf16(v[34], v[35]));
      fence_async_smem();
      __syncwarp();
      if (lane == 0) {
        tma_store3d(&maps.out, stg, 64 * j, w, 64 * rb + 16 * wp);
        tma_store3d(&maps.outc, stg + 2048, 512 + 8 * j, w, 64 * rb + 16 * wp);
        bulk_commit();
        if (wp == 0) st_relaxed(G->flag + 32 + 32 * j, xtag);
        bulk_wait_all();
        mbar_arrive(sb + BAR_DONE + 8 * w);
      }
      PROF(61);
    }
    __syncwarp();
    cluster_sync();
  }
}

typedef CUresult (*EncFn)(CUtensorMap*, CUtensorMapDataType, cuuint32_t, void*, const cuuint64_t*, const cuuint64_t*, const cuuint32_t*,
                          const cuuint32_t*, CUtensorMapInterleave, CUtensorMapSwizzle, CUtensorMapL2promotion, CUtensorMapFloatOOBfill);

void make_map(EncFn enc, CUtensorMap* m, const void* p, int rank, uint64_t d0, uint64_t d1, uint64_t d2, uint64_t s1, uint64_t s2, uint32_t b0,
              uint32_t b1, uint32_t b2, CUtensorMapSwizzle sw) {
  cuuint64_t gd[3] = {d0, d1, d2};
  cuuint64_t gs[2] = {s1, s2};
  cuuint32_t bd[3] = {b0, b1, b2};
  cuuint32_t es[3] = {1, 1, 1};
  enc(m, CU_TENSOR_MAP_DATA_TYPE_BFLOAT16, rank, const_cast<void*>(p), gd, gs, bd, es, CU_TENSOR_MAP_INTERLEAVE_NONE, sw,
      CU_TENSOR_MAP_L2_PROMOTION_L2_128B, CU_TENSOR_MAP_FLOAT_OOB_FILL_NONE);
}

}

extern "C" void kernel_launch(void* const* d_in, const int* in_sizes, int n_in, void* d_out, int out_size) {
  const __nv_bfloat16* x = (const __nv_bfloat16*)d_in[0];
  const char *wqkv = (const char*)d_in[1], *wo = (const char*)d_in[2], *wg = (const char*)d_in[4], *wu = (const char*)d_in[5], *wd = (const char*)d_in[6];
  static EncFn enc = nullptr;
  static Group* ws = nullptr;
  if (!enc) {
    cudaDriverEntryPointQueryResult qr;
    cudaGetDriverEntryPoint("cuTensorMapEncodeTiled", (void**)&enc, cudaEnableDefault, &qr);
    cudaGetSymbolAddress((void**)&ws, g_ws);
    cudaFuncSetAttribute(fused_kernel, cudaFuncAttributeMaxDynamicSharedMemorySize, SMEM_BYTES);
  }
  const CUtensorMapSwizzle S0 = CU_TENSOR_MAP_SWIZZLE_NONE, S64 = CU_TENSOR_MAP_SWIZZLE_64B, S128 = CU_TENSOR_MAP_SWIZZLE_128B;
  Maps m;
  make_map(enc, &m.x, x, 3, 576, 2, 1024, 1152, 2304, 64, 1, 64, S128);
  make_map(enc, &m.qm, wqkv, 3, 576, 576, 3, 3456, 1152, 64, 16, 3, S128);
  make_map(enc, &m.qc, wqkv, 3, 576, 576, 3, 3456, 1152, 8, 16, 3, S0);
  make_map(enc, &m.o, wo, 2, 576, 576, 1, 1152, 0, 64, 72, 1, S128);
  make_map(enc, &m.oc, wo, 2, 576, 576, 1, 1152, 0, 8, 144, 1, S0);
  make_map(enc, &m.g, wg, 3, 64, 576, 72, 9216, 128, 64, 32, 2, S128);
  make_map(enc, &m.u, wu, 3, 64, 576, 72, 9216, 128, 64, 32, 2, S128);
  make_map(enc, &m.g3, wg, 3, 32, 576, 144, 9216, 64, 32, 32, 3, S64);
  make_map(enc, &m.u3, wu, 3, 32, 576, 144, 9216, 64, 32, 32, 3, S64);
  make_map(enc, &m.d, wd, 2, 576, 4608, 1, 1152, 0, 64, 72, 1, S128);
  make_map(enc, &m.out, d_out, 3, 576, 2, 1024, 1152, 2304, 64, 1, 16, S128);
  make_map(enc, &m.outc, d_out, 3, 576, 2, 1024, 1152, 2304, 8, 1, 16, S0);
  fused_kernel<<<NCTA, 384, SMEM_BYTES>>>(x, ws, wqkv, wg, wu, wd, m, wo);
}
```

```cpp
#include <cuda_runtime.h>
#include <cuda_bf16.h>
#include <cuda.h>
#include <stdint.h>
#include <stddef.h>

namespace {

constexpr int D_ = 576;
constexpr int NCTA = 128;
#define NLAYERS 2
#define W_POLICY policy_evict_first
#define A_POLICY policy_evict_normal
#define OPEN 1
#define PFMODE 5
#define WWIN 4
#define WOREL -1
#define WB1 11
#define WB2 21
#define WB3 32
#define WPROBE 1
#define WPROBE2 0
#define SPEC 2
#define POLLFIRST 0
#define SUMFIRST 1
#define EARLYPOLL 1
#define LEAD 0
#define ATTBAR 0
#define GL 18
#define WOBAR 0
#define QD 0
#define QG 4
#define PFQ 1
#define XDELAY 0
#define WOH 1
#define PFSLEEP 700
#define GPCMAP 1
#define PFF 1
#define REDN 1
#define CLRSLEEP 300
#define OPENL 24
#define FG -1
#define NON8 0
#define HMUL 1
#define FCH 1
#define PPK 34
#define RHOOK 0
#define SCHEDBAR 1
#define QH 5
#define XH 3
#define XP 2
#define GSLEEP 32
#define XCH 1
#define MAPPF 1
#define XREL 8
#define WOG 13
#define BREL 1
#define FENCE1 0
#define OWNX 0
#define OWNBAR 1
#define EARLY 1
#define ESPEC 0
#define TESTP 0
#define WOW 1
#define NSPILL 4
#define REGS_C 232
#define REGS_P 40
#define STR2(x) #x
#define STR(x) STR2(x)
constexpr uint32_t SM_X = 0;
constexpr uint32_t XSLOT = 18432;
constexpr uint32_t SM_WOC = SM_X + 3 * XSLOT + 9216;
constexpr uint32_t SM_B = 147456;
constexpr uint32_t BSLOT = 16384;
constexpr uint32_t SM_KEEP = 229376;
constexpr uint32_t SM_WSUM = SM_KEEP + 512;
constexpr uint32_t SM_BAR = SM_KEEP + 2048;
constexpr uint32_t BAR_FULLB = SM_BAR;
constexpr uint32_t BAR_RREADY = SM_BAR + 40;
constexpr uint32_t BAR_CLR = SM_BAR + 56;
constexpr uint32_t BAR_FULLX = SM_BAR + 72;
constexpr uint32_t BAR_EMPTYB = SM_BAR + 144;
constexpr uint32_t BAR_EMPTYX = SM_BAR + 184;
constexpr uint32_t BAR_REDDONE = SM_BAR + 248;
constexpr uint32_t BAR_DONE = SM_BAR + 264;
constexpr uint32_t BAR_WSUM = SM_BAR + 280;
constexpr uint32_t SM_PROG = SM_BAR + 288;
constexpr uint32_t SMEM_BYTES = SM_BAR + 1024;

struct Maps { CUtensorMap x, qm, qc, o, oc, g, u, g3, u3, d, out, outc; };

constexpr int INBOX = 576;
struct Group {
  uint2 sum[4 * 8 * 8];
  uint2 sq[4 * 8 * 8];
  uint32_t wsum[512];
  uint32_t flag[512];
  uint4 halo[8 * 160];
  uint4 obox[36 * 128];
  uint4 xbox[36 * 128];
  uint4 inbox[2][8 * INBOX];
};
__device__ __align__(1024) Group g_ws[32];
#define PROF(i)
#define PROFX(i)

#define PROF2(i) PROF(i)

struct Desc { uint32_t lo, hi; };
__device__ __forceinline__ constexpr Desc desc_hi(uint32_t lbo, uint32_t sbo, uint32_t sw) { return Desc{(lbo >> 4) << 16, (sbo >> 4) | sw << 30}; }
__device__ __forceinline__ constexpr Desc operator+(Desc d, uint32_t a) { return Desc{d.lo + a, d.hi}; }

template<int N> __device__ __forceinline__ void wgmma_ss(float (&d)[N / 2], Desc da, Desc db, int sc);
template<> __device__ __forceinline__ void wgmma_ss<192>(float (&d)[96], Desc da, Desc db, int sc) {
  asm volatile("{\n.reg .pred p;\n.reg .b64 a, b;\nsetp.ne.b32 p, %100, 0;\nmov.b64 a, {%96, %97};\nmov.b64 b, {%98, %99};\n"
    "wgmma.mma_async.sync.aligned.m64n192k16.f32.bf16.bf16 {%0,%1,%2,%3,%4,%5,%6,%7,%8,%9,%10,%11,%12,%13,%14,%15,%16,%17,%18,%19,%20,%21,%22,%23,%24,%25,%26,%27,%28,%29,%30,%31,%32,%33,%34,%35,%36,%37,%38,%39,%40,%41,%42,%43,%44,%45,%46,%47,%48,%49,%50,%51,%52,%53,%54,%55,%56,%57,%58,%59,%60,%61,%62,%63,%64,%65,%66,%67,%68,%69,%70,%71,%72,%73,%74,%75,%76,%77,%78,%79,%80,%81,%82,%83,%84,%85,%86,%87,%88,%89,%90,%91,%92,%93,%94,%95}, a, b, p, 1, 1, 0, 1;\n}\n"
    : "+f"(d[0]),"+f"(d[1]),"+f"(d[2]),"+f"(d[3]),"+f"(d[4]),"+f"(d[5]),"+f"(d[6]),"+f"(d[7]),"+f"(d[8]),"+f"(d[9]),"+f"(d[10]),"+f"(d[11]),"+f"(d[12]),"+f"(d[13]),"+f"(d[14]),"+f"(d[15]),"+f"(d[16]),"+f"(d[17]),"+f"(d[18]),"+f"(d[19]),"+f"(d[20]),"+f"(d[21]),"+f"(d[22]),"+f"(d[23]),"+f"(d[24]),"+f"(d[25]),"+f"(d[26]),"+f"(d[27]),"+f"(d[28]),"+f"(d[29]),"+f"(d[30]),"+f"(d[31]),"+f"(d[32]),"+f"(d[33]),"+f"(d[34]),"+f"(d[35]),"+f"(d[36]),"+f"(d[37]),"+f"(d[38]),"+f"(d[39]),"+f"(d[40]),"+f"(d[41]),"+f"(d[42]),"+f"(d[43]),"+f"(d[44]),"+f"(d[45]),"+f"(d[46]),"+f"(d[47]),"+f"(d[48]),"+f"(d[49]),"+f"(d[50]),"+f"(d[51]),"+f"(d[52]),"+f"(d[53]),"+f"(d[54]),"+f"(d[55]),"+f"(d[56]),"+f"(d[57]),"+f"(d[58]),"+f"(d[59]),"+f"(d[60]),"+f"(d[61]),"+f"(d[62]),"+f"(d[63]),"+f"(d[64]),"+f"(d[65]),"+f"(d[66]),"+f"(d[67]),"+f"(d[68]),"+f"(d[69]),"+f"(d[70]),"+f"(d[71]),"+f"(d[72]),"+f"(d[73]),"+f"(d[74]),"+f"(d[75]),"+f"(d[76]),"+f"(d[77]),"+f"(d[78]),"+f"(d[79]),"+f"(d[80]),"+f"(d[81]),"+f"(d[82]),"+f"(d[83]),"+f"(d[84]),"+f"(d[85]),"+f"(d[86]),"+f"(d[87]),"+f"(d[88]),"+f"(d[89]),"+f"(d[90]),"+f"(d[91]),"+f"(d[92]),"+f"(d[93]),"+f"(d[94]),"+f"(d[95]) : "r"(da.lo), "r"(da.hi), "r"(db.lo), "r"(db.hi), "r"(sc));
}
template<> __device__ __forceinline__ void wgmma_ss<256>(float (&d)[128], Desc da, Desc db, int sc) {
  asm volatile("{\n.reg .pred p;\n.reg .b64 a, b;\nsetp.ne.b32 p, %132, 0;\nmov.b64 a, {%128, %129};\nmov.b64 b, {%130, %131};\n"
    "wgmma.mma_async.sync.aligned.m64n256k16.f32.bf16.bf16 {%0,%1,%2,%3,%4,%5,%6,%7,%8,%9,%10,%11,%12,%13,%14,%15,%16,%17,%18,%19,%20,%21,%22,%23,%24,%25,%26,%27,%28,%29,%30,%31,%32,%33,%34,%35,%36,%37,%38,%39,%40,%41,%42,%43,%44,%45,%46,%47,%48,%49,%50,%51,%52,%53,%54,%55,%56,%57,%58,%59,%60,%61,%62,%63,%64,%65,%66,%67,%68,%69,%70,%71,%72,%73,%74,%75,%76,%77,%78,%79,%80,%81,%82,%83,%84,%85,%86,%87,%88,%89,%90,%91,%92,%93,%94,%95,%96,%97,%98,%99,%100,%101,%102,%103,%104,%105,%106,%107,%108,%109,%110,%111,%112,%113,%114,%115,%116,%117,%118,%119,%120,%121,%122,%123,%124,%125,%126,%127}, a, b, p, 1, 1, 0, 1;\n}\n"
    : "+f"(d[0]),"+f"(d[1]),"+f"(d[2]),"+f"(d[3]),"+f"(d[4]),"+f"(d[5]),"+f"(d[6]),"+f"(d[7]),"+f"(d[8]),"+f"(d[9]),"+f"(d[10]),"+f"(d[11]),"+f"(d[12]),"+f"(d[13]),"+f"(d[14]),"+f"(d[15]),"+f"(d[16]),"+f"(d[17]),"+f"(d[18]),"+f"(d[19]),"+f"(d[20]),"+f"(d[21]),"+f"(d[22]),"+f"(d[23]),"+f"(d[24]),"+f"(d[25]),"+f"(d[26]),"+f"(d[27]),"+f"(d[28]),"+f"(d[29]),"+f"(d[30]),"+f"(d[31]),"+f"(d[32]),"+f"(d[33]),"+f"(d[34]),"+f"(d[35]),"+f"(d[36]),"+f"(d[37]),"+f"(d[38]),"+f"(d[39]),"+f"(d[40]),"+f"(d[41]),"+f"(d[42]),"+f"(d[43]),"+f"(d[44]),"+f"(d[45]),"+f"(d[46]),"+f"(d[47]),"+f"(d[48]),"+f"(d[49]),"+f"(d[50]),"+f"(d[51]),"+f"(d[52]),"+f"(d[53]),"+f"(d[54]),"+f"(d[55]),"+f"(d[56]),"+f"(d[57]),"+f"(d[58]),"+f"(d[59]),"+f"(d[60]),"+f"(d[61]),"+f"(d[62]),"+f"(d[63]),"+f"(d[64]),"+f"(d[65]),"+f"(d[66]),"+f"(d[67]),"+f"(d[68]),"+f"(d[69]),"+f"(d[70]),"+f"(d[71]),"+f"(d[72]),"+f"(d[73]),"+f"(d[74]),"+f"(d[75]),"+f"(d[76]),"+f"(d[77]),"+f"(d[78]),"+f"(d[79]),"+f"(d[80]),"+f"(d[81]),"+f"(d[82]),"+f"(d[83]),"+f"(d[84]),"+f"(d[85]),"+f"(d[86]),"+f"(d[87]),"+f"(d[88]),"+f"(d[89]),"+f"(d[90]),"+f"(d[91]),"+f"(d[92]),"+f"(d[93]),"+f"(d[94]),"+f"(d[95]),"+f"(d[96]),"+f"(d[97]),"+f"(d[98]),"+f"(d[99]),"+f"(d[100]),"+f"(d[101]),"+f"(d[102]),"+f"(d[103]),"+f"(d[104]),"+f"(d[105]),"+f"(d[106]),"+f"(d[107]),"+f"(d[108]),"+f"(d[109]),"+f"(d[110]),"+f"(d[111]),"+f"(d[112]),"+f"(d[113]),"+f"(d[114]),"+f"(d[115]),"+f"(d[116]),"+f"(d[117]),"+f"(d[118]),"+f"(d[119]),"+f"(d[120]),"+f"(d[121]),"+f"(d[122]),"+f"(d[123]),"+f"(d[124]),"+f"(d[125]),"+f"(d[126]),"+f"(d[127]) : "r"(da.lo), "r"(da.hi), "r"(db.lo), "r"(db.hi), "r"(sc));
}
template<int N, int ACC> __device__ __forceinline__ void wgmma_rs(float (&d)[N / 2], const uint4& a, Desc db);
template<> __device__ __forceinline__ void wgmma_rs<8, 1>(float (&d)[4], const uint4& a, Desc db) {
  asm volatile("{\n.reg .pred p;\n.reg .b64 b;\nsetp.ne.b32 p, 1, 0;\nmov.b64 b, {%8, %9};\n"
    "wgmma.mma_async.sync.aligned.m64n8k16.f32.bf16.bf16 {%0,%1,%2,%3}, {%4,%5,%6,%7}, b, p, 1, 1, 1;\n}\n"
    : "+f"(d[0]),"+f"(d[1]),"+f"(d[2]),"+f"(d[3]) : "r"(a.x), "r"(a.y), "r"(a.z), "r"(a.w), "r"(db.lo), "r"(db.hi));
}
template<> __device__ __forceinline__ void wgmma_rs<8, 0>(float (&d)[4], const uint4& a, Desc db) {
  asm volatile("{\n.reg .pred p;\n.reg .b64 b;\nsetp.ne.b32 p, 0, 0;\nmov.b64 b, {%8, %9};\n"
    "wgmma.mma_async.sync.aligned.m64n8k16.f32.bf16.bf16 {%0,%1,%2,%3}, {%4,%5,%6,%7}, b, p, 1, 1, 1;\n}\n"
    : "=f"(d[0]),"=f"(d[1]),"=f"(d[2]),"=f"(d[3]) : "r"(a.x), "r"(a.y), "r"(a.z), "r"(a.w), "r"(db.lo), "r"(db.hi));
}
template<> __device__ __forceinline__ void wgmma_rs<24, 1>(float (&d)[12], const uint4& a, Desc db) {
  asm volatile("{\n.reg .pred p;\n.reg .b64 b;\nsetp.ne.b32 p, 1, 0;\nmov.b64 b, {%16, %17};\n"
    "wgmma.mma_async.sync.aligned.m64n24k16.f32.bf16.bf16 {%0,%1,%2,%3,%4,%5,%6,%7,%8,%9,%10,%11}, {%12,%13,%14,%15}, b, p, 1, 1, 1;\n}\n"
    : "+f"(d[0]),"+f"(d[1]),"+f"(d[2]),"+f"(d[3]),"+f"(d[4]),"+f"(d[5]),"+f"(d[6]),"+f"(d[7]),"+f"(d[8]),"+f"(d[9]),"+f"(d[10]),"+f"(d[11]) : "r"(a.x), "r"(a.y), "r"(a.z), "r"(a.w), "r"(db.lo), "r"(db.hi));
}
template<> __device__ __forceinline__ void wgmma_rs<24, 0>(float (&d)[12], const uint4& a, Desc db) {
  asm volatile("{\n.reg .pred p;\n.reg .b64 b;\nsetp.ne.b32 p, 0, 0;\nmov.b64 b, {%16, %17};\n"
    "wgmma.mma_async.sync.aligned.m64n24k16.f32.bf16.bf16 {%0,%1,%2,%3,%4,%5,%6,%7,%8,%9,%10,%11}, {%12,%13,%14,%15}, b, p, 1, 1, 1;\n}\n"
    : "=f"(d[0]),"=f"(d[1]),"=f"(d[2]),"=f"(d[3]),"=f"(d[4]),"=f"(d[5]),"=f"(d[6]),"=f"(d[7]),"=f"(d[8]),"=f"(d[9]),"=f"(d[10]),"=f"(d[11]) : "r"(a.x), "r"(a.y), "r"(a.z), "r"(a.w), "r"(db.lo), "r"(db.hi));
}
template<> __device__ __forceinline__ void wgmma_rs<64, 1>(float (&d)[32], const uint4& a, Desc db) {
  asm volatile("{\n.reg .pred p;\n.reg .b64 b;\nsetp.ne.b32 p, 1, 0;\nmov.b64 b, {%36, %37};\n"
    "wgmma.mma_async.sync.aligned.m64n64k16.f32.bf16.bf16 {%0,%1,%2,%3,%4,%5,%6,%7,%8,%9,%10,%11,%12,%13,%14,%15,%16,%17,%18,%19,%20,%21,%22,%23,%24,%25,%26,%27,%28,%29,%30,%31}, {%32,%33,%34,%35}, b, p, 1, 1, 1;\n}\n"
    : "+f"(d[0]),"+f"(d[1]),"+f"(d[2]),"+f"(d[3]),"+f"(d[4]),"+f"(d[5]),"+f"(d[6]),"+f"(d[7]),"+f"(d[8]),"+f"(d[9]),"+f"(d[10]),"+f"(d[11]),"+f"(d[12]),"+f"(d[13]),"+f"(d[14]),"+f"(d[15]),"+f"(d[16]),"+f"(d[17]),"+f"(d[18]),"+f"(d[19]),"+f"(d[20]),"+f"(d[21]),"+f"(d[22]),"+f"(d[23]),"+f"(d[24]),"+f"(d[25]),"+f"(d[26]),"+f"(d[27]),"+f"(d[28]),"+f"(d[29]),"+f"(d[30]),"+f"(d[31]) : "r"(a.x), "r"(a.y), "r"(a.z), "r"(a.w), "r"(db.lo), "r"(db.hi));
}
template<> __device__ __forceinline__ void wgmma_rs<64, 0>(float (&d)[32], const uint4& a, Desc db) {
  asm volatile("{\n.reg .pred p;\n.reg .b64 b;\nsetp.ne.b32 p, 0, 0;\nmov.b64 b, {%36, %37};\n"
    "wgmma.mma_async.sync.aligned.m64n64k16.f32.bf16.bf16 {%0,%1,%2,%3,%4,%5,%6,%7,%8,%9,%10,%11,%12,%13,%14,%15,%16,%17,%18,%19,%20,%21,%22,%23,%24,%25,%26,%27,%28,%29,%30,%31}, {%32,%33,%34,%35}, b, p, 1, 1, 1;\n}\n"
    : "=f"(d[0]),"=f"(d[1]),"=f"(d[2]),"=f"(d[3]),"=f"(d[4]),"=f"(d[5]),"=f"(d[6]),"=f"(d[7]),"=f"(d[8]),"=f"(d[9]),"=f"(d[10]),"=f"(d[11]),"=f"(d[12]),"=f"(d[13]),"=f"(d[14]),"=f"(d[15]),"=f"(d[16]),"=f"(d[17]),"=f"(d[18]),"=f"(d[19]),"=f"(d[20]),"=f"(d[21]),"=f"(d[22]),"=f"(d[23]),"=f"(d[24]),"=f"(d[25]),"=f"(d[26]),"=f"(d[27]),"=f"(d[28]),"=f"(d[29]),"=f"(d[30]),"=f"(d[31]) : "r"(a.x), "r"(a.y), "r"(a.z), "r"(a.w), "r"(db.lo), "r"(db.hi));
}
template<> __device__ __forceinline__ void wgmma_rs<192, 1>(float (&d)[96], const uint4& a, Desc db) {
  asm volatile("{\n.reg .pred p;\n.reg .b64 b;\nsetp.ne.b32 p, 1, 0;\nmov.b64 b, {%100, %101};\n"
    "wgmma.mma_async.sync.aligned.m64n192k16.f32.bf16.bf16 {%0,%1,%2,%3,%4,%5,%6,%7,%8,%9,%10,%11,%12,%13,%14,%15,%16,%17,%18,%19,%20,%21,%22,%23,%24,%25,%26,%27,%28,%29,%30,%31,%32,%33,%34,%35,%36,%37,%38,%39,%40,%41,%42,%43,%44,%45,%46,%47,%48,%49,%50,%51,%52,%53,%54,%55,%56,%57,%58,%59,%60,%61,%62,%63,%64,%65,%66,%67,%68,%69,%70,%71,%72,%73,%74,%75,%76,%77,%78,%79,%80,%81,%82,%83,%84,%85,%86,%87,%88,%89,%90,%91,%92,%93,%94,%95}, {%96,%97,%98,%99}, b, p, 1, 1, 1;\n}\n"
    : "+f"(d[0]),"+f"(d[1]),"+f"(d[2]),"+f"(d[3]),"+f"(d[4]),"+f"(d[5]),"+f"(d[6]),"+f"(d[7]),"+f"(d[8]),"+f"(d[9]),"+f"(d[10]),"+f"(d[11]),"+f"(d[12]),"+f"(d[13]),"+f"(d[14]),"+f"(d[15]),"+f"(d[16]),"+f"(d[17]),"+f"(d[18]),"+f"(d[19]),"+f"(d[20]),"+f"(d[21]),"+f"(d[22]),"+f"(d[23]),"+f"(d[24]),"+f"(d[25]),"+f"(d[26]),"+f"(d[27]),"+f"(d[28]),"+f"(d[29]),"+f"(d[30]),"+f"(d[31]),"+f"(d[32]),"+f"(d[33]),"+f"(d[34]),"+f"(d[35]),"+f"(d[36]),"+f"(d[37]),"+f"(d[38]),"+f"(d[39]),"+f"(d[40]),"+f"(d[41]),"+f"(d[42]),"+f"(d[43]),"+f"(d[44]),"+f"(d[45]),"+f"(d[46]),"+f"(d[47]),"+f"(d[48]),"+f"(d[49]),"+f"(d[50]),"+f"(d[51]),"+f"(d[52]),"+f"(d[53]),"+f"(d[54]),"+f"(d[55]),"+f"(d[56]),"+f"(d[57]),"+f"(d[58]),"+f"(d[59]),"+f"(d[60]),"+f"(d[61]),"+f"(d[62]),"+f"(d[63]),"+f"(d[64]),"+f"(d[65]),"+f"(d[66]),"+f"(d[67]),"+f"(d[68]),"+f"(d[69]),"+f"(d[70]),"+f"(d[71]),"+f"(d[72]),"+f"(d[73]),"+f"(d[74]),"+f"(d[75]),"+f"(d[76]),"+f"(d[77]),"+f"(d[78]),"+f"(d[79]),"+f"(d[80]),"+f"(d[81]),"+f"(d[82]),"+f"(d[83]),"+f"(d[84]),"+f"(d[85]),"+f"(d[86]),"+f"(d[87]),"+f"(d[88]),"+f"(d[89]),"+f"(d[90]),"+f"(d[91]),"+f"(d[92]),"+f"(d[93]),"+f"(d[94]),"+f"(d[95]) : "r"(a.x), "r"(a.y), "r"(a.z), "r"(a.w), "r"(db.lo), "r"(db.hi));
}
template<> __device__ __forceinline__ void wgmma_rs<192, 0>(float (&d)[96], const uint4& a, Desc db) {
  asm volatile("{\n.reg .pred p;\n.reg .b64 b;\nsetp.ne.b32 p, 0, 0;\nmov.b64 b, {%100, %101};\n"
    "wgmma.mma_async.sync.aligned.m64n192k16.f32.bf16.bf16 {%0,%1,%2,%3,%4,%5,%6,%7,%8,%9,%10,%11,%12,%13,%14,%15,%16,%17,%18,%19,%20,%21,%22,%23,%24,%25,%26,%27,%28,%29,%30,%31,%32,%33,%34,%35,%36,%37,%38,%39,%40,%41,%42,%43,%44,%45,%46,%47,%48,%49,%50,%51,%52,%53,%54,%55,%56,%57,%58,%59,%60,%61,%62,%63,%64,%65,%66,%67,%68,%69,%70,%71,%72,%73,%74,%75,%76,%77,%78,%79,%80,%81,%82,%83,%84,%85,%86,%87,%88,%89,%90,%91,%92,%93,%94,%95}, {%96,%97,%98,%99}, b, p, 1, 1, 1;\n}\n"
    : "=f"(d[0]),"=f"(d[1]),"=f"(d[2]),"=f"(d[3]),"=f"(d[4]),"=f"(d[5]),"=f"(d[6]),"=f"(d[7]),"=f"(d[8]),"=f"(d[9]),"=f"(d[10]),"=f"(d[11]),"=f"(d[12]),"=f"(d[13]),"=f"(d[14]),"=f"(d[15]),"=f"(d[16]),"=f"(d[17]),"=f"(d[18]),"=f"(d[19]),"=f"(d[20]),"=f"(d[21]),"=f"(d[22]),"=f"(d[23]),"=f"(d[24]),"=f"(d[25]),"=f"(d[26]),"=f"(d[27]),"=f"(d[28]),"=f"(d[29]),"=f"(d[30]),"=f"(d[31]),"=f"(d[32]),"=f"(d[33]),"=f"(d[34]),"=f"(d[35]),"=f"(d[36]),"=f"(d[37]),"=f"(d[38]),"=f"(d[39]),"=f"(d[40]),"=f"(d[41]),"=f"(d[42]),"=f"(d[43]),"=f"(d[44]),"=f"(d[45]),"=f"(d[46]),"=f"(d[47]),"=f"(d[48]),"=f"(d[49]),"=f"(d[50]),"=f"(d[51]),"=f"(d[52]),"=f"(d[53]),"=f"(d[54]),"=f"(d[55]),"=f"(d[56]),"=f"(d[57]),"=f"(d[58]),"=f"(d[59]),"=f"(d[60]),"=f"(d[61]),"=f"(d[62]),"=f"(d[63]),"=f"(d[64]),"=f"(d[65]),"=f"(d[66]),"=f"(d[67]),"=f"(d[68]),"=f"(d[69]),"=f"(d[70]),"=f"(d[71]),"=f"(d[72]),"=f"(d[73]),"=f"(d[74]),"=f"(d[75]),"=f"(d[76]),"=f"(d[77]),"=f"(d[78]),"=f"(d[79]),"=f"(d[80]),"=f"(d[81]),"=f"(d[82]),"=f"(d[83]),"=f"(d[84]),"=f"(d[85]),"=f"(d[86]),"=f"(d[87]),"=f"(d[88]),"=f"(d[89]),"=f"(d[90]),"=f"(d[91]),"=f"(d[92]),"=f"(d[93]),"=f"(d[94]),"=f"(d[95]) : "r"(a.x), "r"(a.y), "r"(a.z), "r"(a.w), "r"(db.lo), "r"(db.hi));
}
template<> __device__ __forceinline__ void wgmma_rs<256, 1>(float (&d)[128], const uint4& a, Desc db) {
  asm volatile("{\n.reg .pred p;\n.reg .b64 b;\nsetp.ne.b32 p, 1, 0;\nmov.b64 b, {%132, %133};\n"
    "wgmma.mma_async.sync.aligned.m64n256k16.f32.bf16.bf16 {%0,%1,%2,%3,%4,%5,%6,%7,%8,%9,%10,%11,%12,%13,%14,%15,%16,%17,%18,%19,%20,%21,%22,%23,%24,%25,%26,%27,%28,%29,%30,%31,%32,%33,%34,%35,%36,%37,%38,%39,%40,%41,%42,%43,%44,%45,%46,%47,%48,%49,%50,%51,%52,%53,%54,%55,%56,%57,%58,%59,%60,%61,%62,%63,%64,%65,%66,%67,%68,%69,%70,%71,%72,%73,%74,%75,%76,%77,%78,%79,%80,%81,%82,%83,%84,%85,%86,%87,%88,%89,%90,%91,%92,%93,%94,%95,%96,%97,%98,%99,%100,%101,%102,%103,%104,%105,%106,%107,%108,%109,%110,%111,%112,%113,%114,%115,%116,%117,%118,%119,%120,%121,%122,%123,%124,%125,%126,%127}, {%128,%129,%130,%131}, b, p, 1, 1, 1;\n}\n"
    : "+f"(d[0]),"+f"(d[1]),"+f"(d[2]),"+f"(d[3]),"+f"(d[4]),"+f"(d[5]),"+f"(d[6]),"+f"(d[7]),"+f"(d[8]),"+f"(d[9]),"+f"(d[10]),"+f"(d[11]),"+f"(d[12]),"+f"(d[13]),"+f"(d[14]),"+f"(d[15]),"+f"(d[16]),"+f"(d[17]),"+f"(d[18]),"+f"(d[19]),"+f"(d[20]),"+f"(d[21]),"+f"(d[22]),"+f"(d[23]),"+f"(d[24]),"+f"(d[25]),"+f"(d[26]),"+f"(d[27]),"+f"(d[28]),"+f"(d[29]),"+f"(d[30]),"+f"(d[31]),"+f"(d[32]),"+f"(d[33]),"+f"(d[34]),"+f"(d[35]),"+f"(d[36]),"+f"(d[37]),"+f"(d[38]),"+f"(d[39]),"+f"(d[40]),"+f"(d[41]),"+f"(d[42]),"+f"(d[43]),"+f"(d[44]),"+f"(d[45]),"+f"(d[46]),"+f"(d[47]),"+f"(d[48]),"+f"(d[49]),"+f"(d[50]),"+f"(d[51]),"+f"(d[52]),"+f"(d[53]),"+f"(d[54]),"+f"(d[55]),"+f"(d[56]),"+f"(d[57]),"+f"(d[58]),"+f"(d[59]),"+f"(d[60]),"+f"(d[61]),"+f"(d[62]),"+f"(d[63]),"+f"(d[64]),"+f"(d[65]),"+f"(d[66]),"+f"(d[67]),"+f"(d[68]),"+f"(d[69]),"+f"(d[70]),"+f"(d[71]),"+f"(d[72]),"+f"(d[73]),"+f"(d[74]),"+f"(d[75]),"+f"(d[76]),"+f"(d[77]),"+f"(d[78]),"+f"(d[79]),"+f"(d[80]),"+f"(d[81]),"+f"(d[82]),"+f"(d[83]),"+f"(d[84]),"+f"(d[85]),"+f"(d[86]),"+f"(d[87]),"+f"(d[88]),"+f"(d[89]),"+f"(d[90]),"+f"(d[91]),"+f"(d[92]),"+f"(d[93]),"+f"(d[94]),"+f"(d[95]),"+f"(d[96]),"+f"(d[97]),"+f"(d[98]),"+f"(d[99]),"+f"(d[100]),"+f"(d[101]),"+f"(d[102]),"+f"(d[103]),"+f"(d[104]),"+f"(d[105]),"+f"(d[106]),"+f"(d[107]),"+f"(d[108]),"+f"(d[109]),"+f"(d[110]),"+f"(d[111]),"+f"(d[112]),"+f"(d[113]),"+f"(d[114]),"+f"(d[115]),"+f"(d[116]),"+f"(d[117]),"+f"(d[118]),"+f"(d[119]),"+f"(d[120]),"+f"(d[121]),"+f"(d[122]),"+f"(d[123]),"+f"(d[124]),"+f"(d[125]),"+f"(d[126]),"+f"(d[127]) : "r"(a.x), "r"(a.y), "r"(a.z), "r"(a.w), "r"(db.lo), "r"(db.hi));
}
template<> __device__ __forceinline__ void wgmma_rs<256, 0>(float (&d)[128], const uint4& a, Desc db) {
  asm volatile("{\n.reg .pred p;\n.reg .b64 b;\nsetp.ne.b32 p, 0, 0;\nmov.b64 b, {%132, %133};\n"
    "wgmma.mma_async.sync.aligned.m64n256k16.f32.bf16.bf16 {%0,%1,%2,%3,%4,%5,%6,%7,%8,%9,%10,%11,%12,%13,%14,%15,%16,%17,%18,%19,%20,%21,%22,%23,%24,%25,%26,%27,%28,%29,%30,%31,%32,%33,%34,%35,%36,%37,%38,%39,%40,%41,%42,%43,%44,%45,%46,%47,%48,%49,%50,%51,%52,%53,%54,%55,%56,%57,%58,%59,%60,%61,%62,%63,%64,%65,%66,%67,%68,%69,%70,%71,%72,%73,%74,%75,%76,%77,%78,%79,%80,%81,%82,%83,%84,%85,%86,%87,%88,%89,%90,%91,%92,%93,%94,%95,%96,%97,%98,%99,%100,%101,%102,%103,%104,%105,%106,%107,%108,%109,%110,%111,%112,%113,%114,%115,%116,%117,%118,%119,%120,%121,%122,%123,%124,%125,%126,%127}, {%128,%129,%130,%131}, b, p, 1, 1, 1;\n}\n"
    : "=f"(d[0]),"=f"(d[1]),"=f"(d[2]),"=f"(d[3]),"=f"(d[4]),"=f"(d[5]),"=f"(d[6]),"=f"(d[7]),"=f"(d[8]),"=f"(d[9]),"=f"(d[10]),"=f"(d[11]),"=f"(d[12]),"=f"(d[13]),"=f"(d[14]),"=f"(d[15]),"=f"(d[16]),"=f"(d[17]),"=f"(d[18]),"=f"(d[19]),"=f"(d[20]),"=f"(d[21]),"=f"(d[22]),"=f"(d[23]),"=f"(d[24]),"=f"(d[25]),"=f"(d[26]),"=f"(d[27]),"=f"(d[28]),"=f"(d[29]),"=f"(d[30]),"=f"(d[31]),"=f"(d[32]),"=f"(d[33]),"=f"(d[34]),"=f"(d[35]),"=f"(d[36]),"=f"(d[37]),"=f"(d[38]),"=f"(d[39]),"=f"(d[40]),"=f"(d[41]),"=f"(d[42]),"=f"(d[43]),"=f"(d[44]),"=f"(d[45]),"=f"(d[46]),"=f"(d[47]),"=f"(d[48]),"=f"(d[49]),"=f"(d[50]),"=f"(d[51]),"=f"(d[52]),"=f"(d[53]),"=f"(d[54]),"=f"(d[55]),"=f"(d[56]),"=f"(d[57]),"=f"(d[58]),"=f"(d[59]),"=f"(d[60]),"=f"(d[61]),"=f"(d[62]),"=f"(d[63]),"=f"(d[64]),"=f"(d[65]),"=f"(d[66]),"=f"(d[67]),"=f"(d[68]),"=f"(d[69]),"=f"(d[70]),"=f"(d[71]),"=f"(d[72]),"=f"(d[73]),"=f"(d[74]),"=f"(d[75]),"=f"(d[76]),"=f"(d[77]),"=f"(d[78]),"=f"(d[79]),"=f"(d[80]),"=f"(d[81]),"=f"(d[82]),"=f"(d[83]),"=f"(d[84]),"=f"(d[85]),"=f"(d[86]),"=f"(d[87]),"=f"(d[88]),"=f"(d[89]),"=f"(d[90]),"=f"(d[91]),"=f"(d[92]),"=f"(d[93]),"=f"(d[94]),"=f"(d[95]),"=f"(d[96]),"=f"(d[97]),"=f"(d[98]),"=f"(d[99]),"=f"(d[100]),"=f"(d[101]),"=f"(d[102]),"=f"(d[103]),"=f"(d[104]),"=f"(d[105]),"=f"(d[106]),"=f"(d[107]),"=f"(d[108]),"=f"(d[109]),"=f"(d[110]),"=f"(d[111]),"=f"(d[112]),"=f"(d[113]),"=f"(d[114]),"=f"(d[115]),"=f"(d[116]),"=f"(d[117]),"=f"(d[118]),"=f"(d[119]),"=f"(d[120]),"=f"(d[121]),"=f"(d[122]),"=f"(d[123]),"=f"(d[124]),"=f"(d[125]),"=f"(d[126]),"=f"(d[127]) : "r"(a.x), "r"(a.y), "r"(a.z), "r"(a.w), "r"(db.lo), "r"(db.hi));
}
template<int N> __device__ __forceinline__ void wgmma_ra(float (&d)[N / 2], const uint4& a, Desc db, bool acc) {
  if (acc) wgmma_rs<N, 1>(d, a, db); else wgmma_rs<N, 0>(d, a, db);
}

__device__ __forceinline__ uint32_t smem_u32(const void* p) { return (uint32_t)__cvta_generic_to_shared(p); }
__device__ __forceinline__ void mbar_init(uint32_t bar, uint32_t cnt) { asm volatile("mbarrier.init.shared::cta.b64 [%0], %1;" ::"r"(bar), "r"(cnt)); }
__device__ __forceinline__ void mbar_expect_tx(uint32_t bar, uint32_t bytes) { asm volatile("mbarrier.arrive.expect_tx.shared::cta.b64 _, [%0], %1;" ::"r"(bar), "r"(bytes) : "memory"); }
__device__ __forceinline__ void mbar_arrive(uint32_t bar) { asm volatile("mbarrier.arrive.shared::cta.b64 _, [%0];" ::"r"(bar) : "memory"); }
__device__ __forceinline__ void mbar_arrive_remote(uint32_t rbar) { asm volatile("mbarrier.arrive.shared::cluster.b64 _, [%0];" ::"r"(rbar) : "memory"); }
__device__ __forceinline__ void mbar_wait(uint32_t bar, uint32_t parity) {
  asm volatile(
      "{\n.reg .pred p;\n.reg .u32 c;\nmov.u32 c, 0;\nLAB_WAIT:\nmbarrier.try_wait.parity.shared::cta.b64 p, [%0], %1;\n@p bra DONE;\n"
      "add.u32 c, c, 1;\nsetp.lt.u32 p, c, 1000000;\n@p bra LAB_WAIT;\ntrap;\nDONE:\n}\n" ::"r"(bar), "r"(parity) : "memory");
}
__device__ __forceinline__ void mbar_wait_c(uint32_t bar, uint32_t parity) {
  asm volatile("{\n.reg .pred p;\nLAB_WAIT:\nmbarrier.try_wait.parity.shared::cta.b64 p, [%0], %1;\n@!p bra LAB_WAIT;\n}\n" ::"r"(bar), "r"(parity) : "memory");
}
__device__ __forceinline__ uint32_t late(uint32_t bar, uint32_t v) {
  uint32_t r;
  asm volatile("{\n.reg .pred p;\nmbarrier.test_wait.parity.shared::cta.b64 p, [%1], 0;\nselp.b32 %0, %2, %1, p;\n}\n" : "=r"(r) : "r"(bar), "r"(v) : "memory");
  return r;
}
__device__ __forceinline__ void wtma2d(uint32_t dst, const CUtensorMap* m, int c0, int c1, uint32_t bar, uint64_t pol) {
  asm volatile("cp.async.bulk.tensor.2d.shared::cluster.global.mbarrier::complete_tx::bytes.multicast::cluster.L2::cache_hint [%0], [%1, {%3, %4}], [%2], %5, %6;"
               ::"r"(dst), "l"(m), "r"(bar), "r"(c0), "r"(c1), "h"((uint16_t)3), "l"(pol) : "memory");
}
__device__ __forceinline__ void wtma3d(uint32_t dst, const CUtensorMap* m, int c0, int c1, int c2, uint32_t bar, uint64_t pol) {
  asm volatile("cp.async.bulk.tensor.3d.shared::cluster.global.mbarrier::complete_tx::bytes.multicast::cluster.L2::cache_hint [%0], [%1, {%3, %4, %5}], [%2], %6, %7;"
               ::"r"(dst), "l"(m), "r"(bar), "r"(c0), "r"(c1), "r"(c2), "h"((uint16_t)3), "l"(pol) : "memory");
}
__device__ __forceinline__ void tma3d(uint32_t dst, const CUtensorMap* m, int c0, int c1, int c2, uint32_t bar) {
  asm volatile("cp.async.bulk.tensor.3d.shared::cluster.global.mbarrier::complete_tx::bytes [%0], [%1, {%3, %4, %5}], [%2];"
               ::"r"(dst), "l"(m), "r"(bar), "r"(c0), "r"(c1), "r"(c2) : "memory");
}
__device__ __forceinline__ void tma_store3d(const CUtensorMap* m, uint32_t src, int c0, int c1, int c2) {
  asm volatile("cp.async.bulk.tensor.3d.global.shared::cta.bulk_group [%0, {%2, %3, %4}], [%1];" ::"l"(m), "r"(src), "r"(c0), "r"(c1), "r"(c2) : "memory");
}
__device__ __forceinline__ void prefetch_l2(const void* p, uint32_t bytes) { asm volatile("cp.async.bulk.prefetch.L2.global [%0], %1;" ::"l"(p), "r"(bytes) : "memory"); }
__device__ __forceinline__ uint64_t policy_evict_first() { uint64_t p; asm volatile("createpolicy.fractional.L2::evict_first.b64 %0, 1.0;" : "=l"(p)); return p; }
__device__ __forceinline__ uint64_t policy_evict_normal() { uint64_t p; asm volatile("createpolicy.fractional.L2::evict_normal.b64 %0, 1.0;" : "=l"(p)); return p; }
__device__ __forceinline__ void bulk_commit() { asm volatile("cp.async.bulk.commit_group;" ::: "memory"); }
__device__ __forceinline__ void bulk_wait_all() { asm volatile("cp.async.bulk.wait_group 0;" ::: "memory"); }
__device__ __forceinline__ void fence_async_smem() { asm volatile("fence.proxy.async.shared::cta;" ::: "memory"); }
__device__ __forceinline__ bool elect_one() {
  uint32_t p;
  asm volatile("{\n.reg .pred P;\nelect.sync _|P, 0xffffffff;\nselp.u32 %0, 1, 0, P;\n}\n" : "=r"(p));
  return p;
}
__device__ __forceinline__ void wg_fence() { asm volatile("wgmma.fence.sync.aligned;" ::: "memory"); }
__device__ __forceinline__ void wg_commit() { asm volatile("wgmma.commit_group.sync.aligned;" ::: "memory"); }
template <int n> __device__ __forceinline__ void wg_wait() { asm volatile("wgmma.wait_group.sync.aligned %0;" ::"n"(n) : "memory"); }
__device__ __forceinline__ void wg_bar(int w) { asm volatile("bar.sync %0, 128;" ::"r"(w + 1) : "memory"); }
__device__ __forceinline__ void cluster_sync() { asm volatile("barrier.cluster.arrive.relaxed.aligned;\nbarrier.cluster.wait.aligned;" ::: "memory"); }
__device__ __forceinline__ void fence_gpu() { asm volatile("fence.acq_rel.gpu;" ::: "memory"); }
__device__ __forceinline__ uint32_t ld_relaxed(const uint32_t* p) { uint32_t v; asm volatile("ld.relaxed.gpu.global.u32 %0, [%1];" : "=r"(v) : "l"(p) : "memory"); return v; }
__device__ __forceinline__ uint4 ld_relaxed4(const uint4* p) {
  uint4 v; asm volatile("ld.relaxed.gpu.global.v4.u32 {%0,%1,%2,%3}, [%4];" : "=r"(v.x), "=r"(v.y), "=r"(v.z), "=r"(v.w) : "l"(p) : "memory"); return v;
}
__device__ __forceinline__ uint2 ld_relaxed2(const uint2* p) {
  uint2 v; asm volatile("ld.relaxed.gpu.global.v2.u32 {%0,%1}, [%2];" : "=r"(v.x), "=r"(v.y) : "l"(p) : "memory"); return v;
}
__device__ __forceinline__ void st_relaxed(uint32_t* p, uint32_t a) { asm volatile("st.relaxed.gpu.global.u32 [%0], %1;" ::"l"(p), "r"(a) : "memory"); }
__device__ __forceinline__ void st_relaxed4(uint4* p, uint32_t a, uint32_t b, uint32_t c, uint32_t d) {
  asm volatile("st.relaxed.gpu.global.v4.u32 [%0], {%1,%2,%3,%4};" ::"l"(p), "r"(a), "r"(b), "r"(c), "r"(d) : "memory");
}
__device__ __forceinline__ void st_relaxed2(uint2* p, uint32_t a, uint32_t b) {
  asm volatile("st.relaxed.gpu.global.v2.u32 [%0], {%1,%2};" ::"l"(p), "r"(a), "r"(b) : "memory");
}
__device__ __forceinline__ void red4(uint4* p, uint32_t a, uint32_t b, uint32_t c, uint32_t d) {
  asm volatile("red.relaxed.gpu.global.add.noftz.v4.bf16x2 [%0], {%1,%2,%3,%4};" ::"l"(p), "r"(a), "r"(b), "r"(c), "r"(d) : "memory");
}
__device__ __forceinline__ void red2(uint2* p, uint32_t a, uint32_t b) {
  asm volatile("red.relaxed.gpu.global.add.noftz.v2.bf16x2 [%0], {%1,%2};" ::"l"(p), "r"(a), "r"(b) : "memory");
}
constexpr int SPIN_MAX = 1 << 21;
__device__ __forceinline__ uint32_t pack_bf16(float lo, float hi) { uint32_t r; asm("cvt.rn.bf16x2.f32 %0, %1, %2;" : "=r"(r) : "f"(hi), "f"(lo)); return r; }
__device__ __forceinline__ float bf_lo(uint32_t v) { return __uint_as_float(v << 16); }
__device__ __forceinline__ float bf_hi(uint32_t v) { return __uint_as_float(v & 0xffff0000u); }
__device__ __forceinline__ float2 lds64(uint32_t a) { float2 v; asm volatile("ld.shared.v2.f32 {%0,%1}, [%2];" : "=f"(v.x), "=f"(v.y) : "r"(a)); return v; }
__device__ __forceinline__ uint32_t lds32(uint32_t a) { uint32_t v; asm volatile("ld.shared.b32 %0, [%1];" : "=r"(v) : "r"(a)); return v; }
__device__ __forceinline__ void sts64f(uint32_t a, float x, float y) { asm volatile("st.shared.v2.f32 [%0], {%1,%2};" ::"r"(a), "f"(x), "f"(y) : "memory"); }
__device__ __forceinline__ void sts32(uint32_t a, uint32_t x) { asm volatile("st.volatile.shared.b32 [%0], %1;" ::"r"(a), "r"(x) : "memory"); }
__device__ __forceinline__ void gate(uint32_t a, int need) {
#pragma unroll 1
  for (int it = 0; it < SPIN_MAX; it++) {
    int v; asm volatile("ld.volatile.shared.b32 %0, [%1];" : "=r"(v) : "r"(a) : "memory");
    if (v >= need) break;
    if (GSLEEP) __nanosleep(GSLEEP);
  }
}
__device__ __forceinline__ void sts128(uint32_t a, uint32_t x, uint32_t y, uint32_t z, uint32_t u) { asm volatile("st.shared.v4.b32 [%0], {%1,%2,%3,%4};" ::"r"(a), "r"(x), "r"(y), "r"(z), "r"(u) : "memory"); }
__device__ __forceinline__ uint4 lds128(uint32_t a) { uint4 v; asm volatile("ld.shared.v4.u32 {%0,%1,%2,%3}, [%4];" : "=r"(v.x), "=r"(v.y), "=r"(v.z), "=r"(v.w) : "r"(a) : "memory"); return v; }
__device__ __forceinline__ uint32_t hmul2(uint32_t a, uint32_t b) { uint32_t r; asm("mul.rn.bf16x2 %0, %1, %2;" : "=r"(r) : "r"(a), "r"(b)); return r; }
__device__ __forceinline__ uint32_t hadd2(uint32_t a, uint32_t b) { uint32_t r; asm("add.rn.bf16x2 %0, %1, %2;" : "=r"(r) : "r"(a), "r"(b)); return r; }
__device__ __forceinline__ void stsm4(uint32_t a, uint32_t r0, uint32_t r1, uint32_t r2, uint32_t r3) {
  asm volatile("stmatrix.sync.aligned.m8n8.x4.shared.b16 [%0], {%1,%2,%3,%4};" ::"r"(a), "r"(r0), "r"(r1), "r"(r2), "r"(r3) : "memory");
}
__device__ __forceinline__ void stsm2(uint32_t a, uint32_t r0, uint32_t r1) {
  asm volatile("stmatrix.sync.aligned.m8n8.x2.shared.b16 [%0], {%1,%2};" ::"r"(a), "r"(r0), "r"(r1) : "memory");
}
__device__ __forceinline__ uint4 ldsm4(uint32_t a) {
  uint4 r; asm volatile("ldmatrix.sync.aligned.m8n8.x4.shared.b16 {%0,%1,%2,%3}, [%4];" : "=r"(r.x), "=r"(r.y), "=r"(r.z), "=r"(r.w) : "r"(a) : "memory"); return r;
}
__device__ __forceinline__ uint32_t movm(uint32_t a) { uint32_t r; asm("movmatrix.sync.aligned.m8n8.trans.b16 %0, %1;" : "=r"(r) : "r"(a)); return r; }
__device__ __forceinline__ void mma16816z(float (&d)[4], uint32_t a0, uint32_t a1, uint32_t a2, uint32_t a3, uint32_t b0, uint32_t b1) {
  asm("mma.sync.aligned.m16n8k16.row.col.f32.bf16.bf16.f32 {%0,%1,%2,%3}, {%4,%5,%6,%7}, {%8,%9}, {%10,%10,%10,%10};"
      : "=f"(d[0]), "=f"(d[1]), "=f"(d[2]), "=f"(d[3]) : "r"(a0), "r"(a1), "r"(a2), "r"(a3), "r"(b0), "r"(b1), "f"(0.f));
}
__device__ __forceinline__ void mma16816(float (&d)[4], const uint4& a, uint32_t b0, uint32_t b1) {
  asm("mma.sync.aligned.m16n8k16.row.col.f32.bf16.bf16.f32 {%0,%1,%2,%3}, {%4,%5,%6,%7}, {%8,%9}, {%0,%1,%2,%3};"
      : "+f"(d[0]), "+f"(d[1]), "+f"(d[2]), "+f"(d[3]) : "r"(a.x), "r"(a.y), "r"(a.z), "r"(a.w), "r"(b0), "r"(b1));
}
__device__ __forceinline__ void mma1688(float (&d)[4], uint32_t a0, uint32_t a1, uint32_t b0) {
  asm("mma.sync.aligned.m16n8k8.row.col.f32.bf16.bf16.f32 {%0,%1,%2,%3}, {%4,%5}, {%6}, {%0,%1,%2,%3};"
      : "+f"(d[0]), "+f"(d[1]), "+f"(d[2]), "+f"(d[3]) : "r"(a0), "r"(a1), "r"(b0));
}
__device__ __forceinline__ float quad_sum(float v) { v += __shfl_xor_sync(0xffffffffu, v, 1); v += __shfl_xor_sync(0xffffffffu, v, 2); return v; }
__device__ __forceinline__ float quad_max(float v) { v = fmaxf(v, __shfl_xor_sync(0xffffffffu, v, 1)); v = fmaxf(v, __shfl_xor_sync(0xffffffffu, v, 2)); return v; }
__device__ __forceinline__ float rcp(float x) { float r; asm("rcp.approx.ftz.f32 %0, %1;" : "=f"(r) : "f"(x)); return r; }
__device__ __forceinline__ float rsq(float x) { float r; asm("rsqrt.approx.ftz.f32 %0, %1;" : "=f"(r) : "f"(x)); return r; }
__device__ __forceinline__ float ex2(float x) { float r; asm("ex2.approx.ftz.f32 %0, %1;" : "=f"(r) : "f"(x)); return r; }
__device__ __forceinline__ uint32_t chk(uint32_t acc, uint32_t v, uint32_t tag) { uint32_t r; asm("lop3.b32 %0, %1, %2, %3, 0xF6;" : "=r"(r) : "r"(acc), "r"(v), "r"(tag)); return r; }
__device__ __forceinline__ uint32_t chk2(uint32_t a, uint32_t b, uint32_t tag) { uint32_t r; asm("lop3.b32 %0, %1, %2, %3, 0x7E;" : "=r"(r) : "r"(a), "r"(b), "r"(tag)); return r; }
__device__ __forceinline__ uint32_t tagged(uint32_t v, uint32_t tag) { return (v & ~1u) | tag; }

__device__ __forceinline__ int group_k0(int g, int j) {
  const int h = g >= 9, r = g - 2 - 7 * h;
  return g < 2 ? 64 * j + 32 * g : g < 16 ? 64 * (r + (r >= j)) + 32 * h : 32 * g;
}
__device__ __forceinline__ uint32_t xin_off(int c, int w) { return SM_X + (2 * c + w + (2 * c + w < 9 ? 9 : -9)) * 8192; }
__device__ __forceinline__ uint32_t xin_bar(int c) { return BAR_FULLX + 8 * (c < 8 ? c ^ 4 : c); }
__device__ __forceinline__ constexpr uint32_t qkv_xslot(int g) { return g < 5 || g > 11 ? 2 : (0x5140762u >> (4 * (g - 5))) & 15; }

template <int N> struct IC { static constexpr int v = N; };

struct Cons {
  uint32_t sb;
  uint32_t rem;
  uint32_t sB, mB;
  uint32_t mX;
  bool elect;
  __device__ __forceinline__ void release2(uint32_t bar) const { if (elect) { mbar_arrive(sb + bar); mbar_arrive_remote(rem + bar); } }
  __device__ __forceinline__ uint32_t nextB(uint32_t& prev) {
    mbar_wait_c(sb + BAR_FULLB + sB, mB);
    const uint32_t a = (((sb & 0x3FFFF) + SM_B) >> 4) + sB * (BSLOT / 128);
    prev = sB == 0 ? 32 : sB - 8;
    sB += 8;
    if (sB == 40) { sB = 0; mB ^= 1; }
    return a;
  }
  __device__ __forceinline__ void progress(uint32_t v) const { if (elect) sts32(sb + SM_PROG + (threadIdx.x >> 5), v); }
  __device__ __forceinline__ void releaseLastB() const { release2(BAR_EMPTYB + (sB == 0 ? 32 : sB - 8)); }
};

__device__ __forceinline__ float2 gather_sums(const uint2* a, uint32_t stag) {
  uint2 sa, sc;
  do { sa = ld_relaxed2(a); sc = ld_relaxed2(a + 8); } while (__any_sync(0xffffffffu, chk2(sa.x, sc.x, stag) & 3));
  return make_float2(quad_sum(__uint_as_float(sa.x) + __uint_as_float(sc.x)), quad_sum(__uint_as_float(sa.y) + __uint_as_float(sc.y)));
}

struct Norm {
  float m0, m1;
  uint32_t nm0, nm1;
  float d0, d1;
  uint2 u0, u1;
  __device__ __forceinline__ Norm(float2 sum) : m0(sum.x * (-1.f / 576)), m1(sum.y * (-1.f / 576)), nm0(pack_bf16(m0, m0)), nm1(pack_bf16(m1, m1)), d0(0.f), d1(0.f) {}
  __device__ __forceinline__ uint4 centre(const uint4& a) const { return make_uint4(hadd2(a.x, nm0), hadd2(a.y, nm1), hadd2(a.z, nm0), hadd2(a.w, nm1)); }
  __device__ __forceinline__ void sqr(uint32_t a, uint32_t b) {
    d0 = fmaf(bf_lo(a), bf_lo(a), fmaf(bf_hi(a), bf_hi(a), d0)); d1 = fmaf(bf_lo(b), bf_lo(b), fmaf(bf_hi(b), bf_hi(b), d1));
  }
  __device__ __forceinline__ void send(uint2* a, int t, uint32_t stag) {
    d0 = quad_sum(d0); d1 = quad_sum(d1);
    if ((t & 3) == 0) st_relaxed2(a, (__float_as_uint(d0) & ~3u) | stag, __float_as_uint(d1));
  }
  __device__ __forceinline__ void fetch(const uint2* a) { u0 = ld_relaxed2(a); u1 = ld_relaxed2(a + 8); }
  __device__ __forceinline__ float2 rstd(const uint2* a, uint32_t stag) {
    while (__any_sync(0xffffffffu, chk2(u0.x, u1.x, stag) & 3)) fetch(a);
    const float e0 = bf_lo(nm0) - m0, e1 = bf_lo(nm1) - m1;
    const float v0 = fmaf(quad_sum(__uint_as_float(u0.x) + __uint_as_float(u1.x)), 1.f / 576, -e0 * e0);
    const float v1 = fmaf(quad_sum(__uint_as_float(u0.y) + __uint_as_float(u1.y)), 1.f / 576, -e1 * e1);
    float2 r = make_float2(rsq(fmaxf(v0, 0.f) + 1e-5f), rsq(fmaxf(v1, 0.f) + 1e-5f));
    asm volatile("" : "+f"(r.x), "+f"(r.y));
    return r;
  }
};

template <class Pre, class Mma>
__device__ __forceinline__ float2 ln_gemm_in(Cons& c, Group* G, uint32_t (&p)[18], float2& sum, int w, int st0, int j, int t, Pre&& pre, Mma&& mma) {
  const uint32_t xa = c.sb + (t >> 5) * 2048 + (t & 15) * 128, sw = (((t >> 4) & 1) ^ (t & 7)) * 16;
  float ra[4] = {0.f, 0.f, 0.f, 0.f}, rb[4] = {0.f, 0.f, 0.f, 0.f};
#pragma unroll 1
  for (int cc = 0; cc < 9; cc++) {
    const uint32_t a = xa + xin_off(cc, w);
    mbar_wait_c(c.sb + xin_bar(cc), 0);
    const uint4 u0 = ldsm4(a + sw), u1 = ldsm4(a + (sw ^ 32)), u2 = ldsm4(a + (sw ^ 64)), u3 = ldsm4(a + (sw ^ 96));
    mma16816(ra, u0, 0x3f803f80u, 0x3f803f80u); mma16816(rb, u1, 0x3f803f80u, 0x3f803f80u);
    mma16816(ra, u2, 0x3f803f80u, 0x3f803f80u); mma16816(rb, u3, 0x3f803f80u, 0x3f803f80u);
  }
  sum = make_float2(ra[0] + rb[0], ra[2] + rb[2]);
  pre(0);
  Norm n(sum);
  n.u0 = n.u1 = make_uint2(0, 0);
#pragma unroll
  for (int i = 0; i < 18; i++) p[i] = 0;
  pre(1);
#pragma unroll 1
  for (int cc = 0; cc < 9; cc++) {
    const uint32_t a = xa + xin_off(cc, w);
#pragma unroll
    for (int i = 0; i < 2; i++) {
      const uint4 f0 = n.centre(ldsm4(a + (sw ^ (64 * i)))), f1 = n.centre(ldsm4(a + (sw ^ (64 * i + 32))));
      uint32_t prev;
      const uint32_t bb = c.nextB(prev);
      mma(true, bb, f0, f1);
      if (i == 1) {
        if (cc == w) {
#pragma unroll
          for (int k = 0; k < 5; k++) {
            const uint4 u = ldsm4(xa + (k < 4 ? xin_off(j, w) + (sw ^ (32 * k)) : xin_off(8, w) + ((j ^ (t & 7)) << 4))), e = n.centre(u);
            p[4 * k] = u.x; p[4 * k + 1] = u.y;
            n.sqr(e.x, e.y);
            if (k < 4) { p[4 * k + 2] = u.z; p[4 * k + 3] = u.w; n.sqr(e.z, e.w); }
          }
          n.send(G->sq + st0 + 8 * j, t, 1);
          c.progress(3);
        }
        if (cc == 7) n.fetch(G->sq + st0 + 16 * (t & 3));
        if (cc == 8 && w == 0) asm volatile("bar.arrive 6, 256;" ::: "memory");
      }
      wg_wait<1>();
      if (i + cc > 0) c.release2(BAR_EMPTYB + prev);
      if (2 * cc + i >= WOG && 2 * cc + i < WOG + 4) c.release2(BAR_EMPTYX + 32 + 8 * (2 * cc + i - WOG));
    }
  }
  c.mX = 0xff;
  const float2 r = n.rstd(G->sq + st0 + 16 * (t & 3), 1);
  if (w == 1) asm volatile("bar.sync 6, 256;" ::: "memory");
  wg_wait<0>();
  c.releaseLastB();
  c.release2(BAR_EMPTYX + 24);
  return r;
}

template <bool QKV, class Pre, class Mma>
__device__ __forceinline__ float2 ln_gemm(Cons& c, Group* G, const float (&v)[36], uint32_t (&p)[18], float2& sum, int st0, int j, int t,
                                          int layer, uint32_t tag, Pre&& pre, Mma&& mma) {
  constexpr bool known = !QKV && EARLY;
  const uint32_t stag = (2 * layer + (QKV ? 1 : 2)) & 3;
  uint4 x[6][2];
  uint4* src = G->xbox + t;
  asm volatile("" : "+l"(src));
  auto buf = [&](int g) -> uint4 (&)[2] { return x[g < 16 ? (g - 2) % 6 : g - 13]; };
  auto load = [&](int g0) {
#pragma unroll
    for (int g = g0; g < g0 + (g0 < 14 ? 3 : 2); g++) {
      const uint4* a = g < 16 ? src + ((g - 2) % 7 >= j ? 256 : 0) + (2 * ((g - 2) % 7) + 16 * (g >= 9)) * 128 : src + 2 * g * 128;
      buf(g)[0] = ld_relaxed4(a); buf(g)[1] = ld_relaxed4(a + 128);
    }
  };
  auto invalid = [&](int g, uint32_t tag) {
    uint32_t bad = chk(chk(chk2(buf(g)[0].x, buf(g)[1].x, tag), buf(g + 1)[0].x, tag), buf(g + 1)[1].x, tag);
    if (g < 14) bad = chk(chk(bad, buf(g + 2)[0].x, tag), buf(g + 2)[1].x, tag);
    if (g == 16) bad = chk(chk(chk(chk(bad, buf(g)[0].z, tag), buf(g)[1].z, tag), buf(g + 1)[0].z, tag), buf(g + 1)[1].z, tag);
    return __any_sync(0xffffffffu, bad & 1);
  };
  uint4* const d = src + 2 * j * 128;
  const int sq = st0 + 16 * (t & 3);
  if (!known) {
    float s0 = v[0] + v[1], s1 = v[2] + v[3];
#pragma unroll
    for (int i = 1; i < 9; i++) { s0 += v[4 * i] + v[4 * i + 1]; s1 += v[4 * i + 2] + v[4 * i + 3]; }
    s0 = quad_sum(s0); s1 = quad_sum(s1);
    if ((t & 3) == 0) st_relaxed2(G->sum + st0 + 8 * j, (__float_as_uint(s0) & ~3u) | stag, __float_as_uint(s1));
  }
#pragma unroll
  for (int i = 0; i < 18; i++) p[i] = pack_bf16(v[2 * i], v[2 * i + 1]);
#pragma unroll
  for (int i = 0; i < 2; i++) st_relaxed4(d + i * 128, tagged(p[4 * i], tag), p[4 * i + 1], p[4 * i + 2], p[4 * i + 3]);
  pre(0);
  if (!known) {
    sum = gather_sums(G->sum + sq, stag);
    load(2);
  }
  Norm n(sum);
  pre(1);
  const uint32_t* probe = &(G->xbox + (2 * (t & 7) + 1) * 128 + (t | 31))->x;
  uint32_t pv;
  auto inx = [](int g) { return QKV && ((g >= 5 && g < 12) || g == 17); };
  auto use = [](int g) { return QKV ? (g < 5 ? 108 : 101) + g : 18 + g; };
#pragma unroll
  for (int g = 0; g < 18; g++) {
    if (g < 16 ? g % 3 == 2 : g == 16) {
      const uint32_t lt = late(c.sb + BAR_FULLX + 64, tag);
      while (invalid(g, lt)) load(g);
      if (g < 16) load(g < 14 ? g + 3 : 16);
    }
    const uint4 f0 = n.centre(g < 2 ? make_uint4(p[8 * g], p[8 * g + 1], p[8 * g + 2], p[8 * g + 3]) : buf(g)[0]);
    const uint4 f1 = n.centre(g < 2 ? make_uint4(p[8 * g + 4], p[8 * g + 5], p[8 * g + 6], p[8 * g + 7]) : buf(g)[1]);
    if (g == 14) n.fetch(G->sq + sq);
    if (inx(g)) mbar_wait_c(c.sb + BAR_FULLX + 8 * qkv_xslot(g), ((0x34 >> qkv_xslot(g)) & 1) ^ (g == 17));
    else mbar_wait_c(c.sb + BAR_FULLB + 8 * (use(g) % 5), (use(g) / 5) & 1);
    mma(g, ((c.sb & 0x3FFFF) >> 4) + ((inx(g) ? SM_X + qkv_xslot(g) * XSLOT : SM_B + (use(g) % 5) * BSLOT) >> 4), f0, f1);
    if (g < 2) {
      if (known) {
        if (g == 0) {
          pv = ld_relaxed(probe);
        } else {
          const uint32_t lt = late(c.sb + BAR_FULLX + 64, tag);
          while (__any_sync(0xffffffffu, (pv ^ lt) & 1)) pv = ld_relaxed(probe);
          load(2);
        }
      }
      if (g == (known ? 1 : 0)) {
#pragma unroll
        for (int i = 2; i < 4; i++) st_relaxed4(d + (14 + i) * 128, tagged(p[4 * i], tag), p[4 * i + 1], p[4 * i + 2], p[4 * i + 3]);
        st_relaxed2((uint2*)(src + (32 + (j >> 1)) * 128) + (j & 1), tagged(p[16], tag), p[17]);
      }
      n.sqr(f0.x, f0.y); n.sqr(f0.z, f0.w); n.sqr(f1.x, f1.y); n.sqr(f1.z, f1.w);
      if (g == 1) {
        n.sqr(hadd2(p[16], n.nm0), hadd2(p[17], n.nm1));
        n.send(G->sq + st0 + 8 * j, t, stag);
      }
    }
    wg_wait<1>();
    if (g > 0 && !inx(g - 1)) c.release2(BAR_EMPTYB + 8 * (use(g - 1) % 5));
    if (QKV && g < 13) c.progress(33 + g);
    if (QKV && g == WOG - 1) c.release2(BAR_EMPTYX + 8 * qkv_xslot(17));
    if (QKV && g >= WOG && g < WOG + 4) c.release2(BAR_EMPTYX + 32 + 8 * (g - WOG));
  }
  if (QKV) c.mX = 0x34 ^ 0xf3;
  else { c.sB = 8 * (36 % 5); c.mB = (36 / 5) & 1; }
  const float2 r = n.rstd(G->sq + sq, late(c.sb + BAR_FULLX + 64, stag));
  wg_wait<0>();
  if (!QKV) c.release2(BAR_EMPTYB + 8 * (use(17) % 5));
  return r;
}

template <int NB, int OFF>
__device__ __forceinline__ void glu(const float (&a)[128], uint32_t (&h)[144]) {
#pragma unroll
  for (int b = 0; b < 2 * NB; b++) {
    if (HMUL) h[OFF + b] = hmul2(pack_bf16(a[2 * b], a[2 * b + 1]), pack_bf16(a[4 * NB + 2 * b], a[4 * NB + 2 * b + 1]));
    else h[OFF + b] = pack_bf16(a[2 * b] * a[4 * NB + 2 * b], a[2 * b + 1] * a[4 * NB + 2 * b + 1]);
  }
}

__global__ void __cluster_dims__(2, 1, 1) __launch_bounds__(384, 1)
fused_kernel(const __nv_bfloat16* __restrict__ x_in, Group* ws, const char* __restrict__ wqkv,
             const char* __restrict__ wg, const char* __restrict__ wu, const char* __restrict__ wd, const __grid_constant__ Maps maps,
             const char* __restrict__ wo) {
  extern __shared__ __align__(1024) uint8_t smem_raw[];
  const uint32_t sb = smem_u32(smem_raw);
  if (threadIdx.x == 0) asm volatile("prefetch.tensormap [%0];" ::"l"(&maps.x) : "memory");
  const int warp = __shfl_sync(0xffffffffu, threadIdx.x >> 5, 0);
  const int lane = threadIdx.x & 31;
  const int rank = blockIdx.x & 1;
  if (elect_one()) {
    if (warp >= 8) {
#pragma unroll
      for (int i = 0; i < 9; i++) mbar_init(sb + SM_BAR + 72 * (warp - 8) + 8 * i, warp < 10 ? 1 : 4);
      sts32(sb + SM_PROG + 4 * (warp - 8), 0);
      asm volatile("fence.mbarrier_init.release.cluster;" ::: "memory");
    } else if (warp == 1 || warp == 2) {
      asm volatile("prefetch.tensormap [%0];" ::"l"(&maps.x + warp) : "memory");
    } else if (warp == 3) {
      if (PFMODE & 1) prefetch_l2((const char*)x_in + blockIdx.x * 18432, 18432);
    } else if (warp == 4) {
      if (PFMODE & 2) prefetch_l2(wqkv + blockIdx.x * (15552 / PFQ), 15552 / PFQ);
    }
  }
  __syncwarp();
  asm volatile("barrier.cluster.arrive.relaxed.aligned;" ::: "memory");
  if (warp == 8) PROFX(53);
  int lb = blockIdx.x;
  if (GPCMAP) {
    const int cl = blockIdx.x >> 1, u = cl - 36;
    lb = (cl < 4 ? cl : cl < 36 ? 8 * ((cl - 4) & 7) + ((cl - 4) >> 3) + (((cl - 4) & 7) ? 0 : 4) : 8 * (1 + u % 7) + 4 + u / 7) * 2 + rank;
  }
#define CTA_J(b) (((b) >> 1) & 7)
#define CTA_RB(b) ((((b) >> 4) << 1) | ((b) & 1))
  const int j = CTA_J(lb), rb = CTA_RB(lb);

  PROF(23);
  if (warp >= 8) {
    asm volatile("setmaxnreg.dec.sync.aligned.u32 " STR(REGS_P) ";");
    auto x_chunk = [&](int cc) {
      mbar_expect_tx(sb + xin_bar(cc), 16384);
      tma3d(sb + xin_off(cc, 0), &maps.x, 64 * cc, 0, 64 * rb, sb + xin_bar(cc));
      tma3d(sb + xin_off(cc, 1), &maps.x, 64 * cc, 1, 64 * rb, sb + xin_bar(cc));
    };
    if (warp == 9 && elect_one()) {
      fence_async_smem();
#pragma unroll 1
      for (int i = 0; i < 9; i++) x_chunk(i);
    }
    __syncwarp();
    if (warp == 9) PROFX(54);
    asm volatile("barrier.cluster.wait.aligned;" ::: "memory");
    if (warp == 8) PROFX(56);
    const uint64_t pol = W_POLICY(), pola = A_POLICY();
    auto qkv_group = [&](int k, uint32_t dst, uint32_t bar) {
      wtma3d(dst + rank * 8192, &maps.qm, 72 * j, k + 16 * rank, 0, bar, pola);
      wtma3d(dst + rank * 8192 + 6144, &maps.qc, 72 * j + 64, k + 16 * rank, 0, bar, pola);
    };
    const int ktab = group_k0(lane, j);
    auto qkv_gate = [&](int g) { if (g >= 8) gate(sb + SM_PROG, 33 + ((g - 8) * 23 >> 4)); };
    if (warp == 8) {
      uint32_t s = 0, ph = 1;
      auto slot = [&](uint32_t bytes, auto&& issue) {
        const uint32_t bar = sb + BAR_FULLB + 8 * s;
        mbar_wait(sb + BAR_EMPTYB + 8 * s, ph);
        if (elect_one()) {
          mbar_expect_tx(bar, bytes);
          issue(sb + SM_B + s * BSLOT, bar);
        }
        if (++s == 5) { s = 0; ph ^= 1; }
      };
#pragma unroll 1
      for (int layer = 0; layer < NLAYERS; layer++) {
#pragma unroll 1
        for (int g = 0; g < 18 - layer; g += layer && g == 4 ? 8 : 1) {
          const int k = layer ? __shfl_sync(0xffffffffu, ktab, g) : 32 * g;
          if (layer) qkv_gate(g);
          else if (g == QD) mbar_wait(sb + xin_bar(XH), 0);
          slot(2 * 6912, [&](uint32_t dst, uint32_t bar) { qkv_group(k, dst, bar); });
        }
        if (!FCH) {
          gate(sb + SM_PROG, 32 * layer + 20);
          gate(sb + SM_PROG + 4, 32 * layer + 20);
        }
#pragma unroll 1
        for (int t = 0; t < 5; t++) {
          const CUtensorMap* m = &maps.g + (t < 3 ? rank : 2 + rank);
          asm volatile("" : "+l"(m));
          const int c2 = t < 3 ? 9 * j + 2 * t : 18 * j + 3 + 3 * t;
          const uint32_t half = t < 3 ? 8192 : 6144;
          auto tile = [&](int g) {
            const int k = __shfl_sync(0xffffffffu, ktab, g);
            slot(2 * half, [&](uint32_t dst, uint32_t bar) { wtma3d(dst + rank * half, m, 0, k, c2, bar, pol); });
          };
          int g = 0;
          if (t == 0) {
#pragma unroll 1
            for (; g < 5; g++) {
              mbar_wait(sb + BAR_FULLB + 8 * (s < FCH ? s + 5 - FCH : s - FCH), s < FCH ? ph : ph ^ 1);
              tile(g);
            }
          }
#pragma unroll 1
          for (; g < 18; g++) tile(g);
        }
      }
    } else if (warp == 9) {
      uint32_t mE = 0;
      auto acquire = [&](uint32_t s) { mbar_wait(sb + BAR_EMPTYX + 8 * s, (mE >> s) & 1); mE ^= 1u << s; };
      auto landed = [&](uint32_t s) { mbar_wait(sb + BAR_FULLX + 8 * s, (mE >> s) & 1); };
      auto slot = [&](uint32_t s, const CUtensorMap* m, int col, int row, uint64_t pol) {
        acquire(s);
        if (elect_one()) {
          mbar_expect_tx(sb + BAR_FULLX + 8 * s, XSLOT);
          wtma2d(sb + SM_X + s * XSLOT + rank * 9216, m, col, row + 72 * rank, sb + BAR_FULLX + 8 * s, pol);
        }
      };
#pragma unroll 1
      for (int layer = 0; layer < NLAYERS; layer++) {
#pragma unroll 1
        for (int g = 5; g < 18 * layer; g += g == 11 ? 6 : 1) {
          const uint32_t s = qkv_xslot(g);
          const int k = __shfl_sync(0xffffffffu, ktab, g);
          if (g < 12) qkv_gate(g);
          acquire(s);
          if (elect_one()) {
            mbar_expect_tx(sb + BAR_FULLX + 8 * s, 2 * 6912);
            qkv_group(k, sb + SM_X + s * XSLOT, sb + BAR_FULLX + 8 * s);
          }
          if (XCH & 1) landed(s);
        }
#pragma unroll 1
        for (int i = 0; i < 4; i++) { slot(4 + i, &maps.o, 64 * j, 144 * i, pola); if (XCH & 2) landed(4 + i); }
        acquire(3);
        if (elect_one()) {
          mbar_expect_tx(sb + BAR_FULLX + 24, 9216);
          wtma2d(sb + SM_WOC + rank * 4608, &maps.oc, 512 + 8 * j, 288 * rank, sb + BAR_FULLX + 24, pola);
          wtma2d(sb + SM_WOC + rank * 4608 + 2304, &maps.oc, 512 + 8 * j, 288 * rank + 144, sb + BAR_FULLX + 24, pola);
        }
#pragma unroll 1
        for (int u = 0; u < 36; u++) {
          const uint32_t s = 4 * (u & 1) + ((u >> 1) & 3);
          slot(s, &maps.d, u < 4 ? 512 : 64 * ((j + (u >> 2)) & 7), 576 * j + 144 * (u & 3), pol);
          if ((XCH & 4) && u < 3) landed(s);
        }
      }
    } else {
      const int w = warp - 10, grp = 2 * rb + w;
      if (PFMODE & 4) {
        mbar_wait(sb + xin_bar(XP), 0);
        if (lane == 0) prefetch_l2(wqkv + (2 * blockIdx.x + w) * 7776, 7776);
        if (EARLY && lane == 0) prefetch_l2(wo + (2 * blockIdx.x + w) * 2592, 2592);
      }
      if (EARLY) {
        const uint32_t par = ~ld_relaxed(ws[grp].flag + 32 + 32 * j) & 1;
        mbar_wait(sb + xin_bar(8), 0);
        if (grp < 18) {
          const uint4* row = (const uint4*)(wo + (72 * j + 4 * grp + (lane >> 3)) * 1152) + (lane & 7);
          float a = 0.f;
#pragma unroll 1
          for (int i = 0; i < 72; i += 24) {
            const uint4 u[3] = {__ldg(row + i), __ldg(row + i + 8), __ldg(row + i + 16)};
#pragma unroll
            for (int k = 0; k < 3; k++)
              a += ((bf_lo(u[k].x) + bf_hi(u[k].x)) + (bf_lo(u[k].y) + bf_hi(u[k].y))) + ((bf_lo(u[k].z) + bf_hi(u[k].z)) + (bf_lo(u[k].w) + bf_hi(u[k].w)));
          }
          a = quad_sum(a);
          a += __shfl_xor_sync(0xffffffffu, a, 4);
          if ((lane & 7) == 0) st_relaxed(ws[j].wsum + 4 * grp + (lane >> 3), tagged(__float_as_uint(a), par));
        }
        if (w == 1) {
          uint32_t u[3];
#pragma unroll 1
          for (int it = 0; it < SPIN_MAX; it++) {
#pragma unroll
            for (int k = 0; k < 3; k++) u[k] = ld_relaxed(ws[j].wsum + min(lane + 32 * k, 71));
            if (!__any_sync(0xffffffffu, chk(chk2(u[0], u[1], par), u[2], par) & 1)) break;
            __nanosleep(100);
          }
#pragma unroll
          for (int k = 0; k < 3; k++) {
            const float f = __uint_as_float(u[k]);
            if (lane + 32 * k < 80) sts128(sb + SM_WSUM + 16 * (lane + 32 * k), pack_bf16(f, f - bf_lo(pack_bf16(f, 0.f))), 0, 0, 0);
          }
          fence_async_smem();
          __syncwarp();
          if (lane < 4) mbar_arrive(sb + BAR_WSUM);
          PROFX(57);
        }
      }
      gate(sb + SM_PROG, 3);
      if (w == 0) PROFX(58);
      auto prefetch_gu = [&](int l0, int n) {
#pragma unroll 1
        for (int i = lane; i < 36 * n; i += 32) {
          asm volatile("prefetch.global.L2 [%0];" ::"l"((w ? wu : wg) + (size_t)(36 * rb + i / n) * 9216 + 1152 * j + 128 * (l0 + i % n)));
          __nanosleep(PFSLEEP);
        }
      };
      auto clear = [&](uint4* p, int n) {
#pragma unroll 1
        for (int i = lane; i < n; i += 64) { st_relaxed4(p + i, 0, 0, 0, 0); st_relaxed4(p + i + 32, 0, 0, 0, 0); __nanosleep(CLRSLEEP); }
      };
      auto exchange = [&](uint32_t v, uint32_t bar) {
        if (FENCE1) { if (lane == 0) fence_gpu(); } else fence_gpu();
        __syncwarp();
        if (w == 0 && v != 1) PROFX(64 + 58 - 2 * v);
        if (lane == 0) st_relaxed(ws[grp].flag + j, v);
#pragma unroll 1
        for (int it = 0; it < SPIN_MAX; it++) {
          const uint32_t f = ld_relaxed(ws[grp].flag + (lane & 7));
          if (__all_sync(0xffffffffu, v ? f >= v : f == 0)) break;
        }
        if (lane == 0) mbar_arrive(sb + bar + 8 * w);
      };
      if (!EARLY && lane == 0) prefetch_l2(wo + (2 * blockIdx.x + w) * 2592, 2592);
      if (MAPPF && w == 0 && lane < 9) asm volatile("prefetch.tensormap [%0];" ::"l"(&maps.o + lane) : "memory");
#pragma unroll 1
      for (int layer = 0; layer < NLAYERS; layer++) {
        gate(sb + SM_PROG, 32 * layer + 3);
        if (PFF & 1) prefetch_gu(0, 2);
        gate(sb + SM_PROG, 32 * layer + 22);
        if (PFF & 2) prefetch_gu(2, 2);
        if (layer == 0) {
          clear(ws[grp].inbox[0] + 2 * j * INBOX, 2 * INBOX);
          exchange(1, BAR_CLR);
          if (w == 0) PROFX(59);
        }
        if (PFF & 2) prefetch_gu(4, 2);
        if (PFF & 4) prefetch_gu(6, 3);
#pragma unroll 1
        for (int i = lane; i < ((PFF & 8) ? 162 : 0); i += 32) {
          asm volatile("prefetch.global.L2 [%0];" ::"l"(wd + (size_t)(576 * j + 36 * rb + 18 * w) * 1152 + 128 * i));
          __nanosleep(PFSLEEP);
        }
        if (w == 0 && layer == 0) PROFX(60);
        mbar_wait(sb + BAR_REDDONE + 8 * w, layer);
        if (w == 0) PROFX(64 + 53 + 4 * layer);
        exchange(2 - 2 * layer, BAR_RREADY);
        if (w == 0) PROFX(64 + 56 + 4 * layer);
      }
      mbar_wait(sb + BAR_DONE + 8 * w, 0);
    }
    __syncwarp();
    cluster_sync();
  } else {
    asm volatile("setmaxnreg.inc.sync.aligned.u32 " STR(REGS_C) ";");
#define THREAD_IDS()                                                                   \
    int tid_ = threadIdx.x, bid_ = lb;                                                  \
    asm volatile("" : "+r"(tid_), "+r"(bid_));                                          \
    const int w = warp >> 2, wp = warp & 3;                                             \
    const int lane = tid_ & 31, t = tid_ & 127, g = lane >> 2, q = lane & 3;           \
    const int j = CTA_J(bid_), rb = CTA_RB(bid_), grp = 2 * rb + w;                    \
    const int st0 = wp * 64 + g;                         \
    Group* const G = ws + grp;                                                         \
    const uint32_t dsb = (sb & 0x3FFFF) >> 4;                                          \
    (void)t; (void)g; (void)q; (void)grp; (void)j; (void)st0; (void)dsb; (void)G
    Cons c;
    c.sb = sb; c.sB = 0; c.mB = 0; c.mX = 0; c.elect = (threadIdx.x & 127) == 0;
    asm volatile("mapa.shared::cluster.u32 %0, %1, %2;" : "=r"(c.rem) : "r"(sb), "r"(rank ^ 1));
    float v[36], a1[96], a2[12];
    float2 sum, rs;
    uint32_t res[18], xtag;
    auto qkv_mma = [&](bool acc, uint32_t bb, const uint4& f0, const uint4& f1) {
      wg_fence();
      wgmma_ra<192>(a1, f0, desc_hi(2048, 1024, 1) + bb, acc);
      wgmma_ra<24>(a2, f0, desc_hi(128, 256, 0) + (bb + 384), acc);
      wgmma_ra<192>(a1, f1, desc_hi(2048, 1024, 1) + (bb + 512), true);
      wgmma_ra<24>(a2, f1, desc_hi(128, 256, 0) + (bb + 896), true);
      wg_commit();
    };
    {
      THREAD_IDS();
      if (OPEN) {
        if (q == 0) { st_relaxed2(G->sum + st0 + 8 * j, 0, 0); st_relaxed2(G->sq + st0 + 8 * j, 0, 0); }
        if (wp == 3) {
#pragma unroll
          for (int i = 0; i < 5; i++) st_relaxed4(G->halo + j * 160 + lane + i * 32, 0, 0, 0, 0);
        }
        if (lane >= OPENL) st_relaxed4(G->obox + (8 * WPROBE + j) * 128 + t, 0, 0, 0, 0);
      }
      xtag = __shfl_sync(0xffffffffu, ~ld_relaxed(G->flag + 32 + 32 * j) & 1, 0);
      if (OPEN && EARLY && lane >= OPENL) st_relaxed4(G->xbox + (2 * j + 1) * 128 + t, xtag ^ 1, 0, 0, 0);
      asm volatile("barrier.cluster.wait.aligned;" ::: "memory");
      PROF(0);
#pragma unroll
      for (int i = 0; i < 96; i++) a1[i] = 0.f;
#pragma unroll
      for (int i = 0; i < 12; i++) a2[i] = 0.f;
      PROF(1);
      rs = ln_gemm_in(c, G, res, sum, w, st0, j, t, [&](int i) { PROF(2 + i); if (i) PROF(4); }, qkv_mma);
    }
#pragma unroll 1
    for (int layer = 0;; layer++) {
      const uint32_t tag = layer ^ 1;
      const int pb = 1 + layer * 30;
      uint4 own[5];
      {
        THREAD_IDS();
        PROF(pb + 4);
        uint32_t kv[3][18];
        auto cvt = [&](int b, float r) {
#pragma unroll
          for (int cc = 0; cc < 18; cc++) {
            const float* a = (cc == 8 ? a2 + 4 : cc == 17 ? a2 + 8 : cc < 8 ? a1 + 32 + 4 * cc : a1 + 28 + 4 * cc) + 2 * (b - 1);
            const uint32_t u = pack_bf16(a[0] * r, a[1] * r);
            kv[b][cc] = cc < 9 ? u : movm(u);
          }
        };
        cvt(2, rs.y);
        const uint32_t msg = sb + SM_X + (w ? 3 * XSLOT : 24576) + wp * 2304 + lane * 16;
        if (wp == 3) {
          uint4* hp = G->halo + j * 160 + lane;
#pragma unroll
          for (int i = 0; i < 4; i++) st_relaxed4(hp + i * 32, tagged(kv[2][4 * i], tag), kv[2][4 * i + 1], kv[2][4 * i + 2], kv[2][4 * i + 3]);
          st_relaxed2((uint2*)(hp + 128), tagged(kv[2][16], tag), kv[2][17]);
        } else {
#pragma unroll
          for (int i = 0; i < 4; i++) sts128(msg + i * 512, kv[2][4 * i], kv[2][4 * i + 1], kv[2][4 * i + 2], kv[2][4 * i + 3]);
          sts64f(msg + 2048 - lane * 8, __uint_as_float(kv[2][16]), __uint_as_float(kv[2][17]));
        }
        cvt(1, rs.x);
        uint32_t Q[4][6];
#pragma unroll
        for (int h = 0; h < 4; h++)
#pragma unroll
          for (int i = 0; i < 6; i++) {
            const float* a = 4 * h + i < 16 ? a1 + 8 * h + 2 * i : a2 + 8 * h + 2 * i - 32;
            const uint32_t u = pack_bf16(a[0], a[1]);
            Q[h][i] = i < 2 ? (q >= h ? u : 0) : i < 4 ? u : (q <= h ? u : 0);
          }
        const bool lo0 = 2 * q > g, lo1 = 2 * q + 1 > g;
        const uint32_t M = (lo0 ? 0xffffu : 0u) | (lo1 ? 0xffff0000u : 0u);
        auto scores = [&](int h, int b, float (&s)[4]) {
          mma16816z(s, Q[h][0], Q[h][1], Q[h][2], Q[h][3], kv[b][2 * h], kv[b][2 * h + 1]);
          mma1688(s, Q[h][4], Q[h][5], kv[b][2 * h + 2]);
        };
        auto softmax = [&](float (&l)[4][2], float r, uint32_t (&P)[4]) {
          const float sl = r * (0.23570226039551584f * 1.4426950408889634f);
          float m[4];
#pragma unroll
          for (int h = 0; h < 4; h++) { m[h] = fmaxf(l[h][0], l[h][1]); m[h] = fmaxf(m[h], __shfl_xor_sync(0xffffffffu, m[h], 1)); }
#pragma unroll
          for (int h = 0; h < 4; h++) m[h] = fmaxf(m[h], __shfl_xor_sync(0xffffffffu, m[h], 2)) * sl;
#pragma unroll
          for (int h = 0; h < 4; h++) {
            l[h][0] = ex2(fmaf(l[h][0], sl, -m[h])); l[h][1] = ex2(fmaf(l[h][1], sl, -m[h]));
            m[h] = l[h][0] + l[h][1]; m[h] += __shfl_xor_sync(0xffffffffu, m[h], 1);
          }
#pragma unroll
          for (int h = 0; h < 4; h++) { m[h] = rcp(m[h] + __shfl_xor_sync(0xffffffffu, m[h], 2)); P[h] = pack_bf16(l[h][0] * m[h], l[h][1] * m[h]); }
        };
        const bool remote = wp == 0 && rb > 0;
        const uint4* hp = (G - 2)->halo + j * 160 + lane;
        auto halo = [&] {
#pragma unroll
          for (int i = 0; i < 4; i++) { const uint4 u = ld_relaxed4(hp + i * 32); kv[0][4 * i] = u.x; kv[0][4 * i + 1] = u.y; kv[0][4 * i + 2] = u.z; kv[0][4 * i + 3] = u.w; }
          const uint2 u = ld_relaxed2((const uint2*)(hp + 128));
          kv[0][16] = u.x; kv[0][17] = u.y;
        };
#pragma unroll
        for (int i = 0; i < 18; i++) kv[0][i] = 0;
        if (remote) halo();
        float l0[4][2], l1[4][2];
#pragma unroll
        for (int h = 0; h < 4; h++) {
          float s1[4], s2[4];
          scores(h, 1, s1); scores(h, 2, s2);
          l0[h][0] = s1[0]; l0[h][1] = s1[1];
          l1[h][0] = lo0 ? s1[2] : s2[2]; l1[h][1] = lo1 ? s1[3] : s2[3];
        }
        uint32_t P0[4], P1[4];
        softmax(l1, rs.y, P1);
        if (remote) {
          while (__any_sync(0xffffffffu, chk(chk2(kv[0][0], kv[0][4], tag) | chk2(kv[0][8], kv[0][12], tag), kv[0][16], tag) & 1)) halo();
        }
        if (FG < 0) c.progress(32 * layer + 20);
        wg_bar(w);
        if (wp > 0) {
          const uint32_t from = msg - 2304;
#pragma unroll
          for (int i = 0; i < 4; i++) { const uint4 u = lds128(from + i * 512); kv[0][4 * i] = u.x; kv[0][4 * i + 1] = u.y; kv[0][4 * i + 2] = u.z; kv[0][4 * i + 3] = u.w; }
          const float2 u = lds64(from + 2048 - lane * 8);
          kv[0][16] = __float_as_uint(u.x); kv[0][17] = __float_as_uint(u.y);
        }
        PROF(pb + 5);
        const bool first = (rb == 0 && wp == 0);
#pragma unroll
        for (int h = 0; h < 4; h++) {
          float s0[4];
          scores(h, 0, s0);
          if (first) s0[0] = s0[1] = -INFINITY;
          l0[h][0] = lo0 ? s0[0] : l0[h][0]; l0[h][1] = lo1 ? s0[1] : l0[h][1];
        }
        softmax(l0, rs.x, P0);
        uint4* ob = G->obox + t;
        uint32_t car0 = 0, car1 = 0;
#pragma unroll
        for (int h = 0; h < 4; h++) {
          float o[3][4];
#pragma unroll
          for (int i = 0; i < 3; i++) {
            mma16816z(o[i], P0[h] & ~M, P1[h] & M, 0u, P1[h] & ~M, kv[1][9 + 2 * h + i], kv[2][9 + 2 * h + i]);
            mma1688(o[i], P0[h] & M, 0u, kv[0][9 + 2 * h + i]);
          }
          const uint32_t o0 = q < h ? car0 : pack_bf16(o[0][0], o[0][1]), o1 = q < h ? car1 : pack_bf16(o[0][2], o[0][3]);
          own[h] = make_uint4(o0 | 1, o1, pack_bf16(o[1][0], o[1][1]), pack_bf16(o[1][2], o[1][3]));
          st_relaxed4(ob + (8 * h + j) * 128, own[h].x, own[h].y, own[h].z, own[h].w);
          car0 = pack_bf16(o[2][0], o[2][1]); car1 = pack_bf16(o[2][2], o[2][3]);
        }
        car0 = tagged(car0, tag);
        st_relaxed2((uint2*)(ob + (32 + (j >> 1)) * 128) + (j & 1), car0, car1);
        own[4] = make_uint4(car0, car1, 0, 0);
        PROF(pb + 6);
      }
      {
        THREAD_IDS();
        const uint4* src = G->obox + t;
        asm volatile("" : "+l"(src));
        float a[32], a8[4];
#pragma unroll
        for (int i = 3; i < 8; i++) mbar_wait_c(sb + BAR_FULLX + 8 * i, (c.mX >> i) & 1);
        c.mX ^= 0xf8;
        auto step = [&](const uint4& f, uint32_t r0, int rs, bool acc) {
          wgmma_ra<64>(a, f, desc_hi(0, rs * 128, 1) + (dsb + ((SM_X + 4 * XSLOT) >> 4) + r0 * 8), acc);
          wgmma_ra<8>(a8, f, desc_hi(rs * 16, 0, 0) + (dsb + (SM_WOC >> 4) + r0), acc);
        };
        const uint32_t* probe = &(G->obox + (8 * WPROBE + (lane & 7)) * 128 + (t | 31))->x;
        uint32_t pv = ld_relaxed(probe);
        if (OWNBAR) asm volatile("bar.sync 4, 256;" ::: "memory");
        if (EARLY) mbar_wait_c(sb + BAR_WSUM, 0);
        float e[4];
        wg_fence();
        if (EARLY) {
#pragma unroll
          for (int i = 0; i < 5; i++) wgmma_ra<8>(e, own[i], desc_hi(128, 0, 0) + (dsb + (SM_WSUM >> 4) + 16 * i), i > 0);
          wg_commit();
        }
#pragma unroll
        for (int i = 0; i < 4; i++) step(own[i], 72 * j + 16 * i, 8, i > 0);
        wg_commit();
        if (EARLY) {
          wg_wait<1>();
          if (q == 0) st_relaxed2(G->sum + st0 + 8 * j, (__float_as_uint(e[0] + e[1]) & ~3u) | ((2 * layer + 2) & 3), __float_as_uint(e[2] + e[3]));
        }
        pv &= late(sb + BAR_FULLX + 64, 1);
        while (__any_sync(0xffffffffu, ~pv & 1)) pv = ld_relaxed(probe);
        if (w == 1) asm volatile("bar.sync 7, 256;" ::: "memory");
        uint2 sa, sc;
        uint4 x[32];
        auto load = [&](int i) { x[i] = ld_relaxed4(i < 28 ? src + (i % 7 >= j ? 128 : 0) + (8 * (i / 7) + i % 7) * 128 : src + (i + 4) * 128); };
        auto batch = [&](auto e0, auto e1, auto e2, int b) {
          constexpr int E0 = decltype(e0)::v, E1 = decltype(e1)::v, E2 = decltype(e2)::v;
          const uint32_t one = E0 > 0 && E1 > E0 ? late(sb + BAR_FULLX + 64, 1) : 1;
          while (E1 > E0) {
            uint32_t bad = 0;
#pragma unroll
            for (int i = E0; i < E1; i++) bad = i < 28 ? chk(bad, x[i].x, one) : chk(chk(bad, x[i].x, tag), x[i].z, tag);
            if (!__any_sync(0xffffffffu, bad & 1)) break;
#pragma unroll
            for (int i = E0; i < E1; i++) load(i);
          }
          if (b == 0) PROF(pb + 7);
          if (b > 0 && E2 > E1) wg_wait<WOW>();
#pragma unroll
          for (int i = E1; i < E2; i++) load(i);
          if (EARLY && b == 1) { sa = ld_relaxed2(G->sum + st0 + 16 * q); sc = ld_relaxed2(G->sum + st0 + 16 * q + 8); }
          if (b == WOREL && w == 0) asm volatile("bar.arrive 7, 256;" ::: "memory");
          if (E1 > E0) {
            wg_fence();
#pragma unroll
            for (int i = E0; i < E1; i++) {
              if (i < 28) step(x[i], 72 * (i % 7) + (i % 7 >= j ? 72 : 0) + 16 * (i / 7), 8, true);
              else step(x[i], 144 * (i - 28) + 64, 72, true);
            }
            wg_commit();
          }
        };
        batch(IC<0>(), IC<0>(), IC<WB1>(), -1);
        batch(IC<0>(), IC<WB1>(), IC<WB2>(), 0);
        batch(IC<WB1>(), IC<WB2>(), IC<WB3>(), 1);
        batch(IC<WB2>(), IC<WB3>(), IC<32>(), 2);
        batch(IC<WB3>(), IC<32>(), IC<32>(), 3);
        if (EARLY) {
          float2 e = make_float2(quad_sum(__uint_as_float(sa.x) + __uint_as_float(sc.x)), quad_sum(__uint_as_float(sa.y) + __uint_as_float(sc.y)));
          if (__any_sync(0xffffffffu, chk2(sa.x, sc.x, (2 * layer + 2) & 3) & 3)) e = gather_sums(G->sum + st0 + 16 * q, (2 * layer + 2) & 3);
          sum.x += e.x; sum.y += e.y;
        }
        wg_wait<0>();
        if (w == 0) asm volatile("bar.arrive 3, 256;" ::: "memory");
        PROF(pb + 8);
#pragma unroll
        for (int i = 0; i < 18; i++) {
          v[2 * i] = bf_lo(res[i]) + (i < 16 ? a[2 * i] : a8[2 * i - 32]);
          v[2 * i + 1] = bf_hi(res[i]) + (i < 16 ? a[2 * i + 1] : a8[2 * i - 31]);
        }
      }
      uint32_t lsb;
      uint32_t h[144];
      {
        THREAD_IDS();
        float a[128];
        const uint32_t xd = sb + SM_X + w * 4 * XSLOT + (lane >> 4) * 1024 + (16 * wp + (lane & 15)) * 16;
        const float2 rs = ln_gemm<false>(c, G, v, res, sum, st0, j, t, layer, xtag,
          [&](int i) {
            if (i == 0) {
              lsb = ((res[0] & 1) | (res[4] & 1) << 1 | (res[8] & 1) << 2 | (res[12] & 1) << 3 | (res[16] & 1) << 4) ^ (xtag * 31);
              if (w == 1) asm volatile("bar.sync 3, 256;" ::: "memory");
            }
            PROF(pb + 9 + i);
          },
          [&](int gi, uint32_t bb, const uint4& f0, const uint4& f1) {
            if (gi == 0) PROF(pb + 11);
            wg_fence();
            wgmma_ra<256>(a, f0, desc_hi(4096, 1024, 1) + bb, gi > 0);
            wgmma_ra<256>(a, f1, desc_hi(4096, 1024, 1) + (bb + 128), true);
            wg_commit();
            stsm4(xd + gi * 4096, f0.x, f0.y, f0.z, f0.w);
            stsm4(xd + gi * 4096 + 2048, f1.x, f1.y, f1.z, f1.w);
            if (gi == 17) { fence_async_smem(); wg_bar(w); }
          });
        sts64f(sb + SM_KEEP + (tid_ >> 2) * 8, rs.x * rs.x, rs.y * rs.y);
        c.progress(32 * layer + 22);
        PROF2(pb + 12);
        glu<16, 0>(a, h);
        const Desc da0 = desc_hi(1024, 128, 0) + (dsb + ((SM_X + w * 4 * XSLOT) >> 4));
        auto tile = [&](auto wide, auto last) {
          const uint32_t xe = BAR_EMPTYX + 32 * (t & 1) + 4 * (t & 6);
#pragma unroll 1
          for (int gi = 0; gi < 18; gi++) {
            uint32_t prev;
            const uint32_t bb = c.nextB(prev);
            const Desc da = da0 + gi * 256;
            wg_fence();
            if (wide()) {
              wgmma_ss<256>(a, da, desc_hi(4096, 1024, 1) + bb, gi);
              wgmma_ss<256>(a, da + 128, desc_hi(4096, 1024, 1) + (bb + 128), 1);
            } else {
              wgmma_ss<192>(*(float(*)[96])a, da, desc_hi(2048, 512, 2) + bb, gi);
              wgmma_ss<192>(*(float(*)[96])a, da + 128, desc_hi(2048, 512, 2) + (bb + 64), 1);
            }
            wg_commit();
            wg_wait<1>();
            if (gi > 0 && !(last() && gi > 13)) c.release2(BAR_EMPTYB + prev);
            if (last() && gi >= XREL && !((gi ^ XREL) & 1)) c.release2(BAR_EMPTYX + 16 * ((gi - XREL) & 2) + 2 * ((gi - XREL) & 12));
          }
          wg_wait<0>();
          if (!last()) c.releaseLastB();
          if (last() && t >= (19 - XREL) / 2 && t < 8) { mbar_arrive(sb + xe); mbar_arrive_remote(c.rem + xe); }
        };
        auto yes = [] { return true; };
        auto no = [] { return false; };
        tile(yes, no); PROF2(pb + 13); glu<16, 32>(a, h);
        tile(yes, no); PROF2(pb + 14); glu<16, 64>(a, h);
        tile(no, no); PROF2(pb + 15); glu<12, 96>(a, h);
        const uint32_t hole = sb + SM_B + 12288 + tid_ * 16;
#pragma unroll
        for (int i = 0; i < NSPILL; i++) sts128(hole + i * BSLOT, h[96 + 4 * i], h[97 + 4 * i], h[98 + 4 * i], h[99 + 4 * i]);
        if (w == 1) asm volatile("bar.arrive 8, 256;" ::: "memory");
        tile(no, yes); PROF2(pb + 16); glu<12, 120>(a, h);
#pragma unroll
        for (int i = 0; i < NSPILL; i++) { const uint4 u = lds128(hole + i * BSLOT); h[96 + 4 * i] = u.x; h[97 + 4 * i] = u.y; h[98 + 4 * i] = u.z; h[99 + 4 * i] = u.w; }
      }
      {
        THREAD_IDS();
        float d[32];
        uint4* gt = G->obox + t;
        asm volatile("" : "+l"(gt));
        uint4* const ib = gt + 2 * 4608 + layer * 8 * INBOX;
        auto pass = [&](uint32_t s0, bool last, auto&& hook) {
          const Desc db = desc_hi(0, 1024, 1) + (dsb + (SM_X >> 4) + s0 * (XSLOT >> 4));
          mbar_wait_c(sb + BAR_FULLX + 8 * s0, (c.mX >> s0) & 1);
          asm volatile("bar.sync %0, 256;" ::"r"(8 + w) : "memory");
#pragma unroll
          for (int i = 0; i < 4; i++) {
            const int si = 4 * (i & 1) + (i >> 1);
            if (i > 0) mbar_wait_c(sb + BAR_FULLX + 8 * (s0 + si), (c.mX >> (s0 + si)) & 1);
            wg_fence();
#pragma unroll
            for (int k = 0; k < 9; k++) {
              const uint32_t* hk = h + 36 * i + 4 * k;
              wgmma_ra<64>(d, make_uint4(hk[0], hk[1], hk[2], hk[3]), db + (si * (XSLOT >> 4) + k * 128), last || i + k > 0);
              if (9 * i + k == PPK && !(last && w == 1)) asm volatile("bar.arrive %0, 256;" ::"r"(9 - w) : "memory");
            }
            wg_commit();
            if (i > 0) { wg_wait<1>(); c.release2(BAR_EMPTYX + 8 * (s0 + 4 * ((i - 1) & 1) + ((i - 1) >> 1))); }
            if (i == RHOOK) hook();
          }
          c.mX ^= 0x33u << s0;
        };
        PROF2(pb + 17);
#pragma unroll 1
        for (int p = 0; p < 8; p++) {
          const uint32_t s0 = 2 * (p & 1);
          pass(s0, false, [] {});
          wg_wait<0>();
          c.release2(BAR_EMPTYX + 8 * (s0 + 5));
          uint32_t pk[16];
#pragma unroll
          for (int i = 0; i < 16; i++) pk[i] = pack_bf16(d[2 * i], d[2 * i + 1]);
          if (p >= BREL && p < BREL + 5) {
            const uint32_t o = c.sB + 8 * (p - BREL);
            c.release2(BAR_EMPTYB + (o < 40 ? o : o - 40));
          }
          uint4* const dst = ib + ((j + p) & 7) * INBOX;
          if (p == 0) {
            mbar_wait_c(sb + BAR_CLR + 8 * w, 0);
#pragma unroll
            for (int k = 0; k < 8; k++) red2((uint2*)(ib + k * INBOX + 512) - t, pk[2 * k], pk[2 * k + 1]);
          } else if (p < 7) {
#pragma unroll
            for (int k = 0; k < 4; k++) red4(dst + k * 128, pk[4 * k], pk[4 * k + 1], pk[4 * k + 2], pk[4 * k + 3]);
            if (p == 6) { __syncwarp(); if (lane == 0) mbar_arrive(sb + BAR_REDDONE + 8 * w); }
          } else {
#pragma unroll
            for (int k = 0; k < 4; k++) st_relaxed4(gt + ((j + 7) & 7) * 128 + k * 1024, pk[4 * k] & ~1u, pk[4 * k + 1], pk[4 * k + 2], pk[4 * k + 3]);
          }
        }
        PROF2(pb + 18);
        const uint4 *in = ib + j * INBOX, *pin = gt + j * 128;
        const uint2* in9 = (const uint2*)(in + 512) - t;
        asm volatile("" : "+l"(in), "+l"(pin), "+l"(in9));
        const float2 r2 = lds64(sb + SM_KEEP + (tid_ >> 2) * 8);
        uint2 X9;
        {
          uint4 X[4];
          const uint4* box = gt + 4608;
#pragma unroll
          for (int k = 0; k < 4; k++) X[k] = ld_relaxed4(box + 256 * j + ((k & 1) + 8 * (k & 2)) * 128);
          X9 = ld_relaxed2((const uint2*)(box + (32 + (j >> 1)) * 128) + (j & 1));
          const float i0 = rcp(r2.x), i1 = rcp(r2.y);
#pragma unroll
          for (int k = 0; k < 4; k++) {
            float* e = d + 8 * k;
            X[k].x ^= (lsb >> k) & 1;
            e[0] = bf_lo(X[k].x) * i0; e[1] = bf_hi(X[k].x) * i0; e[2] = bf_lo(X[k].y) * i1; e[3] = bf_hi(X[k].y) * i1;
            e[4] = bf_lo(X[k].z) * i0; e[5] = bf_hi(X[k].z) * i0; e[6] = bf_lo(X[k].w) * i1; e[7] = bf_hi(X[k].w) * i1;
          }
        }
        uint4 R[4], P[4];
        uint2 R9;
        PROF2(pb + 19);
        pass(0, true, [&] {
          mbar_wait_c(sb + BAR_RREADY + 8 * w, layer);
#pragma unroll
          for (int k = 0; k < 4; k++) R[k] = ld_relaxed4(in + k * 128);
          R9 = ld_relaxed2(in9);
#pragma unroll
          for (int k = 0; k < 4; k++) P[k] = ld_relaxed4(pin + k * 1024);
        });
        const uint32_t zero = late(sb + BAR_FULLX + 64, 0);
        while (__any_sync(0xffffffffu, (chk2(P[0].x, P[1].x, zero) | chk2(P[2].x, P[3].x, zero)) & 1)) {
#pragma unroll
          for (int k = 0; k < 4; k++) P[k] = ld_relaxed4(pin + k * 1024);
        }
#pragma unroll
        for (int k = 0; k < 4; k++) {
          const uint32_t u[4] = {hadd2(R[k].x, P[k].x), hadd2(R[k].y, P[k].y), hadd2(R[k].z, P[k].z), hadd2(R[k].w, P[k].w)};
#pragma unroll
          for (int i = 0; i < 4; i++) { v[8 * k + 2 * i] = bf_lo(u[i]); v[8 * k + 2 * i + 1] = bf_hi(u[i]); }
        }
        X9.x = chk(zero, X9.x, lsb >> 4);
        v[32] = fmaf(bf_lo(R9.x), r2.x, bf_lo(X9.x)); v[33] = fmaf(bf_hi(R9.x), r2.x, bf_hi(X9.x));
        v[34] = fmaf(bf_lo(R9.y), r2.y, bf_lo(X9.y)); v[35] = fmaf(bf_hi(R9.y), r2.y, bf_hi(X9.y));
        PROF2(pb + 20);
        wg_wait<0>();
        c.release2(BAR_EMPTYX + 40);
        PROF2(pb + 21);
#pragma unroll
        for (int i = 0; i < 32; i++) v[i] = (v[i] + d[i]) * (i & 2 ? r2.y : r2.x);
      }
      if (layer == NLAYERS - 1) break;
      {
        THREAD_IDS();
        PROF(31);
        rs = ln_gemm<true>(c, G, v, res, sum, st0, j, t, 1, xtag ^ 1, [&](int i) { PROF(32 + i); if (i) PROF(34); }, qkv_mma);
      }
    }
    {
      THREAD_IDS();
      const uint32_t stg = sb + SM_B + warp * 4096;
      const uint32_t sd = stg + (lane & 15) * 128;
#pragma unroll
      for (int i = 0; i < 4; i++)
        stsm4(sd + (((2 * i + (lane >> 4)) ^ (lane & 7)) << 4), pack_bf16(v[8 * i], v[8 * i + 1]), pack_bf16(v[8 * i + 2], v[8 * i + 3]),
              pack_bf16(v[8 * i + 4], v[8 * i + 5]), pack_bf16(v[8 * i + 6], v[8 * i + 7]));
      stsm2(stg + 2048 + (lane & 15) * 16, pack_bf16(v[32], v[33]), pack_bf16(v[34], v[35]));
      fence_async_smem();
      __syncwarp();
      if (lane == 0) {
        tma_store3d(&maps.out, stg, 64 * j, w, 64 * rb + 16 * wp);
        tma_store3d(&maps.outc, stg + 2048, 512 + 8 * j, w, 64 * rb + 16 * wp);
        bulk_commit();
        if (wp == 0) st_relaxed(G->flag + 32 + 32 * j, xtag);
        bulk_wait_all();
        mbar_arrive(sb + BAR_DONE + 8 * w);
      }
      PROF(61);
    }
    __syncwarp();
    cluster_sync();
  }
}

typedef CUresult (*EncFn)(CUtensorMap*, CUtensorMapDataType, cuuint32_t, void*, const cuuint64_t*, const cuuint64_t*, const cuuint32_t*,
                          const cuuint32_t*, CUtensorMapInterleave, CUtensorMapSwizzle, CUtensorMapL2promotion, CUtensorMapFloatOOBfill);

void make_map(EncFn enc, CUtensorMap* m, const void* p, int rank, uint64_t d0, uint64_t d1, uint64_t d2, uint64_t s1, uint64_t s2, uint32_t b0,
              uint32_t b1, uint32_t b2, CUtensorMapSwizzle sw) {
  cuuint64_t gd[3] = {d0, d1, d2};
  cuuint64_t gs[2] = {s1, s2};
  cuuint32_t bd[3] = {b0, b1, b2};
  cuuint32_t es[3] = {1, 1, 1};
  enc(m, CU_TENSOR_MAP_DATA_TYPE_BFLOAT16, rank, const_cast<void*>(p), gd, gs, bd, es, CU_TENSOR_MAP_INTERLEAVE_NONE, sw,
      CU_TENSOR_MAP_L2_PROMOTION_L2_128B, CU_TENSOR_MAP_FLOAT_OOB_FILL_NONE);
}

}

extern "C" void kernel_launch(void* const* d_in, const int* in_sizes, int n_in, void* d_out, int out_size) {
  const __nv_bfloat16* x = (const __nv_bfloat16*)d_in[0];
  const char *wqkv = (const char*)d_in[1], *wo = (const char*)d_in[2], *wg = (const char*)d_in[4], *wu = (const char*)d_in[5], *wd = (const char*)d_in[6];
  static EncFn enc = nullptr;
  static Group* ws = nullptr;
  if (!enc) {
    cudaDriverEntryPointQueryResult qr;
    cudaGetDriverEntryPoint("cuTensorMapEncodeTiled", (void**)&enc, cudaEnableDefault, &qr);
    cudaGetSymbolAddress((void**)&ws, g_ws);
    cudaFuncSetAttribute(fused_kernel, cudaFuncAttributeMaxDynamicSharedMemorySize, SMEM_BYTES);
  }
  const CUtensorMapSwizzle S0 = CU_TENSOR_MAP_SWIZZLE_NONE, S64 = CU_TENSOR_MAP_SWIZZLE_64B, S128 = CU_TENSOR_MAP_SWIZZLE_128B;
  Maps m;
  make_map(enc, &m.x, x, 3, 576, 2, 1024, 1152, 2304, 64, 1, 64, S128);
  make_map(enc, &m.qm, wqkv, 3, 576, 576, 3, 3456, 1152, 64, 16, 3, S128);
  make_map(enc, &m.qc, wqkv, 3, 576, 576, 3, 3456, 1152, 8, 16, 3, S0);
  make_map(enc, &m.o, wo, 2, 576, 576, 1, 1152, 0, 64, 72, 1, S128);
  make_map(enc, &m.oc, wo, 2, 576, 576, 1, 1152, 0, 8, 144, 1, S0);
  make_map(enc, &m.g, wg, 3, 64, 576, 72, 9216, 128, 64, 32, 2, S128);
  make_map(enc, &m.u, wu, 3, 64, 576, 72, 9216, 128, 64, 32, 2, S128);
  make_map(enc, &m.g3, wg, 3, 32, 576, 144, 9216, 64, 32, 32, 3, S64);
  make_map(enc, &m.u3, wu, 3, 32, 576, 144, 9216, 64, 32, 32, 3, S64);
  make_map(enc, &m.d, wd, 2, 576, 4608, 1, 1152, 0, 64, 72, 1, S128);
  make_map(enc, &m.out, d_out, 3, 576, 2, 1024, 1152, 2304, 64, 1, 16, S128);
  make_map(enc, &m.outc, d_out, 3, 576, 2, 1024, 1152, 2304, 8, 1, 16, S0);
  fused_kernel<<<NCTA, 384, SMEM_BYTES>>>(x, ws, wqkv, wg, wu, wd, m, wo);
}
```

```cpp
#include <cuda_runtime.h>
#include <cuda_bf16.h>
#include <cuda.h>
#include <stdint.h>
#include <stddef.h>

namespace {

constexpr int D_ = 576;
constexpr int NCTA = 128;
#define NLAYERS 2
#define W_POLICY policy_evict_first
#define A_POLICY policy_evict_normal
#define OPEN 1
#define PFMODE 5
#define WWIN 4
#define WOREL -1
#define WB1 11
#define WB2 21
#define WB3 32
#define WPROBE 1
#define WPROBE2 0
#define SPEC 2
#define POLLFIRST 0
#define SUMFIRST 1
#define EARLYPOLL 1
#define LEAD 0
#define ATTBAR 0
#define GL 18
#define WOBAR 0
#define QD 0
#define QG 4
#define PFQ 1
#define XDELAY 0
#define WOH 1
#define PFSLEEP 700
#define GPCMAP 1
#define PFF 1
#define REDN 1
#define CLRSLEEP 300
#define OPENL 24
#define FG -1
#define NON8 0
#define HMUL 1
#define FCH 1
#define PPK 34
#define RHOOK 0
#define SCHEDBAR 1
#define QH 5
#define XH 3
#define XP 0
#define GSLEEP 32
#define XCH 1
#define MAPPF 1
#define XREL 8
#define WOG 13
#define BREL 1
#define FENCE1 0
#define OWNX 0
#define OWNBAR 1
#define EARLY 1
#define ESPEC 0
#define TESTP 0
#define WOW 1
#define STATP -1
#define WSG 0
#define REPACK 1
#define QPACE 23
#define RDELAY 12
#define NSPILL 4
#define REGS_C 232
#define REGS_P 40
#define STR2(x) #x
#define STR(x) STR2(x)
constexpr uint32_t SM_X = 0;
constexpr uint32_t XSLOT = 18432;
constexpr uint32_t SM_WOC = SM_X + 3 * XSLOT + 9216;
constexpr uint32_t SM_B = 147456;
constexpr uint32_t BSLOT = 16384;
constexpr uint32_t SM_KEEP = 229376;
constexpr uint32_t SM_WSUM = SM_KEEP + 512;
constexpr uint32_t SM_BAR = SM_KEEP + 2048;
constexpr uint32_t BAR_FULLB = SM_BAR;
constexpr uint32_t BAR_RREADY = SM_BAR + 40;
constexpr uint32_t BAR_CLR = SM_BAR + 56;
constexpr uint32_t BAR_FULLX = SM_BAR + 72;
constexpr uint32_t BAR_EMPTYB = SM_BAR + 144;
constexpr uint32_t BAR_EMPTYX = SM_BAR + 184;
constexpr uint32_t BAR_REDDONE = SM_BAR + 248;
constexpr uint32_t BAR_DONE = SM_BAR + 264;
constexpr uint32_t BAR_WSUM = SM_BAR + 280;
constexpr uint32_t SM_PROG = SM_BAR + 288;
constexpr uint32_t SMEM_BYTES = SM_BAR + 1024;

struct Maps { CUtensorMap x, qm, qc, o, oc, g, u, g3, u3, d, out, outc; };

constexpr int INBOX = 576;
struct Group {
  uint2 sum[4 * 8 * 8];
  uint2 sq[4 * 8 * 8];
  uint32_t wsum[512];
  uint32_t flag[512];
  uint4 halo[8 * 160];
  uint4 obox[36 * 128];
  uint4 xbox[36 * 128];
  uint4 inbox[2][8 * INBOX];
};
struct Scratch { Group g[32]; uint4 wq[8][36][432]; };
__device__ __align__(1024) Scratch g_ws;
#define PROF(i)
#define PROFX(i)

#define PROF2(i) PROF(i)

struct Desc { uint32_t lo, hi; };
__device__ __forceinline__ constexpr Desc desc_hi(uint32_t lbo, uint32_t sbo, uint32_t sw) { return Desc{(lbo >> 4) << 16, (sbo >> 4) | sw << 30}; }
__device__ __forceinline__ constexpr Desc operator+(Desc d, uint32_t a) { return Desc{d.lo + a, d.hi}; }

template<int N> __device__ __forceinline__ void wgmma_ss(float (&d)[N / 2], Desc da, Desc db, int sc);
template<> __device__ __forceinline__ void wgmma_ss<192>(float (&d)[96], Desc da, Desc db, int sc) {
  asm volatile("{\n.reg .pred p;\n.reg .b64 a, b;\nsetp.ne.b32 p, %100, 0;\nmov.b64 a, {%96, %97};\nmov.b64 b, {%98, %99};\n"
    "wgmma.mma_async.sync.aligned.m64n192k16.f32.bf16.bf16 {%0,%1,%2,%3,%4,%5,%6,%7,%8,%9,%10,%11,%12,%13,%14,%15,%16,%17,%18,%19,%20,%21,%22,%23,%24,%25,%26,%27,%28,%29,%30,%31,%32,%33,%34,%35,%36,%37,%38,%39,%40,%41,%42,%43,%44,%45,%46,%47,%48,%49,%50,%51,%52,%53,%54,%55,%56,%57,%58,%59,%60,%61,%62,%63,%64,%65,%66,%67,%68,%69,%70,%71,%72,%73,%74,%75,%76,%77,%78,%79,%80,%81,%82,%83,%84,%85,%86,%87,%88,%89,%90,%91,%92,%93,%94,%95}, a, b, p, 1, 1, 0, 1;\n}\n"
    : "+f"(d[0]),"+f"(d[1]),"+f"(d[2]),"+f"(d[3]),"+f"(d[4]),"+f"(d[5]),"+f"(d[6]),"+f"(d[7]),"+f"(d[8]),"+f"(d[9]),"+f"(d[10]),"+f"(d[11]),"+f"(d[12]),"+f"(d[13]),"+f"(d[14]),"+f"(d[15]),"+f"(d[16]),"+f"(d[17]),"+f"(d[18]),"+f"(d[19]),"+f"(d[20]),"+f"(d[21]),"+f"(d[22]),"+f"(d[23]),"+f"(d[24]),"+f"(d[25]),"+f"(d[26]),"+f"(d[27]),"+f"(d[28]),"+f"(d[29]),"+f"(d[30]),"+f"(d[31]),"+f"(d[32]),"+f"(d[33]),"+f"(d[34]),"+f"(d[35]),"+f"(d[36]),"+f"(d[37]),"+f"(d[38]),"+f"(d[39]),"+f"(d[40]),"+f"(d[41]),"+f"(d[42]),"+f"(d[43]),"+f"(d[44]),"+f"(d[45]),"+f"(d[46]),"+f"(d[47]),"+f"(d[48]),"+f"(d[49]),"+f"(d[50]),"+f"(d[51]),"+f"(d[52]),"+f"(d[53]),"+f"(d[54]),"+f"(d[55]),"+f"(d[56]),"+f"(d[57]),"+f"(d[58]),"+f"(d[59]),"+f"(d[60]),"+f"(d[61]),"+f"(d[62]),"+f"(d[63]),"+f"(d[64]),"+f"(d[65]),"+f"(d[66]),"+f"(d[67]),"+f"(d[68]),"+f"(d[69]),"+f"(d[70]),"+f"(d[71]),"+f"(d[72]),"+f"(d[73]),"+f"(d[74]),"+f"(d[75]),"+f"(d[76]),"+f"(d[77]),"+f"(d[78]),"+f"(d[79]),"+f"(d[80]),"+f"(d[81]),"+f"(d[82]),"+f"(d[83]),"+f"(d[84]),"+f"(d[85]),"+f"(d[86]),"+f"(d[87]),"+f"(d[88]),"+f"(d[89]),"+f"(d[90]),"+f"(d[91]),"+f"(d[92]),"+f"(d[93]),"+f"(d[94]),"+f"(d[95]) : "r"(da.lo), "r"(da.hi), "r"(db.lo), "r"(db.hi), "r"(sc));
}
template<> __device__ __forceinline__ void wgmma_ss<256>(float (&d)[128], Desc da, Desc db, int sc) {
  asm volatile("{\n.reg .pred p;\n.reg .b64 a, b;\nsetp.ne.b32 p, %132, 0;\nmov.b64 a, {%128, %129};\nmov.b64 b, {%130, %131};\n"
    "wgmma.mma_async.sync.aligned.m64n256k16.f32.bf16.bf16 {%0,%1,%2,%3,%4,%5,%6,%7,%8,%9,%10,%11,%12,%13,%14,%15,%16,%17,%18,%19,%20,%21,%22,%23,%24,%25,%26,%27,%28,%29,%30,%31,%32,%33,%34,%35,%36,%37,%38,%39,%40,%41,%42,%43,%44,%45,%46,%47,%48,%49,%50,%51,%52,%53,%54,%55,%56,%57,%58,%59,%60,%61,%62,%63,%64,%65,%66,%67,%68,%69,%70,%71,%72,%73,%74,%75,%76,%77,%78,%79,%80,%81,%82,%83,%84,%85,%86,%87,%88,%89,%90,%91,%92,%93,%94,%95,%96,%97,%98,%99,%100,%101,%102,%103,%104,%105,%106,%107,%108,%109,%110,%111,%112,%113,%114,%115,%116,%117,%118,%119,%120,%121,%122,%123,%124,%125,%126,%127}, a, b, p, 1, 1, 0, 1;\n}\n"
    : "+f"(d[0]),"+f"(d[1]),"+f"(d[2]),"+f"(d[3]),"+f"(d[4]),"+f"(d[5]),"+f"(d[6]),"+f"(d[7]),"+f"(d[8]),"+f"(d[9]),"+f"(d[10]),"+f"(d[11]),"+f"(d[12]),"+f"(d[13]),"+f"(d[14]),"+f"(d[15]),"+f"(d[16]),"+f"(d[17]),"+f"(d[18]),"+f"(d[19]),"+f"(d[20]),"+f"(d[21]),"+f"(d[22]),"+f"(d[23]),"+f"(d[24]),"+f"(d[25]),"+f"(d[26]),"+f"(d[27]),"+f"(d[28]),"+f"(d[29]),"+f"(d[30]),"+f"(d[31]),"+f"(d[32]),"+f"(d[33]),"+f"(d[34]),"+f"(d[35]),"+f"(d[36]),"+f"(d[37]),"+f"(d[38]),"+f"(d[39]),"+f"(d[40]),"+f"(d[41]),"+f"(d[42]),"+f"(d[43]),"+f"(d[44]),"+f"(d[45]),"+f"(d[46]),"+f"(d[47]),"+f"(d[48]),"+f"(d[49]),"+f"(d[50]),"+f"(d[51]),"+f"(d[52]),"+f"(d[53]),"+f"(d[54]),"+f"(d[55]),"+f"(d[56]),"+f"(d[57]),"+f"(d[58]),"+f"(d[59]),"+f"(d[60]),"+f"(d[61]),"+f"(d[62]),"+f"(d[63]),"+f"(d[64]),"+f"(d[65]),"+f"(d[66]),"+f"(d[67]),"+f"(d[68]),"+f"(d[69]),"+f"(d[70]),"+f"(d[71]),"+f"(d[72]),"+f"(d[73]),"+f"(d[74]),"+f"(d[75]),"+f"(d[76]),"+f"(d[77]),"+f"(d[78]),"+f"(d[79]),"+f"(d[80]),"+f"(d[81]),"+f"(d[82]),"+f"(d[83]),"+f"(d[84]),"+f"(d[85]),"+f"(d[86]),"+f"(d[87]),"+f"(d[88]),"+f"(d[89]),"+f"(d[90]),"+f"(d[91]),"+f"(d[92]),"+f"(d[93]),"+f"(d[94]),"+f"(d[95]),"+f"(d[96]),"+f"(d[97]),"+f"(d[98]),"+f"(d[99]),"+f"(d[100]),"+f"(d[101]),"+f"(d[102]),"+f"(d[103]),"+f"(d[104]),"+f"(d[105]),"+f"(d[106]),"+f"(d[107]),"+f"(d[108]),"+f"(d[109]),"+f"(d[110]),"+f"(d[111]),"+f"(d[112]),"+f"(d[113]),"+f"(d[114]),"+f"(d[115]),"+f"(d[116]),"+f"(d[117]),"+f"(d[118]),"+f"(d[119]),"+f"(d[120]),"+f"(d[121]),"+f"(d[122]),"+f"(d[123]),"+f"(d[124]),"+f"(d[125]),"+f"(d[126]),"+f"(d[127]) : "r"(da.lo), "r"(da.hi), "r"(db.lo), "r"(db.hi), "r"(sc));
}
template<int N, int ACC> __device__ __forceinline__ void wgmma_rs(float (&d)[N / 2], const uint4& a, Desc db);
template<> __device__ __forceinline__ void wgmma_rs<8, 1>(float (&d)[4], const uint4& a, Desc db) {
  asm volatile("{\n.reg .pred p;\n.reg .b64 b;\nsetp.ne.b32 p, 1, 0;\nmov.b64 b, {%8, %9};\n"
    "wgmma.mma_async.sync.aligned.m64n8k16.f32.bf16.bf16 {%0,%1,%2,%3}, {%4,%5,%6,%7}, b, p, 1, 1, 1;\n}\n"
    : "+f"(d[0]),"+f"(d[1]),"+f"(d[2]),"+f"(d[3]) : "r"(a.x), "r"(a.y), "r"(a.z), "r"(a.w), "r"(db.lo), "r"(db.hi));
}
template<> __device__ __forceinline__ void wgmma_rs<8, 0>(float (&d)[4], const uint4& a, Desc db) {
  asm volatile("{\n.reg .pred p;\n.reg .b64 b;\nsetp.ne.b32 p, 0, 0;\nmov.b64 b, {%8, %9};\n"
    "wgmma.mma_async.sync.aligned.m64n8k16.f32.bf16.bf16 {%0,%1,%2,%3}, {%4,%5,%6,%7}, b, p, 1, 1, 1;\n}\n"
    : "=f"(d[0]),"=f"(d[1]),"=f"(d[2]),"=f"(d[3]) : "r"(a.x), "r"(a.y), "r"(a.z), "r"(a.w), "r"(db.lo), "r"(db.hi));
}
template<> __device__ __forceinline__ void wgmma_rs<24, 1>(float (&d)[12], const uint4& a, Desc db) {
  asm volatile("{\n.reg .pred p;\n.reg .b64 b;\nsetp.ne.b32 p, 1, 0;\nmov.b64 b, {%16, %17};\n"
    "wgmma.mma_async.sync.aligned.m64n24k16.f32.bf16.bf16 {%0,%1,%2,%3,%4,%5,%6,%7,%8,%9,%10,%11}, {%12,%13,%14,%15}, b, p, 1, 1, 1;\n}\n"
    : "+f"(d[0]),"+f"(d[1]),"+f"(d[2]),"+f"(d[3]),"+f"(d[4]),"+f"(d[5]),"+f"(d[6]),"+f"(d[7]),"+f"(d[8]),"+f"(d[9]),"+f"(d[10]),"+f"(d[11]) : "r"(a.x), "r"(a.y), "r"(a.z), "r"(a.w), "r"(db.lo), "r"(db.hi));
}
template<> __device__ __forceinline__ void wgmma_rs<24, 0>(float (&d)[12], const uint4& a, Desc db) {
  asm volatile("{\n.reg .pred p;\n.reg .b64 b;\nsetp.ne.b32 p, 0, 0;\nmov.b64 b, {%16, %17};\n"
    "wgmma.mma_async.sync.aligned.m64n24k16.f32.bf16.bf16 {%0,%1,%2,%3,%4,%5,%6,%7,%8,%9,%10,%11}, {%12,%13,%14,%15}, b, p, 1, 1, 1;\n}\n"
    : "=f"(d[0]),"=f"(d[1]),"=f"(d[2]),"=f"(d[3]),"=f"(d[4]),"=f"(d[5]),"=f"(d[6]),"=f"(d[7]),"=f"(d[8]),"=f"(d[9]),"=f"(d[10]),"=f"(d[11]) : "r"(a.x), "r"(a.y), "r"(a.z), "r"(a.w), "r"(db.lo), "r"(db.hi));
}
template<> __device__ __forceinline__ void wgmma_rs<64, 1>(float (&d)[32], const uint4& a, Desc db) {
  asm volatile("{\n.reg .pred p;\n.reg .b64 b;\nsetp.ne.b32 p, 1, 0;\nmov.b64 b, {%36, %37};\n"
    "wgmma.mma_async.sync.aligned.m64n64k16.f32.bf16.bf16 {%0,%1,%2,%3,%4,%5,%6,%7,%8,%9,%10,%11,%12,%13,%14,%15,%16,%17,%18,%19,%20,%21,%22,%23,%24,%25,%26,%27,%28,%29,%30,%31}, {%32,%33,%34,%35}, b, p, 1, 1, 1;\n}\n"
    : "+f"(d[0]),"+f"(d[1]),"+f"(d[2]),"+f"(d[3]),"+f"(d[4]),"+f"(d[5]),"+f"(d[6]),"+f"(d[7]),"+f"(d[8]),"+f"(d[9]),"+f"(d[10]),"+f"(d[11]),"+f"(d[12]),"+f"(d[13]),"+f"(d[14]),"+f"(d[15]),"+f"(d[16]),"+f"(d[17]),"+f"(d[18]),"+f"(d[19]),"+f"(d[20]),"+f"(d[21]),"+f"(d[22]),"+f"(d[23]),"+f"(d[24]),"+f"(d[25]),"+f"(d[26]),"+f"(d[27]),"+f"(d[28]),"+f"(d[29]),"+f"(d[30]),"+f"(d[31]) : "r"(a.x), "r"(a.y), "r"(a.z), "r"(a.w), "r"(db.lo), "r"(db.hi));
}
template<> __device__ __forceinline__ void wgmma_rs<64, 0>(float (&d)[32], const uint4& a, Desc db) {
  asm volatile("{\n.reg .pred p;\n.reg .b64 b;\nsetp.ne.b32 p, 0, 0;\nmov.b64 b, {%36, %37};\n"
    "wgmma.mma_async.sync.aligned.m64n64k16.f32.bf16.bf16 {%0,%1,%2,%3,%4,%5,%6,%7,%8,%9,%10,%11,%12,%13,%14,%15,%16,%17,%18,%19,%20,%21,%22,%23,%24,%25,%26,%27,%28,%29,%30,%31}, {%32,%33,%34,%35}, b, p, 1, 1, 1;\n}\n"
    : "=f"(d[0]),"=f"(d[1]),"=f"(d[2]),"=f"(d[3]),"=f"(d[4]),"=f"(d[5]),"=f"(d[6]),"=f"(d[7]),"=f"(d[8]),"=f"(d[9]),"=f"(d[10]),"=f"(d[11]),"=f"(d[12]),"=f"(d[13]),"=f"(d[14]),"=f"(d[15]),"=f"(d[16]),"=f"(d[17]),"=f"(d[18]),"=f"(d[19]),"=f"(d[20]),"=f"(d[21]),"=f"(d[22]),"=f"(d[23]),"=f"(d[24]),"=f"(d[25]),"=f"(d[26]),"=f"(d[27]),"=f"(d[28]),"=f"(d[29]),"=f"(d[30]),"=f"(d[31]) : "r"(a.x), "r"(a.y), "r"(a.z), "r"(a.w), "r"(db.lo), "r"(db.hi));
}
template<> __device__ __forceinline__ void wgmma_rs<192, 1>(float (&d)[96], const uint4& a, Desc db) {
  asm volatile("{\n.reg .pred p;\n.reg .b64 b;\nsetp.ne.b32 p, 1, 0;\nmov.b64 b, {%100, %101};\n"
    "wgmma.mma_async.sync.aligned.m64n192k16.f32.bf16.bf16 {%0,%1,%2,%3,%4,%5,%6,%7,%8,%9,%10,%11,%12,%13,%14,%15,%16,%17,%18,%19,%20,%21,%22,%23,%24,%25,%26,%27,%28,%29,%30,%31,%32,%33,%34,%35,%36,%37,%38,%39,%40,%41,%42,%43,%44,%45,%46,%47,%48,%49,%50,%51,%52,%53,%54,%55,%56,%57,%58,%59,%60,%61,%62,%63,%64,%65,%66,%67,%68,%69,%70,%71,%72,%73,%74,%75,%76,%77,%78,%79,%80,%81,%82,%83,%84,%85,%86,%87,%88,%89,%90,%91,%92,%93,%94,%95}, {%96,%97,%98,%99}, b, p, 1, 1, 1;\n}\n"
    : "+f"(d[0]),"+f"(d[1]),"+f"(d[2]),"+f"(d[3]),"+f"(d[4]),"+f"(d[5]),"+f"(d[6]),"+f"(d[7]),"+f"(d[8]),"+f"(d[9]),"+f"(d[10]),"+f"(d[11]),"+f"(d[12]),"+f"(d[13]),"+f"(d[14]),"+f"(d[15]),"+f"(d[16]),"+f"(d[17]),"+f"(d[18]),"+f"(d[19]),"+f"(d[20]),"+f"(d[21]),"+f"(d[22]),"+f"(d[23]),"+f"(d[24]),"+f"(d[25]),"+f"(d[26]),"+f"(d[27]),"+f"(d[28]),"+f"(d[29]),"+f"(d[30]),"+f"(d[31]),"+f"(d[32]),"+f"(d[33]),"+f"(d[34]),"+f"(d[35]),"+f"(d[36]),"+f"(d[37]),"+f"(d[38]),"+f"(d[39]),"+f"(d[40]),"+f"(d[41]),"+f"(d[42]),"+f"(d[43]),"+f"(d[44]),"+f"(d[45]),"+f"(d[46]),"+f"(d[47]),"+f"(d[48]),"+f"(d[49]),"+f"(d[50]),"+f"(d[51]),"+f"(d[52]),"+f"(d[53]),"+f"(d[54]),"+f"(d[55]),"+f"(d[56]),"+f"(d[57]),"+f"(d[58]),"+f"(d[59]),"+f"(d[60]),"+f"(d[61]),"+f"(d[62]),"+f"(d[63]),"+f"(d[64]),"+f"(d[65]),"+f"(d[66]),"+f"(d[67]),"+f"(d[68]),"+f"(d[69]),"+f"(d[70]),"+f"(d[71]),"+f"(d[72]),"+f"(d[73]),"+f"(d[74]),"+f"(d[75]),"+f"(d[76]),"+f"(d[77]),"+f"(d[78]),"+f"(d[79]),"+f"(d[80]),"+f"(d[81]),"+f"(d[82]),"+f"(d[83]),"+f"(d[84]),"+f"(d[85]),"+f"(d[86]),"+f"(d[87]),"+f"(d[88]),"+f"(d[89]),"+f"(d[90]),"+f"(d[91]),"+f"(d[92]),"+f"(d[93]),"+f"(d[94]),"+f"(d[95]) : "r"(a.x), "r"(a.y), "r"(a.z), "r"(a.w), "r"(db.lo), "r"(db.hi));
}
template<> __device__ __forceinline__ void wgmma_rs<192, 0>(float (&d)[96], const uint4& a, Desc db) {
  asm volatile("{\n.reg .pred p;\n.reg .b64 b;\nsetp.ne.b32 p, 0, 0;\nmov.b64 b, {%100, %101};\n"
    "wgmma.mma_async.sync.aligned.m64n192k16.f32.bf16.bf16 {%0,%1,%2,%3,%4,%5,%6,%7,%8,%9,%10,%11,%12,%13,%14,%15,%16,%17,%18,%19,%20,%21,%22,%23,%24,%25,%26,%27,%28,%29,%30,%31,%32,%33,%34,%35,%36,%37,%38,%39,%40,%41,%42,%43,%44,%45,%46,%47,%48,%49,%50,%51,%52,%53,%54,%55,%56,%57,%58,%59,%60,%61,%62,%63,%64,%65,%66,%67,%68,%69,%70,%71,%72,%73,%74,%75,%76,%77,%78,%79,%80,%81,%82,%83,%84,%85,%86,%87,%88,%89,%90,%91,%92,%93,%94,%95}, {%96,%97,%98,%99}, b, p, 1, 1, 1;\n}\n"
    : "=f"(d[0]),"=f"(d[1]),"=f"(d[2]),"=f"(d[3]),"=f"(d[4]),"=f"(d[5]),"=f"(d[6]),"=f"(d[7]),"=f"(d[8]),"=f"(d[9]),"=f"(d[10]),"=f"(d[11]),"=f"(d[12]),"=f"(d[13]),"=f"(d[14]),"=f"(d[15]),"=f"(d[16]),"=f"(d[17]),"=f"(d[18]),"=f"(d[19]),"=f"(d[20]),"=f"(d[21]),"=f"(d[22]),"=f"(d[23]),"=f"(d[24]),"=f"(d[25]),"=f"(d[26]),"=f"(d[27]),"=f"(d[28]),"=f"(d[29]),"=f"(d[30]),"=f"(d[31]),"=f"(d[32]),"=f"(d[33]),"=f"(d[34]),"=f"(d[35]),"=f"(d[36]),"=f"(d[37]),"=f"(d[38]),"=f"(d[39]),"=f"(d[40]),"=f"(d[41]),"=f"(d[42]),"=f"(d[43]),"=f"(d[44]),"=f"(d[45]),"=f"(d[46]),"=f"(d[47]),"=f"(d[48]),"=f"(d[49]),"=f"(d[50]),"=f"(d[51]),"=f"(d[52]),"=f"(d[53]),"=f"(d[54]),"=f"(d[55]),"=f"(d[56]),"=f"(d[57]),"=f"(d[58]),"=f"(d[59]),"=f"(d[60]),"=f"(d[61]),"=f"(d[62]),"=f"(d[63]),"=f"(d[64]),"=f"(d[65]),"=f"(d[66]),"=f"(d[67]),"=f"(d[68]),"=f"(d[69]),"=f"(d[70]),"=f"(d[71]),"=f"(d[72]),"=f"(d[73]),"=f"(d[74]),"=f"(d[75]),"=f"(d[76]),"=f"(d[77]),"=f"(d[78]),"=f"(d[79]),"=f"(d[80]),"=f"(d[81]),"=f"(d[82]),"=f"(d[83]),"=f"(d[84]),"=f"(d[85]),"=f"(d[86]),"=f"(d[87]),"=f"(d[88]),"=f"(d[89]),"=f"(d[90]),"=f"(d[91]),"=f"(d[92]),"=f"(d[93]),"=f"(d[94]),"=f"(d[95]) : "r"(a.x), "r"(a.y), "r"(a.z), "r"(a.w), "r"(db.lo), "r"(db.hi));
}
template<> __device__ __forceinline__ void wgmma_rs<256, 1>(float (&d)[128], const uint4& a, Desc db) {
  asm volatile("{\n.reg .pred p;\n.reg .b64 b;\nsetp.ne.b32 p, 1, 0;\nmov.b64 b, {%132, %133};\n"
    "wgmma.mma_async.sync.aligned.m64n256k16.f32.bf16.bf16 {%0,%1,%2,%3,%4,%5,%6,%7,%8,%9,%10,%11,%12,%13,%14,%15,%16,%17,%18,%19,%20,%21,%22,%23,%24,%25,%26,%27,%28,%29,%30,%31,%32,%33,%34,%35,%36,%37,%38,%39,%40,%41,%42,%43,%44,%45,%46,%47,%48,%49,%50,%51,%52,%53,%54,%55,%56,%57,%58,%59,%60,%61,%62,%63,%64,%65,%66,%67,%68,%69,%70,%71,%72,%73,%74,%75,%76,%77,%78,%79,%80,%81,%82,%83,%84,%85,%86,%87,%88,%89,%90,%91,%92,%93,%94,%95,%96,%97,%98,%99,%100,%101,%102,%103,%104,%105,%106,%107,%108,%109,%110,%111,%112,%113,%114,%115,%116,%117,%118,%119,%120,%121,%122,%123,%124,%125,%126,%127}, {%128,%129,%130,%131}, b, p, 1, 1, 1;\n}\n"
    : "+f"(d[0]),"+f"(d[1]),"+f"(d[2]),"+f"(d[3]),"+f"(d[4]),"+f"(d[5]),"+f"(d[6]),"+f"(d[7]),"+f"(d[8]),"+f"(d[9]),"+f"(d[10]),"+f"(d[11]),"+f"(d[12]),"+f"(d[13]),"+f"(d[14]),"+f"(d[15]),"+f"(d[16]),"+f"(d[17]),"+f"(d[18]),"+f"(d[19]),"+f"(d[20]),"+f"(d[21]),"+f"(d[22]),"+f"(d[23]),"+f"(d[24]),"+f"(d[25]),"+f"(d[26]),"+f"(d[27]),"+f"(d[28]),"+f"(d[29]),"+f"(d[30]),"+f"(d[31]),"+f"(d[32]),"+f"(d[33]),"+f"(d[34]),"+f"(d[35]),"+f"(d[36]),"+f"(d[37]),"+f"(d[38]),"+f"(d[39]),"+f"(d[40]),"+f"(d[41]),"+f"(d[42]),"+f"(d[43]),"+f"(d[44]),"+f"(d[45]),"+f"(d[46]),"+f"(d[47]),"+f"(d[48]),"+f"(d[49]),"+f"(d[50]),"+f"(d[51]),"+f"(d[52]),"+f"(d[53]),"+f"(d[54]),"+f"(d[55]),"+f"(d[56]),"+f"(d[57]),"+f"(d[58]),"+f"(d[59]),"+f"(d[60]),"+f"(d[61]),"+f"(d[62]),"+f"(d[63]),"+f"(d[64]),"+f"(d[65]),"+f"(d[66]),"+f"(d[67]),"+f"(d[68]),"+f"(d[69]),"+f"(d[70]),"+f"(d[71]),"+f"(d[72]),"+f"(d[73]),"+f"(d[74]),"+f"(d[75]),"+f"(d[76]),"+f"(d[77]),"+f"(d[78]),"+f"(d[79]),"+f"(d[80]),"+f"(d[81]),"+f"(d[82]),"+f"(d[83]),"+f"(d[84]),"+f"(d[85]),"+f"(d[86]),"+f"(d[87]),"+f"(d[88]),"+f"(d[89]),"+f"(d[90]),"+f"(d[91]),"+f"(d[92]),"+f"(d[93]),"+f"(d[94]),"+f"(d[95]),"+f"(d[96]),"+f"(d[97]),"+f"(d[98]),"+f"(d[99]),"+f"(d[100]),"+f"(d[101]),"+f"(d[102]),"+f"(d[103]),"+f"(d[104]),"+f"(d[105]),"+f"(d[106]),"+f"(d[107]),"+f"(d[108]),"+f"(d[109]),"+f"(d[110]),"+f"(d[111]),"+f"(d[112]),"+f"(d[113]),"+f"(d[114]),"+f"(d[115]),"+f"(d[116]),"+f"(d[117]),"+f"(d[118]),"+f"(d[119]),"+f"(d[120]),"+f"(d[121]),"+f"(d[122]),"+f"(d[123]),"+f"(d[124]),"+f"(d[125]),"+f"(d[126]),"+f"(d[127]) : "r"(a.x), "r"(a.y), "r"(a.z), "r"(a.w), "r"(db.lo), "r"(db.hi));
}
template<> __device__ __forceinline__ void wgmma_rs<256, 0>(float (&d)[128], const uint4& a, Desc db) {
  asm volatile("{\n.reg .pred p;\n.reg .b64 b;\nsetp.ne.b32 p, 0, 0;\nmov.b64 b, {%132, %133};\n"
    "wgmma.mma_async.sync.aligned.m64n256k16.f32.bf16.bf16 {%0,%1,%2,%3,%4,%5,%6,%7,%8,%9,%10,%11,%12,%13,%14,%15,%16,%17,%18,%19,%20,%21,%22,%23,%24,%25,%26,%27,%28,%29,%30,%31,%32,%33,%34,%35,%36,%37,%38,%39,%40,%41,%42,%43,%44,%45,%46,%47,%48,%49,%50,%51,%52,%53,%54,%55,%56,%57,%58,%59,%60,%61,%62,%63,%64,%65,%66,%67,%68,%69,%70,%71,%72,%73,%74,%75,%76,%77,%78,%79,%80,%81,%82,%83,%84,%85,%86,%87,%88,%89,%90,%91,%92,%93,%94,%95,%96,%97,%98,%99,%100,%101,%102,%103,%104,%105,%106,%107,%108,%109,%110,%111,%112,%113,%114,%115,%116,%117,%118,%119,%120,%121,%122,%123,%124,%125,%126,%127}, {%128,%129,%130,%131}, b, p, 1, 1, 1;\n}\n"
    : "=f"(d[0]),"=f"(d[1]),"=f"(d[2]),"=f"(d[3]),"=f"(d[4]),"=f"(d[5]),"=f"(d[6]),"=f"(d[7]),"=f"(d[8]),"=f"(d[9]),"=f"(d[10]),"=f"(d[11]),"=f"(d[12]),"=f"(d[13]),"=f"(d[14]),"=f"(d[15]),"=f"(d[16]),"=f"(d[17]),"=f"(d[18]),"=f"(d[19]),"=f"(d[20]),"=f"(d[21]),"=f"(d[22]),"=f"(d[23]),"=f"(d[24]),"=f"(d[25]),"=f"(d[26]),"=f"(d[27]),"=f"(d[28]),"=f"(d[29]),"=f"(d[30]),"=f"(d[31]),"=f"(d[32]),"=f"(d[33]),"=f"(d[34]),"=f"(d[35]),"=f"(d[36]),"=f"(d[37]),"=f"(d[38]),"=f"(d[39]),"=f"(d[40]),"=f"(d[41]),"=f"(d[42]),"=f"(d[43]),"=f"(d[44]),"=f"(d[45]),"=f"(d[46]),"=f"(d[47]),"=f"(d[48]),"=f"(d[49]),"=f"(d[50]),"=f"(d[51]),"=f"(d[52]),"=f"(d[53]),"=f"(d[54]),"=f"(d[55]),"=f"(d[56]),"=f"(d[57]),"=f"(d[58]),"=f"(d[59]),"=f"(d[60]),"=f"(d[61]),"=f"(d[62]),"=f"(d[63]),"=f"(d[64]),"=f"(d[65]),"=f"(d[66]),"=f"(d[67]),"=f"(d[68]),"=f"(d[69]),"=f"(d[70]),"=f"(d[71]),"=f"(d[72]),"=f"(d[73]),"=f"(d[74]),"=f"(d[75]),"=f"(d[76]),"=f"(d[77]),"=f"(d[78]),"=f"(d[79]),"=f"(d[80]),"=f"(d[81]),"=f"(d[82]),"=f"(d[83]),"=f"(d[84]),"=f"(d[85]),"=f"(d[86]),"=f"(d[87]),"=f"(d[88]),"=f"(d[89]),"=f"(d[90]),"=f"(d[91]),"=f"(d[92]),"=f"(d[93]),"=f"(d[94]),"=f"(d[95]),"=f"(d[96]),"=f"(d[97]),"=f"(d[98]),"=f"(d[99]),"=f"(d[100]),"=f"(d[101]),"=f"(d[102]),"=f"(d[103]),"=f"(d[104]),"=f"(d[105]),"=f"(d[106]),"=f"(d[107]),"=f"(d[108]),"=f"(d[109]),"=f"(d[110]),"=f"(d[111]),"=f"(d[112]),"=f"(d[113]),"=f"(d[114]),"=f"(d[115]),"=f"(d[116]),"=f"(d[117]),"=f"(d[118]),"=f"(d[119]),"=f"(d[120]),"=f"(d[121]),"=f"(d[122]),"=f"(d[123]),"=f"(d[124]),"=f"(d[125]),"=f"(d[126]),"=f"(d[127]) : "r"(a.x), "r"(a.y), "r"(a.z), "r"(a.w), "r"(db.lo), "r"(db.hi));
}
template<int N> __device__ __forceinline__ void wgmma_ra(float (&d)[N / 2], const uint4& a, Desc db, bool acc) {
  if (acc) wgmma_rs<N, 1>(d, a, db); else wgmma_rs<N, 0>(d, a, db);
}

__device__ __forceinline__ uint32_t smem_u32(const void* p) { return (uint32_t)__cvta_generic_to_shared(p); }
__device__ __forceinline__ void mbar_init(uint32_t bar, uint32_t cnt) { asm volatile("mbarrier.init.shared::cta.b64 [%0], %1;" ::"r"(bar), "r"(cnt)); }
__device__ __forceinline__ void mbar_expect_tx(uint32_t bar, uint32_t bytes) { asm volatile("mbarrier.arrive.expect_tx.shared::cta.b64 _, [%0], %1;" ::"r"(bar), "r"(bytes) : "memory"); }
__device__ __forceinline__ void mbar_arrive(uint32_t bar) { asm volatile("mbarrier.arrive.shared::cta.b64 _, [%0];" ::"r"(bar) : "memory"); }
__device__ __forceinline__ void mbar_arrive_remote(uint32_t rbar) { asm volatile("mbarrier.arrive.shared::cluster.b64 _, [%0];" ::"r"(rbar) : "memory"); }
__device__ __forceinline__ void mbar_wait(uint32_t bar, uint32_t parity) {
  asm volatile(
      "{\n.reg .pred p;\n.reg .u32 c;\nmov.u32 c, 0;\nLAB_WAIT:\nmbarrier.try_wait.parity.shared::cta.b64 p, [%0], %1;\n@p bra DONE;\n"
      "add.u32 c, c, 1;\nsetp.lt.u32 p, c, 1000000;\n@p bra LAB_WAIT;\ntrap;\nDONE:\n}\n" ::"r"(bar), "r"(parity) : "memory");
}
__device__ __forceinline__ void mbar_wait_c(uint32_t bar, uint32_t parity) {
  asm volatile("{\n.reg .pred p;\nLAB_WAIT:\nmbarrier.try_wait.parity.shared::cta.b64 p, [%0], %1;\n@!p bra LAB_WAIT;\n}\n" ::"r"(bar), "r"(parity) : "memory");
}
__device__ __forceinline__ uint32_t late(uint32_t bar, uint32_t v) {
  uint32_t r;
  asm volatile("{\n.reg .pred p;\nmbarrier.test_wait.parity.shared::cta.b64 p, [%1], 0;\nselp.b32 %0, %2, %1, p;\n}\n" : "=r"(r) : "r"(bar), "r"(v) : "memory");
  return r;
}
__device__ __forceinline__ void wtma2d(uint32_t dst, const CUtensorMap* m, int c0, int c1, uint32_t bar, uint64_t pol) {
  asm volatile("cp.async.bulk.tensor.2d.shared::cluster.global.mbarrier::complete_tx::bytes.multicast::cluster.L2::cache_hint [%0], [%1, {%3, %4}], [%2], %5, %6;"
               ::"r"(dst), "l"(m), "r"(bar), "r"(c0), "r"(c1), "h"((uint16_t)3), "l"(pol) : "memory");
}
__device__ __forceinline__ void wtma3d(uint32_t dst, const CUtensorMap* m, int c0, int c1, int c2, uint32_t bar, uint64_t pol) {
  asm volatile("cp.async.bulk.tensor.3d.shared::cluster.global.mbarrier::complete_tx::bytes.multicast::cluster.L2::cache_hint [%0], [%1, {%3, %4, %5}], [%2], %6, %7;"
               ::"r"(dst), "l"(m), "r"(bar), "r"(c0), "r"(c1), "r"(c2), "h"((uint16_t)3), "l"(pol) : "memory");
}
__device__ __forceinline__ void wbulk(uint32_t dst, const void* src, uint32_t bytes, uint32_t bar, uint64_t pol) {
  asm volatile("cp.async.bulk.shared::cluster.global.mbarrier::complete_tx::bytes.multicast::cluster.L2::cache_hint [%0], [%1], %2, [%3], %4, %5;"
               ::"r"(dst), "l"(src), "r"(bytes), "r"(bar), "h"((uint16_t)3), "l"(pol) : "memory");
}
__device__ __forceinline__ void tma3d(uint32_t dst, const CUtensorMap* m, int c0, int c1, int c2, uint32_t bar) {
  asm volatile("cp.async.bulk.tensor.3d.shared::cluster.global.mbarrier::complete_tx::bytes [%0], [%1, {%3, %4, %5}], [%2];"
               ::"r"(dst), "l"(m), "r"(bar), "r"(c0), "r"(c1), "r"(c2) : "memory");
}
__device__ __forceinline__ void tma_store3d(const CUtensorMap* m, uint32_t src, int c0, int c1, int c2) {
  asm volatile("cp.async.bulk.tensor.3d.global.shared::cta.bulk_group [%0, {%2, %3, %4}], [%1];" ::"l"(m), "r"(src), "r"(c0), "r"(c1), "r"(c2) : "memory");
}
__device__ __forceinline__ void prefetch_l2(const void* p, uint32_t bytes) { asm volatile("cp.async.bulk.prefetch.L2.global [%0], %1;" ::"l"(p), "r"(bytes) : "memory"); }
__device__ __forceinline__ uint64_t policy_evict_first() { uint64_t p; asm volatile("createpolicy.fractional.L2::evict_first.b64 %0, 1.0;" : "=l"(p)); return p; }
__device__ __forceinline__ uint64_t policy_evict_normal() { uint64_t p; asm volatile("createpolicy.fractional.L2::evict_normal.b64 %0, 1.0;" : "=l"(p)); return p; }
__device__ __forceinline__ void bulk_commit() { asm volatile("cp.async.bulk.commit_group;" ::: "memory"); }
__device__ __forceinline__ void bulk_wait_all() { asm volatile("cp.async.bulk.wait_group 0;" ::: "memory"); }
__device__ __forceinline__ void fence_async_smem() { asm volatile("fence.proxy.async.shared::cta;" ::: "memory"); }
__device__ __forceinline__ bool elect_one() {
  uint32_t p;
  asm volatile("{\n.reg .pred P;\nelect.sync _|P, 0xffffffff;\nselp.u32 %0, 1, 0, P;\n}\n" : "=r"(p));
  return p;
}
__device__ __forceinline__ void wg_fence() { asm volatile("wgmma.fence.sync.aligned;" ::: "memory"); }
__device__ __forceinline__ void wg_commit() { asm volatile("wgmma.commit_group.sync.aligned;" ::: "memory"); }
template <int n> __device__ __forceinline__ void wg_wait() { asm volatile("wgmma.wait_group.sync.aligned %0;" ::"n"(n) : "memory"); }
__device__ __forceinline__ void wg_bar(int w) { asm volatile("bar.sync %0, 128;" ::"r"(w + 1) : "memory"); }
__device__ __forceinline__ void cluster_sync() { asm volatile("barrier.cluster.arrive.relaxed.aligned;\nbarrier.cluster.wait.aligned;" ::: "memory"); }
__device__ __forceinline__ void fence_gpu() { asm volatile("fence.acq_rel.gpu;" ::: "memory"); }
__device__ __forceinline__ uint32_t ld_relaxed(const uint32_t* p) { uint32_t v; asm volatile("ld.relaxed.gpu.global.u32 %0, [%1];" : "=r"(v) : "l"(p) : "memory"); return v; }
__device__ __forceinline__ uint32_t ld_acquire(const uint32_t* p) { uint32_t v; asm volatile("ld.acquire.gpu.global.u32 %0, [%1];" : "=r"(v) : "l"(p) : "memory"); return v; }
__device__ __forceinline__ uint4 ld_relaxed4(const uint4* p) {
  uint4 v; asm volatile("ld.relaxed.gpu.global.v4.u32 {%0,%1,%2,%3}, [%4];" : "=r"(v.x), "=r"(v.y), "=r"(v.z), "=r"(v.w) : "l"(p) : "memory"); return v;
}
__device__ __forceinline__ uint2 ld_relaxed2(const uint2* p) {
  uint2 v; asm volatile("ld.relaxed.gpu.global.v2.u32 {%0,%1}, [%2];" : "=r"(v.x), "=r"(v.y) : "l"(p) : "memory"); return v;
}
__device__ __forceinline__ void st_relaxed(uint32_t* p, uint32_t a) { asm volatile("st.relaxed.gpu.global.u32 [%0], %1;" ::"l"(p), "r"(a) : "memory"); }
__device__ __forceinline__ void st_relaxed4(uint4* p, uint32_t a, uint32_t b, uint32_t c, uint32_t d) {
  asm volatile("st.relaxed.gpu.global.v4.u32 [%0], {%1,%2,%3,%4};" ::"l"(p), "r"(a), "r"(b), "r"(c), "r"(d) : "memory");
}
__device__ __forceinline__ void st_relaxed2(uint2* p, uint32_t a, uint32_t b) {
  asm volatile("st.relaxed.gpu.global.v2.u32 [%0], {%1,%2};" ::"l"(p), "r"(a), "r"(b) : "memory");
}
__device__ __forceinline__ void red4(uint4* p, uint32_t a, uint32_t b, uint32_t c, uint32_t d) {
  asm volatile("red.relaxed.gpu.global.add.noftz.v4.bf16x2 [%0], {%1,%2,%3,%4};" ::"l"(p), "r"(a), "r"(b), "r"(c), "r"(d) : "memory");
}
__device__ __forceinline__ void red2(uint2* p, uint32_t a, uint32_t b) {
  asm volatile("red.relaxed.gpu.global.add.noftz.v2.bf16x2 [%0], {%1,%2};" ::"l"(p), "r"(a), "r"(b) : "memory");
}
constexpr int SPIN_MAX = 1 << 21;
__device__ __forceinline__ uint32_t pack_bf16(float lo, float hi) { uint32_t r; asm("cvt.rn.bf16x2.f32 %0, %1, %2;" : "=r"(r) : "f"(hi), "f"(lo)); return r; }
__device__ __forceinline__ float bf_lo(uint32_t v) { return __uint_as_float(v << 16); }
__device__ __forceinline__ float bf_hi(uint32_t v) { return __uint_as_float(v & 0xffff0000u); }
__device__ __forceinline__ float2 lds64(uint32_t a) { float2 v; asm volatile("ld.shared.v2.f32 {%0,%1}, [%2];" : "=f"(v.x), "=f"(v.y) : "r"(a)); return v; }
__device__ __forceinline__ uint32_t lds32(uint32_t a) { uint32_t v; asm volatile("ld.shared.b32 %0, [%1];" : "=r"(v) : "r"(a)); return v; }
__device__ __forceinline__ void sts64f(uint32_t a, float x, float y) { asm volatile("st.shared.v2.f32 [%0], {%1,%2};" ::"r"(a), "f"(x), "f"(y) : "memory"); }
__device__ __forceinline__ void sts32(uint32_t a, uint32_t x) { asm volatile("st.volatile.shared.b32 [%0], %1;" ::"r"(a), "r"(x) : "memory"); }
__device__ __forceinline__ void gate(uint32_t a, int need) {
#pragma unroll 1
  for (int it = 0; it < SPIN_MAX; it++) {
    int v; asm volatile("ld.volatile.shared.b32 %0, [%1];" : "=r"(v) : "r"(a) : "memory");
    if (v >= need) break;
    if (GSLEEP) __nanosleep(GSLEEP);
  }
}
__device__ __forceinline__ void sts128(uint32_t a, uint32_t x, uint32_t y, uint32_t z, uint32_t u) { asm volatile("st.shared.v4.b32 [%0], {%1,%2,%3,%4};" ::"r"(a), "r"(x), "r"(y), "r"(z), "r"(u) : "memory"); }
__device__ __forceinline__ uint4 lds128(uint32_t a) { uint4 v; asm volatile("ld.shared.v4.u32 {%0,%1,%2,%3}, [%4];" : "=r"(v.x), "=r"(v.y), "=r"(v.z), "=r"(v.w) : "r"(a) : "memory"); return v; }
__device__ __forceinline__ uint32_t hmul2(uint32_t a, uint32_t b) { uint32_t r; asm("mul.rn.bf16x2 %0, %1, %2;" : "=r"(r) : "r"(a), "r"(b)); return r; }
__device__ __forceinline__ uint32_t hadd2(uint32_t a, uint32_t b) { uint32_t r; asm("add.rn.bf16x2 %0, %1, %2;" : "=r"(r) : "r"(a), "r"(b)); return r; }
__device__ __forceinline__ void stsm4(uint32_t a, uint32_t r0, uint32_t r1, uint32_t r2, uint32_t r3) {
  asm volatile("stmatrix.sync.aligned.m8n8.x4.shared.b16 [%0], {%1,%2,%3,%4};" ::"r"(a), "r"(r0), "r"(r1), "r"(r2), "r"(r3) : "memory");
}
__device__ __forceinline__ void stsm2(uint32_t a, uint32_t r0, uint32_t r1) {
  asm volatile("stmatrix.sync.aligned.m8n8.x2.shared.b16 [%0], {%1,%2};" ::"r"(a), "r"(r0), "r"(r1) : "memory");
}
__device__ __forceinline__ uint4 ldsm4(uint32_t a) {
  uint4 r; asm volatile("ldmatrix.sync.aligned.m8n8.x4.shared.b16 {%0,%1,%2,%3}, [%4];" : "=r"(r.x), "=r"(r.y), "=r"(r.z), "=r"(r.w) : "r"(a) : "memory"); return r;
}
__device__ __forceinline__ uint32_t movm(uint32_t a) { uint32_t r; asm("movmatrix.sync.aligned.m8n8.trans.b16 %0, %1;" : "=r"(r) : "r"(a)); return r; }
__device__ __forceinline__ void mma16816z(float (&d)[4], uint32_t a0, uint32_t a1, uint32_t a2, uint32_t a3, uint32_t b0, uint32_t b1) {
  asm("mma.sync.aligned.m16n8k16.row.col.f32.bf16.bf16.f32 {%0,%1,%2,%3}, {%4,%5,%6,%7}, {%8,%9}, {%10,%10,%10,%10};"
      : "=f"(d[0]), "=f"(d[1]), "=f"(d[2]), "=f"(d[3]) : "r"(a0), "r"(a1), "r"(a2), "r"(a3), "r"(b0), "r"(b1), "f"(0.f));
}
__device__ __forceinline__ void mma16816(float (&d)[4], const uint4& a, uint32_t b0, uint32_t b1) {
  asm("mma.sync.aligned.m16n8k16.row.col.f32.bf16.bf16.f32 {%0,%1,%2,%3}, {%4,%5,%6,%7}, {%8,%9}, {%0,%1,%2,%3};"
      : "+f"(d[0]), "+f"(d[1]), "+f"(d[2]), "+f"(d[3]) : "r"(a.x), "r"(a.y), "r"(a.z), "r"(a.w), "r"(b0), "r"(b1));
}
__device__ __forceinline__ void mma1688(float (&d)[4], uint32_t a0, uint32_t a1, uint32_t b0) {
  asm("mma.sync.aligned.m16n8k8.row.col.f32.bf16.bf16.f32 {%0,%1,%2,%3}, {%4,%5}, {%6}, {%0,%1,%2,%3};"
      : "+f"(d[0]), "+f"(d[1]), "+f"(d[2]), "+f"(d[3]) : "r"(a0), "r"(a1), "r"(b0));
}
__device__ __forceinline__ float quad_sum(float v) { v += __shfl_xor_sync(0xffffffffu, v, 1); v += __shfl_xor_sync(0xffffffffu, v, 2); return v; }
__device__ __forceinline__ float quad_max(float v) { v = fmaxf(v, __shfl_xor_sync(0xffffffffu, v, 1)); v = fmaxf(v, __shfl_xor_sync(0xffffffffu, v, 2)); return v; }
__device__ __forceinline__ float rcp(float x) { float r; asm("rcp.approx.ftz.f32 %0, %1;" : "=f"(r) : "f"(x)); return r; }
__device__ __forceinline__ float rsq(float x) { float r; asm("rsqrt.approx.ftz.f32 %0, %1;" : "=f"(r) : "f"(x)); return r; }
__device__ __forceinline__ float ex2(float x) { float r; asm("ex2.approx.ftz.f32 %0, %1;" : "=f"(r) : "f"(x)); return r; }
__device__ __forceinline__ uint32_t chk(uint32_t acc, uint32_t v, uint32_t tag) { uint32_t r; asm("lop3.b32 %0, %1, %2, %3, 0xF6;" : "=r"(r) : "r"(acc), "r"(v), "r"(tag)); return r; }
__device__ __forceinline__ uint32_t chk2(uint32_t a, uint32_t b, uint32_t tag) { uint32_t r; asm("lop3.b32 %0, %1, %2, %3, 0x7E;" : "=r"(r) : "r"(a), "r"(b), "r"(tag)); return r; }
__device__ __forceinline__ uint32_t tagged(uint32_t v, uint32_t tag) { return (v & ~1u) | tag; }

__device__ __forceinline__ int group_k0(int g, int j) {
  const int h = g >= 9, r = g - 2 - 7 * h;
  return g < 2 ? 64 * j + 32 * g : g < 16 ? 64 * (r + (r >= j)) + 32 * h : 32 * g;
}
__device__ __forceinline__ uint32_t xin_off(int c, int w) { return SM_X + (2 * c + w + (2 * c + w < 9 ? 9 : -9)) * 8192; }
__device__ __forceinline__ uint32_t xin_bar(int c) { return BAR_FULLX + 8 * (c < 8 ? c ^ 4 : c); }
__device__ __forceinline__ constexpr uint32_t qkv_xslot(int g) { return g < 5 || g > 11 ? 2 : (0x5140762u >> (4 * (g - 5))) & 15; }

template <int N> struct IC { static constexpr int v = N; };

struct Cons {
  uint32_t sb;
  uint32_t rem;
  uint32_t sB, mB;
  uint32_t mX;
  bool elect;
  __device__ __forceinline__ void release2(uint32_t bar) const { if (elect) { mbar_arrive(sb + bar); mbar_arrive_remote(rem + bar); } }
  __device__ __forceinline__ uint32_t nextB(uint32_t& prev) {
    mbar_wait_c(sb + BAR_FULLB + sB, mB);
    const uint32_t a = (((sb & 0x3FFFF) + SM_B) >> 4) + sB * (BSLOT / 128);
    prev = sB == 0 ? 32 : sB - 8;
    sB += 8;
    if (sB == 40) { sB = 0; mB ^= 1; }
    return a;
  }
  __device__ __forceinline__ void progress(uint32_t v) const { if (elect) sts32(sb + SM_PROG + (threadIdx.x >> 5), v); }
  __device__ __forceinline__ void releaseLastB() const { release2(BAR_EMPTYB + (sB == 0 ? 32 : sB - 8)); }
};

__device__ __forceinline__ float2 gather_sums(const uint2* a, uint32_t stag) {
  uint2 sa, sc;
  do { sa = ld_relaxed2(a); sc = ld_relaxed2(a + 8); } while (__any_sync(0xffffffffu, chk2(sa.x, sc.x, stag) & 3));
  return make_float2(quad_sum(__uint_as_float(sa.x) + __uint_as_float(sc.x)), quad_sum(__uint_as_float(sa.y) + __uint_as_float(sc.y)));
}

struct Norm {
  float m0, m1;
  uint32_t nm0, nm1;
  float d0, d1;
  uint2 u0, u1;
  __device__ __forceinline__ Norm(float2 sum) : m0(sum.x * (-1.f / 576)), m1(sum.y * (-1.f / 576)), nm0(pack_bf16(m0, m0)), nm1(pack_bf16(m1, m1)), d0(0.f), d1(0.f) {}
  __device__ __forceinline__ uint4 centre(const uint4& a) const { return make_uint4(hadd2(a.x, nm0), hadd2(a.y, nm1), hadd2(a.z, nm0), hadd2(a.w, nm1)); }
  __device__ __forceinline__ void sqr(uint32_t a, uint32_t b) {
    d0 = fmaf(bf_lo(a), bf_lo(a), fmaf(bf_hi(a), bf_hi(a), d0)); d1 = fmaf(bf_lo(b), bf_lo(b), fmaf(bf_hi(b), bf_hi(b), d1));
  }
  __device__ __forceinline__ void send(uint2* a, int t, uint32_t stag) {
    d0 = quad_sum(d0); d1 = quad_sum(d1);
    if ((t & 3) == 0) st_relaxed2(a, (__float_as_uint(d0) & ~3u) | stag, __float_as_uint(d1));
  }
  __device__ __forceinline__ void fetch(const uint2* a) { u0 = ld_relaxed2(a); u1 = ld_relaxed2(a + 8); }
  __device__ __forceinline__ float2 rstd(const uint2* a, uint32_t stag) {
    while (__any_sync(0xffffffffu, chk2(u0.x, u1.x, stag) & 3)) fetch(a);
    const float e0 = bf_lo(nm0) - m0, e1 = bf_lo(nm1) - m1;
    const float v0 = fmaf(quad_sum(__uint_as_float(u0.x) + __uint_as_float(u1.x)), 1.f / 576, -e0 * e0);
    const float v1 = fmaf(quad_sum(__uint_as_float(u0.y) + __uint_as_float(u1.y)), 1.f / 576, -e1 * e1);
    float2 r = make_float2(rsq(fmaxf(v0, 0.f) + 1e-5f), rsq(fmaxf(v1, 0.f) + 1e-5f));
    asm volatile("" : "+f"(r.x), "+f"(r.y));
    return r;
  }
};

template <class Pre, class Mma>
__device__ __forceinline__ float2 ln_gemm_in(Cons& c, Group* G, uint32_t (&p)[18], float2& sum, int w, int st0, int j, int t, Pre&& pre, Mma&& mma) {
  const uint32_t xa = c.sb + (t >> 5) * 2048 + (t & 15) * 128, sw = (((t >> 4) & 1) ^ (t & 7)) * 16;
  float ra[4] = {0.f, 0.f, 0.f, 0.f}, rb[4] = {0.f, 0.f, 0.f, 0.f};
#pragma unroll 1
  for (int cc = 0; cc < 9; cc++) {
    const uint32_t a = xa + xin_off(cc, w);
    mbar_wait_c(c.sb + xin_bar(cc), 0);
    const uint4 u0 = ldsm4(a + sw), u1 = ldsm4(a + (sw ^ 32)), u2 = ldsm4(a + (sw ^ 64)), u3 = ldsm4(a + (sw ^ 96));
    mma16816(ra, u0, 0x3f803f80u, 0x3f803f80u); mma16816(rb, u1, 0x3f803f80u, 0x3f803f80u);
    mma16816(ra, u2, 0x3f803f80u, 0x3f803f80u); mma16816(rb, u3, 0x3f803f80u, 0x3f803f80u);
  }
  sum = make_float2(ra[0] + rb[0], ra[2] + rb[2]);
  pre(0);
  Norm n(sum);
  n.u0 = n.u1 = make_uint2(0, 0);
  auto stats = [&] {
#pragma unroll
    for (int k = 0; k < 5; k++) {
      const uint4 u = ldsm4(xa + (k < 4 ? xin_off(j, w) + (sw ^ (32 * k)) : xin_off(8, w) + ((j ^ (t & 7)) << 4))), e = n.centre(u);
      p[4 * k] = u.x; p[4 * k + 1] = u.y;
      n.sqr(e.x, e.y);
      if (k < 4) { p[4 * k + 2] = u.z; p[4 * k + 3] = u.w; n.sqr(e.z, e.w); }
    }
    n.send(G->sq + st0 + 8 * j, t, 1);
  };
  if (STATP < 0) stats();
  else {
#pragma unroll
    for (int i = 0; i < 18; i++) p[i] = 0;
  }
  pre(1);
  uint4 y0 = ldsm4(xa + xin_off(0, w) + sw), y1 = ldsm4(xa + xin_off(0, w) + (sw ^ 32));
#pragma unroll 1
  for (int cc = 0; cc < 9; cc++) {
#pragma unroll
    for (int i = 0; i < 2; i++) {
      const uint4 f0 = n.centre(y0), f1 = n.centre(y1);
      const uint32_t a = xa + xin_off(min(cc + i, 8), w);
      y0 = ldsm4(a + (sw ^ (64 - 64 * i))); y1 = ldsm4(a + (sw ^ (96 - 64 * i)));
      uint32_t prev;
      const uint32_t bb = c.nextB(prev);
      mma(true, bb, f0, f1);
      if (i == 1) {
        if (STATP >= 0 && cc == STATP * w) stats();
        if (cc == 1) c.progress(3);
        if (cc == 7) n.fetch(G->sq + st0 + 16 * (t & 3));
        if (cc == 8 && w == 0) asm volatile("bar.arrive 6, 256;" ::: "memory");
      }
      wg_wait<1>();
      if (i + cc > 0) c.release2(BAR_EMPTYB + prev);
      if (2 * cc + i >= WOG && 2 * cc + i < WOG + 4) c.release2(BAR_EMPTYX + 32 + 8 * (2 * cc + i - WOG));
    }
  }
  c.mX = 0xff;
  const float2 r = n.rstd(G->sq + st0 + 16 * (t & 3), 1);
  if (w == 1) asm volatile("bar.sync 6, 256;" ::: "memory");
  wg_wait<0>();
  c.releaseLastB();
  c.release2(BAR_EMPTYX + 24);
  return r;
}

template <bool QKV, class Pre, class Mma>
__device__ __forceinline__ float2 ln_gemm(Cons& c, Group* G, const float (&v)[36], uint32_t (&p)[18], float2& sum, int st0, int j, int t,
                                          int layer, uint32_t tag, Pre&& pre, Mma&& mma) {
  constexpr bool known = !QKV && EARLY;
  const uint32_t stag = (2 * layer + (QKV ? 1 : 2)) & 3;
  uint4 x[6][2];
  uint4* src = G->xbox + t;
  asm volatile("" : "+l"(src));
  auto buf = [&](int g) -> uint4 (&)[2] { return x[g < 16 ? (g - 2) % 6 : g - 13]; };
  auto load = [&](int g0) {
#pragma unroll
    for (int g = g0; g < g0 + (g0 < 14 ? 3 : 2); g++) {
      const uint4* a = g < 16 ? src + ((g - 2) % 7 >= j ? 256 : 0) + (2 * ((g - 2) % 7) + 16 * (g >= 9)) * 128 : src + 2 * g * 128;
      buf(g)[0] = ld_relaxed4(a); buf(g)[1] = ld_relaxed4(a + 128);
    }
  };
  auto invalid = [&](int g, uint32_t tag) {
    uint32_t bad = chk(chk(chk2(buf(g)[0].x, buf(g)[1].x, tag), buf(g + 1)[0].x, tag), buf(g + 1)[1].x, tag);
    if (g < 14) bad = chk(chk(bad, buf(g + 2)[0].x, tag), buf(g + 2)[1].x, tag);
    if (g == 16) bad = chk(chk(chk(chk(bad, buf(g)[0].z, tag), buf(g)[1].z, tag), buf(g + 1)[0].z, tag), buf(g + 1)[1].z, tag);
    return __any_sync(0xffffffffu, bad & 1);
  };
  uint4* const d = src + 2 * j * 128;
  const int sq = st0 + 16 * (t & 3);
  if (!known) {
    float s0 = v[0] + v[1], s1 = v[2] + v[3];
#pragma unroll
    for (int i = 1; i < 9; i++) { s0 += v[4 * i] + v[4 * i + 1]; s1 += v[4 * i + 2] + v[4 * i + 3]; }
    s0 = quad_sum(s0); s1 = quad_sum(s1);
    if ((t & 3) == 0) st_relaxed2(G->sum + st0 + 8 * j, (__float_as_uint(s0) & ~3u) | stag, __float_as_uint(s1));
  }
#pragma unroll
  for (int i = 0; i < 18; i++) p[i] = pack_bf16(v[2 * i], v[2 * i + 1]);
#pragma unroll
  for (int i = 0; i < 2; i++) st_relaxed4(d + i * 128, tagged(p[4 * i], tag), p[4 * i + 1], p[4 * i + 2], p[4 * i + 3]);
  pre(0);
  if (!known) {
    sum = gather_sums(G->sum + sq, stag);
    load(2);
  }
  Norm n(sum);
  pre(1);
  const uint32_t* probe = &(G->xbox + (2 * (t & 7) + 1) * 128 + (t | 31))->x;
  uint32_t pv;
  auto inx = [](int g) { return QKV && ((g >= 5 && g < 12) || g == 17); };
  auto use = [](int g) { return QKV ? (g < 5 ? 108 : 101) + g : 18 + g; };
#pragma unroll
  for (int g = 0; g < 18; g++) {
    if (g < 16 ? g % 3 == 2 : g == 16) {
      const uint32_t lt = late(c.sb + BAR_FULLX + 64, tag);
      while (invalid(g, lt)) load(g);
      if (g < 16) load(g < 14 ? g + 3 : 16);
    }
    const uint4 f0 = n.centre(g < 2 ? make_uint4(p[8 * g], p[8 * g + 1], p[8 * g + 2], p[8 * g + 3]) : buf(g)[0]);
    const uint4 f1 = n.centre(g < 2 ? make_uint4(p[8 * g + 4], p[8 * g + 5], p[8 * g + 6], p[8 * g + 7]) : buf(g)[1]);
    if (g == 14) n.fetch(G->sq + sq);
    if (inx(g)) mbar_wait_c(c.sb + BAR_FULLX + 8 * qkv_xslot(g), ((0x34 >> qkv_xslot(g)) & 1) ^ (g == 17));
    else mbar_wait_c(c.sb + BAR_FULLB + 8 * (use(g) % 5), (use(g) / 5) & 1);
    mma(g, ((c.sb & 0x3FFFF) >> 4) + ((inx(g) ? SM_X + qkv_xslot(g) * XSLOT : SM_B + (use(g) % 5) * BSLOT) >> 4), f0, f1);
    if (g < 2) {
      if (known) {
        if (g == 0) {
          pv = ld_relaxed(probe);
        } else {
          const uint32_t lt = late(c.sb + BAR_FULLX + 64, tag);
          while (__any_sync(0xffffffffu, (pv ^ lt) & 1)) pv = ld_relaxed(probe);
          load(2);
        }
      }
      if (g == (known ? 1 : 0)) {
#pragma unroll
        for (int i = 2; i < 4; i++) st_relaxed4(d + (14 + i) * 128, tagged(p[4 * i], tag), p[4 * i + 1], p[4 * i + 2], p[4 * i + 3]);
        st_relaxed2((uint2*)(src + (32 + (j >> 1)) * 128) + (j & 1), tagged(p[16], tag), p[17]);
      }
      n.sqr(f0.x, f0.y); n.sqr(f0.z, f0.w); n.sqr(f1.x, f1.y); n.sqr(f1.z, f1.w);
      if (g == 1) {
        n.sqr(hadd2(p[16], n.nm0), hadd2(p[17], n.nm1));
        n.send(G->sq + st0 + 8 * j, t, stag);
      }
    }
    wg_wait<1>();
    if (g > 0 && !inx(g - 1)) c.release2(BAR_EMPTYB + 8 * (use(g - 1) % 5));
    if (QKV && g < 13) c.progress(33 + g);
    if (QKV && g == WOG - 1) c.release2(BAR_EMPTYX + 8 * qkv_xslot(17));
    if (QKV && g >= WOG && g < WOG + 4) c.release2(BAR_EMPTYX + 32 + 8 * (g - WOG));
  }
  if (QKV) c.mX = 0x34 ^ 0xf3;
  else { c.sB = 8 * (36 % 5); c.mB = (36 / 5) & 1; }
  const float2 r = n.rstd(G->sq + sq, late(c.sb + BAR_FULLX + 64, stag));
  wg_wait<0>();
  if (!QKV) c.release2(BAR_EMPTYB + 8 * (use(17) % 5));
  return r;
}

template <int NB, int OFF>
__device__ __forceinline__ void glu(const float (&a)[128], uint32_t (&h)[144]) {
#pragma unroll
  for (int b = 0; b < 2 * NB; b++) {
    if (HMUL) h[OFF + b] = hmul2(pack_bf16(a[2 * b], a[2 * b + 1]), pack_bf16(a[4 * NB + 2 * b], a[4 * NB + 2 * b + 1]));
    else h[OFF + b] = pack_bf16(a[2 * b] * a[4 * NB + 2 * b], a[2 * b + 1] * a[4 * NB + 2 * b + 1]);
  }
}

__global__ void __cluster_dims__(2, 1, 1) __launch_bounds__(384, 1)
fused_kernel(const __nv_bfloat16* __restrict__ x_in, Group* ws, const char* __restrict__ wqkv,
             const char* __restrict__ wg, const char* __restrict__ wu, const char* __restrict__ wd, const __grid_constant__ Maps maps,
             const char* __restrict__ wo) {
  extern __shared__ __align__(1024) uint8_t smem_raw[];
  const uint32_t sb = smem_u32(smem_raw);
  if (blockIdx.x >= NCTA) {
    const uint32_t par = ~ld_relaxed(ws->flag + 32) & 1;
#pragma unroll 1
    for (int i = 0; i < RDELAY; i++) __nanosleep(1000);
    const int cc = threadIdx.x % 54, r0 = threadIdx.x / 54, part = cc / 18, jj = 2 * (blockIdx.x - NCTA) + (cc % 18) / 9, c9 = cc % 9;
    if (r0 < 6) {
#pragma unroll 4
      for (int k = r0; k < 576; k += 6) {
        const uint4 u = __ldg((const uint4*)(wqkv + k * 3456 + part * 1152 + 144 * jj) + c9);
        ((Scratch*)ws)->wq[jj][k >> 4][c9 < 8 ? part * 128 + (k & 15) * 8 + (c9 ^ (k & 7)) : 384 + part * 16 + (k & 15)] = u;
      }
    }
    fence_gpu();
    __syncthreads();
    if (threadIdx.x < 2) st_relaxed(ws[2 * (blockIdx.x - NCTA) + threadIdx.x].wsum + 128, par);
    return;
  }
  if (threadIdx.x == 0) asm volatile("prefetch.tensormap [%0];" ::"l"(&maps.x) : "memory");
  const int warp = __shfl_sync(0xffffffffu, threadIdx.x >> 5, 0);
  const int lane = threadIdx.x & 31;
  const int rank = blockIdx.x & 1;
  if (elect_one()) {
    if (warp >= 8) {
#pragma unroll
      for (int i = 0; i < 9; i++) mbar_init(sb + SM_BAR + 72 * (warp - 8) + 8 * i, warp < 10 ? 1 : 4);
      sts32(sb + SM_PROG + 4 * (warp - 8), 0);
      asm volatile("fence.mbarrier_init.release.cluster;" ::: "memory");
    } else if (warp == 1 || warp == 2) {
      asm volatile("prefetch.tensormap [%0];" ::"l"(&maps.x + warp) : "memory");
    } else if (warp == 3) {
      if (PFMODE & 1) prefetch_l2((const char*)x_in + blockIdx.x * 18432, 18432);
    } else if (warp == 4) {
      if (PFMODE & 2) prefetch_l2(wqkv + blockIdx.x * (15552 / PFQ), 15552 / PFQ);
    }
  }
  __syncwarp();
  asm volatile("barrier.cluster.arrive.relaxed.aligned;" ::: "memory");
  if (warp == 8) PROFX(53);
  int lb = blockIdx.x;
  if (GPCMAP) {
    const int cl = blockIdx.x >> 1, u = cl - 36;
    lb = (cl < 4 ? cl : cl < 36 ? 8 * ((cl - 4) & 7) + ((cl - 4) >> 3) + (((cl - 4) & 7) ? 0 : 4) : 8 * (1 + u % 7) + 4 + u / 7) * 2 + rank;
  }
#define CTA_J(b) (((b) >> 1) & 7)
#define CTA_RB(b) ((((b) >> 4) << 1) | ((b) & 1))
  const int j = CTA_J(lb), rb = CTA_RB(lb);

  PROF(23);
  if (warp >= 8) {
    asm volatile("setmaxnreg.dec.sync.aligned.u32 " STR(REGS_P) ";");
    auto x_chunk = [&](int cc) {
      mbar_expect_tx(sb + xin_bar(cc), 16384);
      tma3d(sb + xin_off(cc, 0), &maps.x, 64 * cc, 0, 64 * rb, sb + xin_bar(cc));
      tma3d(sb + xin_off(cc, 1), &maps.x, 64 * cc, 1, 64 * rb, sb + xin_bar(cc));
    };
    if (warp == 9 && elect_one()) {
      fence_async_smem();
#pragma unroll 1
      for (int i = 0; i < 9; i++) x_chunk(i);
    }
    __syncwarp();
    if (warp == 9) PROFX(54);
    asm volatile("barrier.cluster.wait.aligned;" ::: "memory");
    if (warp == 8) PROFX(56);
    const uint64_t pol = W_POLICY(), pola = A_POLICY();
    uint4 (* const wq)[432] = ((Scratch*)ws)->wq[j];
    const uint32_t par = ~ld_relaxed(ws[2 * rb].flag + 32 + 32 * j) & 1;
    auto qkv_group = [&](bool copy, int k, uint32_t dst, uint32_t bar) {
      if (copy && gridDim.x > NCTA) {
        wbulk(dst + rank * 8192, wq[(k >> 4) + rank], 6912, bar, pol);
      } else {
        wtma3d(dst + rank * 8192, &maps.qm, 72 * j, k + 16 * rank, 0, bar, pola);
        wtma3d(dst + rank * 8192 + 6144, &maps.qc, 72 * j + 64, k + 16 * rank, 0, bar, pola);
      }
    };
    auto repacked = [&] {
#pragma unroll 1
      for (int it = 0; it < SPIN_MAX && gridDim.x > NCTA; it++)
        if (ld_acquire(ws[j].wsum + 128) == par) break;
      asm volatile("fence.proxy.async.global;" ::: "memory");
    };
    const int ktab = group_k0(lane, j);
    auto qkv_gate = [&](int g) { if (g >= 8) gate(sb + SM_PROG, 33 + ((g - 8) * QPACE >> 4)); };
    if (warp == 8) {
      uint32_t s = 0, ph = 1;
      auto slot = [&](uint32_t bytes, auto&& issue) {
        const uint32_t bar = sb + BAR_FULLB + 8 * s;
        mbar_wait(sb + BAR_EMPTYB + 8 * s, ph);
        if (elect_one()) {
          mbar_expect_tx(bar, bytes);
          issue(sb + SM_B + s * BSLOT, bar);
        }
        if (++s == 5) { s = 0; ph ^= 1; }
      };
#pragma unroll 1
      for (int layer = 0; layer < NLAYERS; layer++) {
        if (layer) repacked();
#pragma unroll 1
        for (int g = 0; g < 18 - layer; g += layer && g == 4 ? 8 : 1) {
          const int k = layer ? __shfl_sync(0xffffffffu, ktab, g) : 32 * g;
          if (layer) qkv_gate(g);
          else if (g == QD) mbar_wait(sb + xin_bar(XH), 0);
          slot(2 * 6912, [&](uint32_t dst, uint32_t bar) { qkv_group(layer, k, dst, bar); });
        }
        if (!FCH) {
          gate(sb + SM_PROG, 32 * layer + 20);
          gate(sb + SM_PROG + 4, 32 * layer + 20);
        }
#pragma unroll 1
        for (int t = 0; t < 5; t++) {
          const CUtensorMap* m = &maps.g + (t < 3 ? rank : 2 + rank);
          asm volatile("" : "+l"(m));
          const int c2 = t < 3 ? 9 * j + 2 * t : 18 * j + 3 + 3 * t;
          const uint32_t half = t < 3 ? 8192 : 6144;
          auto tile = [&](int g) {
            const int k = __shfl_sync(0xffffffffu, ktab, g);
            slot(2 * half, [&](uint32_t dst, uint32_t bar) { wtma3d(dst + rank * half, m, 0, k, c2, bar, pol); });
          };
          int g = 0;
          if (t == 0) {
#pragma unroll 1
            for (; g < 5; g++) {
              mbar_wait(sb + BAR_FULLB + 8 * (s < FCH ? s + 5 - FCH : s - FCH), s < FCH ? ph : ph ^ 1);
              tile(g);
            }
          }
#pragma unroll 1
          for (; g < 18; g++) tile(g);
        }
      }
    } else if (warp == 9) {
      uint32_t mE = 0;
      auto acquire = [&](uint32_t s) { mbar_wait(sb + BAR_EMPTYX + 8 * s, (mE >> s) & 1); mE ^= 1u << s; };
      auto landed = [&](uint32_t s) { mbar_wait(sb + BAR_FULLX + 8 * s, (mE >> s) & 1); };
      auto slot = [&](uint32_t s, const CUtensorMap* m, int col, int row, uint64_t pol) {
        acquire(s);
        if (elect_one()) {
          mbar_expect_tx(sb + BAR_FULLX + 8 * s, XSLOT);
          wtma2d(sb + SM_X + s * XSLOT + rank * 9216, m, col, row + 72 * rank, sb + BAR_FULLX + 8 * s, pol);
        }
      };
#pragma unroll 1
      for (int layer = 0; layer < NLAYERS; layer++) {
        if (layer) repacked();
#pragma unroll 1
        for (int g = 5; g < 18 * layer; g += g == 11 ? 6 : 1) {
          const uint32_t s = qkv_xslot(g);
          const int k = __shfl_sync(0xffffffffu, ktab, g);
          if (g < 12) qkv_gate(g);
          acquire(s);
          if (elect_one()) {
            mbar_expect_tx(sb + BAR_FULLX + 8 * s, 2 * 6912);
            qkv_group(true, k, sb + SM_X + s * XSLOT, sb + BAR_FULLX + 8 * s);
          }
          if (XCH & 1) landed(s);
        }
#pragma unroll 1
        for (int i = 0; i < 4; i++) { slot(4 + i, &maps.o, 64 * j, 144 * i, pola); if (XCH & 2) landed(4 + i); }
        acquire(3);
        if (elect_one()) {
          mbar_expect_tx(sb + BAR_FULLX + 24, 9216);
          wtma2d(sb + SM_WOC + rank * 4608, &maps.oc, 512 + 8 * j, 288 * rank, sb + BAR_FULLX + 24, pola);
          wtma2d(sb + SM_WOC + rank * 4608 + 2304, &maps.oc, 512 + 8 * j, 288 * rank + 144, sb + BAR_FULLX + 24, pola);
        }
#pragma unroll 1
        for (int u = 0; u < 36; u++) {
          const uint32_t s = 4 * (u & 1) + ((u >> 1) & 3);
          slot(s, &maps.d, u < 4 ? 512 : 64 * ((j + (u >> 2)) & 7), 576 * j + 144 * (u & 3), pol);
          if ((XCH & 4) && u < 3) landed(s);
        }
      }
    } else {
      const int w = warp - 10, grp = 2 * rb + w;
      if (PFMODE & 4) {
        mbar_wait(sb + xin_bar(XP), 0);
        if (lane == 0) prefetch_l2(wqkv + (2 * blockIdx.x + w) * 7776, 7776);
        if (EARLY && lane == 0) prefetch_l2(wo + (2 * blockIdx.x + w) * 2592, 2592);
      }
      if (EARLY) {
        mbar_wait(sb + xin_bar(8), 0);
        gate(sb + SM_PROG, WSG);
        if (grp < 18) {
          const uint4* row = (const uint4*)(wo + (72 * j + 4 * grp + (lane >> 3)) * 1152) + (lane & 7);
          float a = 0.f;
#pragma unroll 1
          for (int i = 0; i < 72; i += 24) {
            const uint4 u[3] = {__ldg(row + i), __ldg(row + i + 8), __ldg(row + i + 16)};
#pragma unroll
            for (int k = 0; k < 3; k++)
              a += ((bf_lo(u[k].x) + bf_hi(u[k].x)) + (bf_lo(u[k].y) + bf_hi(u[k].y))) + ((bf_lo(u[k].z) + bf_hi(u[k].z)) + (bf_lo(u[k].w) + bf_hi(u[k].w)));
          }
          a = quad_sum(a);
          a += __shfl_xor_sync(0xffffffffu, a, 4);
          if ((lane & 7) == 0) st_relaxed(ws[j].wsum + 4 * grp + (lane >> 3), tagged(__float_as_uint(a), par));
        }
        if (w == 1) {
          uint32_t u[3];
#pragma unroll 1
          for (int it = 0; it < SPIN_MAX; it++) {
#pragma unroll
            for (int k = 0; k < 3; k++) u[k] = ld_relaxed(ws[j].wsum + min(lane + 32 * k, 71));
            if (!__any_sync(0xffffffffu, chk(chk2(u[0], u[1], par), u[2], par) & 1)) break;
            __nanosleep(100);
          }
#pragma unroll
          for (int k = 0; k < 3; k++) {
            const float f = __uint_as_float(u[k]);
            if (lane + 32 * k < 80) sts128(sb + SM_WSUM + 16 * (lane + 32 * k), pack_bf16(f, f - bf_lo(pack_bf16(f, 0.f))), 0, 0, 0);
          }
          fence_async_smem();
          __syncwarp();
          if (lane < 4) mbar_arrive(sb + BAR_WSUM);
          PROFX(57);
        }
      }
      gate(sb + SM_PROG, 3);
      if (w == 0) PROFX(58);
      auto prefetch_gu = [&](int l0, int n) {
#pragma unroll 1
        for (int i = lane; i < 36 * n; i += 32) {
          asm volatile("prefetch.global.L2 [%0];" ::"l"((w ? wu : wg) + (size_t)(36 * rb + i / n) * 9216 + 1152 * j + 128 * (l0 + i % n)));
          __nanosleep(PFSLEEP);
        }
      };
      auto clear = [&](uint4* p, int n) {
#pragma unroll 1
        for (int i = lane; i < n; i += 64) { st_relaxed4(p + i, 0, 0, 0, 0); st_relaxed4(p + i + 32, 0, 0, 0, 0); __nanosleep(CLRSLEEP); }
      };
      auto exchange = [&](uint32_t v, uint32_t bar) {
        if (FENCE1) { if (lane == 0) fence_gpu(); } else fence_gpu();
        __syncwarp();
        if (w == 0 && v != 1) PROFX(64 + 58 - 2 * v);
        if (lane == 0) st_relaxed(ws[grp].flag + j, v);
#pragma unroll 1
        for (int it = 0; it < SPIN_MAX; it++) {
          const uint32_t f = ld_relaxed(ws[grp].flag + (lane & 7));
          if (__all_sync(0xffffffffu, v ? f >= v : f == 0)) break;
        }
        if (lane == 0) mbar_arrive(sb + bar + 8 * w);
      };
      if (!EARLY && lane == 0) prefetch_l2(wo + (2 * blockIdx.x + w) * 2592, 2592);
      if (MAPPF && w == 0 && lane < 9) asm volatile("prefetch.tensormap [%0];" ::"l"(&maps.o + lane) : "memory");
#pragma unroll 1
      for (int layer = 0; layer < NLAYERS; layer++) {
        gate(sb + SM_PROG, 32 * layer + 3);
        if (PFF & 1) prefetch_gu(0, 2);
        gate(sb + SM_PROG, 32 * layer + 22);
        if (PFF & 2) prefetch_gu(2, 2);
        if (layer == 0) {
          clear(ws[grp].inbox[0] + 2 * j * INBOX, 2 * INBOX);
          exchange(1, BAR_CLR);
          if (w == 0) PROFX(59);
        }
        if (PFF & 2) prefetch_gu(4, 2);
        if (PFF & 4) prefetch_gu(6, 3);
#pragma unroll 1
        for (int i = lane; i < ((PFF & 8) ? 162 : 0); i += 32) {
          asm volatile("prefetch.global.L2 [%0];" ::"l"(wd + (size_t)(576 * j + 36 * rb + 18 * w) * 1152 + 128 * i));
          __nanosleep(PFSLEEP);
        }
        if (w == 0 && layer == 0) PROFX(60);
        mbar_wait(sb + BAR_REDDONE + 8 * w, layer);
        if (w == 0) PROFX(64 + 53 + 4 * layer);
        exchange(2 - 2 * layer, BAR_RREADY);
        if (w == 0) PROFX(64 + 56 + 4 * layer);
      }
      mbar_wait(sb + BAR_DONE + 8 * w, 0);
    }
    __syncwarp();
    cluster_sync();
  } else {
    asm volatile("setmaxnreg.inc.sync.aligned.u32 " STR(REGS_C) ";");
#define THREAD_IDS()                                                                   \
    int tid_ = threadIdx.x, bid_ = lb;                                                  \
    asm volatile("" : "+r"(tid_), "+r"(bid_));                                          \
    const int w = warp >> 2, wp = warp & 3;                                             \
    const int lane = tid_ & 31, t = tid_ & 127, g = lane >> 2, q = lane & 3;           \
    const int j = CTA_J(bid_), rb = CTA_RB(bid_), grp = 2 * rb + w;                    \
    const int st0 = wp * 64 + g;                         \
    Group* const G = ws + grp;                                                         \
    const uint32_t dsb = (sb & 0x3FFFF) >> 4;                                          \
    (void)t; (void)g; (void)q; (void)grp; (void)j; (void)st0; (void)dsb; (void)G
    Cons c;
    c.sb = sb; c.sB = 0; c.mB = 0; c.mX = 0; c.elect = (threadIdx.x & 127) == 0;
    asm volatile("mapa.shared::cluster.u32 %0, %1, %2;" : "=r"(c.rem) : "r"(sb), "r"(rank ^ 1));
    float v[36], a1[96], a2[12];
    float2 sum, rs;
    uint32_t res[18], xtag;
    auto qkv_mma = [&](bool acc, uint32_t bb, const uint4& f0, const uint4& f1) {
      wg_fence();
      wgmma_ra<192>(a1, f0, desc_hi(2048, 1024, 1) + bb, acc);
      wgmma_ra<24>(a2, f0, desc_hi(128, 256, 0) + (bb + 384), acc);
      wgmma_ra<192>(a1, f1, desc_hi(2048, 1024, 1) + (bb + 512), true);
      wgmma_ra<24>(a2, f1, desc_hi(128, 256, 0) + (bb + 896), true);
      wg_commit();
    };
    {
      THREAD_IDS();
      if (OPEN) {
        if (q == 0) { st_relaxed2(G->sum + st0 + 8 * j, 0, 0); st_relaxed2(G->sq + st0 + 8 * j, 0, 0); }
        if (wp == 3) {
#pragma unroll
          for (int i = 0; i < 5; i++) st_relaxed4(G->halo + j * 160 + lane + i * 32, 0, 0, 0, 0);
        }
        if (lane >= OPENL) st_relaxed4(G->obox + (8 * WPROBE + j) * 128 + t, 0, 0, 0, 0);
      }
      xtag = __shfl_sync(0xffffffffu, ~ld_relaxed(G->flag + 32 + 32 * j) & 1, 0);
      if (OPEN && EARLY && lane >= OPENL) st_relaxed4(G->xbox + (2 * j + 1) * 128 + t, xtag ^ 1, 0, 0, 0);
      asm volatile("barrier.cluster.wait.aligned;" ::: "memory");
      PROF(0);
#pragma unroll
      for (int i = 0; i < 96; i++) asm volatile("mov.b32 %0, 0;" : "=f"(a1[i]));
#pragma unroll
      for (int i = 0; i < 12; i++) asm volatile("mov.b32 %0, 0;" : "=f"(a2[i]));
      PROF(1);
      rs = ln_gemm_in(c, G, res, sum, w, st0, j, t, [&](int i) { PROF(2 + i); if (i) PROF(4); }, qkv_mma);
    }
#pragma unroll 1
    for (int layer = 0;; layer++) {
      const uint32_t tag = layer ^ 1;
      const int pb = 1 + layer * 30;
      uint4 own[5];
      {
        THREAD_IDS();
        PROF(pb + 4);
        uint32_t kv[3][18];
        auto cvt = [&](int b, float r) {
#pragma unroll
          for (int cc = 0; cc < 18; cc++) {
            const float* a = (cc == 8 ? a2 + 4 : cc == 17 ? a2 + 8 : cc < 8 ? a1 + 32 + 4 * cc : a1 + 28 + 4 * cc) + 2 * (b - 1);
            const uint32_t u = pack_bf16(a[0] * r, a[1] * r);
            kv[b][cc] = cc < 9 ? u : movm(u);
          }
        };
        cvt(2, rs.y);
        const uint32_t msg = sb + SM_X + (w ? 3 * XSLOT : 24576) + wp * 2304 + lane * 16;
        if (wp == 3) {
          uint4* hp = G->halo + j * 160 + lane;
#pragma unroll
          for (int i = 0; i < 4; i++) st_relaxed4(hp + i * 32, tagged(kv[2][4 * i], tag), kv[2][4 * i + 1], kv[2][4 * i + 2], kv[2][4 * i + 3]);
          st_relaxed2((uint2*)(hp + 128), tagged(kv[2][16], tag), kv[2][17]);
        } else {
#pragma unroll
          for (int i = 0; i < 4; i++) sts128(msg + i * 512, kv[2][4 * i], kv[2][4 * i + 1], kv[2][4 * i + 2], kv[2][4 * i + 3]);
          sts64f(msg + 2048 - lane * 8, __uint_as_float(kv[2][16]), __uint_as_float(kv[2][17]));
        }
        cvt(1, rs.x);
        uint32_t Q[4][6];
#pragma unroll
        for (int h = 0; h < 4; h++)
#pragma unroll
          for (int i = 0; i < 6; i++) {
            const float* a = 4 * h + i < 16 ? a1 + 8 * h + 2 * i : a2 + 8 * h + 2 * i - 32;
            const uint32_t u = pack_bf16(a[0], a[1]);
            Q[h][i] = i < 2 ? (q >= h ? u : 0) : i < 4 ? u : (q <= h ? u : 0);
          }
        const bool lo0 = 2 * q > g, lo1 = 2 * q + 1 > g;
        const uint32_t M = (lo0 ? 0xffffu : 0u) | (lo1 ? 0xffff0000u : 0u);
        auto scores = [&](int h, int b, float (&s)[4]) {
          mma16816z(s, Q[h][0], Q[h][1], Q[h][2], Q[h][3], kv[b][2 * h], kv[b][2 * h + 1]);
          mma1688(s, Q[h][4], Q[h][5], kv[b][2 * h + 2]);
        };
        auto softmax = [&](float (&l)[4][2], float r, uint32_t (&P)[4]) {
          const float sl = r * (0.23570226039551584f * 1.4426950408889634f);
          float m[4];
#pragma unroll
          for (int h = 0; h < 4; h++) { m[h] = fmaxf(l[h][0], l[h][1]); m[h] = fmaxf(m[h], __shfl_xor_sync(0xffffffffu, m[h], 1)); }
#pragma unroll
          for (int h = 0; h < 4; h++) m[h] = fmaxf(m[h], __shfl_xor_sync(0xffffffffu, m[h], 2)) * sl;
#pragma unroll
          for (int h = 0; h < 4; h++) {
            l[h][0] = ex2(fmaf(l[h][0], sl, -m[h])); l[h][1] = ex2(fmaf(l[h][1], sl, -m[h]));
            m[h] = l[h][0] + l[h][1]; m[h] += __shfl_xor_sync(0xffffffffu, m[h], 1);
          }
#pragma unroll
          for (int h = 0; h < 4; h++) { m[h] = rcp(m[h] + __shfl_xor_sync(0xffffffffu, m[h], 2)); P[h] = pack_bf16(l[h][0] * m[h], l[h][1] * m[h]); }
        };
        const bool remote = wp == 0 && rb > 0;
        const uint4* hp = (G - 2)->halo + j * 160 + lane;
        auto halo = [&] {
#pragma unroll
          for (int i = 0; i < 4; i++) { const uint4 u = ld_relaxed4(hp + i * 32); kv[0][4 * i] = u.x; kv[0][4 * i + 1] = u.y; kv[0][4 * i + 2] = u.z; kv[0][4 * i + 3] = u.w; }
          const uint2 u = ld_relaxed2((const uint2*)(hp + 128));
          kv[0][16] = u.x; kv[0][17] = u.y;
        };
#pragma unroll
        for (int i = 0; i < 18; i++) kv[0][i] = 0;
        if (remote) halo();
        float l0[4][2], l1[4][2];
#pragma unroll
        for (int h = 0; h < 4; h++) {
          float s1[4], s2[4];
          scores(h, 1, s1); scores(h, 2, s2);
          l0[h][0] = s1[0]; l0[h][1] = s1[1];
          l1[h][0] = lo0 ? s1[2] : s2[2]; l1[h][1] = lo1 ? s1[3] : s2[3];
        }
        uint32_t P0[4], P1[4];
        softmax(l1, rs.y, P1);
        if (remote) {
          while (__any_sync(0xffffffffu, chk(chk2(kv[0][0], kv[0][4], tag) | chk2(kv[0][8], kv[0][12], tag), kv[0][16], tag) & 1)) halo();
        }
        if (FG < 0) c.progress(32 * layer + 20);
        wg_bar(w);
        if (wp > 0) {
          const uint32_t from = msg - 2304;
#pragma unroll
          for (int i = 0; i < 4; i++) { const uint4 u = lds128(from + i * 512); kv[0][4 * i] = u.x; kv[0][4 * i + 1] = u.y; kv[0][4 * i + 2] = u.z; kv[0][4 * i + 3] = u.w; }
          const float2 u = lds64(from + 2048 - lane * 8);
          kv[0][16] = __float_as_uint(u.x); kv[0][17] = __float_as_uint(u.y);
        }
        PROF(pb + 5);
        const bool first = (rb == 0 && wp == 0);
#pragma unroll
        for (int h = 0; h < 4; h++) {
          float s0[4];
          scores(h, 0, s0);
          if (first) s0[0] = s0[1] = -INFINITY;
          l0[h][0] = lo0 ? s0[0] : l0[h][0]; l0[h][1] = lo1 ? s0[1] : l0[h][1];
        }
        softmax(l0, rs.x, P0);
        uint4* ob = G->obox + t;
        uint32_t car0 = 0, car1 = 0;
#pragma unroll
        for (int h = 0; h < 4; h++) {
          float o[3][4];
#pragma unroll
          for (int i = 0; i < 3; i++) {
            mma16816z(o[i], P0[h] & ~M, P1[h] & M, 0u, P1[h] & ~M, kv[1][9 + 2 * h + i], kv[2][9 + 2 * h + i]);
            mma1688(o[i], P0[h] & M, 0u, kv[0][9 + 2 * h + i]);
          }
          const uint32_t o0 = q < h ? car0 : pack_bf16(o[0][0], o[0][1]), o1 = q < h ? car1 : pack_bf16(o[0][2], o[0][3]);
          own[h] = make_uint4(o0 | 1, o1, pack_bf16(o[1][0], o[1][1]), pack_bf16(o[1][2], o[1][3]));
          st_relaxed4(ob + (8 * h + j) * 128, own[h].x, own[h].y, own[h].z, own[h].w);
          car0 = pack_bf16(o[2][0], o[2][1]); car1 = pack_bf16(o[2][2], o[2][3]);
        }
        car0 = tagged(car0, tag);
        st_relaxed2((uint2*)(ob + (32 + (j >> 1)) * 128) + (j & 1), car0, car1);
        own[4] = make_uint4(car0, car1, 0, 0);
        PROF(pb + 6);
      }
      {
        THREAD_IDS();
        const uint4* src = G->obox + t;
        asm volatile("" : "+l"(src));
        float a[32], a8[4];
#pragma unroll
        for (int i = 3; i < 8; i++) mbar_wait_c(sb + BAR_FULLX + 8 * i, (c.mX >> i) & 1);
        c.mX ^= 0xf8;
        auto step = [&](const uint4& f, uint32_t r0, int rs, bool acc) {
          wgmma_ra<64>(a, f, desc_hi(0, rs * 128, 1) + (dsb + ((SM_X + 4 * XSLOT) >> 4) + r0 * 8), acc);
          wgmma_ra<8>(a8, f, desc_hi(rs * 16, 0, 0) + (dsb + (SM_WOC >> 4) + r0), acc);
        };
        const uint32_t* probe = &(G->obox + (8 * WPROBE + (lane & 7)) * 128 + (t | 31))->x;
        uint32_t pv = ld_relaxed(probe);
        if (OWNBAR) asm volatile("bar.sync 4, 256;" ::: "memory");
        if (EARLY) mbar_wait_c(sb + BAR_WSUM, 0);
        float e[4];
        wg_fence();
        if (EARLY) {
#pragma unroll
          for (int i = 0; i < 5; i++) wgmma_ra<8>(e, own[i], desc_hi(128, 0, 0) + (dsb + (SM_WSUM >> 4) + 16 * i), i > 0);
          wg_commit();
        }
#pragma unroll
        for (int i = 0; i < 4; i++) step(own[i], 72 * j + 16 * i, 8, i > 0);
        wg_commit();
        if (EARLY) {
          wg_wait<1>();
          if (q == 0) st_relaxed2(G->sum + st0 + 8 * j, (__float_as_uint(e[0] + e[1]) & ~3u) | ((2 * layer + 2) & 3), __float_as_uint(e[2] + e[3]));
        }
        pv &= late(sb + BAR_FULLX + 64, 1);
        while (__any_sync(0xffffffffu, ~pv & 1)) pv = ld_relaxed(probe);
        if (w == 1) asm volatile("bar.sync 7, 256;" ::: "memory");
        uint2 sa, sc;
        uint4 x[32];
        auto load = [&](int i) { x[i] = ld_relaxed4(i < 28 ? src + (i % 7 >= j ? 128 : 0) + (8 * (i / 7) + i % 7) * 128 : src + (i + 4) * 128); };
        auto batch = [&](auto e0, auto e1, auto e2, int b) {
          constexpr int E0 = decltype(e0)::v, E1 = decltype(e1)::v, E2 = decltype(e2)::v;
          const uint32_t one = E0 > 0 && E1 > E0 ? late(sb + BAR_FULLX + 64, 1) : 1;
          while (E1 > E0) {
            uint32_t bad = 0;
#pragma unroll
            for (int i = E0; i < E1; i++) bad = i < 28 ? chk(bad, x[i].x, one) : chk(chk(bad, x[i].x, tag), x[i].z, tag);
            if (!__any_sync(0xffffffffu, bad & 1)) break;
#pragma unroll
            for (int i = E0; i < E1; i++) load(i);
          }
          if (b == 0) PROF(pb + 7);
          if (b > 0 && E2 > E1) wg_wait<WOW>();
#pragma unroll
          for (int i = E1; i < E2; i++) load(i);
          if (EARLY && b == 1) { sa = ld_relaxed2(G->sum + st0 + 16 * q); sc = ld_relaxed2(G->sum + st0 + 16 * q + 8); }
          if (b == WOREL && w == 0) asm volatile("bar.arrive 7, 256;" ::: "memory");
          if (E1 > E0) {
            wg_fence();
#pragma unroll
            for (int i = E0; i < E1; i++) {
              if (i < 28) step(x[i], 72 * (i % 7) + (i % 7 >= j ? 72 : 0) + 16 * (i / 7), 8, true);
              else step(x[i], 144 * (i - 28) + 64, 72, true);
            }
            wg_commit();
          }
        };
        batch(IC<0>(), IC<0>(), IC<WB1>(), -1);
        batch(IC<0>(), IC<WB1>(), IC<WB2>(), 0);
        batch(IC<WB1>(), IC<WB2>(), IC<WB3>(), 1);
        batch(IC<WB2>(), IC<WB3>(), IC<32>(), 2);
        batch(IC<WB3>(), IC<32>(), IC<32>(), 3);
        if (EARLY) {
          float2 e = make_float2(quad_sum(__uint_as_float(sa.x) + __uint_as_float(sc.x)), quad_sum(__uint_as_float(sa.y) + __uint_as_float(sc.y)));
          if (__any_sync(0xffffffffu, chk2(sa.x, sc.x, (2 * layer + 2) & 3) & 3)) e = gather_sums(G->sum + st0 + 16 * q, (2 * layer + 2) & 3);
          sum.x += e.x; sum.y += e.y;
        }
        wg_wait<0>();
        if (w == 0) asm volatile("bar.arrive 3, 256;" ::: "memory");
        PROF(pb + 8);
#pragma unroll
        for (int i = 0; i < 18; i++) {
          v[2 * i] = bf_lo(res[i]) + (i < 16 ? a[2 * i] : a8[2 * i - 32]);
          v[2 * i + 1] = bf_hi(res[i]) + (i < 16 ? a[2 * i + 1] : a8[2 * i - 31]);
        }
      }
      uint32_t lsb;
      uint32_t h[144];
      {
        THREAD_IDS();
        float a[128];
        const uint32_t xd = sb + SM_X + w * 4 * XSLOT + (lane >> 4) * 1024 + (16 * wp + (lane & 15)) * 16;
        const float2 rs = ln_gemm<false>(c, G, v, res, sum, st0, j, t, layer, xtag,
          [&](int i) {
            if (i == 0) {
              lsb = ((res[0] & 1) | (res[4] & 1) << 1 | (res[8] & 1) << 2 | (res[12] & 1) << 3 | (res[16] & 1) << 4) ^ (xtag * 31);
              if (w == 1) asm volatile("bar.sync 3, 256;" ::: "memory");
            }
            PROF(pb + 9 + i);
          },
          [&](int gi, uint32_t bb, const uint4& f0, const uint4& f1) {
            if (gi == 0) PROF(pb + 11);
            wg_fence();
            wgmma_ra<256>(a, f0, desc_hi(4096, 1024, 1) + bb, gi > 0);
            wgmma_ra<256>(a, f1, desc_hi(4096, 1024, 1) + (bb + 128), true);
            wg_commit();
            stsm4(xd + gi * 4096, f0.x, f0.y, f0.z, f0.w);
            stsm4(xd + gi * 4096 + 2048, f1.x, f1.y, f1.z, f1.w);
            if (gi == 17) { fence_async_smem(); wg_bar(w); }
          });
        sts64f(sb + SM_KEEP + (tid_ >> 2) * 8, rs.x * rs.x, rs.y * rs.y);
        c.progress(32 * layer + 22);
        PROF2(pb + 12);
        glu<16, 0>(a, h);
        const Desc da0 = desc_hi(1024, 128, 0) + (dsb + ((SM_X + w * 4 * XSLOT) >> 4));
        auto tile = [&](auto wide, auto last) {
          const uint32_t xe = BAR_EMPTYX + 32 * (t & 1) + 4 * (t & 6);
#pragma unroll 1
          for (int gi = 0; gi < 18; gi++) {
            uint32_t prev;
            const uint32_t bb = c.nextB(prev);
            const Desc da = da0 + gi * 256;
            wg_fence();
            if (wide()) {
              wgmma_ss<256>(a, da, desc_hi(4096, 1024, 1) + bb, gi);
              wgmma_ss<256>(a, da + 128, desc_hi(4096, 1024, 1) + (bb + 128), 1);
            } else {
              wgmma_ss<192>(*(float(*)[96])a, da, desc_hi(2048, 512, 2) + bb, gi);
              wgmma_ss<192>(*(float(*)[96])a, da + 128, desc_hi(2048, 512, 2) + (bb + 64), 1);
            }
            wg_commit();
            wg_wait<1>();
            if (gi > 0 && !(last() && gi > 13)) c.release2(BAR_EMPTYB + prev);
            if (last() && gi >= XREL && !((gi ^ XREL) & 1)) c.release2(BAR_EMPTYX + 16 * ((gi - XREL) & 2) + 2 * ((gi - XREL) & 12));
          }
          wg_wait<0>();
          if (!last()) c.releaseLastB();
          if (last() && t >= (19 - XREL) / 2 && t < 8) { mbar_arrive(sb + xe); mbar_arrive_remote(c.rem + xe); }
        };
        auto yes = [] { return true; };
        auto no = [] { return false; };
        tile(yes, no); PROF2(pb + 13); glu<16, 32>(a, h);
        tile(yes, no); PROF2(pb + 14); glu<16, 64>(a, h);
        tile(no, no); PROF2(pb + 15); glu<12, 96>(a, h);
        const uint32_t hole = sb + SM_B + 12288 + tid_ * 16;
#pragma unroll
        for (int i = 0; i < NSPILL; i++) sts128(hole + i * BSLOT, h[96 + 4 * i], h[97 + 4 * i], h[98 + 4 * i], h[99 + 4 * i]);
        if (w == 1) asm volatile("bar.arrive 8, 256;" ::: "memory");
        tile(no, yes); PROF2(pb + 16); glu<12, 120>(a, h);
#pragma unroll
        for (int i = 0; i < NSPILL; i++) { const uint4 u = lds128(hole + i * BSLOT); h[96 + 4 * i] = u.x; h[97 + 4 * i] = u.y; h[98 + 4 * i] = u.z; h[99 + 4 * i] = u.w; }
      }
      {
        THREAD_IDS();
        float d[32];
        uint4* gt = G->obox + t;
        asm volatile("" : "+l"(gt));
        uint4* const ib = gt + 2 * 4608 + layer * 8 * INBOX;
        auto pass = [&](uint32_t s0, bool last, auto&& hook) {
          const Desc db = desc_hi(0, 1024, 1) + (dsb + (SM_X >> 4) + s0 * (XSLOT >> 4));
          mbar_wait_c(sb + BAR_FULLX + 8 * s0, (c.mX >> s0) & 1);
          asm volatile("bar.sync %0, 256;" ::"r"(8 + w) : "memory");
#pragma unroll
          for (int i = 0; i < 4; i++) {
            const int si = 4 * (i & 1) + (i >> 1);
            if (i > 0) mbar_wait_c(sb + BAR_FULLX + 8 * (s0 + si), (c.mX >> (s0 + si)) & 1);
            wg_fence();
#pragma unroll
            for (int k = 0; k < 9; k++) {
              const uint32_t* hk = h + 36 * i + 4 * k;
              wgmma_ra<64>(d, make_uint4(hk[0], hk[1], hk[2], hk[3]), db + (si * (XSLOT >> 4) + k * 128), last || i + k > 0);
              if (9 * i + k == PPK && !(last && w == 1)) asm volatile("bar.arrive %0, 256;" ::"r"(9 - w) : "memory");
            }
            wg_commit();
            if (i > 0) { wg_wait<1>(); c.release2(BAR_EMPTYX + 8 * (s0 + 4 * ((i - 1) & 1) + ((i - 1) >> 1))); }
            if (i == RHOOK) hook();
          }
          c.mX ^= 0x33u << s0;
        };
        PROF2(pb + 17);
#pragma unroll 1
        for (int p = 0; p < 8; p++) {
          const uint32_t s0 = 2 * (p & 1);
          pass(s0, false, [] {});
          wg_wait<0>();
          c.release2(BAR_EMPTYX + 8 * (s0 + 5));
          uint32_t pk[16];
#pragma unroll
          for (int i = 0; i < 16; i++) pk[i] = pack_bf16(d[2 * i], d[2 * i + 1]);
          if (p >= BREL && p < BREL + 5) {
            const uint32_t o = c.sB + 8 * (p - BREL);
            c.release2(BAR_EMPTYB + (o < 40 ? o : o - 40));
          }
          uint4* const dst = ib + ((j + p) & 7) * INBOX;
          if (p == 0) {
            mbar_wait_c(sb + BAR_CLR + 8 * w, 0);
#pragma unroll
            for (int k = 0; k < 8; k++) red2((uint2*)(ib + k * INBOX + 512) - t, pk[2 * k], pk[2 * k + 1]);
          } else if (p < 7) {
#pragma unroll
            for (int k = 0; k < 4; k++) red4(dst + k * 128, pk[4 * k], pk[4 * k + 1], pk[4 * k + 2], pk[4 * k + 3]);
            if (p == 6) { __syncwarp(); if (lane == 0) mbar_arrive(sb + BAR_REDDONE + 8 * w); }
          } else {
#pragma unroll
            for (int k = 0; k < 4; k++) st_relaxed4(gt + ((j + 7) & 7) * 128 + k * 1024, pk[4 * k] & ~1u, pk[4 * k + 1], pk[4 * k + 2], pk[4 * k + 3]);
          }
        }
        PROF2(pb + 18);
        const uint4 *in = ib + j * INBOX, *pin = gt + j * 128;
        const uint2* in9 = (const uint2*)(in + 512) - t;
        asm volatile("" : "+l"(in), "+l"(pin), "+l"(in9));
        const float2 r2 = lds64(sb + SM_KEEP + (tid_ >> 2) * 8);
        uint2 X9;
        {
          uint4 X[4];
          const uint4* box = gt + 4608;
#pragma unroll
          for (int k = 0; k < 4; k++) X[k] = ld_relaxed4(box + 256 * j + ((k & 1) + 8 * (k & 2)) * 128);
          X9 = ld_relaxed2((const uint2*)(box + (32 + (j >> 1)) * 128) + (j & 1));
          const float i0 = rcp(r2.x), i1 = rcp(r2.y);
#pragma unroll
          for (int k = 0; k < 4; k++) {
            float* e = d + 8 * k;
            X[k].x ^= (lsb >> k) & 1;
            e[0] = bf_lo(X[k].x) * i0; e[1] = bf_hi(X[k].x) * i0; e[2] = bf_lo(X[k].y) * i1; e[3] = bf_hi(X[k].y) * i1;
            e[4] = bf_lo(X[k].z) * i0; e[5] = bf_hi(X[k].z) * i0; e[6] = bf_lo(X[k].w) * i1; e[7] = bf_hi(X[k].w) * i1;
          }
        }
        uint4 R[4], P[4];
        uint2 R9;
        PROF2(pb + 19);
        pass(0, true, [&] {
          mbar_wait_c(sb + BAR_RREADY + 8 * w, layer);
#pragma unroll
          for (int k = 0; k < 4; k++) R[k] = ld_relaxed4(in + k * 128);
          R9 = ld_relaxed2(in9);
#pragma unroll
          for (int k = 0; k < 4; k++) P[k] = ld_relaxed4(pin + k * 1024);
        });
        const uint32_t zero = late(sb + BAR_FULLX + 64, 0);
        while (__any_sync(0xffffffffu, (chk2(P[0].x, P[1].x, zero) | chk2(P[2].x, P[3].x, zero)) & 1)) {
#pragma unroll
          for (int k = 0; k < 4; k++) P[k] = ld_relaxed4(pin + k * 1024);
        }
#pragma unroll
        for (int k = 0; k < 4; k++) {
          const uint32_t u[4] = {hadd2(R[k].x, P[k].x), hadd2(R[k].y, P[k].y), hadd2(R[k].z, P[k].z), hadd2(R[k].w, P[k].w)};
#pragma unroll
          for (int i = 0; i < 4; i++) { v[8 * k + 2 * i] = bf_lo(u[i]); v[8 * k + 2 * i + 1] = bf_hi(u[i]); }
        }
        X9.x = chk(zero, X9.x, lsb >> 4);
        v[32] = fmaf(bf_lo(R9.x), r2.x, bf_lo(X9.x)); v[33] = fmaf(bf_hi(R9.x), r2.x, bf_hi(X9.x));
        v[34] = fmaf(bf_lo(R9.y), r2.y, bf_lo(X9.y)); v[35] = fmaf(bf_hi(R9.y), r2.y, bf_hi(X9.y));
        PROF2(pb + 20);
        wg_wait<0>();
        c.release2(BAR_EMPTYX + 40);
        PROF2(pb + 21);
#pragma unroll
        for (int i = 0; i < 32; i++) v[i] = (v[i] + d[i]) * (i & 2 ? r2.y : r2.x);
      }
      if (layer == NLAYERS - 1) break;
      {
        THREAD_IDS();
        PROF(31);
        rs = ln_gemm<true>(c, G, v, res, sum, st0, j, t, 1, xtag ^ 1, [&](int i) { PROF(32 + i); if (i) PROF(34); }, qkv_mma);
      }
    }
    {
      THREAD_IDS();
      const uint32_t stg = sb + SM_B + warp * 4096;
      const uint32_t sd = stg + (lane & 15) * 128;
#pragma unroll
      for (int i = 0; i < 4; i++)
        stsm4(sd + (((2 * i + (lane >> 4)) ^ (lane & 7)) << 4), pack_bf16(v[8 * i], v[8 * i + 1]), pack_bf16(v[8 * i + 2], v[8 * i + 3]),
              pack_bf16(v[8 * i + 4], v[8 * i + 5]), pack_bf16(v[8 * i + 6], v[8 * i + 7]));
      stsm2(stg + 2048 + (lane & 15) * 16, pack_bf16(v[32], v[33]), pack_bf16(v[34], v[35]));
      fence_async_smem();
      __syncwarp();
      if (lane == 0) {
        tma_store3d(&maps.out, stg, 64 * j, w, 64 * rb + 16 * wp);
        tma_store3d(&maps.outc, stg + 2048, 512 + 8 * j, w, 64 * rb + 16 * wp);
        bulk_commit();
        if (wp == 0) st_relaxed(G->flag + 32 + 32 * j, xtag);
        bulk_wait_all();
        mbar_arrive(sb + BAR_DONE + 8 * w);
      }
      PROF(61);
    }
    __syncwarp();
    cluster_sync();
  }
}

typedef CUresult (*EncFn)(CUtensorMap*, CUtensorMapDataType, cuuint32_t, void*, const cuuint64_t*, const cuuint64_t*, const cuuint32_t*,
                          const cuuint32_t*, CUtensorMapInterleave, CUtensorMapSwizzle, CUtensorMapL2promotion, CUtensorMapFloatOOBfill);

void make_map(EncFn enc, CUtensorMap* m, const void* p, int rank, uint64_t d0, uint64_t d1, uint64_t d2, uint64_t s1, uint64_t s2, uint32_t b0,
              uint32_t b1, uint32_t b2, CUtensorMapSwizzle sw) {
  cuuint64_t gd[3] = {d0, d1, d2};
  cuuint64_t gs[2] = {s1, s2};
  cuuint32_t bd[3] = {b0, b1, b2};
  cuuint32_t es[3] = {1, 1, 1};
  enc(m, CU_TENSOR_MAP_DATA_TYPE_BFLOAT16, rank, const_cast<void*>(p), gd, gs, bd, es, CU_TENSOR_MAP_INTERLEAVE_NONE, sw,
      CU_TENSOR_MAP_L2_PROMOTION_L2_128B, CU_TENSOR_MAP_FLOAT_OOB_FILL_NONE);
}

}

extern "C" void kernel_launch(void* const* d_in, const int* in_sizes, int n_in, void* d_out, int out_size) {
  const __nv_bfloat16* x = (const __nv_bfloat16*)d_in[0];
  const char *wqkv = (const char*)d_in[1], *wo = (const char*)d_in[2], *wg = (const char*)d_in[4], *wu = (const char*)d_in[5], *wd = (const char*)d_in[6];
  static EncFn enc = nullptr;
  static int grid = NCTA;
  static Group* ws = nullptr;
  if (!enc) {
    cudaDriverEntryPointQueryResult qr;
    cudaGetDriverEntryPoint("cuTensorMapEncodeTiled", (void**)&enc, cudaEnableDefault, &qr);
    cudaGetSymbolAddress((void**)&ws, g_ws);
    cudaFuncSetAttribute(fused_kernel, cudaFuncAttributeMaxDynamicSharedMemorySize, SMEM_BYTES);
    cudaLaunchConfig_t cfg = {};
    cfg.gridDim = NCTA + 4; cfg.blockDim = 384; cfg.dynamicSmemBytes = SMEM_BYTES;
    int clusters = 0;
    if (REPACK && cudaOccupancyMaxActiveClusters(&clusters, fused_kernel, &cfg) == cudaSuccess && 2 * clusters >= NCTA + 4) grid = NCTA + 4;
    cudaGetLastError();
  }
  const CUtensorMapSwizzle S0 = CU_TENSOR_MAP_SWIZZLE_NONE, S64 = CU_TENSOR_MAP_SWIZZLE_64B, S128 = CU_TENSOR_MAP_SWIZZLE_128B;
  Maps m;
  make_map(enc, &m.x, x, 3, 576, 2, 1024, 1152, 2304, 64, 1, 64, S128);
  make_map(enc, &m.qm, wqkv, 3, 576, 576, 3, 3456, 1152, 64, 16, 3, S128);
  make_map(enc, &m.qc, wqkv, 3, 576, 576, 3, 3456, 1152, 8, 16, 3, S0);
  make_map(enc, &m.o, wo, 2, 576, 576, 1, 1152, 0, 64, 72, 1, S128);
  make_map(enc, &m.oc, wo, 2, 576, 576, 1, 1152, 0, 8, 144, 1, S0);
  make_map(enc, &m.g, wg, 3, 64, 576, 72, 9216, 128, 64, 32, 2, S128);
  make_map(enc, &m.u, wu, 3, 64, 576, 72, 9216, 128, 64, 32, 2, S128);
  make_map(enc, &m.g3, wg, 3, 32, 576, 144, 9216, 64, 32, 32, 3, S64);
  make_map(enc, &m.u3, wu, 3, 32, 576, 144, 9216, 64, 32, 32, 3, S64);
  make_map(enc, &m.d, wd, 2, 576, 4608, 1, 1152, 0, 64, 72, 1, S128);
  make_map(enc, &m.out, d_out, 3, 576, 2, 1024, 1152, 2304, 64, 1, 16, S128);
  make_map(enc, &m.outc, d_out, 3, 576, 2, 1024, 1152, 2304, 8, 1, 16, S0);
  fused_kernel<<<grid, 384, SMEM_BYTES>>>(x, ws, wqkv, wg, wu, wd, m, wo);
}
```

```cpp
#include <cuda_runtime.h>
#include <cuda_bf16.h>
#include <cuda.h>
#include <stdint.h>
#include <stddef.h>

namespace {

constexpr int D_ = 576;
constexpr int NCTA = 128;
#define NLAYERS 2
#define W_POLICY policy_evict_first
#define A_POLICY policy_evict_normal
#define OPEN 1
#define PFMODE 5
#define WWIN 4
#define WOREL -1
#define WB1 11
#define WB2 21
#define WB3 32
#define WPROBE 1
#define WPROBE2 0
#define SPEC 2
#define POLLFIRST 0
#define SUMFIRST 1
#define EARLYPOLL 1
#define LEAD 0
#define ATTBAR 0
#define GL 18
#define WOBAR 0
#define QD 0
#define QG 4
#define PFQ 1
#define XDELAY 0
#define WOH 1
#define PFSLEEP 700
#define GPCMAP 1
#define PFF 1
#define REDN 1
#define CLRSLEEP 300
#define OPENL 24
#define FG -1
#define NON8 0
#define HMUL 1
#define FCH 1
#define PPK 34
#define RHOOK -1
#define SCHEDBAR 1
#define QH 5
#define XH 3
#define XP 0
#define GSLEEP 32
#define XCH 1
#define MAPPF 1
#define XREL 8
#define WOG 13
#define BREL 1
#define FENCE1 0
#define OWNX 0
#define OWNBAR 1
#define EARLY 1
#define ESPEC 0
#define TESTP 0
#define WOW 1
#define STATP -1
#define WSG 0
#define REPACK 1
#define QPACE 23
#define RDELAY 12
#define TLEAD 2
#define TLEAD2 2
#define TLEAD0 2
#define NSPILL 4
#define REGS_C 232
#define REGS_P 40
#define STR2(x) #x
#define STR(x) STR2(x)
constexpr uint32_t SM_X = 0;
constexpr uint32_t XSLOT = 18432;
constexpr uint32_t SM_WOC = SM_X + 3 * XSLOT + 9216;
constexpr uint32_t SM_B = 147456;
constexpr uint32_t BSLOT = 16384;
constexpr uint32_t SM_KEEP = 229376;
constexpr uint32_t SM_WSUM = SM_KEEP + 512;
constexpr uint32_t SM_BAR = SM_KEEP + 2048;
constexpr uint32_t BAR_FULLB = SM_BAR;
constexpr uint32_t BAR_RREADY = SM_BAR + 40;
constexpr uint32_t BAR_CLR = SM_BAR + 56;
constexpr uint32_t BAR_FULLX = SM_BAR + 72;
constexpr uint32_t BAR_EMPTYB = SM_BAR + 144;
constexpr uint32_t BAR_EMPTYX = SM_BAR + 184;
constexpr uint32_t BAR_REDDONE = SM_BAR + 248;
constexpr uint32_t BAR_DONE = SM_BAR + 264;
constexpr uint32_t BAR_WSUM = SM_BAR + 280;
constexpr uint32_t SM_PROG = SM_BAR + 288;
constexpr uint32_t SMEM_BYTES = SM_BAR + 1024;

struct Maps { CUtensorMap x, qm, qc, o, oc, g, u, g3, u3, d, out, outc; };

constexpr int INBOX = 576;
struct Group {
  uint2 sum[4 * 8 * 8];
  uint2 sq[4 * 8 * 8];
  uint32_t wsum[512];
  uint32_t flag[512];
  uint4 halo[8 * 160];
  uint4 obox[36 * 128];
  uint4 xbox[36 * 128];
  uint4 inbox[2][8 * INBOX];
};
struct Scratch { Group g[32]; uint4 wq[8][36][432]; };
__device__ __align__(1024) Scratch g_ws;
#define PROF(i)
#define PROFX(i)

#define PROF2(i) PROF(i)

struct Desc { uint32_t lo, hi; };
__device__ __forceinline__ constexpr Desc desc_hi(uint32_t lbo, uint32_t sbo, uint32_t sw) { return Desc{(lbo >> 4) << 16, (sbo >> 4) | sw << 30}; }
__device__ __forceinline__ constexpr Desc operator+(Desc d, uint32_t a) { return Desc{d.lo + a, d.hi}; }

template<int N> __device__ __forceinline__ void wgmma_ss(float (&d)[N / 2], Desc da, Desc db, int sc);
template<> __device__ __forceinline__ void wgmma_ss<192>(float (&d)[96], Desc da, Desc db, int sc) {
  asm volatile("{\n.reg .pred p;\n.reg .b64 a, b;\nsetp.ne.b32 p, %100, 0;\nmov.b64 a, {%96, %97};\nmov.b64 b, {%98, %99};\n"
    "wgmma.mma_async.sync.aligned.m64n192k16.f32.bf16.bf16 {%0,%1,%2,%3,%4,%5,%6,%7,%8,%9,%10,%11,%12,%13,%14,%15,%16,%17,%18,%19,%20,%21,%22,%23,%24,%25,%26,%27,%28,%29,%30,%31,%32,%33,%34,%35,%36,%37,%38,%39,%40,%41,%42,%43,%44,%45,%46,%47,%48,%49,%50,%51,%52,%53,%54,%55,%56,%57,%58,%59,%60,%61,%62,%63,%64,%65,%66,%67,%68,%69,%70,%71,%72,%73,%74,%75,%76,%77,%78,%79,%80,%81,%82,%83,%84,%85,%86,%87,%88,%89,%90,%91,%92,%93,%94,%95}, a, b, p, 1, 1, 0, 1;\n}\n"
    : "+f"(d[0]),"+f"(d[1]),"+f"(d[2]),"+f"(d[3]),"+f"(d[4]),"+f"(d[5]),"+f"(d[6]),"+f"(d[7]),"+f"(d[8]),"+f"(d[9]),"+f"(d[10]),"+f"(d[11]),"+f"(d[12]),"+f"(d[13]),"+f"(d[14]),"+f"(d[15]),"+f"(d[16]),"+f"(d[17]),"+f"(d[18]),"+f"(d[19]),"+f"(d[20]),"+f"(d[21]),"+f"(d[22]),"+f"(d[23]),"+f"(d[24]),"+f"(d[25]),"+f"(d[26]),"+f"(d[27]),"+f"(d[28]),"+f"(d[29]),"+f"(d[30]),"+f"(d[31]),"+f"(d[32]),"+f"(d[33]),"+f"(d[34]),"+f"(d[35]),"+f"(d[36]),"+f"(d[37]),"+f"(d[38]),"+f"(d[39]),"+f"(d[40]),"+f"(d[41]),"+f"(d[42]),"+f"(d[43]),"+f"(d[44]),"+f"(d[45]),"+f"(d[46]),"+f"(d[47]),"+f"(d[48]),"+f"(d[49]),"+f"(d[50]),"+f"(d[51]),"+f"(d[52]),"+f"(d[53]),"+f"(d[54]),"+f"(d[55]),"+f"(d[56]),"+f"(d[57]),"+f"(d[58]),"+f"(d[59]),"+f"(d[60]),"+f"(d[61]),"+f"(d[62]),"+f"(d[63]),"+f"(d[64]),"+f"(d[65]),"+f"(d[66]),"+f"(d[67]),"+f"(d[68]),"+f"(d[69]),"+f"(d[70]),"+f"(d[71]),"+f"(d[72]),"+f"(d[73]),"+f"(d[74]),"+f"(d[75]),"+f"(d[76]),"+f"(d[77]),"+f"(d[78]),"+f"(d[79]),"+f"(d[80]),"+f"(d[81]),"+f"(d[82]),"+f"(d[83]),"+f"(d[84]),"+f"(d[85]),"+f"(d[86]),"+f"(d[87]),"+f"(d[88]),"+f"(d[89]),"+f"(d[90]),"+f"(d[91]),"+f"(d[92]),"+f"(d[93]),"+f"(d[94]),"+f"(d[95]) : "r"(da.lo), "r"(da.hi), "r"(db.lo), "r"(db.hi), "r"(sc));
}
template<> __device__ __forceinline__ void wgmma_ss<256>(float (&d)[128], Desc da, Desc db, int sc) {
  asm volatile("{\n.reg .pred p;\n.reg .b64 a, b;\nsetp.ne.b32 p, %132, 0;\nmov.b64 a, {%128, %129};\nmov.b64 b, {%130, %131};\n"
    "wgmma.mma_async.sync.aligned.m64n256k16.f32.bf16.bf16 {%0,%1,%2,%3,%4,%5,%6,%7,%8,%9,%10,%11,%12,%13,%14,%15,%16,%17,%18,%19,%20,%21,%22,%23,%24,%25,%26,%27,%28,%29,%30,%31,%32,%33,%34,%35,%36,%37,%38,%39,%40,%41,%42,%43,%44,%45,%46,%47,%48,%49,%50,%51,%52,%53,%54,%55,%56,%57,%58,%59,%60,%61,%62,%63,%64,%65,%66,%67,%68,%69,%70,%71,%72,%73,%74,%75,%76,%77,%78,%79,%80,%81,%82,%83,%84,%85,%86,%87,%88,%89,%90,%91,%92,%93,%94,%95,%96,%97,%98,%99,%100,%101,%102,%103,%104,%105,%106,%107,%108,%109,%110,%111,%112,%113,%114,%115,%116,%117,%118,%119,%120,%121,%122,%123,%124,%125,%126,%127}, a, b, p, 1, 1, 0, 1;\n}\n"
    : "+f"(d[0]),"+f"(d[1]),"+f"(d[2]),"+f"(d[3]),"+f"(d[4]),"+f"(d[5]),"+f"(d[6]),"+f"(d[7]),"+f"(d[8]),"+f"(d[9]),"+f"(d[10]),"+f"(d[11]),"+f"(d[12]),"+f"(d[13]),"+f"(d[14]),"+f"(d[15]),"+f"(d[16]),"+f"(d[17]),"+f"(d[18]),"+f"(d[19]),"+f"(d[20]),"+f"(d[21]),"+f"(d[22]),"+f"(d[23]),"+f"(d[24]),"+f"(d[25]),"+f"(d[26]),"+f"(d[27]),"+f"(d[28]),"+f"(d[29]),"+f"(d[30]),"+f"(d[31]),"+f"(d[32]),"+f"(d[33]),"+f"(d[34]),"+f"(d[35]),"+f"(d[36]),"+f"(d[37]),"+f"(d[38]),"+f"(d[39]),"+f"(d[40]),"+f"(d[41]),"+f"(d[42]),"+f"(d[43]),"+f"(d[44]),"+f"(d[45]),"+f"(d[46]),"+f"(d[47]),"+f"(d[48]),"+f"(d[49]),"+f"(d[50]),"+f"(d[51]),"+f"(d[52]),"+f"(d[53]),"+f"(d[54]),"+f"(d[55]),"+f"(d[56]),"+f"(d[57]),"+f"(d[58]),"+f"(d[59]),"+f"(d[60]),"+f"(d[61]),"+f"(d[62]),"+f"(d[63]),"+f"(d[64]),"+f"(d[65]),"+f"(d[66]),"+f"(d[67]),"+f"(d[68]),"+f"(d[69]),"+f"(d[70]),"+f"(d[71]),"+f"(d[72]),"+f"(d[73]),"+f"(d[74]),"+f"(d[75]),"+f"(d[76]),"+f"(d[77]),"+f"(d[78]),"+f"(d[79]),"+f"(d[80]),"+f"(d[81]),"+f"(d[82]),"+f"(d[83]),"+f"(d[84]),"+f"(d[85]),"+f"(d[86]),"+f"(d[87]),"+f"(d[88]),"+f"(d[89]),"+f"(d[90]),"+f"(d[91]),"+f"(d[92]),"+f"(d[93]),"+f"(d[94]),"+f"(d[95]),"+f"(d[96]),"+f"(d[97]),"+f"(d[98]),"+f"(d[99]),"+f"(d[100]),"+f"(d[101]),"+f"(d[102]),"+f"(d[103]),"+f"(d[104]),"+f"(d[105]),"+f"(d[106]),"+f"(d[107]),"+f"(d[108]),"+f"(d[109]),"+f"(d[110]),"+f"(d[111]),"+f"(d[112]),"+f"(d[113]),"+f"(d[114]),"+f"(d[115]),"+f"(d[116]),"+f"(d[117]),"+f"(d[118]),"+f"(d[119]),"+f"(d[120]),"+f"(d[121]),"+f"(d[122]),"+f"(d[123]),"+f"(d[124]),"+f"(d[125]),"+f"(d[126]),"+f"(d[127]) : "r"(da.lo), "r"(da.hi), "r"(db.lo), "r"(db.hi), "r"(sc));
}
template<int N, int ACC> __device__ __forceinline__ void wgmma_rs(float (&d)[N / 2], const uint4& a, Desc db);
template<> __device__ __forceinline__ void wgmma_rs<8, 1>(float (&d)[4], const uint4& a, Desc db) {
  asm volatile("{\n.reg .pred p;\n.reg .b64 b;\nsetp.ne.b32 p, 1, 0;\nmov.b64 b, {%8, %9};\n"
    "wgmma.mma_async.sync.aligned.m64n8k16.f32.bf16.bf16 {%0,%1,%2,%3}, {%4,%5,%6,%7}, b, p, 1, 1, 1;\n}\n"
    : "+f"(d[0]),"+f"(d[1]),"+f"(d[2]),"+f"(d[3]) : "r"(a.x), "r"(a.y), "r"(a.z), "r"(a.w), "r"(db.lo), "r"(db.hi));
}
template<> __device__ __forceinline__ void wgmma_rs<8, 0>(float (&d)[4], const uint4& a, Desc db) {
  asm volatile("{\n.reg .pred p;\n.reg .b64 b;\nsetp.ne.b32 p, 0, 0;\nmov.b64 b, {%8, %9};\n"
    "wgmma.mma_async.sync.aligned.m64n8k16.f32.bf16.bf16 {%0,%1,%2,%3}, {%4,%5,%6,%7}, b, p, 1, 1, 1;\n}\n"
    : "=f"(d[0]),"=f"(d[1]),"=f"(d[2]),"=f"(d[3]) : "r"(a.x), "r"(a.y), "r"(a.z), "r"(a.w), "r"(db.lo), "r"(db.hi));
}
template<> __device__ __forceinline__ void wgmma_rs<24, 1>(float (&d)[12], const uint4& a, Desc db) {
  asm volatile("{\n.reg .pred p;\n.reg .b64 b;\nsetp.ne.b32 p, 1, 0;\nmov.b64 b, {%16, %17};\n"
    "wgmma.mma_async.sync.aligned.m64n24k16.f32.bf16.bf16 {%0,%1,%2,%3,%4,%5,%6,%7,%8,%9,%10,%11}, {%12,%13,%14,%15}, b, p, 1, 1, 1;\n}\n"
    : "+f"(d[0]),"+f"(d[1]),"+f"(d[2]),"+f"(d[3]),"+f"(d[4]),"+f"(d[5]),"+f"(d[6]),"+f"(d[7]),"+f"(d[8]),"+f"(d[9]),"+f"(d[10]),"+f"(d[11]) : "r"(a.x), "r"(a.y), "r"(a.z), "r"(a.w), "r"(db.lo), "r"(db.hi));
}
template<> __device__ __forceinline__ void wgmma_rs<24, 0>(float (&d)[12], const uint4& a, Desc db) {
  asm volatile("{\n.reg .pred p;\n.reg .b64 b;\nsetp.ne.b32 p, 0, 0;\nmov.b64 b, {%16, %17};\n"
    "wgmma.mma_async.sync.aligned.m64n24k16.f32.bf16.bf16 {%0,%1,%2,%3,%4,%5,%6,%7,%8,%9,%10,%11}, {%12,%13,%14,%15}, b, p, 1, 1, 1;\n}\n"
    : "=f"(d[0]),"=f"(d[1]),"=f"(d[2]),"=f"(d[3]),"=f"(d[4]),"=f"(d[5]),"=f"(d[6]),"=f"(d[7]),"=f"(d[8]),"=f"(d[9]),"=f"(d[10]),"=f"(d[11]) : "r"(a.x), "r"(a.y), "r"(a.z), "r"(a.w), "r"(db.lo), "r"(db.hi));
}
template<> __device__ __forceinline__ void wgmma_rs<64, 1>(float (&d)[32], const uint4& a, Desc db) {
  asm volatile("{\n.reg .pred p;\n.reg .b64 b;\nsetp.ne.b32 p, 1, 0;\nmov.b64 b, {%36, %37};\n"
    "wgmma.mma_async.sync.aligned.m64n64k16.f32.bf16.bf16 {%0,%1,%2,%3,%4,%5,%6,%7,%8,%9,%10,%11,%12,%13,%14,%15,%16,%17,%18,%19,%20,%21,%22,%23,%24,%25,%26,%27,%28,%29,%30,%31}, {%32,%33,%34,%35}, b, p, 1, 1, 1;\n}\n"
    : "+f"(d[0]),"+f"(d[1]),"+f"(d[2]),"+f"(d[3]),"+f"(d[4]),"+f"(d[5]),"+f"(d[6]),"+f"(d[7]),"+f"(d[8]),"+f"(d[9]),"+f"(d[10]),"+f"(d[11]),"+f"(d[12]),"+f"(d[13]),"+f"(d[14]),"+f"(d[15]),"+f"(d[16]),"+f"(d[17]),"+f"(d[18]),"+f"(d[19]),"+f"(d[20]),"+f"(d[21]),"+f"(d[22]),"+f"(d[23]),"+f"(d[24]),"+f"(d[25]),"+f"(d[26]),"+f"(d[27]),"+f"(d[28]),"+f"(d[29]),"+f"(d[30]),"+f"(d[31]) : "r"(a.x), "r"(a.y), "r"(a.z), "r"(a.w), "r"(db.lo), "r"(db.hi));
}
template<> __device__ __forceinline__ void wgmma_rs<64, 0>(float (&d)[32], const uint4& a, Desc db) {
  asm volatile("{\n.reg .pred p;\n.reg .b64 b;\nsetp.ne.b32 p, 0, 0;\nmov.b64 b, {%36, %37};\n"
    "wgmma.mma_async.sync.aligned.m64n64k16.f32.bf16.bf16 {%0,%1,%2,%3,%4,%5,%6,%7,%8,%9,%10,%11,%12,%13,%14,%15,%16,%17,%18,%19,%20,%21,%22,%23,%24,%25,%26,%27,%28,%29,%30,%31}, {%32,%33,%34,%35}, b, p, 1, 1, 1;\n}\n"
    : "=f"(d[0]),"=f"(d[1]),"=f"(d[2]),"=f"(d[3]),"=f"(d[4]),"=f"(d[5]),"=f"(d[6]),"=f"(d[7]),"=f"(d[8]),"=f"(d[9]),"=f"(d[10]),"=f"(d[11]),"=f"(d[12]),"=f"(d[13]),"=f"(d[14]),"=f"(d[15]),"=f"(d[16]),"=f"(d[17]),"=f"(d[18]),"=f"(d[19]),"=f"(d[20]),"=f"(d[21]),"=f"(d[22]),"=f"(d[23]),"=f"(d[24]),"=f"(d[25]),"=f"(d[26]),"=f"(d[27]),"=f"(d[28]),"=f"(d[29]),"=f"(d[30]),"=f"(d[31]) : "r"(a.x), "r"(a.y), "r"(a.z), "r"(a.w), "r"(db.lo), "r"(db.hi));
}
template<> __device__ __forceinline__ void wgmma_rs<192, 1>(float (&d)[96], const uint4& a, Desc db) {
  asm volatile("{\n.reg .pred p;\n.reg .b64 b;\nsetp.ne.b32 p, 1, 0;\nmov.b64 b, {%100, %101};\n"
    "wgmma.mma_async.sync.aligned.m64n192k16.f32.bf16.bf16 {%0,%1,%2,%3,%4,%5,%6,%7,%8,%9,%10,%11,%12,%13,%14,%15,%16,%17,%18,%19,%20,%21,%22,%23,%24,%25,%26,%27,%28,%29,%30,%31,%32,%33,%34,%35,%36,%37,%38,%39,%40,%41,%42,%43,%44,%45,%46,%47,%48,%49,%50,%51,%52,%53,%54,%55,%56,%57,%58,%59,%60,%61,%62,%63,%64,%65,%66,%67,%68,%69,%70,%71,%72,%73,%74,%75,%76,%77,%78,%79,%80,%81,%82,%83,%84,%85,%86,%87,%88,%89,%90,%91,%92,%93,%94,%95}, {%96,%97,%98,%99}, b, p, 1, 1, 1;\n}\n"
    : "+f"(d[0]),"+f"(d[1]),"+f"(d[2]),"+f"(d[3]),"+f"(d[4]),"+f"(d[5]),"+f"(d[6]),"+f"(d[7]),"+f"(d[8]),"+f"(d[9]),"+f"(d[10]),"+f"(d[11]),"+f"(d[12]),"+f"(d[13]),"+f"(d[14]),"+f"(d[15]),"+f"(d[16]),"+f"(d[17]),"+f"(d[18]),"+f"(d[19]),"+f"(d[20]),"+f"(d[21]),"+f"(d[22]),"+f"(d[23]),"+f"(d[24]),"+f"(d[25]),"+f"(d[26]),"+f"(d[27]),"+f"(d[28]),"+f"(d[29]),"+f"(d[30]),"+f"(d[31]),"+f"(d[32]),"+f"(d[33]),"+f"(d[34]),"+f"(d[35]),"+f"(d[36]),"+f"(d[37]),"+f"(d[38]),"+f"(d[39]),"+f"(d[40]),"+f"(d[41]),"+f"(d[42]),"+f"(d[43]),"+f"(d[44]),"+f"(d[45]),"+f"(d[46]),"+f"(d[47]),"+f"(d[48]),"+f"(d[49]),"+f"(d[50]),"+f"(d[51]),"+f"(d[52]),"+f"(d[53]),"+f"(d[54]),"+f"(d[55]),"+f"(d[56]),"+f"(d[57]),"+f"(d[58]),"+f"(d[59]),"+f"(d[60]),"+f"(d[61]),"+f"(d[62]),"+f"(d[63]),"+f"(d[64]),"+f"(d[65]),"+f"(d[66]),"+f"(d[67]),"+f"(d[68]),"+f"(d[69]),"+f"(d[70]),"+f"(d[71]),"+f"(d[72]),"+f"(d[73]),"+f"(d[74]),"+f"(d[75]),"+f"(d[76]),"+f"(d[77]),"+f"(d[78]),"+f"(d[79]),"+f"(d[80]),"+f"(d[81]),"+f"(d[82]),"+f"(d[83]),"+f"(d[84]),"+f"(d[85]),"+f"(d[86]),"+f"(d[87]),"+f"(d[88]),"+f"(d[89]),"+f"(d[90]),"+f"(d[91]),"+f"(d[92]),"+f"(d[93]),"+f"(d[94]),"+f"(d[95]) : "r"(a.x), "r"(a.y), "r"(a.z), "r"(a.w), "r"(db.lo), "r"(db.hi));
}
template<> __device__ __forceinline__ void wgmma_rs<192, 0>(float (&d)[96], const uint4& a, Desc db) {
  asm volatile("{\n.reg .pred p;\n.reg .b64 b;\nsetp.ne.b32 p, 0, 0;\nmov.b64 b, {%100, %101};\n"
    "wgmma.mma_async.sync.aligned.m64n192k16.f32.bf16.bf16 {%0,%1,%2,%3,%4,%5,%6,%7,%8,%9,%10,%11,%12,%13,%14,%15,%16,%17,%18,%19,%20,%21,%22,%23,%24,%25,%26,%27,%28,%29,%30,%31,%32,%33,%34,%35,%36,%37,%38,%39,%40,%41,%42,%43,%44,%45,%46,%47,%48,%49,%50,%51,%52,%53,%54,%55,%56,%57,%58,%59,%60,%61,%62,%63,%64,%65,%66,%67,%68,%69,%70,%71,%72,%73,%74,%75,%76,%77,%78,%79,%80,%81,%82,%83,%84,%85,%86,%87,%88,%89,%90,%91,%92,%93,%94,%95}, {%96,%97,%98,%99}, b, p, 1, 1, 1;\n}\n"
    : "=f"(d[0]),"=f"(d[1]),"=f"(d[2]),"=f"(d[3]),"=f"(d[4]),"=f"(d[5]),"=f"(d[6]),"=f"(d[7]),"=f"(d[8]),"=f"(d[9]),"=f"(d[10]),"=f"(d[11]),"=f"(d[12]),"=f"(d[13]),"=f"(d[14]),"=f"(d[15]),"=f"(d[16]),"=f"(d[17]),"=f"(d[18]),"=f"(d[19]),"=f"(d[20]),"=f"(d[21]),"=f"(d[22]),"=f"(d[23]),"=f"(d[24]),"=f"(d[25]),"=f"(d[26]),"=f"(d[27]),"=f"(d[28]),"=f"(d[29]),"=f"(d[30]),"=f"(d[31]),"=f"(d[32]),"=f"(d[33]),"=f"(d[34]),"=f"(d[35]),"=f"(d[36]),"=f"(d[37]),"=f"(d[38]),"=f"(d[39]),"=f"(d[40]),"=f"(d[41]),"=f"(d[42]),"=f"(d[43]),"=f"(d[44]),"=f"(d[45]),"=f"(d[46]),"=f"(d[47]),"=f"(d[48]),"=f"(d[49]),"=f"(d[50]),"=f"(d[51]),"=f"(d[52]),"=f"(d[53]),"=f"(d[54]),"=f"(d[55]),"=f"(d[56]),"=f"(d[57]),"=f"(d[58]),"=f"(d[59]),"=f"(d[60]),"=f"(d[61]),"=f"(d[62]),"=f"(d[63]),"=f"(d[64]),"=f"(d[65]),"=f"(d[66]),"=f"(d[67]),"=f"(d[68]),"=f"(d[69]),"=f"(d[70]),"=f"(d[71]),"=f"(d[72]),"=f"(d[73]),"=f"(d[74]),"=f"(d[75]),"=f"(d[76]),"=f"(d[77]),"=f"(d[78]),"=f"(d[79]),"=f"(d[80]),"=f"(d[81]),"=f"(d[82]),"=f"(d[83]),"=f"(d[84]),"=f"(d[85]),"=f"(d[86]),"=f"(d[87]),"=f"(d[88]),"=f"(d[89]),"=f"(d[90]),"=f"(d[91]),"=f"(d[92]),"=f"(d[93]),"=f"(d[94]),"=f"(d[95]) : "r"(a.x), "r"(a.y), "r"(a.z), "r"(a.w), "r"(db.lo), "r"(db.hi));
}
template<> __device__ __forceinline__ void wgmma_rs<256, 1>(float (&d)[128], const uint4& a, Desc db) {
  asm volatile("{\n.reg .pred p;\n.reg .b64 b;\nsetp.ne.b32 p, 1, 0;\nmov.b64 b, {%132, %133};\n"
    "wgmma.mma_async.sync.aligned.m64n256k16.f32.bf16.bf16 {%0,%1,%2,%3,%4,%5,%6,%7,%8,%9,%10,%11,%12,%13,%14,%15,%16,%17,%18,%19,%20,%21,%22,%23,%24,%25,%26,%27,%28,%29,%30,%31,%32,%33,%34,%35,%36,%37,%38,%39,%40,%41,%42,%43,%44,%45,%46,%47,%48,%49,%50,%51,%52,%53,%54,%55,%56,%57,%58,%59,%60,%61,%62,%63,%64,%65,%66,%67,%68,%69,%70,%71,%72,%73,%74,%75,%76,%77,%78,%79,%80,%81,%82,%83,%84,%85,%86,%87,%88,%89,%90,%91,%92,%93,%94,%95,%96,%97,%98,%99,%100,%101,%102,%103,%104,%105,%106,%107,%108,%109,%110,%111,%112,%113,%114,%115,%116,%117,%118,%119,%120,%121,%122,%123,%124,%125,%126,%127}, {%128,%129,%130,%131}, b, p, 1, 1, 1;\n}\n"
    : "+f"(d[0]),"+f"(d[1]),"+f"(d[2]),"+f"(d[3]),"+f"(d[4]),"+f"(d[5]),"+f"(d[6]),"+f"(d[7]),"+f"(d[8]),"+f"(d[9]),"+f"(d[10]),"+f"(d[11]),"+f"(d[12]),"+f"(d[13]),"+f"(d[14]),"+f"(d[15]),"+f"(d[16]),"+f"(d[17]),"+f"(d[18]),"+f"(d[19]),"+f"(d[20]),"+f"(d[21]),"+f"(d[22]),"+f"(d[23]),"+f"(d[24]),"+f"(d[25]),"+f"(d[26]),"+f"(d[27]),"+f"(d[28]),"+f"(d[29]),"+f"(d[30]),"+f"(d[31]),"+f"(d[32]),"+f"(d[33]),"+f"(d[34]),"+f"(d[35]),"+f"(d[36]),"+f"(d[37]),"+f"(d[38]),"+f"(d[39]),"+f"(d[40]),"+f"(d[41]),"+f"(d[42]),"+f"(d[43]),"+f"(d[44]),"+f"(d[45]),"+f"(d[46]),"+f"(d[47]),"+f"(d[48]),"+f"(d[49]),"+f"(d[50]),"+f"(d[51]),"+f"(d[52]),"+f"(d[53]),"+f"(d[54]),"+f"(d[55]),"+f"(d[56]),"+f"(d[57]),"+f"(d[58]),"+f"(d[59]),"+f"(d[60]),"+f"(d[61]),"+f"(d[62]),"+f"(d[63]),"+f"(d[64]),"+f"(d[65]),"+f"(d[66]),"+f"(d[67]),"+f"(d[68]),"+f"(d[69]),"+f"(d[70]),"+f"(d[71]),"+f"(d[72]),"+f"(d[73]),"+f"(d[74]),"+f"(d[75]),"+f"(d[76]),"+f"(d[77]),"+f"(d[78]),"+f"(d[79]),"+f"(d[80]),"+f"(d[81]),"+f"(d[82]),"+f"(d[83]),"+f"(d[84]),"+f"(d[85]),"+f"(d[86]),"+f"(d[87]),"+f"(d[88]),"+f"(d[89]),"+f"(d[90]),"+f"(d[91]),"+f"(d[92]),"+f"(d[93]),"+f"(d[94]),"+f"(d[95]),"+f"(d[96]),"+f"(d[97]),"+f"(d[98]),"+f"(d[99]),"+f"(d[100]),"+f"(d[101]),"+f"(d[102]),"+f"(d[103]),"+f"(d[104]),"+f"(d[105]),"+f"(d[106]),"+f"(d[107]),"+f"(d[108]),"+f"(d[109]),"+f"(d[110]),"+f"(d[111]),"+f"(d[112]),"+f"(d[113]),"+f"(d[114]),"+f"(d[115]),"+f"(d[116]),"+f"(d[117]),"+f"(d[118]),"+f"(d[119]),"+f"(d[120]),"+f"(d[121]),"+f"(d[122]),"+f"(d[123]),"+f"(d[124]),"+f"(d[125]),"+f"(d[126]),"+f"(d[127]) : "r"(a.x), "r"(a.y), "r"(a.z), "r"(a.w), "r"(db.lo), "r"(db.hi));
}
template<> __device__ __forceinline__ void wgmma_rs<256, 0>(float (&d)[128], const uint4& a, Desc db) {
  asm volatile("{\n.reg .pred p;\n.reg .b64 b;\nsetp.ne.b32 p, 0, 0;\nmov.b64 b, {%132, %133};\n"
    "wgmma.mma_async.sync.aligned.m64n256k16.f32.bf16.bf16 {%0,%1,%2,%3,%4,%5,%6,%7,%8,%9,%10,%11,%12,%13,%14,%15,%16,%17,%18,%19,%20,%21,%22,%23,%24,%25,%26,%27,%28,%29,%30,%31,%32,%33,%34,%35,%36,%37,%38,%39,%40,%41,%42,%43,%44,%45,%46,%47,%48,%49,%50,%51,%52,%53,%54,%55,%56,%57,%58,%59,%60,%61,%62,%63,%64,%65,%66,%67,%68,%69,%70,%71,%72,%73,%74,%75,%76,%77,%78,%79,%80,%81,%82,%83,%84,%85,%86,%87,%88,%89,%90,%91,%92,%93,%94,%95,%96,%97,%98,%99,%100,%101,%102,%103,%104,%105,%106,%107,%108,%109,%110,%111,%112,%113,%114,%115,%116,%117,%118,%119,%120,%121,%122,%123,%124,%125,%126,%127}, {%128,%129,%130,%131}, b, p, 1, 1, 1;\n}\n"
    : "=f"(d[0]),"=f"(d[1]),"=f"(d[2]),"=f"(d[3]),"=f"(d[4]),"=f"(d[5]),"=f"(d[6]),"=f"(d[7]),"=f"(d[8]),"=f"(d[9]),"=f"(d[10]),"=f"(d[11]),"=f"(d[12]),"=f"(d[13]),"=f"(d[14]),"=f"(d[15]),"=f"(d[16]),"=f"(d[17]),"=f"(d[18]),"=f"(d[19]),"=f"(d[20]),"=f"(d[21]),"=f"(d[22]),"=f"(d[23]),"=f"(d[24]),"=f"(d[25]),"=f"(d[26]),"=f"(d[27]),"=f"(d[28]),"=f"(d[29]),"=f"(d[30]),"=f"(d[31]),"=f"(d[32]),"=f"(d[33]),"=f"(d[34]),"=f"(d[35]),"=f"(d[36]),"=f"(d[37]),"=f"(d[38]),"=f"(d[39]),"=f"(d[40]),"=f"(d[41]),"=f"(d[42]),"=f"(d[43]),"=f"(d[44]),"=f"(d[45]),"=f"(d[46]),"=f"(d[47]),"=f"(d[48]),"=f"(d[49]),"=f"(d[50]),"=f"(d[51]),"=f"(d[52]),"=f"(d[53]),"=f"(d[54]),"=f"(d[55]),"=f"(d[56]),"=f"(d[57]),"=f"(d[58]),"=f"(d[59]),"=f"(d[60]),"=f"(d[61]),"=f"(d[62]),"=f"(d[63]),"=f"(d[64]),"=f"(d[65]),"=f"(d[66]),"=f"(d[67]),"=f"(d[68]),"=f"(d[69]),"=f"(d[70]),"=f"(d[71]),"=f"(d[72]),"=f"(d[73]),"=f"(d[74]),"=f"(d[75]),"=f"(d[76]),"=f"(d[77]),"=f"(d[78]),"=f"(d[79]),"=f"(d[80]),"=f"(d[81]),"=f"(d[82]),"=f"(d[83]),"=f"(d[84]),"=f"(d[85]),"=f"(d[86]),"=f"(d[87]),"=f"(d[88]),"=f"(d[89]),"=f"(d[90]),"=f"(d[91]),"=f"(d[92]),"=f"(d[93]),"=f"(d[94]),"=f"(d[95]),"=f"(d[96]),"=f"(d[97]),"=f"(d[98]),"=f"(d[99]),"=f"(d[100]),"=f"(d[101]),"=f"(d[102]),"=f"(d[103]),"=f"(d[104]),"=f"(d[105]),"=f"(d[106]),"=f"(d[107]),"=f"(d[108]),"=f"(d[109]),"=f"(d[110]),"=f"(d[111]),"=f"(d[112]),"=f"(d[113]),"=f"(d[114]),"=f"(d[115]),"=f"(d[116]),"=f"(d[117]),"=f"(d[118]),"=f"(d[119]),"=f"(d[120]),"=f"(d[121]),"=f"(d[122]),"=f"(d[123]),"=f"(d[124]),"=f"(d[125]),"=f"(d[126]),"=f"(d[127]) : "r"(a.x), "r"(a.y), "r"(a.z), "r"(a.w), "r"(db.lo), "r"(db.hi));
}
template<int N> __device__ __forceinline__ void wgmma_ra(float (&d)[N / 2], const uint4& a, Desc db, bool acc) {
  if (acc) wgmma_rs<N, 1>(d, a, db); else wgmma_rs<N, 0>(d, a, db);
}

__device__ __forceinline__ uint32_t smem_u32(const void* p) { return (uint32_t)__cvta_generic_to_shared(p); }
__device__ __forceinline__ void mbar_init(uint32_t bar, uint32_t cnt) { asm volatile("mbarrier.init.shared::cta.b64 [%0], %1;" ::"r"(bar), "r"(cnt)); }
__device__ __forceinline__ void mbar_expect_tx(uint32_t bar, uint32_t bytes) { asm volatile("mbarrier.arrive.expect_tx.shared::cta.b64 _, [%0], %1;" ::"r"(bar), "r"(bytes) : "memory"); }
__device__ __forceinline__ void mbar_arrive(uint32_t bar) { asm volatile("mbarrier.arrive.shared::cta.b64 _, [%0];" ::"r"(bar) : "memory"); }
__device__ __forceinline__ void mbar_arrive_remote(uint32_t rbar) { asm volatile("mbarrier.arrive.shared::cluster.b64 _, [%0];" ::"r"(rbar) : "memory"); }
__device__ __forceinline__ void mbar_wait(uint32_t bar, uint32_t parity) {
  asm volatile(
      "{\n.reg .pred p;\n.reg .u32 c;\nmov.u32 c, 0;\nLAB_WAIT:\nmbarrier.try_wait.parity.shared::cta.b64 p, [%0], %1;\n@p bra DONE;\n"
      "add.u32 c, c, 1;\nsetp.lt.u32 p, c, 1000000;\n@p bra LAB_WAIT;\ntrap;\nDONE:\n}\n" ::"r"(bar), "r"(parity) : "memory");
}
__device__ __forceinline__ void mbar_wait_c(uint32_t bar, uint32_t parity) {
  asm volatile("{\n.reg .pred p;\nLAB_WAIT:\nmbarrier.try_wait.parity.shared::cta.b64 p, [%0], %1;\n@!p bra LAB_WAIT;\n}\n" ::"r"(bar), "r"(parity) : "memory");
}
__device__ __forceinline__ uint32_t late(uint32_t bar, uint32_t v) {
  uint32_t r;
  asm volatile("{\n.reg .pred p;\nmbarrier.test_wait.parity.shared::cta.b64 p, [%1], 0;\nselp.b32 %0, %2, %1, p;\n}\n" : "=r"(r) : "r"(bar), "r"(v) : "memory");
  return r;
}
__device__ __forceinline__ void wtma2d(uint32_t dst, const CUtensorMap* m, int c0, int c1, uint32_t bar, uint64_t pol) {
  asm volatile("cp.async.bulk.tensor.2d.shared::cluster.global.mbarrier::complete_tx::bytes.multicast::cluster.L2::cache_hint [%0], [%1, {%3, %4}], [%2], %5, %6;"
               ::"r"(dst), "l"(m), "r"(bar), "r"(c0), "r"(c1), "h"((uint16_t)3), "l"(pol) : "memory");
}
__device__ __forceinline__ void wtma3d(uint32_t dst, const CUtensorMap* m, int c0, int c1, int c2, uint32_t bar, uint64_t pol) {
  asm volatile("cp.async.bulk.tensor.3d.shared::cluster.global.mbarrier::complete_tx::bytes.multicast::cluster.L2::cache_hint [%0], [%1, {%3, %4, %5}], [%2], %6, %7;"
               ::"r"(dst), "l"(m), "r"(bar), "r"(c0), "r"(c1), "r"(c2), "h"((uint16_t)3), "l"(pol) : "memory");
}
__device__ __forceinline__ void wbulk(uint32_t dst, const void* src, uint32_t bytes, uint32_t bar, uint64_t pol) {
  asm volatile("cp.async.bulk.shared::cluster.global.mbarrier::complete_tx::bytes.multicast::cluster.L2::cache_hint [%0], [%1], %2, [%3], %4, %5;"
               ::"r"(dst), "l"(src), "r"(bytes), "r"(bar), "h"((uint16_t)3), "l"(pol) : "memory");
}
__device__ __forceinline__ void tma3d(uint32_t dst, const CUtensorMap* m, int c0, int c1, int c2, uint32_t bar) {
  asm volatile("cp.async.bulk.tensor.3d.shared::cluster.global.mbarrier::complete_tx::bytes [%0], [%1, {%3, %4, %5}], [%2];"
               ::"r"(dst), "l"(m), "r"(bar), "r"(c0), "r"(c1), "r"(c2) : "memory");
}
__device__ __forceinline__ void tma_store3d(const CUtensorMap* m, uint32_t src, int c0, int c1, int c2) {
  asm volatile("cp.async.bulk.tensor.3d.global.shared::cta.bulk_group [%0, {%2, %3, %4}], [%1];" ::"l"(m), "r"(src), "r"(c0), "r"(c1), "r"(c2) : "memory");
}
__device__ __forceinline__ void prefetch_l2(const void* p, uint32_t bytes) { asm volatile("cp.async.bulk.prefetch.L2.global [%0], %1;" ::"l"(p), "r"(bytes) : "memory"); }
__device__ __forceinline__ uint64_t policy_evict_first() { uint64_t p; asm volatile("createpolicy.fractional.L2::evict_first.b64 %0, 1.0;" : "=l"(p)); return p; }
__device__ __forceinline__ uint64_t policy_evict_normal() { uint64_t p; asm volatile("createpolicy.fractional.L2::evict_normal.b64 %0, 1.0;" : "=l"(p)); return p; }
__device__ __forceinline__ void bulk_commit() { asm volatile("cp.async.bulk.commit_group;" ::: "memory"); }
__device__ __forceinline__ void bulk_wait_all() { asm volatile("cp.async.bulk.wait_group 0;" ::: "memory"); }
__device__ __forceinline__ void fence_async_smem() { asm volatile("fence.proxy.async.shared::cta;" ::: "memory"); }
__device__ __forceinline__ bool elect_one() {
  uint32_t p;
  asm volatile("{\n.reg .pred P;\nelect.sync _|P, 0xffffffff;\nselp.u32 %0, 1, 0, P;\n}\n" : "=r"(p));
  return p;
}
__device__ __forceinline__ void wg_fence() { asm volatile("wgmma.fence.sync.aligned;" ::: "memory"); }
__device__ __forceinline__ void wg_commit() { asm volatile("wgmma.commit_group.sync.aligned;" ::: "memory"); }
template <int n> __device__ __forceinline__ void wg_wait() { asm volatile("wgmma.wait_group.sync.aligned %0;" ::"n"(n) : "memory"); }
__device__ __forceinline__ void wg_bar(int w) { asm volatile("bar.sync %0, 128;" ::"r"(w + 1) : "memory"); }
__device__ __forceinline__ void cluster_sync() { asm volatile("barrier.cluster.arrive.relaxed.aligned;\nbarrier.cluster.wait.aligned;" ::: "memory"); }
__device__ __forceinline__ void fence_gpu() { asm volatile("fence.acq_rel.gpu;" ::: "memory"); }
__device__ __forceinline__ uint32_t ld_relaxed(const uint32_t* p) { uint32_t v; asm volatile("ld.relaxed.gpu.global.u32 %0, [%1];" : "=r"(v) : "l"(p) : "memory"); return v; }
__device__ __forceinline__ uint32_t ld_acquire(const uint32_t* p) { uint32_t v; asm volatile("ld.acquire.gpu.global.u32 %0, [%1];" : "=r"(v) : "l"(p) : "memory"); return v; }
__device__ __forceinline__ uint4 ld_relaxed4(const uint4* p) {
  uint4 v; asm volatile("ld.relaxed.gpu.global.v4.u32 {%0,%1,%2,%3}, [%4];" : "=r"(v.x), "=r"(v.y), "=r"(v.z), "=r"(v.w) : "l"(p) : "memory"); return v;
}
__device__ __forceinline__ uint2 ld_relaxed2(const uint2* p) {
  uint2 v; asm volatile("ld.relaxed.gpu.global.v2.u32 {%0,%1}, [%2];" : "=r"(v.x), "=r"(v.y) : "l"(p) : "memory"); return v;
}
__device__ __forceinline__ void st_relaxed(uint32_t* p, uint32_t a) { asm volatile("st.relaxed.gpu.global.u32 [%0], %1;" ::"l"(p), "r"(a) : "memory"); }
__device__ __forceinline__ void st_relaxed4(uint4* p, uint32_t a, uint32_t b, uint32_t c, uint32_t d) {
  asm volatile("st.relaxed.gpu.global.v4.u32 [%0], {%1,%2,%3,%4};" ::"l"(p), "r"(a), "r"(b), "r"(c), "r"(d) : "memory");
}
__device__ __forceinline__ void st_relaxed2(uint2* p, uint32_t a, uint32_t b) {
  asm volatile("st.relaxed.gpu.global.v2.u32 [%0], {%1,%2};" ::"l"(p), "r"(a), "r"(b) : "memory");
}
__device__ __forceinline__ void red4(uint4* p, uint32_t a, uint32_t b, uint32_t c, uint32_t d) {
  asm volatile("red.relaxed.gpu.global.add.noftz.v4.bf16x2 [%0], {%1,%2,%3,%4};" ::"l"(p), "r"(a), "r"(b), "r"(c), "r"(d) : "memory");
}
__device__ __forceinline__ void red2(uint2* p, uint32_t a, uint32_t b) {
  asm volatile("red.relaxed.gpu.global.add.noftz.v2.bf16x2 [%0], {%1,%2};" ::"l"(p), "r"(a), "r"(b) : "memory");
}
constexpr int SPIN_MAX = 1 << 21;
__device__ __forceinline__ uint32_t pack_bf16(float lo, float hi) { uint32_t r; asm("cvt.rn.bf16x2.f32 %0, %1, %2;" : "=r"(r) : "f"(hi), "f"(lo)); return r; }
__device__ __forceinline__ float bf_lo(uint32_t v) { return __uint_as_float(v << 16); }
__device__ __forceinline__ float bf_hi(uint32_t v) { return __uint_as_float(v & 0xffff0000u); }
__device__ __forceinline__ float2 lds64(uint32_t a) { float2 v; asm volatile("ld.shared.v2.f32 {%0,%1}, [%2];" : "=f"(v.x), "=f"(v.y) : "r"(a)); return v; }
__device__ __forceinline__ uint32_t lds32(uint32_t a) { uint32_t v; asm volatile("ld.shared.b32 %0, [%1];" : "=r"(v) : "r"(a)); return v; }
__device__ __forceinline__ void sts64f(uint32_t a, float x, float y) { asm volatile("st.shared.v2.f32 [%0], {%1,%2};" ::"r"(a), "f"(x), "f"(y) : "memory"); }
__device__ __forceinline__ void sts32(uint32_t a, uint32_t x) { asm volatile("st.volatile.shared.b32 [%0], %1;" ::"r"(a), "r"(x) : "memory"); }
__device__ __forceinline__ void gate(uint32_t a, int need) {
#pragma unroll 1
  for (int it = 0; it < SPIN_MAX; it++) {
    int v; asm volatile("ld.volatile.shared.b32 %0, [%1];" : "=r"(v) : "r"(a) : "memory");
    if (v >= need) break;
    if (GSLEEP) __nanosleep(GSLEEP);
  }
}
__device__ __forceinline__ void sts128(uint32_t a, uint32_t x, uint32_t y, uint32_t z, uint32_t u) { asm volatile("st.shared.v4.b32 [%0], {%1,%2,%3,%4};" ::"r"(a), "r"(x), "r"(y), "r"(z), "r"(u) : "memory"); }
__device__ __forceinline__ uint4 lds128(uint32_t a) { uint4 v; asm volatile("ld.shared.v4.u32 {%0,%1,%2,%3}, [%4];" : "=r"(v.x), "=r"(v.y), "=r"(v.z), "=r"(v.w) : "r"(a) : "memory"); return v; }
__device__ __forceinline__ uint32_t hmul2(uint32_t a, uint32_t b) { uint32_t r; asm("mul.rn.bf16x2 %0, %1, %2;" : "=r"(r) : "r"(a), "r"(b)); return r; }
__device__ __forceinline__ uint32_t hadd2(uint32_t a, uint32_t b) { uint32_t r; asm("add.rn.bf16x2 %0, %1, %2;" : "=r"(r) : "r"(a), "r"(b)); return r; }
__device__ __forceinline__ void stsm4(uint32_t a, uint32_t r0, uint32_t r1, uint32_t r2, uint32_t r3) {
  asm volatile("stmatrix.sync.aligned.m8n8.x4.shared.b16 [%0], {%1,%2,%3,%4};" ::"r"(a), "r"(r0), "r"(r1), "r"(r2), "r"(r3) : "memory");
}
__device__ __forceinline__ void stsm2(uint32_t a, uint32_t r0, uint32_t r1) {
  asm volatile("stmatrix.sync.aligned.m8n8.x2.shared.b16 [%0], {%1,%2};" ::"r"(a), "r"(r0), "r"(r1) : "memory");
}
__device__ __forceinline__ uint4 ldsm4(uint32_t a) {
  uint4 r; asm volatile("ldmatrix.sync.aligned.m8n8.x4.shared.b16 {%0,%1,%2,%3}, [%4];" : "=r"(r.x), "=r"(r.y), "=r"(r.z), "=r"(r.w) : "r"(a) : "memory"); return r;
}
__device__ __forceinline__ uint32_t movm(uint32_t a) { uint32_t r; asm("movmatrix.sync.aligned.m8n8.trans.b16 %0, %1;" : "=r"(r) : "r"(a)); return r; }
__device__ __forceinline__ void mma16816z(float (&d)[4], uint32_t a0, uint32_t a1, uint32_t a2, uint32_t a3, uint32_t b0, uint32_t b1) {
  asm("mma.sync.aligned.m16n8k16.row.col.f32.bf16.bf16.f32 {%0,%1,%2,%3}, {%4,%5,%6,%7}, {%8,%9}, {%10,%10,%10,%10};"
      : "=f"(d[0]), "=f"(d[1]), "=f"(d[2]), "=f"(d[3]) : "r"(a0), "r"(a1), "r"(a2), "r"(a3), "r"(b0), "r"(b1), "f"(0.f));
}
__device__ __forceinline__ void mma16816(float (&d)[4], const uint4& a, uint32_t b0, uint32_t b1) {
  asm("mma.sync.aligned.m16n8k16.row.col.f32.bf16.bf16.f32 {%0,%1,%2,%3}, {%4,%5,%6,%7}, {%8,%9}, {%0,%1,%2,%3};"
      : "+f"(d[0]), "+f"(d[1]), "+f"(d[2]), "+f"(d[3]) : "r"(a.x), "r"(a.y), "r"(a.z), "r"(a.w), "r"(b0), "r"(b1));
}
__device__ __forceinline__ void mma1688(float (&d)[4], uint32_t a0, uint32_t a1, uint32_t b0) {
  asm("mma.sync.aligned.m16n8k8.row.col.f32.bf16.bf16.f32 {%0,%1,%2,%3}, {%4,%5}, {%6}, {%0,%1,%2,%3};"
      : "+f"(d[0]), "+f"(d[1]), "+f"(d[2]), "+f"(d[3]) : "r"(a0), "r"(a1), "r"(b0));
}
__device__ __forceinline__ float quad_sum(float v) { v += __shfl_xor_sync(0xffffffffu, v, 1); v += __shfl_xor_sync(0xffffffffu, v, 2); return v; }
__device__ __forceinline__ float quad_max(float v) { v = fmaxf(v, __shfl_xor_sync(0xffffffffu, v, 1)); v = fmaxf(v, __shfl_xor_sync(0xffffffffu, v, 2)); return v; }
__device__ __forceinline__ float rcp(float x) { float r; asm("rcp.approx.ftz.f32 %0, %1;" : "=f"(r) : "f"(x)); return r; }
__device__ __forceinline__ float rsq(float x) { float r; asm("rsqrt.approx.ftz.f32 %0, %1;" : "=f"(r) : "f"(x)); return r; }
__device__ __forceinline__ float ex2(float x) { float r; asm("ex2.approx.ftz.f32 %0, %1;" : "=f"(r) : "f"(x)); return r; }
__device__ __forceinline__ uint32_t chk(uint32_t acc, uint32_t v, uint32_t tag) { uint32_t r; asm("lop3.b32 %0, %1, %2, %3, 0xF6;" : "=r"(r) : "r"(acc), "r"(v), "r"(tag)); return r; }
__device__ __forceinline__ uint32_t chk2(uint32_t a, uint32_t b, uint32_t tag) { uint32_t r; asm("lop3.b32 %0, %1, %2, %3, 0x7E;" : "=r"(r) : "r"(a), "r"(b), "r"(tag)); return r; }
__device__ __forceinline__ uint32_t tagged(uint32_t v, uint32_t tag) { return (v & ~1u) | tag; }

__device__ __forceinline__ int group_k0(int g, int j) {
  const int h = g >= 9, r = g - 2 - 7 * h;
  return g < 2 ? 64 * j + 32 * g : g < 16 ? 64 * (r + (r >= j)) + 32 * h : 32 * g;
}
__device__ __forceinline__ uint32_t xin_off(int c, int w) { return SM_X + (2 * c + w + (2 * c + w < 9 ? 9 : -9)) * 8192; }
__device__ __forceinline__ uint32_t xin_bar(int c) { return BAR_FULLX + 8 * (c < 8 ? c ^ 4 : c); }
__device__ __forceinline__ constexpr uint32_t qkv_xslot(int g) { return g < 5 || g > 11 ? 2 : (0x5140762u >> (4 * (g - 5))) & 15; }

template <int N> struct IC { static constexpr int v = N; };

struct Cons {
  uint32_t sb;
  uint32_t rem;
  uint32_t sB, mB;
  uint32_t mX;
  bool elect;
  __device__ __forceinline__ void release2(uint32_t bar) const { if (elect) { mbar_arrive(sb + bar); mbar_arrive_remote(rem + bar); } }
  __device__ __forceinline__ uint32_t nextB(uint32_t& prev) {
    mbar_wait_c(sb + BAR_FULLB + sB, mB);
    const uint32_t a = (((sb & 0x3FFFF) + SM_B) >> 4) + sB * (BSLOT / 128);
    prev = sB == 0 ? 32 : sB - 8;
    sB += 8;
    if (sB == 40) { sB = 0; mB ^= 1; }
    return a;
  }
  __device__ __forceinline__ void progress(uint32_t v) const { if (elect) sts32(sb + SM_PROG + (threadIdx.x >> 5), v); }
  __device__ __forceinline__ void releaseLastB() const { release2(BAR_EMPTYB + (sB == 0 ? 32 : sB - 8)); }
};

__device__ __forceinline__ float2 gather_sums(const uint2* a, uint32_t stag) {
  uint2 sa, sc;
  do { sa = ld_relaxed2(a); sc = ld_relaxed2(a + 8); } while (__any_sync(0xffffffffu, chk2(sa.x, sc.x, stag) & 3));
  return make_float2(quad_sum(__uint_as_float(sa.x) + __uint_as_float(sc.x)), quad_sum(__uint_as_float(sa.y) + __uint_as_float(sc.y)));
}

struct Norm {
  float m0, m1;
  uint32_t nm0, nm1;
  float d0, d1;
  uint2 u0, u1;
  __device__ __forceinline__ Norm(float2 sum) : m0(sum.x * (-1.f / 576)), m1(sum.y * (-1.f / 576)), nm0(pack_bf16(m0, m0)), nm1(pack_bf16(m1, m1)), d0(0.f), d1(0.f) {}
  __device__ __forceinline__ uint4 centre(const uint4& a) const { return make_uint4(hadd2(a.x, nm0), hadd2(a.y, nm1), hadd2(a.z, nm0), hadd2(a.w, nm1)); }
  __device__ __forceinline__ void sqr(uint32_t a, uint32_t b) {
    d0 = fmaf(bf_lo(a), bf_lo(a), fmaf(bf_hi(a), bf_hi(a), d0)); d1 = fmaf(bf_lo(b), bf_lo(b), fmaf(bf_hi(b), bf_hi(b), d1));
  }
  __device__ __forceinline__ void send(uint2* a, int t, uint32_t stag) {
    d0 = quad_sum(d0); d1 = quad_sum(d1);
    if ((t & 3) == 0) st_relaxed2(a, (__float_as_uint(d0) & ~3u) | stag, __float_as_uint(d1));
  }
  __device__ __forceinline__ void fetch(const uint2* a) { u0 = ld_relaxed2(a); u1 = ld_relaxed2(a + 8); }
  __device__ __forceinline__ float2 rstd(const uint2* a, uint32_t stag) {
    while (__any_sync(0xffffffffu, chk2(u0.x, u1.x, stag) & 3)) fetch(a);
    const float e0 = bf_lo(nm0) - m0, e1 = bf_lo(nm1) - m1;
    const float v0 = fmaf(quad_sum(__uint_as_float(u0.x) + __uint_as_float(u1.x)), 1.f / 576, -e0 * e0);
    const float v1 = fmaf(quad_sum(__uint_as_float(u0.y) + __uint_as_float(u1.y)), 1.f / 576, -e1 * e1);
    float2 r = make_float2(rsq(fmaxf(v0, 0.f) + 1e-5f), rsq(fmaxf(v1, 0.f) + 1e-5f));
    asm volatile("" : "+f"(r.x), "+f"(r.y));
    return r;
  }
};

template <class Pre, class Mma>
__device__ __forceinline__ float2 ln_gemm_in(Cons& c, Group* G, uint32_t (&p)[18], float2& sum, int w, int st0, int j, int t, Pre&& pre, Mma&& mma) {
  const uint32_t xa = c.sb + (t >> 5) * 2048 + (t & 15) * 128, sw = (((t >> 4) & 1) ^ (t & 7)) * 16;
  float ra[4] = {0.f, 0.f, 0.f, 0.f}, rb[4] = {0.f, 0.f, 0.f, 0.f};
#pragma unroll 1
  for (int cc = 0; cc < 9; cc++) {
    const uint32_t a = xa + xin_off(cc, w);
    mbar_wait_c(c.sb + xin_bar(cc), 0);
    const uint4 u0 = ldsm4(a + sw), u1 = ldsm4(a + (sw ^ 32)), u2 = ldsm4(a + (sw ^ 64)), u3 = ldsm4(a + (sw ^ 96));
    mma16816(ra, u0, 0x3f803f80u, 0x3f803f80u); mma16816(rb, u1, 0x3f803f80u, 0x3f803f80u);
    mma16816(ra, u2, 0x3f803f80u, 0x3f803f80u); mma16816(rb, u3, 0x3f803f80u, 0x3f803f80u);
  }
  sum = make_float2(ra[0] + rb[0], ra[2] + rb[2]);
  pre(0);
  Norm n(sum);
  n.u0 = n.u1 = make_uint2(0, 0);
  auto stats = [&] {
#pragma unroll
    for (int k = 0; k < 5; k++) {
      const uint4 u = ldsm4(xa + (k < 4 ? xin_off(j, w) + (sw ^ (32 * k)) : xin_off(8, w) + ((j ^ (t & 7)) << 4))), e = n.centre(u);
      p[4 * k] = u.x; p[4 * k + 1] = u.y;
      n.sqr(e.x, e.y);
      if (k < 4) { p[4 * k + 2] = u.z; p[4 * k + 3] = u.w; n.sqr(e.z, e.w); }
    }
    n.send(G->sq + st0 + 8 * j, t, 1);
  };
  if (STATP < 0) stats();
  else {
#pragma unroll
    for (int i = 0; i < 18; i++) p[i] = 0;
  }
  pre(1);
  uint4 y0 = ldsm4(xa + xin_off(0, w) + sw), y1 = ldsm4(xa + xin_off(0, w) + (sw ^ 32));
#pragma unroll 1
  for (int cc = 0; cc < 9; cc++) {
#pragma unroll
    for (int i = 0; i < 2; i++) {
      const uint4 f0 = n.centre(y0), f1 = n.centre(y1);
      const uint32_t a = xa + xin_off(min(cc + i, 8), w);
      y0 = ldsm4(a + (sw ^ (64 - 64 * i))); y1 = ldsm4(a + (sw ^ (96 - 64 * i)));
      uint32_t prev;
      const uint32_t bb = c.nextB(prev);
      mma(true, bb, f0, f1);
      if (i == 1) {
        if (STATP >= 0 && cc == STATP * w) stats();
        if (cc == 1) c.progress(3);
        if (cc == 7) n.fetch(G->sq + st0 + 16 * (t & 3));
        if (cc == 8 && w == 0) asm volatile("bar.arrive 6, 256;" ::: "memory");
      }
      wg_wait<1>();
      if (i + cc > 0) c.release2(BAR_EMPTYB + prev);
      if (2 * cc + i >= WOG && 2 * cc + i < WOG + 4) c.release2(BAR_EMPTYX + 32 + 8 * (2 * cc + i - WOG));
    }
  }
  c.mX = 0xff;
  const float2 r = n.rstd(G->sq + st0 + 16 * (t & 3), 1);
  if (w == 1) asm volatile("bar.sync 6, 256;" ::: "memory");
  wg_wait<0>();
  c.releaseLastB();
  c.release2(BAR_EMPTYX + 24);
  return r;
}

template <bool QKV, class Pre, class Mma>
__device__ __forceinline__ float2 ln_gemm(Cons& c, Group* G, const float (&v)[36], uint32_t (&p)[18], float2& sum, int st0, int j, int t,
                                          int layer, uint32_t tag, Pre&& pre, Mma&& mma) {
  constexpr bool known = !QKV && EARLY;
  const uint32_t stag = (2 * layer + (QKV ? 1 : 2)) & 3;
  uint4 x[6][2];
  uint4* src = G->xbox + t;
  asm volatile("" : "+l"(src));
  auto buf = [&](int g) -> uint4 (&)[2] { return x[g < 16 ? (g - 2) % 6 : g - 13]; };
  auto load = [&](int g0) {
#pragma unroll
    for (int g = g0; g < g0 + (g0 < 14 ? 3 : 2); g++) {
      const uint4* a = g < 16 ? src + ((g - 2) % 7 >= j ? 256 : 0) + (2 * ((g - 2) % 7) + 16 * (g >= 9)) * 128 : src + 2 * g * 128;
      buf(g)[0] = ld_relaxed4(a); buf(g)[1] = ld_relaxed4(a + 128);
    }
  };
  auto invalid = [&](int g, uint32_t tag) {
    uint32_t bad = chk(chk(chk2(buf(g)[0].x, buf(g)[1].x, tag), buf(g + 1)[0].x, tag), buf(g + 1)[1].x, tag);
    if (g < 14) bad = chk(chk(bad, buf(g + 2)[0].x, tag), buf(g + 2)[1].x, tag);
    if (g == 16) bad = chk(chk(chk(chk(bad, buf(g)[0].z, tag), buf(g)[1].z, tag), buf(g + 1)[0].z, tag), buf(g + 1)[1].z, tag);
    return __any_sync(0xffffffffu, bad & 1);
  };
  uint4* const d = src + 2 * j * 128;
  const int sq = st0 + 16 * (t & 3);
  if (!known) {
    float s0 = v[0] + v[1], s1 = v[2] + v[3];
#pragma unroll
    for (int i = 1; i < 9; i++) { s0 += v[4 * i] + v[4 * i + 1]; s1 += v[4 * i + 2] + v[4 * i + 3]; }
    s0 = quad_sum(s0); s1 = quad_sum(s1);
    if ((t & 3) == 0) st_relaxed2(G->sum + st0 + 8 * j, (__float_as_uint(s0) & ~3u) | stag, __float_as_uint(s1));
  }
#pragma unroll
  for (int i = 0; i < 18; i++) p[i] = pack_bf16(v[2 * i], v[2 * i + 1]);
#pragma unroll
  for (int i = 0; i < 2; i++) st_relaxed4(d + i * 128, tagged(p[4 * i], tag), p[4 * i + 1], p[4 * i + 2], p[4 * i + 3]);
  pre(0);
  if (!known) {
    sum = gather_sums(G->sum + sq, stag);
    load(2);
  }
  Norm n(sum);
  pre(1);
  const uint32_t* probe = &(G->xbox + (2 * (t & 7) + 1) * 128 + (t | 31))->x;
  uint32_t pv;
  auto inx = [](int g) { return QKV && ((g >= 5 && g < 12) || g == 17); };
  auto use = [](int g) { return QKV ? (g < 5 ? 108 : 101) + g : 18 + g; };
#pragma unroll
  for (int g = 0; g < 18; g++) {
    if (g < 16 ? g % 3 == 2 : g == 16) {
      const uint32_t lt = late(c.sb + BAR_FULLX + 64, tag);
      while (invalid(g, lt)) load(g);
      if (g < 16) load(g < 14 ? g + 3 : 16);
    }
    const uint4 f0 = n.centre(g < 2 ? make_uint4(p[8 * g], p[8 * g + 1], p[8 * g + 2], p[8 * g + 3]) : buf(g)[0]);
    const uint4 f1 = n.centre(g < 2 ? make_uint4(p[8 * g + 4], p[8 * g + 5], p[8 * g + 6], p[8 * g + 7]) : buf(g)[1]);
    if (g == 14) n.fetch(G->sq + sq);
    if (inx(g)) mbar_wait_c(c.sb + BAR_FULLX + 8 * qkv_xslot(g), ((0x34 >> qkv_xslot(g)) & 1) ^ (g == 17));
    else mbar_wait_c(c.sb + BAR_FULLB + 8 * (use(g) % 5), (use(g) / 5) & 1);
    mma(g, ((c.sb & 0x3FFFF) >> 4) + ((inx(g) ? SM_X + qkv_xslot(g) * XSLOT : SM_B + (use(g) % 5) * BSLOT) >> 4), f0, f1);
    if (g < 2) {
      if (known) {
        if (g == 0) {
          pv = ld_relaxed(probe);
        } else {
          const uint32_t lt = late(c.sb + BAR_FULLX + 64, tag);
          while (__any_sync(0xffffffffu, (pv ^ lt) & 1)) pv = ld_relaxed(probe);
          load(2);
        }
      }
      if (g == (known ? 1 : 0)) {
#pragma unroll
        for (int i = 2; i < 4; i++) st_relaxed4(d + (14 + i) * 128, tagged(p[4 * i], tag), p[4 * i + 1], p[4 * i + 2], p[4 * i + 3]);
        st_relaxed2((uint2*)(src + (32 + (j >> 1)) * 128) + (j & 1), tagged(p[16], tag), p[17]);
      }
      n.sqr(f0.x, f0.y); n.sqr(f0.z, f0.w); n.sqr(f1.x, f1.y); n.sqr(f1.z, f1.w);
      if (g == 1) {
        n.sqr(hadd2(p[16], n.nm0), hadd2(p[17], n.nm1));
        n.send(G->sq + st0 + 8 * j, t, stag);
      }
    }
    wg_wait<1>();
    if (g > 0 && !inx(g - 1)) c.release2(BAR_EMPTYB + 8 * (use(g - 1) % 5));
    if (QKV && g < 13) c.progress(33 + g);
    if (QKV && g == WOG - 1) c.release2(BAR_EMPTYX + 8 * qkv_xslot(17));
    if (QKV && g >= WOG && g < WOG + 4) c.release2(BAR_EMPTYX + 32 + 8 * (g - WOG));
  }
  if (QKV) c.mX = 0x34 ^ 0xf3;
  else { c.sB = 8 * (36 % 5); c.mB = (36 / 5) & 1; }
  const float2 r = n.rstd(G->sq + sq, late(c.sb + BAR_FULLX + 64, stag));
  wg_wait<0>();
  if (!QKV) c.release2(BAR_EMPTYB + 8 * (use(17) % 5));
  return r;
}

template <int NB, int OFF>
__device__ __forceinline__ void glu(const float (&a)[128], uint32_t (&h)[144]) {
#pragma unroll
  for (int b = 0; b < 2 * NB; b++) {
    if (HMUL) h[OFF + b] = hmul2(pack_bf16(a[2 * b], a[2 * b + 1]), pack_bf16(a[4 * NB + 2 * b], a[4 * NB + 2 * b + 1]));
    else h[OFF + b] = pack_bf16(a[2 * b] * a[4 * NB + 2 * b], a[2 * b + 1] * a[4 * NB + 2 * b + 1]);
  }
}

__global__ void __cluster_dims__(2, 1, 1) __launch_bounds__(384, 1)
fused_kernel(const __nv_bfloat16* __restrict__ x_in, Group* ws, const char* __restrict__ wqkv,
             const char* __restrict__ wg, const char* __restrict__ wu, const char* __restrict__ wd, const __grid_constant__ Maps maps,
             const char* __restrict__ wo) {
  extern __shared__ __align__(1024) uint8_t smem_raw[];
  const uint32_t sb = smem_u32(smem_raw);
  if (blockIdx.x >= NCTA) {
    const uint32_t par = ~ld_relaxed(ws->flag + 32) & 1;
#pragma unroll 1
    for (int i = 0; i < RDELAY; i++) __nanosleep(1000);
    const int cc = threadIdx.x % 54, r0 = threadIdx.x / 54, part = cc / 18, jj = 2 * (blockIdx.x - NCTA) + (cc % 18) / 9, c9 = cc % 9;
    if (r0 < 6) {
#pragma unroll 4
      for (int k = r0; k < 576; k += 6) {
        const uint4 u = __ldg((const uint4*)(wqkv + k * 3456 + part * 1152 + 144 * jj) + c9);
        ((Scratch*)ws)->wq[jj][k >> 4][c9 < 8 ? part * 128 + (k & 15) * 8 + (c9 ^ (k & 7)) : 384 + part * 16 + (k & 15)] = u;
      }
    }
    fence_gpu();
    __syncthreads();
    if (threadIdx.x < 2) st_relaxed(ws[2 * (blockIdx.x - NCTA) + threadIdx.x].wsum + 128, par);
    return;
  }
  if (threadIdx.x == 0) asm volatile("prefetch.tensormap [%0];" ::"l"(&maps.x) : "memory");
  const int warp = __shfl_sync(0xffffffffu, threadIdx.x >> 5, 0);
  const int lane = threadIdx.x & 31;
  const int rank = blockIdx.x & 1;
  if (elect_one()) {
    if (warp >= 8) {
#pragma unroll
      for (int i = 0; i < 9; i++) mbar_init(sb + SM_BAR + 72 * (warp - 8) + 8 * i, warp < 10 ? 1 : 4);
      sts32(sb + SM_PROG + 4 * (warp - 8), 0);
      asm volatile("fence.mbarrier_init.release.cluster;" ::: "memory");
    } else if (warp == 1 || warp == 2) {
      asm volatile("prefetch.tensormap [%0];" ::"l"(&maps.x + warp) : "memory");
    } else if (warp == 3) {
      if (PFMODE & 1) prefetch_l2((const char*)x_in + blockIdx.x * 18432, 18432);
    } else if (warp == 4) {
      if (PFMODE & 2) prefetch_l2(wqkv + blockIdx.x * (15552 / PFQ), 15552 / PFQ);
    }
  }
  __syncwarp();
  asm volatile("barrier.cluster.arrive.relaxed.aligned;" ::: "memory");
  if (warp == 8) PROFX(53);
  int lb = blockIdx.x;
  if (GPCMAP) {
    const int cl = blockIdx.x >> 1, u = cl - 36;
    lb = (cl < 4 ? cl : cl < 36 ? 8 * ((cl - 4) & 7) + ((cl - 4) >> 3) + (((cl - 4) & 7) ? 0 : 4) : 8 * (1 + u % 7) + 4 + u / 7) * 2 + rank;
  }
#define CTA_J(b) (((b) >> 1) & 7)
#define CTA_RB(b) ((((b) >> 4) << 1) | ((b) & 1))
  const int j = CTA_J(lb), rb = CTA_RB(lb);

  PROF(23);
  if (warp >= 8) {
    asm volatile("setmaxnreg.dec.sync.aligned.u32 " STR(REGS_P) ";");
    auto x_chunk = [&](int cc) {
      mbar_expect_tx(sb + xin_bar(cc), 16384);
      tma3d(sb + xin_off(cc, 0), &maps.x, 64 * cc, 0, 64 * rb, sb + xin_bar(cc));
      tma3d(sb + xin_off(cc, 1), &maps.x, 64 * cc, 1, 64 * rb, sb + xin_bar(cc));
    };
    if (warp == 9 && elect_one()) {
      fence_async_smem();
#pragma unroll 1
      for (int i = 0; i < 9; i++) x_chunk(i);
    }
    __syncwarp();
    if (warp == 9) PROFX(54);
    asm volatile("barrier.cluster.wait.aligned;" ::: "memory");
    if (warp == 8) PROFX(56);
    const uint64_t pol = W_POLICY(), pola = A_POLICY();
    uint4 (* const wq)[432] = ((Scratch*)ws)->wq[j];
    const uint32_t par = ~ld_relaxed(ws[2 * rb].flag + 32 + 32 * j) & 1;
    auto qkv_group = [&](bool copy, int k, uint32_t dst, uint32_t bar) {
      if (copy && gridDim.x > NCTA) {
        wbulk(dst + rank * 8192, wq[(k >> 4) + rank], 6912, bar, pol);
      } else {
        wtma3d(dst + rank * 8192, &maps.qm, 72 * j, k + 16 * rank, 0, bar, pola);
        wtma3d(dst + rank * 8192 + 6144, &maps.qc, 72 * j + 64, k + 16 * rank, 0, bar, pola);
      }
    };
    auto repacked = [&] {
#pragma unroll 1
      for (int it = 0; it < SPIN_MAX && gridDim.x > NCTA; it++)
        if (ld_acquire(ws[j].wsum + 128) == par) break;
      asm volatile("fence.proxy.async.global;" ::: "memory");
    };
    const int ktab = group_k0(lane, j);
    auto qkv_gate = [&](int g) { if (g >= 8) gate(sb + SM_PROG, 33 + ((g - 8) * QPACE >> 4)); };
    if (warp == 8) {
      uint32_t s = 0, ph = 1;
      auto slot = [&](uint32_t bytes, auto&& issue) {
        const uint32_t bar = sb + BAR_FULLB + 8 * s;
        mbar_wait(sb + BAR_EMPTYB + 8 * s, ph);
        if (elect_one()) {
          mbar_expect_tx(bar, bytes);
          issue(sb + SM_B + s * BSLOT, bar);
        }
        if (++s == 5) { s = 0; ph ^= 1; }
      };
#pragma unroll 1
      for (int layer = 0; layer < NLAYERS; layer++) {
        if (layer) repacked();
#pragma unroll 1
        for (int g = 0; g < 18 - layer; g += layer && g == 4 ? 8 : 1) {
          const int k = layer ? __shfl_sync(0xffffffffu, ktab, g) : 32 * g;
          if (layer) qkv_gate(g);
          else if (g == QD) mbar_wait(sb + xin_bar(XH), 0);
          slot(2 * 6912, [&](uint32_t dst, uint32_t bar) { qkv_group(layer, k, dst, bar); });
        }
        if (!FCH) {
          gate(sb + SM_PROG, 32 * layer + 20);
          gate(sb + SM_PROG + 4, 32 * layer + 20);
        }
#pragma unroll 1
        for (int t = 0; t < 5; t++) {
          const CUtensorMap* m = &maps.g + (t < 3 ? rank : 2 + rank);
          asm volatile("" : "+l"(m));
          const int c2 = t < 3 ? 9 * j + 2 * t : 18 * j + 3 + 3 * t;
          const uint32_t half = t < 3 ? 8192 : 6144;
          auto tile = [&](int g) {
            const int k = __shfl_sync(0xffffffffu, ktab, g);
            slot(2 * half, [&](uint32_t dst, uint32_t bar) { wtma3d(dst + rank * half, m, 0, k, c2, bar, pol); });
          };
          int g = 0;
          if (t == 0) {
#pragma unroll 1
            for (; g < 5; g++) {
              mbar_wait(sb + BAR_FULLB + 8 * (s < FCH ? s + 5 - FCH : s - FCH), s < FCH ? ph : ph ^ 1);
              tile(g);
            }
          }
#pragma unroll 1
          for (; g < 18; g++) tile(g);
        }
      }
    } else if (warp == 9) {
      uint32_t mE = 0;
      auto acquire = [&](uint32_t s) { mbar_wait(sb + BAR_EMPTYX + 8 * s, (mE >> s) & 1); mE ^= 1u << s; };
      auto landed = [&](uint32_t s) { mbar_wait(sb + BAR_FULLX + 8 * s, (mE >> s) & 1); };
      auto slot = [&](uint32_t s, const CUtensorMap* m, int col, int row, uint64_t pol) {
        acquire(s);
        if (elect_one()) {
          mbar_expect_tx(sb + BAR_FULLX + 8 * s, XSLOT);
          wtma2d(sb + SM_X + s * XSLOT + rank * 9216, m, col, row + 72 * rank, sb + BAR_FULLX + 8 * s, pol);
        }
      };
#pragma unroll 1
      for (int layer = 0; layer < NLAYERS; layer++) {
        if (layer) repacked();
#pragma unroll 1
        for (int g = 5; g < 18 * layer; g += g == 11 ? 6 : 1) {
          const uint32_t s = qkv_xslot(g);
          const int k = __shfl_sync(0xffffffffu, ktab, g);
          if (g < 12) qkv_gate(g);
          acquire(s);
          if (elect_one()) {
            mbar_expect_tx(sb + BAR_FULLX + 8 * s, 2 * 6912);
            qkv_group(true, k, sb + SM_X + s * XSLOT, sb + BAR_FULLX + 8 * s);
          }
          if (XCH & 1) landed(s);
        }
#pragma unroll 1
        for (int i = 0; i < 4; i++) { slot(4 + i, &maps.o, 64 * j, 144 * i, pola); if (XCH & 2) landed(4 + i); }
        acquire(3);
        if (elect_one()) {
          mbar_expect_tx(sb + BAR_FULLX + 24, 9216);
          wtma2d(sb + SM_WOC + rank * 4608, &maps.oc, 512 + 8 * j, 288 * rank, sb + BAR_FULLX + 24, pola);
          wtma2d(sb + SM_WOC + rank * 4608 + 2304, &maps.oc, 512 + 8 * j, 288 * rank + 144, sb + BAR_FULLX + 24, pola);
        }
#pragma unroll 1
        for (int u = 0; u < 36; u++) {
          const uint32_t s = 4 * (u & 1) + ((u >> 1) & 3);
          slot(s, &maps.d, u < 4 ? 512 : 64 * ((j + (u >> 2)) & 7), 576 * j + 144 * (u & 3), pol);
          if ((XCH & 4) && u < 3) landed(s);
        }
      }
    } else {
      const int w = warp - 10, grp = 2 * rb + w;
      if (PFMODE & 4) {
        mbar_wait(sb + xin_bar(XP), 0);
        if (lane == 0) prefetch_l2(wqkv + (2 * blockIdx.x + w) * 7776, 7776);
        if (EARLY && lane == 0) prefetch_l2(wo + (2 * blockIdx.x + w) * 2592, 2592);
      }
      if (EARLY) {
        mbar_wait(sb + xin_bar(8), 0);
        gate(sb + SM_PROG, WSG);
        if (grp < 18) {
          const uint4* row = (const uint4*)(wo + (72 * j + 4 * grp + (lane >> 3)) * 1152) + (lane & 7);
          float a = 0.f;
#pragma unroll 1
          for (int i = 0; i < 72; i += 24) {
            const uint4 u[3] = {__ldg(row + i), __ldg(row + i + 8), __ldg(row + i + 16)};
#pragma unroll
            for (int k = 0; k < 3; k++)
              a += ((bf_lo(u[k].x) + bf_hi(u[k].x)) + (bf_lo(u[k].y) + bf_hi(u[k].y))) + ((bf_lo(u[k].z) + bf_hi(u[k].z)) + (bf_lo(u[k].w) + bf_hi(u[k].w)));
          }
          a = quad_sum(a);
          a += __shfl_xor_sync(0xffffffffu, a, 4);
          if ((lane & 7) == 0) st_relaxed(ws[j].wsum + 4 * grp + (lane >> 3), tagged(__float_as_uint(a), par));
        }
        if (w == 1) {
          uint32_t u[3];
#pragma unroll 1
          for (int it = 0; it < SPIN_MAX; it++) {
#pragma unroll
            for (int k = 0; k < 3; k++) u[k] = ld_relaxed(ws[j].wsum + min(lane + 32 * k, 71));
            if (!__any_sync(0xffffffffu, chk(chk2(u[0], u[1], par), u[2], par) & 1)) break;
            __nanosleep(100);
          }
#pragma unroll
          for (int k = 0; k < 3; k++) {
            const float f = __uint_as_float(u[k]);
            if (lane + 32 * k < 80) sts128(sb + SM_WSUM + 16 * (lane + 32 * k), pack_bf16(f, f - bf_lo(pack_bf16(f, 0.f))), 0, 0, 0);
          }
          fence_async_smem();
          __syncwarp();
          if (lane < 4) mbar_arrive(sb + BAR_WSUM);
          PROFX(57);
        }
      }
      gate(sb + SM_PROG, 3);
      if (w == 0) PROFX(58);
      auto prefetch_gu = [&](int l0, int n) {
#pragma unroll 1
        for (int i = lane; i < 36 * n; i += 32) {
          asm volatile("prefetch.global.L2 [%0];" ::"l"((w ? wu : wg) + (size_t)(36 * rb + i / n) * 9216 + 1152 * j + 128 * (l0 + i % n)));
          __nanosleep(PFSLEEP);
        }
      };
      auto clear = [&](uint4* p, int n) {
#pragma unroll 1
        for (int i = lane; i < n; i += 64) { st_relaxed4(p + i, 0, 0, 0, 0); st_relaxed4(p + i + 32, 0, 0, 0, 0); __nanosleep(CLRSLEEP); }
      };
      auto exchange = [&](uint32_t v, uint32_t bar) {
        if (FENCE1) { if (lane == 0) fence_gpu(); } else fence_gpu();
        __syncwarp();
        if (w == 0 && v != 1) PROFX(64 + 58 - 2 * v);
        if (lane == 0) st_relaxed(ws[grp].flag + j, v);
#pragma unroll 1
        for (int it = 0; it < SPIN_MAX; it++) {
          const uint32_t f = ld_relaxed(ws[grp].flag + (lane & 7));
          if (__all_sync(0xffffffffu, v ? f >= v : f == 0)) break;
        }
        if (lane == 0) mbar_arrive(sb + bar + 8 * w);
      };
      if (!EARLY && lane == 0) prefetch_l2(wo + (2 * blockIdx.x + w) * 2592, 2592);
      if (MAPPF && w == 0 && lane < 9) asm volatile("prefetch.tensormap [%0];" ::"l"(&maps.o + lane) : "memory");
#pragma unroll 1
      for (int layer = 0; layer < NLAYERS; layer++) {
        gate(sb + SM_PROG, 32 * layer + 3);
        if (PFF & 1) prefetch_gu(0, 2);
        gate(sb + SM_PROG, 32 * layer + 22);
        if (PFF & 2) prefetch_gu(2, 2);
        if (layer == 0) {
          clear(ws[grp].inbox[0] + 2 * j * INBOX, 2 * INBOX);
          exchange(1, BAR_CLR);
          if (w == 0) PROFX(59);
        }
        if (PFF & 2) prefetch_gu(4, 2);
        if (PFF & 4) prefetch_gu(6, 3);
#pragma unroll 1
        for (int i = lane; i < ((PFF & 8) ? 162 : 0); i += 32) {
          asm volatile("prefetch.global.L2 [%0];" ::"l"(wd + (size_t)(576 * j + 36 * rb + 18 * w) * 1152 + 128 * i));
          __nanosleep(PFSLEEP);
        }
        if (w == 0 && layer == 0) PROFX(60);
        mbar_wait(sb + BAR_REDDONE + 8 * w, layer);
        if (w == 0) PROFX(64 + 53 + 4 * layer);
        exchange(2 - 2 * layer, BAR_RREADY);
        if (w == 0) PROFX(64 + 56 + 4 * layer);
      }
      mbar_wait(sb + BAR_DONE + 8 * w, 0);
    }
    __syncwarp();
    cluster_sync();
  } else {
    asm volatile("setmaxnreg.inc.sync.aligned.u32 " STR(REGS_C) ";");
#define THREAD_IDS()                                                                   \
    int tid_ = threadIdx.x, bid_ = lb;                                                  \
    asm volatile("" : "+r"(tid_), "+r"(bid_));                                          \
    const int w = warp >> 2, wp = warp & 3;                                             \
    const int lane = tid_ & 31, t = tid_ & 127, g = lane >> 2, q = lane & 3;           \
    const int j = CTA_J(bid_), rb = CTA_RB(bid_), grp = 2 * rb + w;                    \
    const int st0 = wp * 64 + g;                         \
    Group* const G = ws + grp;                                                         \
    const uint32_t dsb = (sb & 0x3FFFF) >> 4;                                          \
    (void)t; (void)g; (void)q; (void)grp; (void)j; (void)st0; (void)dsb; (void)G
    Cons c;
    c.sb = sb; c.sB = 0; c.mB = 0; c.mX = 0; c.elect = (threadIdx.x & 127) == 0;
    asm volatile("mapa.shared::cluster.u32 %0, %1, %2;" : "=r"(c.rem) : "r"(sb), "r"(rank ^ 1));
    float v[36], a1[96], a2[12];
    float2 sum, rs;
    uint32_t res[18], xtag;
    auto qkv_mma = [&](bool acc, uint32_t bb, const uint4& f0, const uint4& f1) {
      wg_fence();
      wgmma_ra<192>(a1, f0, desc_hi(2048, 1024, 1) + bb, acc);
      wgmma_ra<24>(a2, f0, desc_hi(128, 256, 0) + (bb + 384), acc);
      wgmma_ra<192>(a1, f1, desc_hi(2048, 1024, 1) + (bb + 512), true);
      wgmma_ra<24>(a2, f1, desc_hi(128, 256, 0) + (bb + 896), true);
      wg_commit();
    };
    {
      THREAD_IDS();
      if (OPEN) {
        if (q == 0) { st_relaxed2(G->sum + st0 + 8 * j, 0, 0); st_relaxed2(G->sq + st0 + 8 * j, 0, 0); }
        if (wp == 3) {
#pragma unroll
          for (int i = 0; i < 5; i++) st_relaxed4(G->halo + j * 160 + lane + i * 32, 0, 0, 0, 0);
        }
        if (lane >= OPENL) st_relaxed4(G->obox + (8 * WPROBE + j) * 128 + t, 0, 0, 0, 0);
      }
      xtag = __shfl_sync(0xffffffffu, ~ld_relaxed(G->flag + 32 + 32 * j) & 1, 0);
      if (OPEN && EARLY && lane >= OPENL) st_relaxed4(G->xbox + (2 * j + 1) * 128 + t, xtag ^ 1, 0, 0, 0);
      asm volatile("barrier.cluster.wait.aligned;" ::: "memory");
      PROF(0);
#pragma unroll
      for (int i = 0; i < 96; i++) asm volatile("mov.b32 %0, 0;" : "=f"(a1[i]));
#pragma unroll
      for (int i = 0; i < 12; i++) asm volatile("mov.b32 %0, 0;" : "=f"(a2[i]));
      PROF(1);
      rs = ln_gemm_in(c, G, res, sum, w, st0, j, t, [&](int i) { PROF(2 + i); if (i) PROF(4); }, qkv_mma);
    }
#pragma unroll 1
    for (int layer = 0;; layer++) {
      const uint32_t tag = layer ^ 1;
      const int pb = 1 + layer * 30;
      uint4 own[5];
      {
        THREAD_IDS();
        PROF(pb + 4);
        uint32_t kv[3][18];
        auto cvt = [&](int b, float r) {
#pragma unroll
          for (int cc = 0; cc < 18; cc++) {
            const float* a = (cc == 8 ? a2 + 4 : cc == 17 ? a2 + 8 : cc < 8 ? a1 + 32 + 4 * cc : a1 + 28 + 4 * cc) + 2 * (b - 1);
            const uint32_t u = pack_bf16(a[0] * r, a[1] * r);
            kv[b][cc] = cc < 9 ? u : movm(u);
          }
        };
        cvt(2, rs.y);
        const uint32_t msg = sb + SM_X + (w ? 3 * XSLOT : 24576) + wp * 2304 + lane * 16;
        if (wp == 3) {
          uint4* hp = G->halo + j * 160 + lane;
#pragma unroll
          for (int i = 0; i < 4; i++) st_relaxed4(hp + i * 32, tagged(kv[2][4 * i], tag), kv[2][4 * i + 1], kv[2][4 * i + 2], kv[2][4 * i + 3]);
          st_relaxed2((uint2*)(hp + 128), tagged(kv[2][16], tag), kv[2][17]);
        } else {
#pragma unroll
          for (int i = 0; i < 4; i++) sts128(msg + i * 512, kv[2][4 * i], kv[2][4 * i + 1], kv[2][4 * i + 2], kv[2][4 * i + 3]);
          sts64f(msg + 2048 - lane * 8, __uint_as_float(kv[2][16]), __uint_as_float(kv[2][17]));
        }
        cvt(1, rs.x);
        uint32_t Q[4][6];
#pragma unroll
        for (int h = 0; h < 4; h++)
#pragma unroll
          for (int i = 0; i < 6; i++) {
            const float* a = 4 * h + i < 16 ? a1 + 8 * h + 2 * i : a2 + 8 * h + 2 * i - 32;
            const uint32_t u = pack_bf16(a[0], a[1]);
            Q[h][i] = i < 2 ? (q >= h ? u : 0) : i < 4 ? u : (q <= h ? u : 0);
          }
        const bool lo0 = 2 * q > g, lo1 = 2 * q + 1 > g;
        const uint32_t M = (lo0 ? 0xffffu : 0u) | (lo1 ? 0xffff0000u : 0u);
        auto scores = [&](int h, int b, float (&s)[4]) {
          mma16816z(s, Q[h][0], Q[h][1], Q[h][2], Q[h][3], kv[b][2 * h], kv[b][2 * h + 1]);
          mma1688(s, Q[h][4], Q[h][5], kv[b][2 * h + 2]);
        };
        auto softmax = [&](float (&l)[4][2], float r, uint32_t (&P)[4]) {
          const float sl = r * (0.23570226039551584f * 1.4426950408889634f);
          float m[4];
#pragma unroll
          for (int h = 0; h < 4; h++) { m[h] = fmaxf(l[h][0], l[h][1]); m[h] = fmaxf(m[h], __shfl_xor_sync(0xffffffffu, m[h], 1)); }
#pragma unroll
          for (int h = 0; h < 4; h++) m[h] = fmaxf(m[h], __shfl_xor_sync(0xffffffffu, m[h], 2)) * sl;
#pragma unroll
          for (int h = 0; h < 4; h++) {
            l[h][0] = ex2(fmaf(l[h][0], sl, -m[h])); l[h][1] = ex2(fmaf(l[h][1], sl, -m[h]));
            m[h] = l[h][0] + l[h][1]; m[h] += __shfl_xor_sync(0xffffffffu, m[h], 1);
          }
#pragma unroll
          for (int h = 0; h < 4; h++) { m[h] = rcp(m[h] + __shfl_xor_sync(0xffffffffu, m[h], 2)); P[h] = pack_bf16(l[h][0] * m[h], l[h][1] * m[h]); }
        };
        const bool remote = wp == 0 && rb > 0;
        const uint4* hp = (G - 2)->halo + j * 160 + lane;
        auto halo = [&] {
#pragma unroll
          for (int i = 0; i < 4; i++) { const uint4 u = ld_relaxed4(hp + i * 32); kv[0][4 * i] = u.x; kv[0][4 * i + 1] = u.y; kv[0][4 * i + 2] = u.z; kv[0][4 * i + 3] = u.w; }
          const uint2 u = ld_relaxed2((const uint2*)(hp + 128));
          kv[0][16] = u.x; kv[0][17] = u.y;
        };
#pragma unroll
        for (int i = 0; i < 18; i++) kv[0][i] = 0;
        if (remote) halo();
        float l0[4][2], l1[4][2];
#pragma unroll
        for (int h = 0; h < 4; h++) {
          float s1[4], s2[4];
          scores(h, 1, s1); scores(h, 2, s2);
          l0[h][0] = s1[0]; l0[h][1] = s1[1];
          l1[h][0] = lo0 ? s1[2] : s2[2]; l1[h][1] = lo1 ? s1[3] : s2[3];
        }
        uint32_t P0[4], P1[4];
        softmax(l1, rs.y, P1);
        if (remote) {
          while (__any_sync(0xffffffffu, chk(chk2(kv[0][0], kv[0][4], tag) | chk2(kv[0][8], kv[0][12], tag), kv[0][16], tag) & 1)) halo();
        }
        if (FG < 0) c.progress(32 * layer + 20);
        wg_bar(w);
        if (wp > 0) {
          const uint32_t from = msg - 2304;
#pragma unroll
          for (int i = 0; i < 4; i++) { const uint4 u = lds128(from + i * 512); kv[0][4 * i] = u.x; kv[0][4 * i + 1] = u.y; kv[0][4 * i + 2] = u.z; kv[0][4 * i + 3] = u.w; }
          const float2 u = lds64(from + 2048 - lane * 8);
          kv[0][16] = __float_as_uint(u.x); kv[0][17] = __float_as_uint(u.y);
        }
        PROF(pb + 5);
        const bool first = (rb == 0 && wp == 0);
#pragma unroll
        for (int h = 0; h < 4; h++) {
          float s0[4];
          scores(h, 0, s0);
          if (first) s0[0] = s0[1] = -INFINITY;
          l0[h][0] = lo0 ? s0[0] : l0[h][0]; l0[h][1] = lo1 ? s0[1] : l0[h][1];
        }
        softmax(l0, rs.x, P0);
        uint4* ob = G->obox + t;
        uint32_t car0 = 0, car1 = 0;
#pragma unroll
        for (int h = 0; h < 4; h++) {
          float o[3][4];
#pragma unroll
          for (int i = 0; i < 3; i++) {
            mma16816z(o[i], P0[h] & ~M, P1[h] & M, 0u, P1[h] & ~M, kv[1][9 + 2 * h + i], kv[2][9 + 2 * h + i]);
            mma1688(o[i], P0[h] & M, 0u, kv[0][9 + 2 * h + i]);
          }
          const uint32_t o0 = q < h ? car0 : pack_bf16(o[0][0], o[0][1]), o1 = q < h ? car1 : pack_bf16(o[0][2], o[0][3]);
          own[h] = make_uint4(o0 | 1, o1, pack_bf16(o[1][0], o[1][1]), pack_bf16(o[1][2], o[1][3]));
          st_relaxed4(ob + (8 * h + j) * 128, own[h].x, own[h].y, own[h].z, own[h].w);
          car0 = pack_bf16(o[2][0], o[2][1]); car1 = pack_bf16(o[2][2], o[2][3]);
        }
        car0 = tagged(car0, tag);
        st_relaxed2((uint2*)(ob + (32 + (j >> 1)) * 128) + (j & 1), car0, car1);
        own[4] = make_uint4(car0, car1, 0, 0);
        PROF(pb + 6);
      }
      {
        THREAD_IDS();
        const uint4* src = G->obox + t;
        asm volatile("" : "+l"(src));
        float a[32], a8[4];
#pragma unroll
        for (int i = 3; i < 8; i++) mbar_wait_c(sb + BAR_FULLX + 8 * i, (c.mX >> i) & 1);
        c.mX ^= 0xf8;
        auto step = [&](const uint4& f, uint32_t r0, int rs, bool acc) {
          wgmma_ra<64>(a, f, desc_hi(0, rs * 128, 1) + (dsb + ((SM_X + 4 * XSLOT) >> 4) + r0 * 8), acc);
          wgmma_ra<8>(a8, f, desc_hi(rs * 16, 0, 0) + (dsb + (SM_WOC >> 4) + r0), acc);
        };
        const uint32_t* probe = &(G->obox + (8 * WPROBE + (lane & 7)) * 128 + (t | 31))->x;
        uint32_t pv = ld_relaxed(probe);
        if (OWNBAR) asm volatile("bar.sync 4, 256;" ::: "memory");
        if (EARLY) mbar_wait_c(sb + BAR_WSUM, 0);
        float e[4];
        wg_fence();
        if (EARLY) {
#pragma unroll
          for (int i = 0; i < 5; i++) wgmma_ra<8>(e, own[i], desc_hi(128, 0, 0) + (dsb + (SM_WSUM >> 4) + 16 * i), i > 0);
          wg_commit();
        }
#pragma unroll
        for (int i = 0; i < 4; i++) step(own[i], 72 * j + 16 * i, 8, i > 0);
        wg_commit();
        if (EARLY) {
          wg_wait<1>();
          if (q == 0) st_relaxed2(G->sum + st0 + 8 * j, (__float_as_uint(e[0] + e[1]) & ~3u) | ((2 * layer + 2) & 3), __float_as_uint(e[2] + e[3]));
        }
        pv &= late(sb + BAR_FULLX + 64, 1);
        while (__any_sync(0xffffffffu, ~pv & 1)) pv = ld_relaxed(probe);
        if (w == 1) asm volatile("bar.sync 7, 256;" ::: "memory");
        uint2 sa, sc;
        uint4 x[32];
        auto load = [&](int i) { x[i] = ld_relaxed4(i < 28 ? src + (i % 7 >= j ? 128 : 0) + (8 * (i / 7) + i % 7) * 128 : src + (i + 4) * 128); };
        auto batch = [&](auto e0, auto e1, auto e2, int b) {
          constexpr int E0 = decltype(e0)::v, E1 = decltype(e1)::v, E2 = decltype(e2)::v;
          const uint32_t one = E0 > 0 && E1 > E0 ? late(sb + BAR_FULLX + 64, 1) : 1;
          while (E1 > E0) {
            uint32_t bad = 0;
#pragma unroll
            for (int i = E0; i < E1; i++) bad = i < 28 ? chk(bad, x[i].x, one) : chk(chk(bad, x[i].x, tag), x[i].z, tag);
            if (!__any_sync(0xffffffffu, bad & 1)) break;
#pragma unroll
            for (int i = E0; i < E1; i++) load(i);
          }
          if (b == 0) PROF(pb + 7);
          if (b > 0 && E2 > E1) wg_wait<WOW>();
#pragma unroll
          for (int i = E1; i < E2; i++) load(i);
          if (EARLY && b == 1) { sa = ld_relaxed2(G->sum + st0 + 16 * q); sc = ld_relaxed2(G->sum + st0 + 16 * q + 8); }
          if (b == WOREL && w == 0) asm volatile("bar.arrive 7, 256;" ::: "memory");
          if (E1 > E0) {
            wg_fence();
#pragma unroll
            for (int i = E0; i < E1; i++) {
              if (i < 28) step(x[i], 72 * (i % 7) + (i % 7 >= j ? 72 : 0) + 16 * (i / 7), 8, true);
              else step(x[i], 144 * (i - 28) + 64, 72, true);
            }
            wg_commit();
          }
        };
        batch(IC<0>(), IC<0>(), IC<WB1>(), -1);
        batch(IC<0>(), IC<WB1>(), IC<WB2>(), 0);
        batch(IC<WB1>(), IC<WB2>(), IC<WB3>(), 1);
        batch(IC<WB2>(), IC<WB3>(), IC<32>(), 2);
        batch(IC<WB3>(), IC<32>(), IC<32>(), 3);
        if (EARLY) {
          float2 e = make_float2(quad_sum(__uint_as_float(sa.x) + __uint_as_float(sc.x)), quad_sum(__uint_as_float(sa.y) + __uint_as_float(sc.y)));
          if (__any_sync(0xffffffffu, chk2(sa.x, sc.x, (2 * layer + 2) & 3) & 3)) e = gather_sums(G->sum + st0 + 16 * q, (2 * layer + 2) & 3);
          sum.x += e.x; sum.y += e.y;
        }
        wg_wait<0>();
        if (w == 0) asm volatile("bar.arrive 3, 256;" ::: "memory");
        PROF(pb + 8);
#pragma unroll
        for (int i = 0; i < 18; i++) {
          v[2 * i] = bf_lo(res[i]) + (i < 16 ? a[2 * i] : a8[2 * i - 32]);
          v[2 * i + 1] = bf_hi(res[i]) + (i < 16 ? a[2 * i + 1] : a8[2 * i - 31]);
        }
      }
      uint32_t lsb;
      uint32_t h[144];
      {
        THREAD_IDS();
        float a[128];
        const uint32_t xd = sb + SM_X + w * 4 * XSLOT + (lane >> 4) * 1024 + (16 * wp + (lane & 15)) * 16;
        const float2 rs = ln_gemm<false>(c, G, v, res, sum, st0, j, t, layer, xtag,
          [&](int i) {
            if (i == 0) {
              lsb = ((res[0] & 1) | (res[4] & 1) << 1 | (res[8] & 1) << 2 | (res[12] & 1) << 3 | (res[16] & 1) << 4) ^ (xtag * 31);
              if (w == 1) asm volatile("bar.sync 3, 256;" ::: "memory");
            }
            PROF(pb + 9 + i);
          },
          [&](int gi, uint32_t bb, const uint4& f0, const uint4& f1) {
            if (gi == 0) PROF(pb + 11);
            if (TLEAD0 && gi == 18 - TLEAD0 && w == 1) asm volatile("bar.sync 5, 256;" ::: "memory");
            wg_fence();
            wgmma_ra<256>(a, f0, desc_hi(4096, 1024, 1) + bb, gi > 0);
            wgmma_ra<256>(a, f1, desc_hi(4096, 1024, 1) + (bb + 128), true);
            wg_commit();
            if (TLEAD0 && gi == 17 && w == 0) asm volatile("bar.arrive 5, 256;" ::: "memory");
            stsm4(xd + gi * 4096, f0.x, f0.y, f0.z, f0.w);
            stsm4(xd + gi * 4096 + 2048, f1.x, f1.y, f1.z, f1.w);
            if (gi == 17) { fence_async_smem(); wg_bar(w); }
          });
        sts64f(sb + SM_KEEP + (tid_ >> 2) * 8, rs.x * rs.x, rs.y * rs.y);
        c.progress(32 * layer + 22);
        PROF2(pb + 12);
        glu<16, 0>(a, h);
        const Desc da0 = desc_hi(1024, 128, 0) + (dsb + ((SM_X + w * 4 * XSLOT) >> 4));
        auto tile = [&](auto wide, auto last) {
          const uint32_t xe = BAR_EMPTYX + 32 * (t & 1) + 4 * (t & 6);
          auto group = [&](int gi) {
            uint32_t prev;
            const uint32_t bb = c.nextB(prev);
            const Desc da = da0 + gi * 256;
            wg_fence();
            if (wide()) {
              wgmma_ss<256>(a, da, desc_hi(4096, 1024, 1) + bb, gi);
              wgmma_ss<256>(a, da + 128, desc_hi(4096, 1024, 1) + (bb + 128), 1);
            } else {
              wgmma_ss<192>(*(float(*)[96])a, da, desc_hi(2048, 512, 2) + bb, gi);
              wgmma_ss<192>(*(float(*)[96])a, da + 128, desc_hi(2048, 512, 2) + (bb + 64), 1);
            }
            wg_commit();
            if (gi == 17 && w == 0) asm volatile("bar.arrive 5, 256;" ::: "memory");
            wg_wait<1>();
            if (gi > 0 && !(last() && gi > 13)) c.release2(BAR_EMPTYB + prev);
            if (last() && gi >= XREL && !((gi ^ XREL) & 1)) c.release2(BAR_EMPTYX + 16 * ((gi - XREL) & 2) + 2 * ((gi - XREL) & 12));
          };
          int gi = 0, end = w ? 18 - (wide() ? TLEAD2 : TLEAD) : 18;
#pragma unroll 1
          while (true) {
#pragma unroll 1
            for (; gi < end; gi++) group(gi);
            if (end == 18) break;
            asm volatile("bar.sync 5, 256;" ::: "memory");
            end = 18;
          }
          wg_wait<0>();
          if (!last()) c.releaseLastB();
          if (last() && t >= (19 - XREL) / 2 && t < 8) { mbar_arrive(sb + xe); mbar_arrive_remote(c.rem + xe); }
        };
        auto yes = [] { return true; };
        auto no = [] { return false; };
        tile(yes, no); PROF2(pb + 13); glu<16, 32>(a, h);
        tile(yes, no); PROF2(pb + 14); glu<16, 64>(a, h);
        tile(no, no); PROF2(pb + 15); glu<12, 96>(a, h);
        const uint32_t hole = sb + SM_B + 12288 + tid_ * 16;
#pragma unroll
        for (int i = 0; i < NSPILL; i++) sts128(hole + i * BSLOT, h[96 + 4 * i], h[97 + 4 * i], h[98 + 4 * i], h[99 + 4 * i]);
        if (w == 1) asm volatile("bar.arrive 8, 256;" ::: "memory");
        tile(no, yes); PROF2(pb + 16); glu<12, 120>(a, h);
#pragma unroll
        for (int i = 0; i < NSPILL; i++) { const uint4 u = lds128(hole + i * BSLOT); h[96 + 4 * i] = u.x; h[97 + 4 * i] = u.y; h[98 + 4 * i] = u.z; h[99 + 4 * i] = u.w; }
      }
      {
        THREAD_IDS();
        float d[32];
        uint4* gt = G->obox + t;
        asm volatile("" : "+l"(gt));
        uint4* const ib = gt + 2 * 4608 + layer * 8 * INBOX;
        auto pass = [&](uint32_t s0, bool last, auto&& hook) {
          const Desc db = desc_hi(0, 1024, 1) + (dsb + (SM_X >> 4) + s0 * (XSLOT >> 4));
          mbar_wait_c(sb + BAR_FULLX + 8 * s0, (c.mX >> s0) & 1);
          if (RHOOK < 0) hook();
          asm volatile("bar.sync %0, 256;" ::"r"(8 + w) : "memory");
#pragma unroll
          for (int i = 0; i < 4; i++) {
            const int si = 4 * (i & 1) + (i >> 1);
            if (i > 0) mbar_wait_c(sb + BAR_FULLX + 8 * (s0 + si), (c.mX >> (s0 + si)) & 1);
            wg_fence();
#pragma unroll
            for (int k = 0; k < 9; k++) {
              const uint32_t* hk = h + 36 * i + 4 * k;
              wgmma_ra<64>(d, make_uint4(hk[0], hk[1], hk[2], hk[3]), db + (si * (XSLOT >> 4) + k * 128), last || i + k > 0);
              if (9 * i + k == PPK && !(last && w == 1)) asm volatile("bar.arrive %0, 256;" ::"r"(9 - w) : "memory");
            }
            wg_commit();
            if (i > 0) { wg_wait<1>(); c.release2(BAR_EMPTYX + 8 * (s0 + 4 * ((i - 1) & 1) + ((i - 1) >> 1))); }
            if (i == RHOOK) hook();
          }
          c.mX ^= 0x33u << s0;
        };
        PROF2(pb + 17);
#pragma unroll 1
        for (int p = 0; p < 8; p++) {
          const uint32_t s0 = 2 * (p & 1);
          pass(s0, false, [] {});
          wg_wait<0>();
          c.release2(BAR_EMPTYX + 8 * (s0 + 5));
          uint32_t pk[16];
#pragma unroll
          for (int i = 0; i < 16; i++) pk[i] = pack_bf16(d[2 * i], d[2 * i + 1]);
          if (p >= BREL && p < BREL + 5) {
            const uint32_t o = c.sB + 8 * (p - BREL);
            c.release2(BAR_EMPTYB + (o < 40 ? o : o - 40));
          }
          uint4* const dst = ib + ((j + p) & 7) * INBOX;
          if (p == 0) {
            mbar_wait_c(sb + BAR_CLR + 8 * w, 0);
#pragma unroll
            for (int k = 0; k < 8; k++) red2((uint2*)(ib + k * INBOX + 512) - t, pk[2 * k], pk[2 * k + 1]);
          } else if (p < 7) {
#pragma unroll
            for (int k = 0; k < 4; k++) red4(dst + k * 128, pk[4 * k], pk[4 * k + 1], pk[4 * k + 2], pk[4 * k + 3]);
            if (p == 6) { __syncwarp(); if (lane == 0) mbar_arrive(sb + BAR_REDDONE + 8 * w); }
          } else {
#pragma unroll
            for (int k = 0; k < 4; k++) st_relaxed4(gt + ((j + 7) & 7) * 128 + k * 1024, pk[4 * k] & ~1u, pk[4 * k + 1], pk[4 * k + 2], pk[4 * k + 3]);
          }
        }
        PROF2(pb + 18);
        const uint4 *in = ib + j * INBOX, *pin = gt + j * 128;
        const uint2* in9 = (const uint2*)(in + 512) - t;
        asm volatile("" : "+l"(in), "+l"(pin), "+l"(in9));
        const float2 r2 = lds64(sb + SM_KEEP + (tid_ >> 2) * 8);
        uint2 X9;
        {
          uint4 X[4];
          const uint4* box = gt + 4608;
#pragma unroll
          for (int k = 0; k < 4; k++) X[k] = ld_relaxed4(box + 256 * j + ((k & 1) + 8 * (k & 2)) * 128);
          X9 = ld_relaxed2((const uint2*)(box + (32 + (j >> 1)) * 128) + (j & 1));
          const float i0 = rcp(r2.x), i1 = rcp(r2.y);
#pragma unroll
          for (int k = 0; k < 4; k++) {
            float* e = d + 8 * k;
            X[k].x ^= (lsb >> k) & 1;
            e[0] = bf_lo(X[k].x) * i0; e[1] = bf_hi(X[k].x) * i0; e[2] = bf_lo(X[k].y) * i1; e[3] = bf_hi(X[k].y) * i1;
            e[4] = bf_lo(X[k].z) * i0; e[5] = bf_hi(X[k].z) * i0; e[6] = bf_lo(X[k].w) * i1; e[7] = bf_hi(X[k].w) * i1;
          }
        }
        uint4 R[4], P[4];
        uint2 R9;
        PROF2(pb + 19);
        pass(0, true, [&] {
          mbar_wait_c(sb + BAR_RREADY + 8 * w, layer);
#pragma unroll
          for (int k = 0; k < 4; k++) R[k] = ld_relaxed4(in + k * 128);
          R9 = ld_relaxed2(in9);
#pragma unroll
          for (int k = 0; k < 4; k++) P[k] = ld_relaxed4(pin + k * 1024);
        });
        const uint32_t zero = late(sb + BAR_FULLX + 64, 0);
        while (__any_sync(0xffffffffu, (chk2(P[0].x, P[1].x, zero) | chk2(P[2].x, P[3].x, zero)) & 1)) {
#pragma unroll
          for (int k = 0; k < 4; k++) P[k] = ld_relaxed4(pin + k * 1024);
        }
#pragma unroll
        for (int k = 0; k < 4; k++) {
          const uint32_t u[4] = {hadd2(R[k].x, P[k].x), hadd2(R[k].y, P[k].y), hadd2(R[k].z, P[k].z), hadd2(R[k].w, P[k].w)};
#pragma unroll
          for (int i = 0; i < 4; i++) { v[8 * k + 2 * i] = bf_lo(u[i]); v[8 * k + 2 * i + 1] = bf_hi(u[i]); }
        }
        X9.x = chk(zero, X9.x, lsb >> 4);
        v[32] = fmaf(bf_lo(R9.x), r2.x, bf_lo(X9.x)); v[33] = fmaf(bf_hi(R9.x), r2.x, bf_hi(X9.x));
        v[34] = fmaf(bf_lo(R9.y), r2.y, bf_lo(X9.y)); v[35] = fmaf(bf_hi(R9.y), r2.y, bf_hi(X9.y));
        PROF2(pb + 20);
        wg_wait<0>();
        c.release2(BAR_EMPTYX + 40);
        PROF2(pb + 21);
#pragma unroll
        for (int i = 0; i < 32; i++) v[i] = (v[i] + d[i]) * (i & 2 ? r2.y : r2.x);
      }
      if (layer == NLAYERS - 1) break;
      {
        THREAD_IDS();
        PROF(31);
        rs = ln_gemm<true>(c, G, v, res, sum, st0, j, t, 1, xtag ^ 1, [&](int i) { PROF(32 + i); if (i) PROF(34); }, qkv_mma);
      }
    }
    {
      THREAD_IDS();
      const uint32_t stg = sb + SM_B + warp * 4096;
      const uint32_t sd = stg + (lane & 15) * 128;
#pragma unroll
      for (int i = 0; i < 4; i++)
        stsm4(sd + (((2 * i + (lane >> 4)) ^ (lane & 7)) << 4), pack_bf16(v[8 * i], v[8 * i + 1]), pack_bf16(v[8 * i + 2], v[8 * i + 3]),
              pack_bf16(v[8 * i + 4], v[8 * i + 5]), pack_bf16(v[8 * i + 6], v[8 * i + 7]));
      stsm2(stg + 2048 + (lane & 15) * 16, pack_bf16(v[32], v[33]), pack_bf16(v[34], v[35]));
      fence_async_smem();
      __syncwarp();
      if (lane == 0) {
        tma_store3d(&maps.out, stg, 64 * j, w, 64 * rb + 16 * wp);
        tma_store3d(&maps.outc, stg + 2048, 512 + 8 * j, w, 64 * rb + 16 * wp);
        bulk_commit();
        if (wp == 0) st_relaxed(G->flag + 32 + 32 * j, xtag);
        bulk_wait_all();
        mbar_arrive(sb + BAR_DONE + 8 * w);
      }
      PROF(61);
    }
    __syncwarp();
    cluster_sync();
  }
}

typedef CUresult (*EncFn)(CUtensorMap*, CUtensorMapDataType, cuuint32_t, void*, const cuuint64_t*, const cuuint64_t*, const cuuint32_t*,
                          const cuuint32_t*, CUtensorMapInterleave, CUtensorMapSwizzle, CUtensorMapL2promotion, CUtensorMapFloatOOBfill);

void make_map(EncFn enc, CUtensorMap* m, const void* p, int rank, uint64_t d0, uint64_t d1, uint64_t d2, uint64_t s1, uint64_t s2, uint32_t b0,
              uint32_t b1, uint32_t b2, CUtensorMapSwizzle sw) {
  cuuint64_t gd[3] = {d0, d1, d2};
  cuuint64_t gs[2] = {s1, s2};
  cuuint32_t bd[3] = {b0, b1, b2};
  cuuint32_t es[3] = {1, 1, 1};
  enc(m, CU_TENSOR_MAP_DATA_TYPE_BFLOAT16, rank, const_cast<void*>(p), gd, gs, bd, es, CU_TENSOR_MAP_INTERLEAVE_NONE, sw,
      CU_TENSOR_MAP_L2_PROMOTION_L2_128B, CU_TENSOR_MAP_FLOAT_OOB_FILL_NONE);
}

}

extern "C" void kernel_launch(void* const* d_in, const int* in_sizes, int n_in, void* d_out, int out_size) {
  const __nv_bfloat16* x = (const __nv_bfloat16*)d_in[0];
  const char *wqkv = (const char*)d_in[1], *wo = (const char*)d_in[2], *wg = (const char*)d_in[4], *wu = (const char*)d_in[5], *wd = (const char*)d_in[6];
  static EncFn enc = nullptr;
  static int grid = NCTA;
  static Group* ws = nullptr;
  if (!enc) {
    cudaDriverEntryPointQueryResult qr;
    cudaGetDriverEntryPoint("cuTensorMapEncodeTiled", (void**)&enc, cudaEnableDefault, &qr);
    cudaGetSymbolAddress((void**)&ws, g_ws);
    cudaFuncSetAttribute(fused_kernel, cudaFuncAttributeMaxDynamicSharedMemorySize, SMEM_BYTES);
    cudaLaunchConfig_t cfg = {};
    cfg.gridDim = NCTA + 4; cfg.blockDim = 384; cfg.dynamicSmemBytes = SMEM_BYTES;
    int clusters = 0;
    if (REPACK && cudaOccupancyMaxActiveClusters(&clusters, fused_kernel, &cfg) == cudaSuccess && 2 * clusters >= NCTA + 4) grid = NCTA + 4;
    cudaGetLastError();
  }
  const CUtensorMapSwizzle S0 = CU_TENSOR_MAP_SWIZZLE_NONE, S64 = CU_TENSOR_MAP_SWIZZLE_64B, S128 = CU_TENSOR_MAP_SWIZZLE_128B;
  Maps m;
  make_map(enc, &m.x, x, 3, 576, 2, 1024, 1152, 2304, 64, 1, 64, S128);
  make_map(enc, &m.qm, wqkv, 3, 576, 576, 3, 3456, 1152, 64, 16, 3, S128);
  make_map(enc, &m.qc, wqkv, 3, 576, 576, 3, 3456, 1152, 8, 16, 3, S0);
  make_map(enc, &m.o, wo, 2, 576, 576, 1, 1152, 0, 64, 72, 1, S128);
  make_map(enc, &m.oc, wo, 2, 576, 576, 1, 1152, 0, 8, 144, 1, S0);
  make_map(enc, &m.g, wg, 3, 64, 576, 72, 9216, 128, 64, 32, 2, S128);
  make_map(enc, &m.u, wu, 3, 64, 576, 72, 9216, 128, 64, 32, 2, S128);
  make_map(enc, &m.g3, wg, 3, 32, 576, 144, 9216, 64, 32, 32, 3, S64);
  make_map(enc, &m.u3, wu, 3, 32, 576, 144, 9216, 64, 32, 32, 3, S64);
  make_map(enc, &m.d, wd, 2, 576, 4608, 1, 1152, 0, 64, 72, 1, S128);
  make_map(enc, &m.out, d_out, 3, 576, 2, 1024, 1152, 2304, 64, 1, 16, S128);
  make_map(enc, &m.outc, d_out, 3, 576, 2, 1024, 1152, 2304, 8, 1, 16, S0);
  fused_kernel<<<grid, 384, SMEM_BYTES>>>(x, ws, wqkv, wg, wu, wd, m, wo);
}
```

```cpp
#include <cuda_runtime.h>
#include <cuda_bf16.h>
#include <cuda.h>
#include <stdint.h>
#include <stddef.h>

namespace {

constexpr int D_ = 576;
constexpr int NCTA = 128;
#define NLAYERS 2
#define W_POLICY policy_evict_first
#define A_POLICY policy_evict_normal
#define OPEN 1
#define PFMODE 5
#define WWIN 4
#define WOREL -1
#define WB1 11
#define WB2 21
#define WB3 32
#define WPROBE 1
#define WPROBE2 0
#define SPEC 2
#define POLLFIRST 0
#define SUMFIRST 1
#define EARLYPOLL 1
#define LEAD 0
#define ATTBAR 0
#define GL 18
#define WOBAR 1
#define QD 0
#define QG 4
#define PFQ 1
#define XDELAY 0
#define WOH 1
#define PFSLEEP 700
#define GPCMAP 1
#define PFF 1
#define REDN 1
#define CLRSLEEP 300
#define OPENL 24
#define FG -1
#define NON8 0
#define HMUL 1
#define FCH 1
#define PPK 34
#define RHOOK -1
#define SCHEDBAR 1
#define QH 5
#define XH 3
#define XP 0
#define GSLEEP 32
#define XCH 1
#define MAPPF 1
#define XREL 8
#define WOG 13
#define BREL 1
#define FENCE1 0
#define OWNX 0
#define OWNBAR 0
#define EARLY 1
#define ESPEC 0
#define TESTP 0
#define WOW 1
#define STATP -1
#define WSG 0
#define REPACK 1
#define QPACE 23
#define RDELAY 12
#define TLEAD 2
#define TLEAD2 2
#define TLEAD0 2
#define OFIRST 3
#define OSPEC 0
#define FN 0
#define LATE0 0
#define NSPILL 4
#define REGS_C 232
#define REGS_P 40
#define STR2(x) #x
#define STR(x) STR2(x)
constexpr uint32_t SM_X = 0;
constexpr uint32_t XSLOT = 18432;
constexpr uint32_t SM_WOC = SM_X + 3 * XSLOT + 9216;
constexpr uint32_t SM_B = 147456;
constexpr uint32_t BSLOT = 16384;
constexpr uint32_t SM_KEEP = 229376;
constexpr uint32_t SM_WSUM = SM_KEEP + 512;
constexpr uint32_t SM_BAR = SM_KEEP + 2048;
constexpr uint32_t BAR_FULLB = SM_BAR;
constexpr uint32_t BAR_RREADY = SM_BAR + 40;
constexpr uint32_t BAR_CLR = SM_BAR + 56;
constexpr uint32_t BAR_FULLX = SM_BAR + 72;
constexpr uint32_t BAR_EMPTYB = SM_BAR + 144;
constexpr uint32_t BAR_EMPTYX = SM_BAR + 184;
constexpr uint32_t BAR_REDDONE = SM_BAR + 248;
constexpr uint32_t BAR_DONE = SM_BAR + 264;
constexpr uint32_t BAR_WSUM = SM_BAR + 280;
constexpr uint32_t SM_PROG = SM_BAR + 288;
constexpr uint32_t SMEM_BYTES = SM_BAR + 1024;

struct Maps { CUtensorMap x, qm, qc, o, oc, g, u, g3, u3, d, out, outc; };

constexpr int INBOX = 576;
struct Group {
  uint2 sum[4 * 8 * 8];
  uint2 sq[4 * 8 * 8];
  uint32_t wsum[512];
  uint32_t flag[512];
  uint4 halo[8 * 160];
  uint4 obox[36 * 128];
  uint4 xbox[36 * 128];
  uint4 inbox[2][8 * INBOX];
};
struct Scratch { Group g[32]; uint4 wq[8][36][432]; };
__device__ __align__(1024) Scratch g_ws;
#define PROF(i)
#define PROFX(i)

#define PROF2(i) PROF(i)

struct Desc { uint32_t lo, hi; };
__device__ __forceinline__ constexpr Desc desc_hi(uint32_t lbo, uint32_t sbo, uint32_t sw) { return Desc{(lbo >> 4) << 16, (sbo >> 4) | sw << 30}; }
__device__ __forceinline__ constexpr Desc operator+(Desc d, uint32_t a) { return Desc{d.lo + a, d.hi}; }

template<int N> __device__ __forceinline__ void wgmma_ss(float (&d)[N / 2], Desc da, Desc db, int sc);
template<> __device__ __forceinline__ void wgmma_ss<192>(float (&d)[96], Desc da, Desc db, int sc) {
  asm volatile("{\n.reg .pred p;\n.reg .b64 a, b;\nsetp.ne.b32 p, %100, 0;\nmov.b64 a, {%96, %97};\nmov.b64 b, {%98, %99};\n"
    "wgmma.mma_async.sync.aligned.m64n192k16.f32.bf16.bf16 {%0,%1,%2,%3,%4,%5,%6,%7,%8,%9,%10,%11,%12,%13,%14,%15,%16,%17,%18,%19,%20,%21,%22,%23,%24,%25,%26,%27,%28,%29,%30,%31,%32,%33,%34,%35,%36,%37,%38,%39,%40,%41,%42,%43,%44,%45,%46,%47,%48,%49,%50,%51,%52,%53,%54,%55,%56,%57,%58,%59,%60,%61,%62,%63,%64,%65,%66,%67,%68,%69,%70,%71,%72,%73,%74,%75,%76,%77,%78,%79,%80,%81,%82,%83,%84,%85,%86,%87,%88,%89,%90,%91,%92,%93,%94,%95}, a, b, p, 1, 1, 0, 1;\n}\n"
    : "+f"(d[0]),"+f"(d[1]),"+f"(d[2]),"+f"(d[3]),"+f"(d[4]),"+f"(d[5]),"+f"(d[6]),"+f"(d[7]),"+f"(d[8]),"+f"(d[9]),"+f"(d[10]),"+f"(d[11]),"+f"(d[12]),"+f"(d[13]),"+f"(d[14]),"+f"(d[15]),"+f"(d[16]),"+f"(d[17]),"+f"(d[18]),"+f"(d[19]),"+f"(d[20]),"+f"(d[21]),"+f"(d[22]),"+f"(d[23]),"+f"(d[24]),"+f"(d[25]),"+f"(d[26]),"+f"(d[27]),"+f"(d[28]),"+f"(d[29]),"+f"(d[30]),"+f"(d[31]),"+f"(d[32]),"+f"(d[33]),"+f"(d[34]),"+f"(d[35]),"+f"(d[36]),"+f"(d[37]),"+f"(d[38]),"+f"(d[39]),"+f"(d[40]),"+f"(d[41]),"+f"(d[42]),"+f"(d[43]),"+f"(d[44]),"+f"(d[45]),"+f"(d[46]),"+f"(d[47]),"+f"(d[48]),"+f"(d[49]),"+f"(d[50]),"+f"(d[51]),"+f"(d[52]),"+f"(d[53]),"+f"(d[54]),"+f"(d[55]),"+f"(d[56]),"+f"(d[57]),"+f"(d[58]),"+f"(d[59]),"+f"(d[60]),"+f"(d[61]),"+f"(d[62]),"+f"(d[63]),"+f"(d[64]),"+f"(d[65]),"+f"(d[66]),"+f"(d[67]),"+f"(d[68]),"+f"(d[69]),"+f"(d[70]),"+f"(d[71]),"+f"(d[72]),"+f"(d[73]),"+f"(d[74]),"+f"(d[75]),"+f"(d[76]),"+f"(d[77]),"+f"(d[78]),"+f"(d[79]),"+f"(d[80]),"+f"(d[81]),"+f"(d[82]),"+f"(d[83]),"+f"(d[84]),"+f"(d[85]),"+f"(d[86]),"+f"(d[87]),"+f"(d[88]),"+f"(d[89]),"+f"(d[90]),"+f"(d[91]),"+f"(d[92]),"+f"(d[93]),"+f"(d[94]),"+f"(d[95]) : "r"(da.lo), "r"(da.hi), "r"(db.lo), "r"(db.hi), "r"(sc));
}
template<> __device__ __forceinline__ void wgmma_ss<256>(float (&d)[128], Desc da, Desc db, int sc) {
  asm volatile("{\n.reg .pred p;\n.reg .b64 a, b;\nsetp.ne.b32 p, %132, 0;\nmov.b64 a, {%128, %129};\nmov.b64 b, {%130, %131};\n"
    "wgmma.mma_async.sync.aligned.m64n256k16.f32.bf16.bf16 {%0,%1,%2,%3,%4,%5,%6,%7,%8,%9,%10,%11,%12,%13,%14,%15,%16,%17,%18,%19,%20,%21,%22,%23,%24,%25,%26,%27,%28,%29,%30,%31,%32,%33,%34,%35,%36,%37,%38,%39,%40,%41,%42,%43,%44,%45,%46,%47,%48,%49,%50,%51,%52,%53,%54,%55,%56,%57,%58,%59,%60,%61,%62,%63,%64,%65,%66,%67,%68,%69,%70,%71,%72,%73,%74,%75,%76,%77,%78,%79,%80,%81,%82,%83,%84,%85,%86,%87,%88,%89,%90,%91,%92,%93,%94,%95,%96,%97,%98,%99,%100,%101,%102,%103,%104,%105,%106,%107,%108,%109,%110,%111,%112,%113,%114,%115,%116,%117,%118,%119,%120,%121,%122,%123,%124,%125,%126,%127}, a, b, p, 1, 1, 0, 1;\n}\n"
    : "+f"(d[0]),"+f"(d[1]),"+f"(d[2]),"+f"(d[3]),"+f"(d[4]),"+f"(d[5]),"+f"(d[6]),"+f"(d[7]),"+f"(d[8]),"+f"(d[9]),"+f"(d[10]),"+f"(d[11]),"+f"(d[12]),"+f"(d[13]),"+f"(d[14]),"+f"(d[15]),"+f"(d[16]),"+f"(d[17]),"+f"(d[18]),"+f"(d[19]),"+f"(d[20]),"+f"(d[21]),"+f"(d[22]),"+f"(d[23]),"+f"(d[24]),"+f"(d[25]),"+f"(d[26]),"+f"(d[27]),"+f"(d[28]),"+f"(d[29]),"+f"(d[30]),"+f"(d[31]),"+f"(d[32]),"+f"(d[33]),"+f"(d[34]),"+f"(d[35]),"+f"(d[36]),"+f"(d[37]),"+f"(d[38]),"+f"(d[39]),"+f"(d[40]),"+f"(d[41]),"+f"(d[42]),"+f"(d[43]),"+f"(d[44]),"+f"(d[45]),"+f"(d[46]),"+f"(d[47]),"+f"(d[48]),"+f"(d[49]),"+f"(d[50]),"+f"(d[51]),"+f"(d[52]),"+f"(d[53]),"+f"(d[54]),"+f"(d[55]),"+f"(d[56]),"+f"(d[57]),"+f"(d[58]),"+f"(d[59]),"+f"(d[60]),"+f"(d[61]),"+f"(d[62]),"+f"(d[63]),"+f"(d[64]),"+f"(d[65]),"+f"(d[66]),"+f"(d[67]),"+f"(d[68]),"+f"(d[69]),"+f"(d[70]),"+f"(d[71]),"+f"(d[72]),"+f"(d[73]),"+f"(d[74]),"+f"(d[75]),"+f"(d[76]),"+f"(d[77]),"+f"(d[78]),"+f"(d[79]),"+f"(d[80]),"+f"(d[81]),"+f"(d[82]),"+f"(d[83]),"+f"(d[84]),"+f"(d[85]),"+f"(d[86]),"+f"(d[87]),"+f"(d[88]),"+f"(d[89]),"+f"(d[90]),"+f"(d[91]),"+f"(d[92]),"+f"(d[93]),"+f"(d[94]),"+f"(d[95]),"+f"(d[96]),"+f"(d[97]),"+f"(d[98]),"+f"(d[99]),"+f"(d[100]),"+f"(d[101]),"+f"(d[102]),"+f"(d[103]),"+f"(d[104]),"+f"(d[105]),"+f"(d[106]),"+f"(d[107]),"+f"(d[108]),"+f"(d[109]),"+f"(d[110]),"+f"(d[111]),"+f"(d[112]),"+f"(d[113]),"+f"(d[114]),"+f"(d[115]),"+f"(d[116]),"+f"(d[117]),"+f"(d[118]),"+f"(d[119]),"+f"(d[120]),"+f"(d[121]),"+f"(d[122]),"+f"(d[123]),"+f"(d[124]),"+f"(d[125]),"+f"(d[126]),"+f"(d[127]) : "r"(da.lo), "r"(da.hi), "r"(db.lo), "r"(db.hi), "r"(sc));
}
template<int N, int ACC> __device__ __forceinline__ void wgmma_rs(float (&d)[N / 2], const uint4& a, Desc db);
template<> __device__ __forceinline__ void wgmma_rs<8, 1>(float (&d)[4], const uint4& a, Desc db) {
  asm volatile("{\n.reg .pred p;\n.reg .b64 b;\nsetp.ne.b32 p, 1, 0;\nmov.b64 b, {%8, %9};\n"
    "wgmma.mma_async.sync.aligned.m64n8k16.f32.bf16.bf16 {%0,%1,%2,%3}, {%4,%5,%6,%7}, b, p, 1, 1, 1;\n}\n"
    : "+f"(d[0]),"+f"(d[1]),"+f"(d[2]),"+f"(d[3]) : "r"(a.x), "r"(a.y), "r"(a.z), "r"(a.w), "r"(db.lo), "r"(db.hi));
}
template<> __device__ __forceinline__ void wgmma_rs<8, 0>(float (&d)[4], const uint4& a, Desc db) {
  asm volatile("{\n.reg .pred p;\n.reg .b64 b;\nsetp.ne.b32 p, 0, 0;\nmov.b64 b, {%8, %9};\n"
    "wgmma.mma_async.sync.aligned.m64n8k16.f32.bf16.bf16 {%0,%1,%2,%3}, {%4,%5,%6,%7}, b, p, 1, 1, 1;\n}\n"
    : "=f"(d[0]),"=f"(d[1]),"=f"(d[2]),"=f"(d[3]) : "r"(a.x), "r"(a.y), "r"(a.z), "r"(a.w), "r"(db.lo), "r"(db.hi));
}
template<> __device__ __forceinline__ void wgmma_rs<24, 1>(float (&d)[12], const uint4& a, Desc db) {
  asm volatile("{\n.reg .pred p;\n.reg .b64 b;\nsetp.ne.b32 p, 1, 0;\nmov.b64 b, {%16, %17};\n"
    "wgmma.mma_async.sync.aligned.m64n24k16.f32.bf16.bf16 {%0,%1,%2,%3,%4,%5,%6,%7,%8,%9,%10,%11}, {%12,%13,%14,%15}, b, p, 1, 1, 1;\n}\n"
    : "+f"(d[0]),"+f"(d[1]),"+f"(d[2]),"+f"(d[3]),"+f"(d[4]),"+f"(d[5]),"+f"(d[6]),"+f"(d[7]),"+f"(d[8]),"+f"(d[9]),"+f"(d[10]),"+f"(d[11]) : "r"(a.x), "r"(a.y), "r"(a.z), "r"(a.w), "r"(db.lo), "r"(db.hi));
}
template<> __device__ __forceinline__ void wgmma_rs<24, 0>(float (&d)[12], const uint4& a, Desc db) {
  asm volatile("{\n.reg .pred p;\n.reg .b64 b;\nsetp.ne.b32 p, 0, 0;\nmov.b64 b, {%16, %17};\n"
    "wgmma.mma_async.sync.aligned.m64n24k16.f32.bf16.bf16 {%0,%1,%2,%3,%4,%5,%6,%7,%8,%9,%10,%11}, {%12,%13,%14,%15}, b, p, 1, 1, 1;\n}\n"
    : "=f"(d[0]),"=f"(d[1]),"=f"(d[2]),"=f"(d[3]),"=f"(d[4]),"=f"(d[5]),"=f"(d[6]),"=f"(d[7]),"=f"(d[8]),"=f"(d[9]),"=f"(d[10]),"=f"(d[11]) : "r"(a.x), "r"(a.y), "r"(a.z), "r"(a.w), "r"(db.lo), "r"(db.hi));
}
template<> __device__ __forceinline__ void wgmma_rs<64, 1>(float (&d)[32], const uint4& a, Desc db) {
  asm volatile("{\n.reg .pred p;\n.reg .b64 b;\nsetp.ne.b32 p, 1, 0;\nmov.b64 b, {%36, %37};\n"
    "wgmma.mma_async.sync.aligned.m64n64k16.f32.bf16.bf16 {%0,%1,%2,%3,%4,%5,%6,%7,%8,%9,%10,%11,%12,%13,%14,%15,%16,%17,%18,%19,%20,%21,%22,%23,%24,%25,%26,%27,%28,%29,%30,%31}, {%32,%33,%34,%35}, b, p, 1, 1, 1;\n}\n"
    : "+f"(d[0]),"+f"(d[1]),"+f"(d[2]),"+f"(d[3]),"+f"(d[4]),"+f"(d[5]),"+f"(d[6]),"+f"(d[7]),"+f"(d[8]),"+f"(d[9]),"+f"(d[10]),"+f"(d[11]),"+f"(d[12]),"+f"(d[13]),"+f"(d[14]),"+f"(d[15]),"+f"(d[16]),"+f"(d[17]),"+f"(d[18]),"+f"(d[19]),"+f"(d[20]),"+f"(d[21]),"+f"(d[22]),"+f"(d[23]),"+f"(d[24]),"+f"(d[25]),"+f"(d[26]),"+f"(d[27]),"+f"(d[28]),"+f"(d[29]),"+f"(d[30]),"+f"(d[31]) : "r"(a.x), "r"(a.y), "r"(a.z), "r"(a.w), "r"(db.lo), "r"(db.hi));
}
template<> __device__ __forceinline__ void wgmma_rs<64, 0>(float (&d)[32], const uint4& a, Desc db) {
  asm volatile("{\n.reg .pred p;\n.reg .b64 b;\nsetp.ne.b32 p, 0, 0;\nmov.b64 b, {%36, %37};\n"
    "wgmma.mma_async.sync.aligned.m64n64k16.f32.bf16.bf16 {%0,%1,%2,%3,%4,%5,%6,%7,%8,%9,%10,%11,%12,%13,%14,%15,%16,%17,%18,%19,%20,%21,%22,%23,%24,%25,%26,%27,%28,%29,%30,%31}, {%32,%33,%34,%35}, b, p, 1, 1, 1;\n}\n"
    : "=f"(d[0]),"=f"(d[1]),"=f"(d[2]),"=f"(d[3]),"=f"(d[4]),"=f"(d[5]),"=f"(d[6]),"=f"(d[7]),"=f"(d[8]),"=f"(d[9]),"=f"(d[10]),"=f"(d[11]),"=f"(d[12]),"=f"(d[13]),"=f"(d[14]),"=f"(d[15]),"=f"(d[16]),"=f"(d[17]),"=f"(d[18]),"=f"(d[19]),"=f"(d[20]),"=f"(d[21]),"=f"(d[22]),"=f"(d[23]),"=f"(d[24]),"=f"(d[25]),"=f"(d[26]),"=f"(d[27]),"=f"(d[28]),"=f"(d[29]),"=f"(d[30]),"=f"(d[31]) : "r"(a.x), "r"(a.y), "r"(a.z), "r"(a.w), "r"(db.lo), "r"(db.hi));
}
template<> __device__ __forceinline__ void wgmma_rs<192, 1>(float (&d)[96], const uint4& a, Desc db) {
  asm volatile("{\n.reg .pred p;\n.reg .b64 b;\nsetp.ne.b32 p, 1, 0;\nmov.b64 b, {%100, %101};\n"
    "wgmma.mma_async.sync.aligned.m64n192k16.f32.bf16.bf16 {%0,%1,%2,%3,%4,%5,%6,%7,%8,%9,%10,%11,%12,%13,%14,%15,%16,%17,%18,%19,%20,%21,%22,%23,%24,%25,%26,%27,%28,%29,%30,%31,%32,%33,%34,%35,%36,%37,%38,%39,%40,%41,%42,%43,%44,%45,%46,%47,%48,%49,%50,%51,%52,%53,%54,%55,%56,%57,%58,%59,%60,%61,%62,%63,%64,%65,%66,%67,%68,%69,%70,%71,%72,%73,%74,%75,%76,%77,%78,%79,%80,%81,%82,%83,%84,%85,%86,%87,%88,%89,%90,%91,%92,%93,%94,%95}, {%96,%97,%98,%99}, b, p, 1, 1, 1;\n}\n"
    : "+f"(d[0]),"+f"(d[1]),"+f"(d[2]),"+f"(d[3]),"+f"(d[4]),"+f"(d[5]),"+f"(d[6]),"+f"(d[7]),"+f"(d[8]),"+f"(d[9]),"+f"(d[10]),"+f"(d[11]),"+f"(d[12]),"+f"(d[13]),"+f"(d[14]),"+f"(d[15]),"+f"(d[16]),"+f"(d[17]),"+f"(d[18]),"+f"(d[19]),"+f"(d[20]),"+f"(d[21]),"+f"(d[22]),"+f"(d[23]),"+f"(d[24]),"+f"(d[25]),"+f"(d[26]),"+f"(d[27]),"+f"(d[28]),"+f"(d[29]),"+f"(d[30]),"+f"(d[31]),"+f"(d[32]),"+f"(d[33]),"+f"(d[34]),"+f"(d[35]),"+f"(d[36]),"+f"(d[37]),"+f"(d[38]),"+f"(d[39]),"+f"(d[40]),"+f"(d[41]),"+f"(d[42]),"+f"(d[43]),"+f"(d[44]),"+f"(d[45]),"+f"(d[46]),"+f"(d[47]),"+f"(d[48]),"+f"(d[49]),"+f"(d[50]),"+f"(d[51]),"+f"(d[52]),"+f"(d[53]),"+f"(d[54]),"+f"(d[55]),"+f"(d[56]),"+f"(d[57]),"+f"(d[58]),"+f"(d[59]),"+f"(d[60]),"+f"(d[61]),"+f"(d[62]),"+f"(d[63]),"+f"(d[64]),"+f"(d[65]),"+f"(d[66]),"+f"(d[67]),"+f"(d[68]),"+f"(d[69]),"+f"(d[70]),"+f"(d[71]),"+f"(d[72]),"+f"(d[73]),"+f"(d[74]),"+f"(d[75]),"+f"(d[76]),"+f"(d[77]),"+f"(d[78]),"+f"(d[79]),"+f"(d[80]),"+f"(d[81]),"+f"(d[82]),"+f"(d[83]),"+f"(d[84]),"+f"(d[85]),"+f"(d[86]),"+f"(d[87]),"+f"(d[88]),"+f"(d[89]),"+f"(d[90]),"+f"(d[91]),"+f"(d[92]),"+f"(d[93]),"+f"(d[94]),"+f"(d[95]) : "r"(a.x), "r"(a.y), "r"(a.z), "r"(a.w), "r"(db.lo), "r"(db.hi));
}
template<> __device__ __forceinline__ void wgmma_rs<192, 0>(float (&d)[96], const uint4& a, Desc db) {
  asm volatile("{\n.reg .pred p;\n.reg .b64 b;\nsetp.ne.b32 p, 0, 0;\nmov.b64 b, {%100, %101};\n"
    "wgmma.mma_async.sync.aligned.m64n192k16.f32.bf16.bf16 {%0,%1,%2,%3,%4,%5,%6,%7,%8,%9,%10,%11,%12,%13,%14,%15,%16,%17,%18,%19,%20,%21,%22,%23,%24,%25,%26,%27,%28,%29,%30,%31,%32,%33,%34,%35,%36,%37,%38,%39,%40,%41,%42,%43,%44,%45,%46,%47,%48,%49,%50,%51,%52,%53,%54,%55,%56,%57,%58,%59,%60,%61,%62,%63,%64,%65,%66,%67,%68,%69,%70,%71,%72,%73,%74,%75,%76,%77,%78,%79,%80,%81,%82,%83,%84,%85,%86,%87,%88,%89,%90,%91,%92,%93,%94,%95}, {%96,%97,%98,%99}, b, p, 1, 1, 1;\n}\n"
    : "=f"(d[0]),"=f"(d[1]),"=f"(d[2]),"=f"(d[3]),"=f"(d[4]),"=f"(d[5]),"=f"(d[6]),"=f"(d[7]),"=f"(d[8]),"=f"(d[9]),"=f"(d[10]),"=f"(d[11]),"=f"(d[12]),"=f"(d[13]),"=f"(d[14]),"=f"(d[15]),"=f"(d[16]),"=f"(d[17]),"=f"(d[18]),"=f"(d[19]),"=f"(d[20]),"=f"(d[21]),"=f"(d[22]),"=f"(d[23]),"=f"(d[24]),"=f"(d[25]),"=f"(d[26]),"=f"(d[27]),"=f"(d[28]),"=f"(d[29]),"=f"(d[30]),"=f"(d[31]),"=f"(d[32]),"=f"(d[33]),"=f"(d[34]),"=f"(d[35]),"=f"(d[36]),"=f"(d[37]),"=f"(d[38]),"=f"(d[39]),"=f"(d[40]),"=f"(d[41]),"=f"(d[42]),"=f"(d[43]),"=f"(d[44]),"=f"(d[45]),"=f"(d[46]),"=f"(d[47]),"=f"(d[48]),"=f"(d[49]),"=f"(d[50]),"=f"(d[51]),"=f"(d[52]),"=f"(d[53]),"=f"(d[54]),"=f"(d[55]),"=f"(d[56]),"=f"(d[57]),"=f"(d[58]),"=f"(d[59]),"=f"(d[60]),"=f"(d[61]),"=f"(d[62]),"=f"(d[63]),"=f"(d[64]),"=f"(d[65]),"=f"(d[66]),"=f"(d[67]),"=f"(d[68]),"=f"(d[69]),"=f"(d[70]),"=f"(d[71]),"=f"(d[72]),"=f"(d[73]),"=f"(d[74]),"=f"(d[75]),"=f"(d[76]),"=f"(d[77]),"=f"(d[78]),"=f"(d[79]),"=f"(d[80]),"=f"(d[81]),"=f"(d[82]),"=f"(d[83]),"=f"(d[84]),"=f"(d[85]),"=f"(d[86]),"=f"(d[87]),"=f"(d[88]),"=f"(d[89]),"=f"(d[90]),"=f"(d[91]),"=f"(d[92]),"=f"(d[93]),"=f"(d[94]),"=f"(d[95]) : "r"(a.x), "r"(a.y), "r"(a.z), "r"(a.w), "r"(db.lo), "r"(db.hi));
}
template<> __device__ __forceinline__ void wgmma_rs<256, 1>(float (&d)[128], const uint4& a, Desc db) {
  asm volatile("{\n.reg .pred p;\n.reg .b64 b;\nsetp.ne.b32 p, 1, 0;\nmov.b64 b, {%132, %133};\n"
    "wgmma.mma_async.sync.aligned.m64n256k16.f32.bf16.bf16 {%0,%1,%2,%3,%4,%5,%6,%7,%8,%9,%10,%11,%12,%13,%14,%15,%16,%17,%18,%19,%20,%21,%22,%23,%24,%25,%26,%27,%28,%29,%30,%31,%32,%33,%34,%35,%36,%37,%38,%39,%40,%41,%42,%43,%44,%45,%46,%47,%48,%49,%50,%51,%52,%53,%54,%55,%56,%57,%58,%59,%60,%61,%62,%63,%64,%65,%66,%67,%68,%69,%70,%71,%72,%73,%74,%75,%76,%77,%78,%79,%80,%81,%82,%83,%84,%85,%86,%87,%88,%89,%90,%91,%92,%93,%94,%95,%96,%97,%98,%99,%100,%101,%102,%103,%104,%105,%106,%107,%108,%109,%110,%111,%112,%113,%114,%115,%116,%117,%118,%119,%120,%121,%122,%123,%124,%125,%126,%127}, {%128,%129,%130,%131}, b, p, 1, 1, 1;\n}\n"
    : "+f"(d[0]),"+f"(d[1]),"+f"(d[2]),"+f"(d[3]),"+f"(d[4]),"+f"(d[5]),"+f"(d[6]),"+f"(d[7]),"+f"(d[8]),"+f"(d[9]),"+f"(d[10]),"+f"(d[11]),"+f"(d[12]),"+f"(d[13]),"+f"(d[14]),"+f"(d[15]),"+f"(d[16]),"+f"(d[17]),"+f"(d[18]),"+f"(d[19]),"+f"(d[20]),"+f"(d[21]),"+f"(d[22]),"+f"(d[23]),"+f"(d[24]),"+f"(d[25]),"+f"(d[26]),"+f"(d[27]),"+f"(d[28]),"+f"(d[29]),"+f"(d[30]),"+f"(d[31]),"+f"(d[32]),"+f"(d[33]),"+f"(d[34]),"+f"(d[35]),"+f"(d[36]),"+f"(d[37]),"+f"(d[38]),"+f"(d[39]),"+f"(d[40]),"+f"(d[41]),"+f"(d[42]),"+f"(d[43]),"+f"(d[44]),"+f"(d[45]),"+f"(d[46]),"+f"(d[47]),"+f"(d[48]),"+f"(d[49]),"+f"(d[50]),"+f"(d[51]),"+f"(d[52]),"+f"(d[53]),"+f"(d[54]),"+f"(d[55]),"+f"(d[56]),"+f"(d[57]),"+f"(d[58]),"+f"(d[59]),"+f"(d[60]),"+f"(d[61]),"+f"(d[62]),"+f"(d[63]),"+f"(d[64]),"+f"(d[65]),"+f"(d[66]),"+f"(d[67]),"+f"(d[68]),"+f"(d[69]),"+f"(d[70]),"+f"(d[71]),"+f"(d[72]),"+f"(d[73]),"+f"(d[74]),"+f"(d[75]),"+f"(d[76]),"+f"(d[77]),"+f"(d[78]),"+f"(d[79]),"+f"(d[80]),"+f"(d[81]),"+f"(d[82]),"+f"(d[83]),"+f"(d[84]),"+f"(d[85]),"+f"(d[86]),"+f"(d[87]),"+f"(d[88]),"+f"(d[89]),"+f"(d[90]),"+f"(d[91]),"+f"(d[92]),"+f"(d[93]),"+f"(d[94]),"+f"(d[95]),"+f"(d[96]),"+f"(d[97]),"+f"(d[98]),"+f"(d[99]),"+f"(d[100]),"+f"(d[101]),"+f"(d[102]),"+f"(d[103]),"+f"(d[104]),"+f"(d[105]),"+f"(d[106]),"+f"(d[107]),"+f"(d[108]),"+f"(d[109]),"+f"(d[110]),"+f"(d[111]),"+f"(d[112]),"+f"(d[113]),"+f"(d[114]),"+f"(d[115]),"+f"(d[116]),"+f"(d[117]),"+f"(d[118]),"+f"(d[119]),"+f"(d[120]),"+f"(d[121]),"+f"(d[122]),"+f"(d[123]),"+f"(d[124]),"+f"(d[125]),"+f"(d[126]),"+f"(d[127]) : "r"(a.x), "r"(a.y), "r"(a.z), "r"(a.w), "r"(db.lo), "r"(db.hi));
}
template<> __device__ __forceinline__ void wgmma_rs<256, 0>(float (&d)[128], const uint4& a, Desc db) {
  asm volatile("{\n.reg .pred p;\n.reg .b64 b;\nsetp.ne.b32 p, 0, 0;\nmov.b64 b, {%132, %133};\n"
    "wgmma.mma_async.sync.aligned.m64n256k16.f32.bf16.bf16 {%0,%1,%2,%3,%4,%5,%6,%7,%8,%9,%10,%11,%12,%13,%14,%15,%16,%17,%18,%19,%20,%21,%22,%23,%24,%25,%26,%27,%28,%29,%30,%31,%32,%33,%34,%35,%36,%37,%38,%39,%40,%41,%42,%43,%44,%45,%46,%47,%48,%49,%50,%51,%52,%53,%54,%55,%56,%57,%58,%59,%60,%61,%62,%63,%64,%65,%66,%67,%68,%69,%70,%71,%72,%73,%74,%75,%76,%77,%78,%79,%80,%81,%82,%83,%84,%85,%86,%87,%88,%89,%90,%91,%92,%93,%94,%95,%96,%97,%98,%99,%100,%101,%102,%103,%104,%105,%106,%107,%108,%109,%110,%111,%112,%113,%114,%115,%116,%117,%118,%119,%120,%121,%122,%123,%124,%125,%126,%127}, {%128,%129,%130,%131}, b, p, 1, 1, 1;\n}\n"
    : "=f"(d[0]),"=f"(d[1]),"=f"(d[2]),"=f"(d[3]),"=f"(d[4]),"=f"(d[5]),"=f"(d[6]),"=f"(d[7]),"=f"(d[8]),"=f"(d[9]),"=f"(d[10]),"=f"(d[11]),"=f"(d[12]),"=f"(d[13]),"=f"(d[14]),"=f"(d[15]),"=f"(d[16]),"=f"(d[17]),"=f"(d[18]),"=f"(d[19]),"=f"(d[20]),"=f"(d[21]),"=f"(d[22]),"=f"(d[23]),"=f"(d[24]),"=f"(d[25]),"=f"(d[26]),"=f"(d[27]),"=f"(d[28]),"=f"(d[29]),"=f"(d[30]),"=f"(d[31]),"=f"(d[32]),"=f"(d[33]),"=f"(d[34]),"=f"(d[35]),"=f"(d[36]),"=f"(d[37]),"=f"(d[38]),"=f"(d[39]),"=f"(d[40]),"=f"(d[41]),"=f"(d[42]),"=f"(d[43]),"=f"(d[44]),"=f"(d[45]),"=f"(d[46]),"=f"(d[47]),"=f"(d[48]),"=f"(d[49]),"=f"(d[50]),"=f"(d[51]),"=f"(d[52]),"=f"(d[53]),"=f"(d[54]),"=f"(d[55]),"=f"(d[56]),"=f"(d[57]),"=f"(d[58]),"=f"(d[59]),"=f"(d[60]),"=f"(d[61]),"=f"(d[62]),"=f"(d[63]),"=f"(d[64]),"=f"(d[65]),"=f"(d[66]),"=f"(d[67]),"=f"(d[68]),"=f"(d[69]),"=f"(d[70]),"=f"(d[71]),"=f"(d[72]),"=f"(d[73]),"=f"(d[74]),"=f"(d[75]),"=f"(d[76]),"=f"(d[77]),"=f"(d[78]),"=f"(d[79]),"=f"(d[80]),"=f"(d[81]),"=f"(d[82]),"=f"(d[83]),"=f"(d[84]),"=f"(d[85]),"=f"(d[86]),"=f"(d[87]),"=f"(d[88]),"=f"(d[89]),"=f"(d[90]),"=f"(d[91]),"=f"(d[92]),"=f"(d[93]),"=f"(d[94]),"=f"(d[95]),"=f"(d[96]),"=f"(d[97]),"=f"(d[98]),"=f"(d[99]),"=f"(d[100]),"=f"(d[101]),"=f"(d[102]),"=f"(d[103]),"=f"(d[104]),"=f"(d[105]),"=f"(d[106]),"=f"(d[107]),"=f"(d[108]),"=f"(d[109]),"=f"(d[110]),"=f"(d[111]),"=f"(d[112]),"=f"(d[113]),"=f"(d[114]),"=f"(d[115]),"=f"(d[116]),"=f"(d[117]),"=f"(d[118]),"=f"(d[119]),"=f"(d[120]),"=f"(d[121]),"=f"(d[122]),"=f"(d[123]),"=f"(d[124]),"=f"(d[125]),"=f"(d[126]),"=f"(d[127]) : "r"(a.x), "r"(a.y), "r"(a.z), "r"(a.w), "r"(db.lo), "r"(db.hi));
}
template<int N> __device__ __forceinline__ void wgmma_ra(float (&d)[N / 2], const uint4& a, Desc db, bool acc) {
  if (acc) wgmma_rs<N, 1>(d, a, db); else wgmma_rs<N, 0>(d, a, db);
}

__device__ __forceinline__ uint32_t smem_u32(const void* p) { return (uint32_t)__cvta_generic_to_shared(p); }
__device__ __forceinline__ void mbar_init(uint32_t bar, uint32_t cnt) { asm volatile("mbarrier.init.shared::cta.b64 [%0], %1;" ::"r"(bar), "r"(cnt)); }
__device__ __forceinline__ void mbar_expect_tx(uint32_t bar, uint32_t bytes) { asm volatile("mbarrier.arrive.expect_tx.shared::cta.b64 _, [%0], %1;" ::"r"(bar), "r"(bytes) : "memory"); }
__device__ __forceinline__ void mbar_arrive(uint32_t bar) { asm volatile("mbarrier.arrive.shared::cta.b64 _, [%0];" ::"r"(bar) : "memory"); }
__device__ __forceinline__ void mbar_arrive_remote(uint32_t rbar) { asm volatile("mbarrier.arrive.shared::cluster.b64 _, [%0];" ::"r"(rbar) : "memory"); }
__device__ __forceinline__ void mbar_wait(uint32_t bar, uint32_t parity) {
  asm volatile(
      "{\n.reg .pred p;\n.reg .u32 c;\nmov.u32 c, 0;\nLAB_WAIT:\nmbarrier.try_wait.parity.shared::cta.b64 p, [%0], %1;\n@p bra DONE;\n"
      "add.u32 c, c, 1;\nsetp.lt.u32 p, c, 1000000;\n@p bra LAB_WAIT;\ntrap;\nDONE:\n}\n" ::"r"(bar), "r"(parity) : "memory");
}
__device__ __forceinline__ void mbar_wait_c(uint32_t bar, uint32_t parity) {
  asm volatile("{\n.reg .pred p;\nLAB_WAIT:\nmbarrier.try_wait.parity.shared::cta.b64 p, [%0], %1;\n@!p bra LAB_WAIT;\n}\n" ::"r"(bar), "r"(parity) : "memory");
}
__device__ __forceinline__ uint32_t late(uint32_t bar, uint32_t v) {
  uint32_t r;
  asm volatile("{\n.reg .pred p;\nmbarrier.test_wait.parity.shared::cta.b64 p, [%1], 0;\nselp.b32 %0, %2, %1, p;\n}\n" : "=r"(r) : "r"(bar), "r"(v) : "memory");
  return r;
}
__device__ __forceinline__ void wtma2d(uint32_t dst, const CUtensorMap* m, int c0, int c1, uint32_t bar, uint64_t pol) {
  asm volatile("cp.async.bulk.tensor.2d.shared::cluster.global.mbarrier::complete_tx::bytes.multicast::cluster.L2::cache_hint [%0], [%1, {%3, %4}], [%2], %5, %6;"
               ::"r"(dst), "l"(m), "r"(bar), "r"(c0), "r"(c1), "h"((uint16_t)3), "l"(pol) : "memory");
}
__device__ __forceinline__ void wtma3d(uint32_t dst, const CUtensorMap* m, int c0, int c1, int c2, uint32_t bar, uint64_t pol) {
  asm volatile("cp.async.bulk.tensor.3d.shared::cluster.global.mbarrier::complete_tx::bytes.multicast::cluster.L2::cache_hint [%0], [%1, {%3, %4, %5}], [%2], %6, %7;"
               ::"r"(dst), "l"(m), "r"(bar), "r"(c0), "r"(c1), "r"(c2), "h"((uint16_t)3), "l"(pol) : "memory");
}
__device__ __forceinline__ void wbulk(uint32_t dst, const void* src, uint32_t bytes, uint32_t bar, uint64_t pol) {
  asm volatile("cp.async.bulk.shared::cluster.global.mbarrier::complete_tx::bytes.multicast::cluster.L2::cache_hint [%0], [%1], %2, [%3], %4, %5;"
               ::"r"(dst), "l"(src), "r"(bytes), "r"(bar), "h"((uint16_t)3), "l"(pol) : "memory");
}
__device__ __forceinline__ void tma3d(uint32_t dst, const CUtensorMap* m, int c0, int c1, int c2, uint32_t bar) {
  asm volatile("cp.async.bulk.tensor.3d.shared::cluster.global.mbarrier::complete_tx::bytes [%0], [%1, {%3, %4, %5}], [%2];"
               ::"r"(dst), "l"(m), "r"(bar), "r"(c0), "r"(c1), "r"(c2) : "memory");
}
__device__ __forceinline__ void tma_store3d(const CUtensorMap* m, uint32_t src, int c0, int c1, int c2) {
  asm volatile("cp.async.bulk.tensor.3d.global.shared::cta.bulk_group [%0, {%2, %3, %4}], [%1];" ::"l"(m), "r"(src), "r"(c0), "r"(c1), "r"(c2) : "memory");
}
__device__ __forceinline__ void prefetch_l2(const void* p, uint32_t bytes) { asm volatile("cp.async.bulk.prefetch.L2.global [%0], %1;" ::"l"(p), "r"(bytes) : "memory"); }
__device__ __forceinline__ uint64_t policy_evict_first() { uint64_t p; asm volatile("createpolicy.fractional.L2::evict_first.b64 %0, 1.0;" : "=l"(p)); return p; }
__device__ __forceinline__ uint64_t policy_evict_normal() { uint64_t p; asm volatile("createpolicy.fractional.L2::evict_normal.b64 %0, 1.0;" : "=l"(p)); return p; }
__device__ __forceinline__ void bulk_commit() { asm volatile("cp.async.bulk.commit_group;" ::: "memory"); }
__device__ __forceinline__ void bulk_wait_all() { asm volatile("cp.async.bulk.wait_group 0;" ::: "memory"); }
__device__ __forceinline__ void fence_async_smem() { asm volatile("fence.proxy.async.shared::cta;" ::: "memory"); }
__device__ __forceinline__ bool elect_one() {
  uint32_t p;
  asm volatile("{\n.reg .pred P;\nelect.sync _|P, 0xffffffff;\nselp.u32 %0, 1, 0, P;\n}\n" : "=r"(p));
  return p;
}
__device__ __forceinline__ void wg_fence() { asm volatile("wgmma.fence.sync.aligned;" ::: "memory"); }
__device__ __forceinline__ void wg_commit() { asm volatile("wgmma.commit_group.sync.aligned;" ::: "memory"); }
template <int n> __device__ __forceinline__ void wg_wait() { asm volatile("wgmma.wait_group.sync.aligned %0;" ::"n"(n) : "memory"); }
__device__ __forceinline__ void wg_bar(int w) { asm volatile("bar.sync %0, 128;" ::"r"(w + 1) : "memory"); }
__device__ __forceinline__ void cluster_sync() { asm volatile("barrier.cluster.arrive.relaxed.aligned;\nbarrier.cluster.wait.aligned;" ::: "memory"); }
__device__ __forceinline__ void fence_gpu() { asm volatile("fence.acq_rel.gpu;" ::: "memory"); }
__device__ __forceinline__ uint32_t ld_relaxed(const uint32_t* p) { uint32_t v; asm volatile("ld.relaxed.gpu.global.u32 %0, [%1];" : "=r"(v) : "l"(p) : "memory"); return v; }
__device__ __forceinline__ uint32_t ld_acquire(const uint32_t* p) { uint32_t v; asm volatile("ld.acquire.gpu.global.u32 %0, [%1];" : "=r"(v) : "l"(p) : "memory"); return v; }
__device__ __forceinline__ uint4 ld_relaxed4(const uint4* p) {
  uint4 v; asm volatile("ld.relaxed.gpu.global.v4.u32 {%0,%1,%2,%3}, [%4];" : "=r"(v.x), "=r"(v.y), "=r"(v.z), "=r"(v.w) : "l"(p) : "memory"); return v;
}
__device__ __forceinline__ uint2 ld_relaxed2(const uint2* p) {
  uint2 v; asm volatile("ld.relaxed.gpu.global.v2.u32 {%0,%1}, [%2];" : "=r"(v.x), "=r"(v.y) : "l"(p) : "memory"); return v;
}
__device__ __forceinline__ void st_relaxed(uint32_t* p, uint32_t a) { asm volatile("st.relaxed.gpu.global.u32 [%0], %1;" ::"l"(p), "r"(a) : "memory"); }
__device__ __forceinline__ void st_relaxed4(uint4* p, uint32_t a, uint32_t b, uint32_t c, uint32_t d) {
  asm volatile("st.relaxed.gpu.global.v4.u32 [%0], {%1,%2,%3,%4};" ::"l"(p), "r"(a), "r"(b), "r"(c), "r"(d) : "memory");
}
__device__ __forceinline__ void st_relaxed2(uint2* p, uint32_t a, uint32_t b) {
  asm volatile("st.relaxed.gpu.global.v2.u32 [%0], {%1,%2};" ::"l"(p), "r"(a), "r"(b) : "memory");
}
__device__ __forceinline__ void red4(uint4* p, uint32_t a, uint32_t b, uint32_t c, uint32_t d) {
  asm volatile("red.relaxed.gpu.global.add.noftz.v4.bf16x2 [%0], {%1,%2,%3,%4};" ::"l"(p), "r"(a), "r"(b), "r"(c), "r"(d) : "memory");
}
__device__ __forceinline__ void red2(uint2* p, uint32_t a, uint32_t b) {
  asm volatile("red.relaxed.gpu.global.add.noftz.v2.bf16x2 [%0], {%1,%2};" ::"l"(p), "r"(a), "r"(b) : "memory");
}
constexpr int SPIN_MAX = 1 << 21;
__device__ __forceinline__ uint32_t pack_bf16(float lo, float hi) { uint32_t r; asm("cvt.rn.bf16x2.f32 %0, %1, %2;" : "=r"(r) : "f"(hi), "f"(lo)); return r; }
__device__ __forceinline__ float bf_lo(uint32_t v) { return __uint_as_float(v << 16); }
__device__ __forceinline__ float bf_hi(uint32_t v) { return __uint_as_float(v & 0xffff0000u); }
__device__ __forceinline__ float2 lds64(uint32_t a) { float2 v; asm volatile("ld.shared.v2.f32 {%0,%1}, [%2];" : "=f"(v.x), "=f"(v.y) : "r"(a)); return v; }
__device__ __forceinline__ uint32_t lds32(uint32_t a) { uint32_t v; asm volatile("ld.shared.b32 %0, [%1];" : "=r"(v) : "r"(a)); return v; }
__device__ __forceinline__ void sts64f(uint32_t a, float x, float y) { asm volatile("st.shared.v2.f32 [%0], {%1,%2};" ::"r"(a), "f"(x), "f"(y) : "memory"); }
__device__ __forceinline__ void sts32(uint32_t a, uint32_t x) { asm volatile("st.volatile.shared.b32 [%0], %1;" ::"r"(a), "r"(x) : "memory"); }
__device__ __forceinline__ void gate(uint32_t a, int need) {
#pragma unroll 1
  for (int it = 0; it < SPIN_MAX; it++) {
    int v; asm volatile("ld.volatile.shared.b32 %0, [%1];" : "=r"(v) : "r"(a) : "memory");
    if (v >= need) break;
    if (GSLEEP) __nanosleep(GSLEEP);
  }
}
__device__ __forceinline__ void sts128(uint32_t a, uint32_t x, uint32_t y, uint32_t z, uint32_t u) { asm volatile("st.shared.v4.b32 [%0], {%1,%2,%3,%4};" ::"r"(a), "r"(x), "r"(y), "r"(z), "r"(u) : "memory"); }
__device__ __forceinline__ uint4 lds128(uint32_t a) { uint4 v; asm volatile("ld.shared.v4.u32 {%0,%1,%2,%3}, [%4];" : "=r"(v.x), "=r"(v.y), "=r"(v.z), "=r"(v.w) : "r"(a) : "memory"); return v; }
__device__ __forceinline__ uint32_t hmul2(uint32_t a, uint32_t b) { uint32_t r; asm("mul.rn.bf16x2 %0, %1, %2;" : "=r"(r) : "r"(a), "r"(b)); return r; }
__device__ __forceinline__ uint32_t hadd2(uint32_t a, uint32_t b) { uint32_t r; asm("add.rn.bf16x2 %0, %1, %2;" : "=r"(r) : "r"(a), "r"(b)); return r; }
__device__ __forceinline__ void stsm4(uint32_t a, uint32_t r0, uint32_t r1, uint32_t r2, uint32_t r3) {
  asm volatile("stmatrix.sync.aligned.m8n8.x4.shared.b16 [%0], {%1,%2,%3,%4};" ::"r"(a), "r"(r0), "r"(r1), "r"(r2), "r"(r3) : "memory");
}
__device__ __forceinline__ void stsm2(uint32_t a, uint32_t r0, uint32_t r1) {
  asm volatile("stmatrix.sync.aligned.m8n8.x2.shared.b16 [%0], {%1,%2};" ::"r"(a), "r"(r0), "r"(r1) : "memory");
}
__device__ __forceinline__ uint4 ldsm4(uint32_t a) {
  uint4 r; asm volatile("ldmatrix.sync.aligned.m8n8.x4.shared.b16 {%0,%1,%2,%3}, [%4];" : "=r"(r.x), "=r"(r.y), "=r"(r.z), "=r"(r.w) : "r"(a) : "memory"); return r;
}
__device__ __forceinline__ uint32_t movm(uint32_t a) { uint32_t r; asm("movmatrix.sync.aligned.m8n8.trans.b16 %0, %1;" : "=r"(r) : "r"(a)); return r; }
__device__ __forceinline__ void mma16816z(float (&d)[4], uint32_t a0, uint32_t a1, uint32_t a2, uint32_t a3, uint32_t b0, uint32_t b1) {
  asm("mma.sync.aligned.m16n8k16.row.col.f32.bf16.bf16.f32 {%0,%1,%2,%3}, {%4,%5,%6,%7}, {%8,%9}, {%10,%10,%10,%10};"
      : "=f"(d[0]), "=f"(d[1]), "=f"(d[2]), "=f"(d[3]) : "r"(a0), "r"(a1), "r"(a2), "r"(a3), "r"(b0), "r"(b1), "f"(0.f));
}
__device__ __forceinline__ void mma16816(float (&d)[4], const uint4& a, uint32_t b0, uint32_t b1) {
  asm("mma.sync.aligned.m16n8k16.row.col.f32.bf16.bf16.f32 {%0,%1,%2,%3}, {%4,%5,%6,%7}, {%8,%9}, {%0,%1,%2,%3};"
      : "+f"(d[0]), "+f"(d[1]), "+f"(d[2]), "+f"(d[3]) : "r"(a.x), "r"(a.y), "r"(a.z), "r"(a.w), "r"(b0), "r"(b1));
}
__device__ __forceinline__ void mma1688(float (&d)[4], uint32_t a0, uint32_t a1, uint32_t b0) {
  asm("mma.sync.aligned.m16n8k8.row.col.f32.bf16.bf16.f32 {%0,%1,%2,%3}, {%4,%5}, {%6}, {%0,%1,%2,%3};"
      : "+f"(d[0]), "+f"(d[1]), "+f"(d[2]), "+f"(d[3]) : "r"(a0), "r"(a1), "r"(b0));
}
__device__ __forceinline__ float quad_sum(float v) { v += __shfl_xor_sync(0xffffffffu, v, 1); v += __shfl_xor_sync(0xffffffffu, v, 2); return v; }
__device__ __forceinline__ float quad_max(float v) { v = fmaxf(v, __shfl_xor_sync(0xffffffffu, v, 1)); v = fmaxf(v, __shfl_xor_sync(0xffffffffu, v, 2)); return v; }
__device__ __forceinline__ float rcp(float x) { float r; asm("rcp.approx.ftz.f32 %0, %1;" : "=f"(r) : "f"(x)); return r; }
__device__ __forceinline__ float rsq(float x) { float r; asm("rsqrt.approx.ftz.f32 %0, %1;" : "=f"(r) : "f"(x)); return r; }
__device__ __forceinline__ float ex2(float x) { float r; asm("ex2.approx.ftz.f32 %0, %1;" : "=f"(r) : "f"(x)); return r; }
__device__ __forceinline__ uint32_t chk(uint32_t acc, uint32_t v, uint32_t tag) { uint32_t r; asm("lop3.b32 %0, %1, %2, %3, 0xF6;" : "=r"(r) : "r"(acc), "r"(v), "r"(tag)); return r; }
__device__ __forceinline__ uint32_t chk2(uint32_t a, uint32_t b, uint32_t tag) { uint32_t r; asm("lop3.b32 %0, %1, %2, %3, 0x7E;" : "=r"(r) : "r"(a), "r"(b), "r"(tag)); return r; }
__device__ __forceinline__ uint32_t tagged(uint32_t v, uint32_t tag) { return (v & ~1u) | tag; }

__device__ __forceinline__ int group_k0(int g, int j) {
  const int h = g >= 9, r = g - 2 - 7 * h;
  return g < 2 ? 64 * j + 32 * g : g < 16 ? 64 * (r + (r >= j)) + 32 * h : 32 * g;
}
__device__ __forceinline__ uint32_t xin_off(int c, int w) { return SM_X + (2 * c + w + (2 * c + w < 9 ? 9 : -9)) * 8192; }
__device__ __forceinline__ uint32_t xin_bar(int c) { return BAR_FULLX + 8 * (c < 8 ? c ^ 4 : c); }
__device__ __forceinline__ constexpr uint32_t qkv_xslot(int g) { return g < 5 || g > 11 ? 2 : (0x5140762u >> (4 * (g - 5))) & 15; }

template <int N> struct IC { static constexpr int v = N; };

struct Cons {
  uint32_t sb;
  uint32_t rem;
  uint32_t sB, mB;
  uint32_t mX;
  bool elect;
  __device__ __forceinline__ void release2(uint32_t bar) const { if (elect) { mbar_arrive(sb + bar); mbar_arrive_remote(rem + bar); } }
  __device__ __forceinline__ uint32_t nextB(uint32_t& prev) {
    mbar_wait_c(sb + BAR_FULLB + sB, mB);
    const uint32_t a = (((sb & 0x3FFFF) + SM_B) >> 4) + sB * (BSLOT / 128);
    prev = sB == 0 ? 32 : sB - 8;
    sB += 8;
    if (sB == 40) { sB = 0; mB ^= 1; }
    return a;
  }
  __device__ __forceinline__ void progress(uint32_t v) const { if (elect) sts32(sb + SM_PROG + (threadIdx.x >> 5), v); }
  __device__ __forceinline__ void releaseLastB() const { release2(BAR_EMPTYB + (sB == 0 ? 32 : sB - 8)); }
};

__device__ __forceinline__ float2 gather_sums(const uint2* a, uint32_t stag) {
  uint2 sa, sc;
  do { sa = ld_relaxed2(a); sc = ld_relaxed2(a + 8); } while (__any_sync(0xffffffffu, chk2(sa.x, sc.x, stag) & 3));
  return make_float2(quad_sum(__uint_as_float(sa.x) + __uint_as_float(sc.x)), quad_sum(__uint_as_float(sa.y) + __uint_as_float(sc.y)));
}

struct Norm {
  float m0, m1;
  uint32_t nm0, nm1;
  float d0, d1;
  uint2 u0, u1;
  __device__ __forceinline__ Norm(float2 sum) : m0(sum.x * (-1.f / 576)), m1(sum.y * (-1.f / 576)), nm0(pack_bf16(m0, m0)), nm1(pack_bf16(m1, m1)), d0(0.f), d1(0.f) {}
  __device__ __forceinline__ uint4 centre(const uint4& a) const { return make_uint4(hadd2(a.x, nm0), hadd2(a.y, nm1), hadd2(a.z, nm0), hadd2(a.w, nm1)); }
  __device__ __forceinline__ void sqr(uint32_t a, uint32_t b) {
    d0 = fmaf(bf_lo(a), bf_lo(a), fmaf(bf_hi(a), bf_hi(a), d0)); d1 = fmaf(bf_lo(b), bf_lo(b), fmaf(bf_hi(b), bf_hi(b), d1));
  }
  __device__ __forceinline__ void send(uint2* a, int t, uint32_t stag) {
    d0 = quad_sum(d0); d1 = quad_sum(d1);
    if ((t & 3) == 0) st_relaxed2(a, (__float_as_uint(d0) & ~3u) | stag, __float_as_uint(d1));
  }
  __device__ __forceinline__ void fetch(const uint2* a) { u0 = ld_relaxed2(a); u1 = ld_relaxed2(a + 8); }
  __device__ __forceinline__ float2 rstd(const uint2* a, uint32_t stag) {
    while (__any_sync(0xffffffffu, chk2(u0.x, u1.x, stag) & 3)) fetch(a);
    const float e0 = bf_lo(nm0) - m0, e1 = bf_lo(nm1) - m1;
    const float v0 = fmaf(quad_sum(__uint_as_float(u0.x) + __uint_as_float(u1.x)), 1.f / 576, -e0 * e0);
    const float v1 = fmaf(quad_sum(__uint_as_float(u0.y) + __uint_as_float(u1.y)), 1.f / 576, -e1 * e1);
    float2 r = make_float2(rsq(fmaxf(v0, 0.f) + 1e-5f), rsq(fmaxf(v1, 0.f) + 1e-5f));
    asm volatile("" : "+f"(r.x), "+f"(r.y));
    return r;
  }
};

template <class Pre, class Mma>
__device__ __forceinline__ float2 ln_gemm_in(Cons& c, Group* G, uint32_t (&p)[18], float2& sum, int w, int st0, int j, int t, Pre&& pre, Mma&& mma) {
  const uint32_t xa = c.sb + (t >> 5) * 2048 + (t & 15) * 128, sw = (((t >> 4) & 1) ^ (t & 7)) * 16;
  float ra[4] = {0.f, 0.f, 0.f, 0.f}, rb[4] = {0.f, 0.f, 0.f, 0.f};
#pragma unroll 1
  for (int cc = 0; cc < 9; cc++) {
    const uint32_t a = xa + xin_off(cc, w);
    mbar_wait_c(c.sb + xin_bar(cc), 0);
    const uint4 u0 = ldsm4(a + sw), u1 = ldsm4(a + (sw ^ 32)), u2 = ldsm4(a + (sw ^ 64)), u3 = ldsm4(a + (sw ^ 96));
    mma16816(ra, u0, 0x3f803f80u, 0x3f803f80u); mma16816(rb, u1, 0x3f803f80u, 0x3f803f80u);
    mma16816(ra, u2, 0x3f803f80u, 0x3f803f80u); mma16816(rb, u3, 0x3f803f80u, 0x3f803f80u);
  }
  sum = make_float2(ra[0] + rb[0], ra[2] + rb[2]);
  pre(0);
  Norm n(sum);
  n.u0 = n.u1 = make_uint2(0, 0);
  auto stats = [&] {
#pragma unroll
    for (int k = 0; k < 5; k++) {
      const uint4 u = ldsm4(xa + (k < 4 ? xin_off(j, w) + (sw ^ (32 * k)) : xin_off(8, w) + ((j ^ (t & 7)) << 4))), e = n.centre(u);
      p[4 * k] = u.x; p[4 * k + 1] = u.y;
      n.sqr(e.x, e.y);
      if (k < 4) { p[4 * k + 2] = u.z; p[4 * k + 3] = u.w; n.sqr(e.z, e.w); }
    }
    n.send(G->sq + st0 + 8 * j, t, 1);
  };
  if (STATP < 0) stats();
  else {
#pragma unroll
    for (int i = 0; i < 18; i++) p[i] = 0;
  }
  pre(1);
  uint4 y0 = ldsm4(xa + xin_off(0, w) + sw), y1 = ldsm4(xa + xin_off(0, w) + (sw ^ 32));
#pragma unroll 1
  for (int cc = 0; cc < 9; cc++) {
#pragma unroll
    for (int i = 0; i < 2; i++) {
      const uint4 f0 = n.centre(y0), f1 = n.centre(y1);
      const uint32_t a = xa + xin_off(min(cc + i, 8), w);
      y0 = ldsm4(a + (sw ^ (64 - 64 * i))); y1 = ldsm4(a + (sw ^ (96 - 64 * i)));
      uint32_t prev;
      const uint32_t bb = c.nextB(prev);
      mma(true, bb, f0, f1);
      if (i == 1) {
        if (STATP >= 0 && cc == STATP * w) stats();
        if (cc == 1) c.progress(3);
        if (cc == 7) n.fetch(G->sq + st0 + 16 * (t & 3));
        if (cc == 8 && w == 0) asm volatile("bar.arrive 6, 256;" ::: "memory");
      }
      wg_wait<1>();
      if (i + cc > 0) c.release2(BAR_EMPTYB + prev);
      if (2 * cc + i >= WOG && 2 * cc + i < WOG + 4) c.release2(BAR_EMPTYX + 32 + 8 * (2 * cc + i - WOG));
    }
  }
  c.mX = 0xff;
  const float2 r = n.rstd(G->sq + st0 + 16 * (t & 3), 1);
  if (w == 1) asm volatile("bar.sync 6, 256;" ::: "memory");
  wg_wait<0>();
  c.releaseLastB();
  c.release2(BAR_EMPTYX + 24);
  return r;
}

template <bool QKV, class Pre, class Mma>
__device__ __forceinline__ float2 ln_gemm(Cons& c, Group* G, const float (&v)[36], uint32_t (&p)[18], float2& sum, int st0, int j, int t,
                                          int layer, uint32_t tag, Pre&& pre, Mma&& mma) {
  constexpr bool known = !QKV && EARLY;
  const uint32_t stag = (2 * layer + (QKV ? 1 : 2)) & 3;
  uint4 x[6][2];
  uint4* src = G->xbox + t;
  asm volatile("" : "+l"(src));
  auto buf = [&](int g) -> uint4 (&)[2] { return x[g < 16 ? (g - 2) % 6 : g - 13]; };
  auto load = [&](int g0) {
#pragma unroll
    for (int g = g0; g < g0 + (g0 < 14 ? 3 : 2); g++) {
      const uint4* a = g < 16 ? src + ((g - 2) % 7 >= j ? 256 : 0) + (2 * ((g - 2) % 7) + 16 * (g >= 9)) * 128 : src + 2 * g * 128;
      buf(g)[0] = ld_relaxed4(a); buf(g)[1] = ld_relaxed4(a + 128);
    }
  };
  auto invalid = [&](int g, uint32_t tag) {
    uint32_t bad = chk(chk(chk2(buf(g)[0].x, buf(g)[1].x, tag), buf(g + 1)[0].x, tag), buf(g + 1)[1].x, tag);
    if (g < 14) bad = chk(chk(bad, buf(g + 2)[0].x, tag), buf(g + 2)[1].x, tag);
    if (g == 16) bad = chk(chk(chk(chk(bad, buf(g)[0].z, tag), buf(g)[1].z, tag), buf(g + 1)[0].z, tag), buf(g + 1)[1].z, tag);
    return __any_sync(0xffffffffu, bad & 1);
  };
  uint4* const d = src + 2 * j * 128;
  const int sq = st0 + 16 * (t & 3);
  if (!known) {
    float s0 = v[0] + v[1], s1 = v[2] + v[3];
#pragma unroll
    for (int i = 1; i < 9; i++) { s0 += v[4 * i] + v[4 * i + 1]; s1 += v[4 * i + 2] + v[4 * i + 3]; }
    s0 = quad_sum(s0); s1 = quad_sum(s1);
    if ((t & 3) == 0) st_relaxed2(G->sum + st0 + 8 * j, (__float_as_uint(s0) & ~3u) | stag, __float_as_uint(s1));
  }
#pragma unroll
  for (int i = 0; i < 18; i++) p[i] = pack_bf16(v[2 * i], v[2 * i + 1]);
#pragma unroll
  for (int i = 0; i < 2; i++) st_relaxed4(d + i * 128, tagged(p[4 * i], tag), p[4 * i + 1], p[4 * i + 2], p[4 * i + 3]);
  pre(0);
  if (!known) {
    sum = gather_sums(G->sum + sq, stag);
    load(2);
  }
  Norm n(sum);
  pre(1);
  const uint32_t* probe = &(G->xbox + (2 * (t & 7) + 1) * 128 + (t | 31))->x;
  uint32_t pv;
  auto inx = [](int g) { return QKV && ((g >= 5 && g < 12) || g == 17); };
  auto use = [](int g) { return QKV ? (g < 5 ? 108 : 101) + g : 18 + g; };
#pragma unroll
  for (int g = 0; g < 18; g++) {
    if (g < 16 ? g % 3 == 2 : g == 16) {
      const uint32_t lt = late(c.sb + BAR_FULLX + 64, tag);
      while (invalid(g, lt)) load(g);
      if (g < 16) load(g < 14 ? g + 3 : 16);
    }
    const uint4 f0 = n.centre(g < 2 ? make_uint4(p[8 * g], p[8 * g + 1], p[8 * g + 2], p[8 * g + 3]) : buf(g)[0]);
    const uint4 f1 = n.centre(g < 2 ? make_uint4(p[8 * g + 4], p[8 * g + 5], p[8 * g + 6], p[8 * g + 7]) : buf(g)[1]);
    if (g == 14) n.fetch(G->sq + sq);
    if (inx(g)) mbar_wait_c(c.sb + BAR_FULLX + 8 * qkv_xslot(g), ((0x34 >> qkv_xslot(g)) & 1) ^ (g == 17));
    else mbar_wait_c(c.sb + BAR_FULLB + 8 * (use(g) % 5), (use(g) / 5) & 1);
    mma(g, ((c.sb & 0x3FFFF) >> 4) + ((inx(g) ? SM_X + qkv_xslot(g) * XSLOT : SM_B + (use(g) % 5) * BSLOT) >> 4), f0, f1);
    if (g < 2) {
      if (known) {
        if (g == 0) {
          pv = ld_relaxed(probe);
        } else {
          const uint32_t lt = late(c.sb + BAR_FULLX + 64, tag);
          while (__any_sync(0xffffffffu, (pv ^ lt) & 1)) pv = ld_relaxed(probe);
          load(2);
        }
      }
      if (g == (known ? 1 : 0)) {
#pragma unroll
        for (int i = 2; i < 4; i++) st_relaxed4(d + (14 + i) * 128, tagged(p[4 * i], tag), p[4 * i + 1], p[4 * i + 2], p[4 * i + 3]);
        st_relaxed2((uint2*)(src + (32 + (j >> 1)) * 128) + (j & 1), tagged(p[16], tag), p[17]);
      }
      n.sqr(f0.x, f0.y); n.sqr(f0.z, f0.w); n.sqr(f1.x, f1.y); n.sqr(f1.z, f1.w);
      if (g == 1) {
        n.sqr(hadd2(p[16], n.nm0), hadd2(p[17], n.nm1));
        n.send(G->sq + st0 + 8 * j, t, stag);
      }
    }
    wg_wait<1>();
    if (g > 0 && !inx(g - 1)) c.release2(BAR_EMPTYB + 8 * (use(g - 1) % 5));
    if (QKV && g < 13) c.progress(33 + g);
    if (QKV && g == WOG - 1) c.release2(BAR_EMPTYX + 8 * qkv_xslot(17));
    if (QKV && g >= WOG && g < WOG + 4) c.release2(BAR_EMPTYX + 32 + 8 * (g - WOG));
  }
  if (QKV) c.mX = 0x34 ^ 0xf3;
  else { c.sB = 8 * (36 % 5); c.mB = (36 / 5) & 1; }
  const float2 r = n.rstd(G->sq + sq, late(c.sb + BAR_FULLX + 64, stag));
  wg_wait<0>();
  if (!QKV) c.release2(BAR_EMPTYB + 8 * (use(17) % 5));
  return r;
}

template <int NB, int OFF>
__device__ __forceinline__ void glu(const float (&a)[128], uint32_t (&h)[144]) {
#pragma unroll
  for (int b = 0; b < 2 * NB; b++) {
    if (HMUL) h[OFF + b] = hmul2(pack_bf16(a[2 * b], a[2 * b + 1]), pack_bf16(a[4 * NB + 2 * b], a[4 * NB + 2 * b + 1]));
    else h[OFF + b] = pack_bf16(a[2 * b] * a[4 * NB + 2 * b], a[2 * b + 1] * a[4 * NB + 2 * b + 1]);
  }
}

__global__ void __cluster_dims__(2, 1, 1) __launch_bounds__(384, 1)
fused_kernel(const __nv_bfloat16* __restrict__ x_in, Group* ws, const char* __restrict__ wqkv,
             const char* __restrict__ wg, const char* __restrict__ wu, const char* __restrict__ wd, const __grid_constant__ Maps maps,
             const char* __restrict__ wo) {
  extern __shared__ __align__(1024) uint8_t smem_raw[];
  const uint32_t sb = smem_u32(smem_raw);
  if (blockIdx.x >= NCTA) {
    const uint32_t par = ~ld_relaxed(ws->flag + 32) & 1;
#pragma unroll 1
    for (int i = 0; i < RDELAY; i++) __nanosleep(1000);
    const int cc = threadIdx.x % 54, r0 = threadIdx.x / 54, part = cc / 18, jj = 2 * (blockIdx.x - NCTA) + (cc % 18) / 9, c9 = cc % 9;
    if (r0 < 6) {
#pragma unroll 4
      for (int k = r0; k < 576; k += 6) {
        const uint4 u = __ldg((const uint4*)(wqkv + k * 3456 + part * 1152 + 144 * jj) + c9);
        ((Scratch*)ws)->wq[jj][k >> 4][c9 < 8 ? part * 128 + (k & 15) * 8 + (c9 ^ (k & 7)) : 384 + part * 16 + (k & 15)] = u;
      }
    }
    fence_gpu();
    __syncthreads();
    if (threadIdx.x < 2) st_relaxed(ws[2 * (blockIdx.x - NCTA) + threadIdx.x].wsum + 128, par);
    return;
  }
  if (threadIdx.x == 0) asm volatile("prefetch.tensormap [%0];" ::"l"(&maps.x) : "memory");
  const int warp = __shfl_sync(0xffffffffu, threadIdx.x >> 5, 0);
  const int lane = threadIdx.x & 31;
  const int rank = blockIdx.x & 1;
  if (elect_one()) {
    if (warp >= 8) {
#pragma unroll
      for (int i = 0; i < 9; i++) mbar_init(sb + SM_BAR + 72 * (warp - 8) + 8 * i, warp < 10 ? 1 : 4);
      sts32(sb + SM_PROG + 4 * (warp - 8), 0);
      asm volatile("fence.mbarrier_init.release.cluster;" ::: "memory");
    } else if (warp == 1 || warp == 2) {
      asm volatile("prefetch.tensormap [%0];" ::"l"(&maps.x + warp) : "memory");
    } else if (warp == 3) {
      if (PFMODE & 1) prefetch_l2((const char*)x_in + blockIdx.x * 18432, 18432);
    } else if (warp == 4) {
      if (PFMODE & 2) prefetch_l2(wqkv + blockIdx.x * (15552 / PFQ), 15552 / PFQ);
    }
  }
  __syncwarp();
  asm volatile("barrier.cluster.arrive.relaxed.aligned;" ::: "memory");
  if (warp == 8) PROFX(53);
  int lb = blockIdx.x;
  if (GPCMAP) {
    const int cl = blockIdx.x >> 1, u = cl - 36;
    lb = (cl < 4 ? cl : cl < 36 ? 8 * ((cl - 4) & 7) + ((cl - 4) >> 3) + (((cl - 4) & 7) ? 0 : 4) : 8 * (1 + u % 7) + 4 + u / 7) * 2 + rank;
  }
#define CTA_J(b) (((b) >> 1) & 7)
#define CTA_RB(b) ((((b) >> 4) << 1) | ((b) & 1))
  const int j = CTA_J(lb), rb = CTA_RB(lb);

  PROF(23);
  if (warp >= 8) {
    asm volatile("setmaxnreg.dec.sync.aligned.u32 " STR(REGS_P) ";");
    auto x_chunk = [&](int cc) {
      mbar_expect_tx(sb + xin_bar(cc), 16384);
      tma3d(sb + xin_off(cc, 0), &maps.x, 64 * cc, 0, 64 * rb, sb + xin_bar(cc));
      tma3d(sb + xin_off(cc, 1), &maps.x, 64 * cc, 1, 64 * rb, sb + xin_bar(cc));
    };
    if (warp == 9 && elect_one()) {
      fence_async_smem();
#pragma unroll 1
      for (int i = 0; i < 9; i++) x_chunk(i);
    }
    __syncwarp();
    if (warp == 9) PROFX(54);
    asm volatile("barrier.cluster.wait.aligned;" ::: "memory");
    if (warp == 8) PROFX(56);
    const uint64_t pol = W_POLICY(), pola = A_POLICY();
    uint4 (* const wq)[432] = ((Scratch*)ws)->wq[j];
    const uint32_t par = ~ld_relaxed(ws[2 * rb].flag + 32 + 32 * j) & 1;
    auto qkv_group = [&](bool copy, int k, uint32_t dst, uint32_t bar) {
      if (copy && gridDim.x > NCTA) {
        wbulk(dst + rank * 8192, wq[(k >> 4) + rank], 6912, bar, pol);
      } else {
        wtma3d(dst + rank * 8192, &maps.qm, 72 * j, k + 16 * rank, 0, bar, pola);
        wtma3d(dst + rank * 8192 + 6144, &maps.qc, 72 * j + 64, k + 16 * rank, 0, bar, pola);
      }
    };
    auto repacked = [&] {
#pragma unroll 1
      for (int it = 0; it < SPIN_MAX && gridDim.x > NCTA; it++)
        if (ld_acquire(ws[j].wsum + 128) == par) break;
      asm volatile("fence.proxy.async.global;" ::: "memory");
    };
    const int ktab = group_k0(lane, j);
    auto qkv_gate = [&](int g) { if (g >= 8) gate(sb + SM_PROG, 33 + ((g - 8) * QPACE >> 4)); };
    if (warp == 8) {
      uint32_t s = 0, ph = 1;
      auto slot = [&](uint32_t bytes, auto&& issue) {
        const uint32_t bar = sb + BAR_FULLB + 8 * s;
        mbar_wait(sb + BAR_EMPTYB + 8 * s, ph);
        if (elect_one()) {
          mbar_expect_tx(bar, bytes);
          issue(sb + SM_B + s * BSLOT, bar);
        }
        if (++s == 5) { s = 0; ph ^= 1; }
      };
#pragma unroll 1
      for (int layer = 0; layer < NLAYERS; layer++) {
        if (layer) repacked();
#pragma unroll 1
        for (int g = 0; g < 18 - layer; g += layer && g == 4 ? 8 : 1) {
          const int k = layer ? __shfl_sync(0xffffffffu, ktab, g) : 32 * g;
          if (layer) qkv_gate(g);
          else if (g == QD) mbar_wait(sb + xin_bar(XH), 0);
          slot(2 * 6912, [&](uint32_t dst, uint32_t bar) { qkv_group(layer, k, dst, bar); });
        }
        if (!FCH) {
          gate(sb + SM_PROG, 32 * layer + 20);
          gate(sb + SM_PROG + 4, 32 * layer + 20);
        }
#pragma unroll 1
        for (int t = 0; t < 5; t++) {
          const CUtensorMap* m = &maps.g + (t < 3 ? rank : 2 + rank);
          asm volatile("" : "+l"(m));
          const int c2 = t < 3 ? 9 * j + 2 * t : 18 * j + 3 + 3 * t;
          const uint32_t half = t < 3 ? 8192 : 6144;
          auto tile = [&](int g) {
            const int k = __shfl_sync(0xffffffffu, ktab, g);
            slot(2 * half, [&](uint32_t dst, uint32_t bar) { wtma3d(dst + rank * half, m, 0, k, c2, bar, pol); });
          };
          int g = 0;
          if (t == 0) {
#pragma unroll 1
            for (; g < 5; g++) {
              mbar_wait(sb + BAR_FULLB + 8 * (s < FCH ? s + 5 - FCH : s - FCH), s < FCH ? ph : ph ^ 1);
              if (FG >= 0 && g == FN) gate(sb + SM_PROG + 4, 32 * layer + 20);
              tile(g);
            }
          }
#pragma unroll 1
          for (; g < 18; g++) tile(g);
        }
      }
    } else if (warp == 9) {
      uint32_t mE = 0;
      auto acquire = [&](uint32_t s) { mbar_wait(sb + BAR_EMPTYX + 8 * s, (mE >> s) & 1); mE ^= 1u << s; };
      auto landed = [&](uint32_t s) { mbar_wait(sb + BAR_FULLX + 8 * s, (mE >> s) & 1); };
      auto slot = [&](uint32_t s, const CUtensorMap* m, int col, int row, uint64_t pol) {
        acquire(s);
        if (elect_one()) {
          mbar_expect_tx(sb + BAR_FULLX + 8 * s, XSLOT);
          wtma2d(sb + SM_X + s * XSLOT + rank * 9216, m, col, row + 72 * rank, sb + BAR_FULLX + 8 * s, pol);
        }
      };
#pragma unroll 1
      for (int layer = 0; layer < NLAYERS; layer++) {
        if (layer) repacked();
#pragma unroll 1
        for (int g = 5; g < 18 * layer; g += g == 11 ? 6 : 1) {
          const uint32_t s = qkv_xslot(g);
          const int k = __shfl_sync(0xffffffffu, ktab, g);
          if (g < 12) qkv_gate(g);
          acquire(s);
          if (elect_one()) {
            mbar_expect_tx(sb + BAR_FULLX + 8 * s, 2 * 6912);
            qkv_group(true, k, sb + SM_X + s * XSLOT, sb + BAR_FULLX + 8 * s);
          }
          if (XCH & 1) landed(s);
        }
#pragma unroll 1
        for (int i = 0; i < 4; i++) { slot(4 + i, &maps.o, 64 * j, 144 * i, pola); if (XCH & 2) landed(4 + i); }
        acquire(3);
        if (elect_one()) {
          mbar_expect_tx(sb + BAR_FULLX + 24, 9216);
          wtma2d(sb + SM_WOC + rank * 4608, &maps.oc, 512 + 8 * j, 288 * rank, sb + BAR_FULLX + 24, pola);
          wtma2d(sb + SM_WOC + rank * 4608 + 2304, &maps.oc, 512 + 8 * j, 288 * rank + 144, sb + BAR_FULLX + 24, pola);
        }
#pragma unroll 1
        for (int u = 0; u < 36; u++) {
          const uint32_t s = 4 * (u & 1) + ((u >> 1) & 3);
          slot(s, &maps.d, u < 4 ? 512 : 64 * ((j + (u >> 2)) & 7), 576 * j + 144 * (u & 3), pol);
          if ((XCH & 4) && u < 3) landed(s);
        }
      }
    } else {
      const int w = warp - 10, grp = 2 * rb + w;
      if (PFMODE & 4) {
        mbar_wait(sb + xin_bar(XP), 0);
        if (lane == 0) prefetch_l2(wqkv + (2 * blockIdx.x + w) * 7776, 7776);
        if (EARLY && lane == 0) prefetch_l2(wo + (2 * blockIdx.x + w) * 2592, 2592);
      }
      if (EARLY) {
        mbar_wait(sb + xin_bar(8), 0);
        gate(sb + SM_PROG, WSG);
        if (grp < 18) {
          const uint4* row = (const uint4*)(wo + (72 * j + 4 * grp + (lane >> 3)) * 1152) + (lane & 7);
          float a = 0.f;
#pragma unroll 1
          for (int i = 0; i < 72; i += 24) {
            const uint4 u[3] = {__ldg(row + i), __ldg(row + i + 8), __ldg(row + i + 16)};
#pragma unroll
            for (int k = 0; k < 3; k++)
              a += ((bf_lo(u[k].x) + bf_hi(u[k].x)) + (bf_lo(u[k].y) + bf_hi(u[k].y))) + ((bf_lo(u[k].z) + bf_hi(u[k].z)) + (bf_lo(u[k].w) + bf_hi(u[k].w)));
          }
          a = quad_sum(a);
          a += __shfl_xor_sync(0xffffffffu, a, 4);
          if ((lane & 7) == 0) st_relaxed(ws[j].wsum + 4 * grp + (lane >> 3), tagged(__float_as_uint(a), par));
        }
        if (w == 1) {
          uint32_t u[3];
#pragma unroll 1
          for (int it = 0; it < SPIN_MAX; it++) {
#pragma unroll
            for (int k = 0; k < 3; k++) u[k] = ld_relaxed(ws[j].wsum + min(lane + 32 * k, 71));
            if (!__any_sync(0xffffffffu, chk(chk2(u[0], u[1], par), u[2], par) & 1)) break;
            __nanosleep(100);
          }
#pragma unroll
          for (int k = 0; k < 3; k++) {
            const float f = __uint_as_float(u[k]);
            if (lane + 32 * k < 80) sts128(sb + SM_WSUM + 16 * (lane + 32 * k), pack_bf16(f, f - bf_lo(pack_bf16(f, 0.f))), 0, 0, 0);
          }
          fence_async_smem();
          __syncwarp();
          if (lane < 4) mbar_arrive(sb + BAR_WSUM);
          PROFX(57);
        }
      }
      gate(sb + SM_PROG, 3);
      if (w == 0) PROFX(58);
      auto prefetch_gu = [&](int l0, int n) {
#pragma unroll 1
        for (int i = lane; i < 36 * n; i += 32) {
          asm volatile("prefetch.global.L2 [%0];" ::"l"((w ? wu : wg) + (size_t)(36 * rb + i / n) * 9216 + 1152 * j + 128 * (l0 + i % n)));
          __nanosleep(PFSLEEP);
        }
      };
      auto clear = [&](uint4* p, int n) {
#pragma unroll 1
        for (int i = lane; i < n; i += 64) { st_relaxed4(p + i, 0, 0, 0, 0); st_relaxed4(p + i + 32, 0, 0, 0, 0); __nanosleep(CLRSLEEP); }
      };
      auto exchange = [&](uint32_t v, uint32_t bar) {
        if (FENCE1) { if (lane == 0) fence_gpu(); } else fence_gpu();
        __syncwarp();
        if (w == 0 && v != 1) PROFX(64 + 58 - 2 * v);
        if (lane == 0) st_relaxed(ws[grp].flag + j, v);
#pragma unroll 1
        for (int it = 0; it < SPIN_MAX; it++) {
          const uint32_t f = ld_relaxed(ws[grp].flag + (lane & 7));
          if (__all_sync(0xffffffffu, v ? f >= v : f == 0)) break;
        }
        if (lane == 0) mbar_arrive(sb + bar + 8 * w);
      };
      if (!EARLY && lane == 0) prefetch_l2(wo + (2 * blockIdx.x + w) * 2592, 2592);
      if (MAPPF && w == 0 && lane < 9) asm volatile("prefetch.tensormap [%0];" ::"l"(&maps.o + lane) : "memory");
#pragma unroll 1
      for (int layer = 0; layer < NLAYERS; layer++) {
        gate(sb + SM_PROG, 32 * layer + 3);
        if (PFF & 1) prefetch_gu(0, 2);
        gate(sb + SM_PROG, 32 * layer + 22);
        if (PFF & 2) prefetch_gu(2, 2);
        if (layer == 0) {
          clear(ws[grp].inbox[0] + 2 * j * INBOX, 2 * INBOX);
          exchange(1, BAR_CLR);
          if (w == 0) PROFX(59);
        }
        if (PFF & 2) prefetch_gu(4, 2);
        if (PFF & 4) prefetch_gu(6, 3);
#pragma unroll 1
        for (int i = lane; i < ((PFF & 8) ? 162 : 0); i += 32) {
          asm volatile("prefetch.global.L2 [%0];" ::"l"(wd + (size_t)(576 * j + 36 * rb + 18 * w) * 1152 + 128 * i));
          __nanosleep(PFSLEEP);
        }
        if (w == 0 && layer == 0) PROFX(60);
        mbar_wait(sb + BAR_REDDONE + 8 * w, layer);
        if (w == 0) PROFX(64 + 53 + 4 * layer);
        exchange(2 - 2 * layer, BAR_RREADY);
        if (w == 0) PROFX(64 + 56 + 4 * layer);
      }
      mbar_wait(sb + BAR_DONE + 8 * w, 0);
    }
    __syncwarp();
    cluster_sync();
  } else {
    asm volatile("setmaxnreg.inc.sync.aligned.u32 " STR(REGS_C) ";");
#define THREAD_IDS()                                                                   \
    int tid_ = threadIdx.x, bid_ = lb;                                                  \
    asm volatile("" : "+r"(tid_), "+r"(bid_));                                          \
    const int w = warp >> 2, wp = warp & 3;                                             \
    const int lane = tid_ & 31, t = tid_ & 127, g = lane >> 2, q = lane & 3;           \
    const int j = CTA_J(bid_), rb = CTA_RB(bid_), grp = 2 * rb + w;                    \
    const int st0 = wp * 64 + g;                         \
    Group* const G = ws + grp;                                                         \
    const uint32_t dsb = (sb & 0x3FFFF) >> 4;                                          \
    (void)t; (void)g; (void)q; (void)grp; (void)j; (void)st0; (void)dsb; (void)G
    Cons c;
    c.sb = sb; c.sB = 0; c.mB = 0; c.mX = 0; c.elect = (threadIdx.x & 127) == 0;
    asm volatile("mapa.shared::cluster.u32 %0, %1, %2;" : "=r"(c.rem) : "r"(sb), "r"(rank ^ 1));
    float v[36], a1[96], a2[12];
    float2 sum, rs;
    uint32_t res[18], xtag;
    auto qkv_mma = [&](bool acc, uint32_t bb, const uint4& f0, const uint4& f1) {
      wg_fence();
      wgmma_ra<192>(a1, f0, desc_hi(2048, 1024, 1) + bb, acc);
      wgmma_ra<24>(a2, f0, desc_hi(128, 256, 0) + (bb + 384), acc);
      wgmma_ra<192>(a1, f1, desc_hi(2048, 1024, 1) + (bb + 512), true);
      wgmma_ra<24>(a2, f1, desc_hi(128, 256, 0) + (bb + 896), true);
      wg_commit();
    };
    {
      THREAD_IDS();
      if (OPEN) {
        if (q == 0) { st_relaxed2(G->sum + st0 + 8 * j, 0, 0); st_relaxed2(G->sq + st0 + 8 * j, 0, 0); }
        if (wp == 3) {
#pragma unroll
          for (int i = 0; i < 5; i++) st_relaxed4(G->halo + j * 160 + lane + i * 32, 0, 0, 0, 0);
        }
        if (lane >= OPENL) st_relaxed4(G->obox + (8 * WPROBE + j) * 128 + t, 0, 0, 0, 0);
      }
      xtag = __shfl_sync(0xffffffffu, ~ld_relaxed(G->flag + 32 + 32 * j) & 1, 0);
      if (OPEN && EARLY && lane >= OPENL) st_relaxed4(G->xbox + (2 * j + 1) * 128 + t, xtag ^ 1, 0, 0, 0);
      asm volatile("barrier.cluster.wait.aligned;" ::: "memory");
      PROF(0);
#pragma unroll
      for (int i = 0; i < 96; i++) asm volatile("mov.b32 %0, 0;" : "=f"(a1[i]));
#pragma unroll
      for (int i = 0; i < 12; i++) asm volatile("mov.b32 %0, 0;" : "=f"(a2[i]));
      PROF(1);
      rs = ln_gemm_in(c, G, res, sum, w, st0, j, t, [&](int i) { PROF(2 + i); if (i) PROF(4); }, qkv_mma);
    }
#pragma unroll 1
    for (int layer = 0;; layer++) {
      const uint32_t tag = layer ^ 1;
      const int pb = 1 + layer * 30;
      uint4 own[5];
      {
        THREAD_IDS();
        PROF(pb + 4);
        uint32_t kv[3][18];
        auto cvt = [&](int b, float r) {
#pragma unroll
          for (int cc = 0; cc < 18; cc++) {
            const float* a = (cc == 8 ? a2 + 4 : cc == 17 ? a2 + 8 : cc < 8 ? a1 + 32 + 4 * cc : a1 + 28 + 4 * cc) + 2 * (b - 1);
            const uint32_t u = pack_bf16(a[0] * r, a[1] * r);
            kv[b][cc] = cc < 9 ? u : movm(u);
          }
        };
        cvt(2, rs.y);
        const uint32_t msg = sb + SM_X + (w ? 3 * XSLOT : 24576) + wp * 2304 + lane * 16;
        if (wp == 3) {
          uint4* hp = G->halo + j * 160 + lane;
#pragma unroll
          for (int i = 0; i < 4; i++) st_relaxed4(hp + i * 32, tagged(kv[2][4 * i], tag), kv[2][4 * i + 1], kv[2][4 * i + 2], kv[2][4 * i + 3]);
          st_relaxed2((uint2*)(hp + 128), tagged(kv[2][16], tag), kv[2][17]);
        } else {
#pragma unroll
          for (int i = 0; i < 4; i++) sts128(msg + i * 512, kv[2][4 * i], kv[2][4 * i + 1], kv[2][4 * i + 2], kv[2][4 * i + 3]);
          sts64f(msg + 2048 - lane * 8, __uint_as_float(kv[2][16]), __uint_as_float(kv[2][17]));
        }
        cvt(1, rs.x);
        uint32_t Q[4][6];
#pragma unroll
        for (int h = 0; h < 4; h++)
#pragma unroll
          for (int i = 0; i < 6; i++) {
            const float* a = 4 * h + i < 16 ? a1 + 8 * h + 2 * i : a2 + 8 * h + 2 * i - 32;
            const uint32_t u = pack_bf16(a[0], a[1]);
            Q[h][i] = i < 2 ? (q >= h ? u : 0) : i < 4 ? u : (q <= h ? u : 0);
          }
        const bool lo0 = 2 * q > g, lo1 = 2 * q + 1 > g;
        const uint32_t M = (lo0 ? 0xffffu : 0u) | (lo1 ? 0xffff0000u : 0u);
        auto scores = [&](int h, int b, float (&s)[4]) {
          mma16816z(s, Q[h][0], Q[h][1], Q[h][2], Q[h][3], kv[b][2 * h], kv[b][2 * h + 1]);
          mma1688(s, Q[h][4], Q[h][5], kv[b][2 * h + 2]);
        };
        auto softmax = [&](float (&l)[4][2], float r, uint32_t (&P)[4]) {
          const float sl = r * (0.23570226039551584f * 1.4426950408889634f);
          float m[4];
#pragma unroll
          for (int h = 0; h < 4; h++) { m[h] = fmaxf(l[h][0], l[h][1]); m[h] = fmaxf(m[h], __shfl_xor_sync(0xffffffffu, m[h], 1)); }
#pragma unroll
          for (int h = 0; h < 4; h++) m[h] = fmaxf(m[h], __shfl_xor_sync(0xffffffffu, m[h], 2)) * sl;
#pragma unroll
          for (int h = 0; h < 4; h++) {
            l[h][0] = ex2(fmaf(l[h][0], sl, -m[h])); l[h][1] = ex2(fmaf(l[h][1], sl, -m[h]));
            m[h] = l[h][0] + l[h][1]; m[h] += __shfl_xor_sync(0xffffffffu, m[h], 1);
          }
#pragma unroll
          for (int h = 0; h < 4; h++) { m[h] = rcp(m[h] + __shfl_xor_sync(0xffffffffu, m[h], 2)); P[h] = pack_bf16(l[h][0] * m[h], l[h][1] * m[h]); }
        };
        const bool remote = wp == 0 && rb > 0;
        const uint4* hp = (G - 2)->halo + j * 160 + lane;
        auto halo = [&] {
#pragma unroll
          for (int i = 0; i < 4; i++) { const uint4 u = ld_relaxed4(hp + i * 32); kv[0][4 * i] = u.x; kv[0][4 * i + 1] = u.y; kv[0][4 * i + 2] = u.z; kv[0][4 * i + 3] = u.w; }
          const uint2 u = ld_relaxed2((const uint2*)(hp + 128));
          kv[0][16] = u.x; kv[0][17] = u.y;
        };
#pragma unroll
        for (int i = 0; i < 18; i++) kv[0][i] = 0;
        if (remote) halo();
        float l0[4][2], l1[4][2];
#pragma unroll
        for (int h = 0; h < 4; h++) {
          float s1[4], s2[4];
          scores(h, 1, s1); scores(h, 2, s2);
          l0[h][0] = s1[0]; l0[h][1] = s1[1];
          l1[h][0] = lo0 ? s1[2] : s2[2]; l1[h][1] = lo1 ? s1[3] : s2[3];
        }
        uint32_t P0[4], P1[4];
        softmax(l1, rs.y, P1);
        if (remote) {
          while (__any_sync(0xffffffffu, chk(chk2(kv[0][0], kv[0][4], tag) | chk2(kv[0][8], kv[0][12], tag), kv[0][16], tag) & 1)) halo();
        }
        if (FG < 0) c.progress(32 * layer + 20);
        wg_bar(w);
        if (wp > 0) {
          const uint32_t from = msg - 2304;
#pragma unroll
          for (int i = 0; i < 4; i++) { const uint4 u = lds128(from + i * 512); kv[0][4 * i] = u.x; kv[0][4 * i + 1] = u.y; kv[0][4 * i + 2] = u.z; kv[0][4 * i + 3] = u.w; }
          const float2 u = lds64(from + 2048 - lane * 8);
          kv[0][16] = __float_as_uint(u.x); kv[0][17] = __float_as_uint(u.y);
        }
        PROF(pb + 5);
        const bool first = (rb == 0 && wp == 0);
#pragma unroll
        for (int h = 0; h < 4; h++) {
          float s0[4];
          scores(h, 0, s0);
          if (first) s0[0] = s0[1] = -INFINITY;
          l0[h][0] = lo0 ? s0[0] : l0[h][0]; l0[h][1] = lo1 ? s0[1] : l0[h][1];
        }
        softmax(l0, rs.x, P0);
        uint4* ob = G->obox + t;
        uint32_t car0 = 0, car1 = 0;
#pragma unroll
        for (int h = 0; h < 4; h++) {
          float o[3][4];
#pragma unroll
          for (int i = 0; i < 3; i++) {
            mma16816z(o[i], P0[h] & ~M, P1[h] & M, 0u, P1[h] & ~M, kv[1][9 + 2 * h + i], kv[2][9 + 2 * h + i]);
            mma1688(o[i], P0[h] & M, 0u, kv[0][9 + 2 * h + i]);
          }
          const uint32_t o0 = q < h ? car0 : pack_bf16(o[0][0], o[0][1]), o1 = q < h ? car1 : pack_bf16(o[0][2], o[0][3]);
          own[h] = make_uint4(o0 | 1, o1, pack_bf16(o[1][0], o[1][1]), pack_bf16(o[1][2], o[1][3]));
          if (h < OFIRST) st_relaxed4(ob + (8 * h + j) * 128, own[h].x, own[h].y, own[h].z, own[h].w);
          car0 = pack_bf16(o[2][0], o[2][1]); car1 = pack_bf16(o[2][2], o[2][3]);
        }
        car0 = tagged(car0, tag);
        own[4] = make_uint4(car0, car1, 0, 0);
        PROF(pb + 6);
      }
      {
        THREAD_IDS();
        uint4* src = G->obox + t;
        asm volatile("" : "+l"(src));
        uint2 sa, sc;
        uint4 x[32];
        auto load = [&](int i) { x[i] = ld_relaxed4(i < 28 ? src + (i % 7 >= j ? 128 : 0) + (8 * (i / 7) + i % 7) * 128 : src + (i + 4) * 128); };
        const uint32_t* probe = &(G->obox + (8 * WPROBE + (lane & 7)) * 128 + (t | 31))->x;
        uint32_t pv = ld_relaxed(probe);
#pragma unroll
        for (int i = 3; i < 8; i++) mbar_wait_c(sb + BAR_FULLX + 8 * i, (c.mX >> i) & 1);
        c.mX ^= 0xf8;
        if (EARLY) mbar_wait_c(sb + BAR_WSUM, 0);
        while (__any_sync(0xffffffffu, ~pv & 1)) pv = ld_relaxed(probe);
        if (layer) PROF(24); else PROF(25);
        if (WOBAR && w == 1) asm volatile("bar.sync 7, 256;" ::: "memory");
#pragma unroll
        for (int i = 0; i < WB1; i++) load(i);
        if (WOBAR && w == 0) asm volatile("bar.arrive 7, 256;" ::: "memory");
#pragma unroll
        for (int h = OFIRST; h < 4; h++) st_relaxed4(src + (8 * h + j) * 128, own[h].x, own[h].y, own[h].z, own[h].w);
        st_relaxed2((uint2*)(src + (32 + (j >> 1)) * 128) + (j & 1), own[4].x, own[4].y);
        if (layer) PROF(26); else PROF(27);
        float a[32], a8[4];
        auto step = [&](const uint4& f, uint32_t r0, int rs, bool acc) {
          wgmma_ra<64>(a, f, desc_hi(0, rs * 128, 1) + (dsb + ((SM_X + 4 * XSLOT) >> 4) + r0 * 8), acc);
          wgmma_ra<8>(a8, f, desc_hi(rs * 16, 0, 0) + (dsb + (SM_WOC >> 4) + r0), acc);
        };
        if (OWNBAR) asm volatile("bar.sync 4, 256;" ::: "memory");
        float e[4];
        wg_fence();
        if (EARLY) {
#pragma unroll
          for (int i = 0; i < 5; i++) wgmma_ra<8>(e, own[i], desc_hi(128, 0, 0) + (dsb + (SM_WSUM >> 4) + 16 * i), i > 0);
          wg_commit();
        }
#pragma unroll
        for (int i = 0; i < 4; i++) step(own[i], 72 * j + 16 * i, 8, i > 0);
        wg_commit();
        if (EARLY) {
          wg_wait<1>();
          if (q == 0) st_relaxed2(G->sum + st0 + 8 * j, (__float_as_uint(e[0] + e[1]) & ~3u) | ((2 * layer + 2) & 3), __float_as_uint(e[2] + e[3]));
        }
        if (layer) PROF(28); else PROF(29);
        auto batch = [&](auto e0, auto e1, auto e2, int b) {
          constexpr int E0 = decltype(e0)::v, E1 = decltype(e1)::v, E2 = decltype(e2)::v;
          const uint32_t one = (LATE0 || E0 > 0) && E1 > E0 ? late(sb + BAR_FULLX + 64, 1) : 1;
          while (E1 > E0) {
            uint32_t bad = 0;
#pragma unroll
            for (int i = E0; i < E1; i++) bad = i < 28 ? chk(bad, x[i].x, one) : chk(chk(bad, x[i].x, tag), x[i].z, tag);
            if (!__any_sync(0xffffffffu, bad & 1)) break;
#pragma unroll
            for (int i = E0; i < E1; i++) load(i);
          }
          if (b == 0) PROF(pb + 7);
          if (b == FG) c.progress(32 * layer + 20);
          if (b > 0 && E2 > E1) wg_wait<WOW>();
#pragma unroll
          for (int i = E1; i < E2; i++) load(i);
          if (EARLY && b == 1) { sa = ld_relaxed2(G->sum + st0 + 16 * q); sc = ld_relaxed2(G->sum + st0 + 16 * q + 8); }
          if (E1 > E0) {
            wg_fence();
#pragma unroll
            for (int i = E0; i < E1; i++) {
              if (i < 28) step(x[i], 72 * (i % 7) + (i % 7 >= j ? 72 : 0) + 16 * (i / 7), 8, true);
              else step(x[i], 144 * (i - 28) + 64, 72, true);
            }
            wg_commit();
          }
        };
        batch(IC<0>(), IC<WB1>(), IC<WB2>(), 0);
        batch(IC<WB1>(), IC<WB2>(), IC<WB3>(), 1);
        batch(IC<WB2>(), IC<WB3>(), IC<32>(), 2);
        batch(IC<WB3>(), IC<32>(), IC<32>(), 3);
        if (EARLY) {
          float2 e = make_float2(quad_sum(__uint_as_float(sa.x) + __uint_as_float(sc.x)), quad_sum(__uint_as_float(sa.y) + __uint_as_float(sc.y)));
          if (__any_sync(0xffffffffu, chk2(sa.x, sc.x, (2 * layer + 2) & 3) & 3)) e = gather_sums(G->sum + st0 + 16 * q, (2 * layer + 2) & 3);
          sum.x += e.x; sum.y += e.y;
        }
        wg_wait<0>();
        if (w == 0) asm volatile("bar.arrive 3, 256;" ::: "memory");
        PROF(pb + 8);
#pragma unroll
        for (int i = 0; i < 18; i++) {
          v[2 * i] = bf_lo(res[i]) + (i < 16 ? a[2 * i] : a8[2 * i - 32]);
          v[2 * i + 1] = bf_hi(res[i]) + (i < 16 ? a[2 * i + 1] : a8[2 * i - 31]);
        }
      }
      uint32_t lsb;
      uint32_t h[144];
      {
        THREAD_IDS();
        float a[128];
        const uint32_t xd = sb + SM_X + w * 4 * XSLOT + (lane >> 4) * 1024 + (16 * wp + (lane & 15)) * 16;
        const float2 rs = ln_gemm<false>(c, G, v, res, sum, st0, j, t, layer, xtag,
          [&](int i) {
            if (i == 0) {
              lsb = ((res[0] & 1) | (res[4] & 1) << 1 | (res[8] & 1) << 2 | (res[12] & 1) << 3 | (res[16] & 1) << 4) ^ (xtag * 31);
              if (w == 1) asm volatile("bar.sync 3, 256;" ::: "memory");
            }
            PROF(pb + 9 + i);
          },
          [&](int gi, uint32_t bb, const uint4& f0, const uint4& f1) {
            if (gi == 0) PROF(pb + 11);
            if (TLEAD0 && gi == 18 - TLEAD0 && w == 1) asm volatile("bar.sync 5, 256;" ::: "memory");
            wg_fence();
            wgmma_ra<256>(a, f0, desc_hi(4096, 1024, 1) + bb, gi > 0);
            wgmma_ra<256>(a, f1, desc_hi(4096, 1024, 1) + (bb + 128), true);
            wg_commit();
            if (TLEAD0 && gi == 17 && w == 0) asm volatile("bar.arrive 5, 256;" ::: "memory");
            stsm4(xd + gi * 4096, f0.x, f0.y, f0.z, f0.w);
            stsm4(xd + gi * 4096 + 2048, f1.x, f1.y, f1.z, f1.w);
            if (gi == 17) { fence_async_smem(); wg_bar(w); }
          });
        sts64f(sb + SM_KEEP + (tid_ >> 2) * 8, rs.x * rs.x, rs.y * rs.y);
        c.progress(32 * layer + 22);
        PROF2(pb + 12);
        glu<16, 0>(a, h);
        const Desc da0 = desc_hi(1024, 128, 0) + (dsb + ((SM_X + w * 4 * XSLOT) >> 4));
        auto tile = [&](auto wide, auto last) {
          const uint32_t xe = BAR_EMPTYX + 32 * (t & 1) + 4 * (t & 6);
          auto group = [&](int gi) {
            uint32_t prev;
            const uint32_t bb = c.nextB(prev);
            const Desc da = da0 + gi * 256;
            wg_fence();
            if (wide()) {
              wgmma_ss<256>(a, da, desc_hi(4096, 1024, 1) + bb, gi);
              wgmma_ss<256>(a, da + 128, desc_hi(4096, 1024, 1) + (bb + 128), 1);
            } else {
              wgmma_ss<192>(*(float(*)[96])a, da, desc_hi(2048, 512, 2) + bb, gi);
              wgmma_ss<192>(*(float(*)[96])a, da + 128, desc_hi(2048, 512, 2) + (bb + 64), 1);
            }
            wg_commit();
            if (gi == 17 && w == 0) asm volatile("bar.arrive 5, 256;" ::: "memory");
            wg_wait<1>();
            if (gi > 0 && !(last() && gi > 13)) c.release2(BAR_EMPTYB + prev);
            if (last() && gi >= XREL && !((gi ^ XREL) & 1)) c.release2(BAR_EMPTYX + 16 * ((gi - XREL) & 2) + 2 * ((gi - XREL) & 12));
          };
          int gi = 0, end = w ? 18 - (wide() ? TLEAD2 : TLEAD) : 18;
#pragma unroll 1
          while (true) {
#pragma unroll 1
            for (; gi < end; gi++) group(gi);
            if (end == 18) break;
            asm volatile("bar.sync 5, 256;" ::: "memory");
            end = 18;
          }
          wg_wait<0>();
          if (!last()) c.releaseLastB();
          if (last() && t >= (19 - XREL) / 2 && t < 8) { mbar_arrive(sb + xe); mbar_arrive_remote(c.rem + xe); }
        };
        auto yes = [] { return true; };
        auto no = [] { return false; };
        tile(yes, no); PROF2(pb + 13); glu<16, 32>(a, h);
        tile(yes, no); PROF2(pb + 14); glu<16, 64>(a, h);
        tile(no, no); PROF2(pb + 15); glu<12, 96>(a, h);
        const uint32_t hole = sb + SM_B + 12288 + tid_ * 16;
#pragma unroll
        for (int i = 0; i < NSPILL; i++) sts128(hole + i * BSLOT, h[96 + 4 * i], h[97 + 4 * i], h[98 + 4 * i], h[99 + 4 * i]);
        if (w == 1) asm volatile("bar.arrive 8, 256;" ::: "memory");
        tile(no, yes); PROF2(pb + 16); glu<12, 120>(a, h);
#pragma unroll
        for (int i = 0; i < NSPILL; i++) { const uint4 u = lds128(hole + i * BSLOT); h[96 + 4 * i] = u.x; h[97 + 4 * i] = u.y; h[98 + 4 * i] = u.z; h[99 + 4 * i] = u.w; }
      }
      {
        THREAD_IDS();
        float d[32];
        uint4* gt = G->obox + t;
        asm volatile("" : "+l"(gt));
        uint4* const ib = gt + 2 * 4608 + layer * 8 * INBOX;
        auto pass = [&](uint32_t s0, bool last, auto&& hook) {
          const Desc db = desc_hi(0, 1024, 1) + (dsb + (SM_X >> 4) + s0 * (XSLOT >> 4));
          mbar_wait_c(sb + BAR_FULLX + 8 * s0, (c.mX >> s0) & 1);
          if (RHOOK < 0) hook();
          asm volatile("bar.sync %0, 256;" ::"r"(8 + w) : "memory");
#pragma unroll
          for (int i = 0; i < 4; i++) {
            const int si = 4 * (i & 1) + (i >> 1);
            if (i > 0) mbar_wait_c(sb + BAR_FULLX + 8 * (s0 + si), (c.mX >> (s0 + si)) & 1);
            wg_fence();
#pragma unroll
            for (int k = 0; k < 9; k++) {
              const uint32_t* hk = h + 36 * i + 4 * k;
              wgmma_ra<64>(d, make_uint4(hk[0], hk[1], hk[2], hk[3]), db + (si * (XSLOT >> 4) + k * 128), last || i + k > 0);
              if (9 * i + k == PPK && !(last && w == 1)) asm volatile("bar.arrive %0, 256;" ::"r"(9 - w) : "memory");
            }
            wg_commit();
            if (i > 0) { wg_wait<1>(); c.release2(BAR_EMPTYX + 8 * (s0 + 4 * ((i - 1) & 1) + ((i - 1) >> 1))); }
            if (i == RHOOK) hook();
          }
          c.mX ^= 0x33u << s0;
        };
        PROF2(pb + 17);
#pragma unroll 1
        for (int p = 0; p < 8; p++) {
          const uint32_t s0 = 2 * (p & 1);
          pass(s0, false, [] {});
          wg_wait<0>();
          c.release2(BAR_EMPTYX + 8 * (s0 + 5));
          uint32_t pk[16];
#pragma unroll
          for (int i = 0; i < 16; i++) pk[i] = pack_bf16(d[2 * i], d[2 * i + 1]);
          if (p >= BREL && p < BREL + 5) {
            const uint32_t o = c.sB + 8 * (p - BREL);
            c.release2(BAR_EMPTYB + (o < 40 ? o : o - 40));
          }
          uint4* const dst = ib + ((j + p) & 7) * INBOX;
          if (p == 0) {
            mbar_wait_c(sb + BAR_CLR + 8 * w, 0);
#pragma unroll
            for (int k = 0; k < 8; k++) red2((uint2*)(ib + k * INBOX + 512) - t, pk[2 * k], pk[2 * k + 1]);
          } else if (p < 7) {
#pragma unroll
            for (int k = 0; k < 4; k++) red4(dst + k * 128, pk[4 * k], pk[4 * k + 1], pk[4 * k + 2], pk[4 * k + 3]);
            if (p == 6) { __syncwarp(); if (lane == 0) mbar_arrive(sb + BAR_REDDONE + 8 * w); }
          } else {
#pragma unroll
            for (int k = 0; k < 4; k++) st_relaxed4(gt + ((j + 7) & 7) * 128 + k * 1024, pk[4 * k] & ~1u, pk[4 * k + 1], pk[4 * k + 2], pk[4 * k + 3]);
          }
        }
        PROF2(pb + 18);
        const uint4 *in = ib + j * INBOX, *pin = gt + j * 128;
        const uint2* in9 = (const uint2*)(in + 512) - t;
        asm volatile("" : "+l"(in), "+l"(pin), "+l"(in9));
        const float2 r2 = lds64(sb + SM_KEEP + (tid_ >> 2) * 8);
        uint2 X9;
        {
          uint4 X[4];
          const uint4* box = gt + 4608;
#pragma unroll
          for (int k = 0; k < 4; k++) X[k] = ld_relaxed4(box + 256 * j + ((k & 1) + 8 * (k & 2)) * 128);
          X9 = ld_relaxed2((const uint2*)(box + (32 + (j >> 1)) * 128) + (j & 1));
          const float i0 = rcp(r2.x), i1 = rcp(r2.y);
#pragma unroll
          for (int k = 0; k < 4; k++) {
            float* e = d + 8 * k;
            X[k].x ^= (lsb >> k) & 1;
            e[0] = bf_lo(X[k].x) * i0; e[1] = bf_hi(X[k].x) * i0; e[2] = bf_lo(X[k].y) * i1; e[3] = bf_hi(X[k].y) * i1;
            e[4] = bf_lo(X[k].z) * i0; e[5] = bf_hi(X[k].z) * i0; e[6] = bf_lo(X[k].w) * i1; e[7] = bf_hi(X[k].w) * i1;
          }
        }
        uint4 R[4], P[4];
        uint2 R9;
        PROF2(pb + 19);
        pass(0, true, [&] {
          mbar_wait_c(sb + BAR_RREADY + 8 * w, layer);
#pragma unroll
          for (int k = 0; k < 4; k++) R[k] = ld_relaxed4(in + k * 128);
          R9 = ld_relaxed2(in9);
#pragma unroll
          for (int k = 0; k < 4; k++) P[k] = ld_relaxed4(pin + k * 1024);
        });
        const uint32_t zero = late(sb + BAR_FULLX + 64, 0);
        while (__any_sync(0xffffffffu, (chk2(P[0].x, P[1].x, zero) | chk2(P[2].x, P[3].x, zero)) & 1)) {
#pragma unroll
          for (int k = 0; k < 4; k++) P[k] = ld_relaxed4(pin + k * 1024);
        }
#pragma unroll
        for (int k = 0; k < 4; k++) {
          const uint32_t u[4] = {hadd2(R[k].x, P[k].x), hadd2(R[k].y, P[k].y), hadd2(R[k].z, P[k].z), hadd2(R[k].w, P[k].w)};
#pragma unroll
          for (int i = 0; i < 4; i++) { v[8 * k + 2 * i] = bf_lo(u[i]); v[8 * k + 2 * i + 1] = bf_hi(u[i]); }
        }
        X9.x = chk(zero, X9.x, lsb >> 4);
        v[32] = fmaf(bf_lo(R9.x), r2.x, bf_lo(X9.x)); v[33] = fmaf(bf_hi(R9.x), r2.x, bf_hi(X9.x));
        v[34] = fmaf(bf_lo(R9.y), r2.y, bf_lo(X9.y)); v[35] = fmaf(bf_hi(R9.y), r2.y, bf_hi(X9.y));
        PROF2(pb + 20);
        wg_wait<0>();
        c.release2(BAR_EMPTYX + 40);
        PROF2(pb + 21);
#pragma unroll
        for (int i = 0; i < 32; i++) v[i] = (v[i] + d[i]) * (i & 2 ? r2.y : r2.x);
      }
      if (layer == NLAYERS - 1) break;
      {
        THREAD_IDS();
        PROF(31);
        rs = ln_gemm<true>(c, G, v, res, sum, st0, j, t, 1, xtag ^ 1, [&](int i) { PROF(32 + i); if (i) PROF(34); }, qkv_mma);
      }
    }
    {
      THREAD_IDS();
      const uint32_t stg = sb + SM_B + warp * 4096;
      const uint32_t sd = stg + (lane & 15) * 128;
#pragma unroll
      for (int i = 0; i < 4; i++)
        stsm4(sd + (((2 * i + (lane >> 4)) ^ (lane & 7)) << 4), pack_bf16(v[8 * i], v[8 * i + 1]), pack_bf16(v[8 * i + 2], v[8 * i + 3]),
              pack_bf16(v[8 * i + 4], v[8 * i + 5]), pack_bf16(v[8 * i + 6], v[8 * i + 7]));
      stsm2(stg + 2048 + (lane & 15) * 16, pack_bf16(v[32], v[33]), pack_bf16(v[34], v[35]));
      fence_async_smem();
      __syncwarp();
      if (lane == 0) {
        tma_store3d(&maps.out, stg, 64 * j, w, 64 * rb + 16 * wp);
        tma_store3d(&maps.outc, stg + 2048, 512 + 8 * j, w, 64 * rb + 16 * wp);
        bulk_commit();
        if (wp == 0) st_relaxed(G->flag + 32 + 32 * j, xtag);
        bulk_wait_all();
        mbar_arrive(sb + BAR_DONE + 8 * w);
      }
      PROF(61);
    }
    __syncwarp();
    cluster_sync();
  }
}

typedef CUresult (*EncFn)(CUtensorMap*, CUtensorMapDataType, cuuint32_t, void*, const cuuint64_t*, const cuuint64_t*, const cuuint32_t*,
                          const cuuint32_t*, CUtensorMapInterleave, CUtensorMapSwizzle, CUtensorMapL2promotion, CUtensorMapFloatOOBfill);

void make_map(EncFn enc, CUtensorMap* m, const void* p, int rank, uint64_t d0, uint64_t d1, uint64_t d2, uint64_t s1, uint64_t s2, uint32_t b0,
              uint32_t b1, uint32_t b2, CUtensorMapSwizzle sw) {
  cuuint64_t gd[3] = {d0, d1, d2};
  cuuint64_t gs[2] = {s1, s2};
  cuuint32_t bd[3] = {b0, b1, b2};
  cuuint32_t es[3] = {1, 1, 1};
  enc(m, CU_TENSOR_MAP_DATA_TYPE_BFLOAT16, rank, const_cast<void*>(p), gd, gs, bd, es, CU_TENSOR_MAP_INTERLEAVE_NONE, sw,
      CU_TENSOR_MAP_L2_PROMOTION_L2_128B, CU_TENSOR_MAP_FLOAT_OOB_FILL_NONE);
}

}

extern "C" void kernel_launch(void* const* d_in, const int* in_sizes, int n_in, void* d_out, int out_size) {
  const __nv_bfloat16* x = (const __nv_bfloat16*)d_in[0];
  const char *wqkv = (const char*)d_in[1], *wo = (const char*)d_in[2], *wg = (const char*)d_in[4], *wu = (const char*)d_in[5], *wd = (const char*)d_in[6];
  static EncFn enc = nullptr;
  static int grid = NCTA;
  static Group* ws = nullptr;
  if (!enc) {
    cudaDriverEntryPointQueryResult qr;
    cudaGetDriverEntryPoint("cuTensorMapEncodeTiled", (void**)&enc, cudaEnableDefault, &qr);
    cudaGetSymbolAddress((void**)&ws, g_ws);
    cudaFuncSetAttribute(fused_kernel, cudaFuncAttributeMaxDynamicSharedMemorySize, SMEM_BYTES);
    cudaLaunchConfig_t cfg = {};
    cfg.gridDim = NCTA + 4; cfg.blockDim = 384; cfg.dynamicSmemBytes = SMEM_BYTES;
    int clusters = 0;
    if (REPACK && cudaOccupancyMaxActiveClusters(&clusters, fused_kernel, &cfg) == cudaSuccess && 2 * clusters >= NCTA + 4) grid = NCTA + 4;
    cudaGetLastError();
  }
  const CUtensorMapSwizzle S0 = CU_TENSOR_MAP_SWIZZLE_NONE, S64 = CU_TENSOR_MAP_SWIZZLE_64B, S128 = CU_TENSOR_MAP_SWIZZLE_128B;
  Maps m;
  make_map(enc, &m.x, x, 3, 576, 2, 1024, 1152, 2304, 64, 1, 64, S128);
  make_map(enc, &m.qm, wqkv, 3, 576, 576, 3, 3456, 1152, 64, 16, 3, S128);
  make_map(enc, &m.qc, wqkv, 3, 576, 576, 3, 3456, 1152, 8, 16, 3, S0);
  make_map(enc, &m.o, wo, 2, 576, 576, 1, 1152, 0, 64, 72, 1, S128);
  make_map(enc, &m.oc, wo, 2, 576, 576, 1, 1152, 0, 8, 144, 1, S0);
  make_map(enc, &m.g, wg, 3, 64, 576, 72, 9216, 128, 64, 32, 2, S128);
  make_map(enc, &m.u, wu, 3, 64, 576, 72, 9216, 128, 64, 32, 2, S128);
  make_map(enc, &m.g3, wg, 3, 32, 576, 144, 9216, 64, 32, 32, 3, S64);
  make_map(enc, &m.u3, wu, 3, 32, 576, 144, 9216, 64, 32, 32, 3, S64);
  make_map(enc, &m.d, wd, 2, 576, 4608, 1, 1152, 0, 64, 72, 1, S128);
  make_map(enc, &m.out, d_out, 3, 576, 2, 1024, 1152, 2304, 64, 1, 16, S128);
  make_map(enc, &m.outc, d_out, 3, 576, 2, 1024, 1152, 2304, 8, 1, 16, S0);
  fused_kernel<<<grid, 384, SMEM_BYTES>>>(x, ws, wqkv, wg, wu, wd, m, wo);
}
```

```cpp
#include <cuda_runtime.h>
#include <cuda_bf16.h>
#include <cuda.h>
#include <stdint.h>
#include <stddef.h>

namespace {

constexpr int D_ = 576;
constexpr int NCTA = 128;
#define NLAYERS 2
#define W_POLICY policy_evict_first
#define A_POLICY policy_evict_normal
#define OPEN 1
#define PFMODE 5
#define WWIN 4
#define WOREL -1
#define WB1 11
#define WB2 21
#define WB3 32
#define WPROBE 1
#define WPROBE2 0
#define SPEC 2
#define POLLFIRST 0
#define SUMFIRST 1
#define EARLYPOLL 1
#define LEAD 0
#define ATTBAR 0
#define GL 18
#define WOBAR 1
#define QD 0
#define QG 4
#define PFQ 1
#define XDELAY 0
#define WOH 1
#define PFSLEEP 700
#define GPCMAP 1
#define PFF 1
#define REDN 1
#define CLRSLEEP 300
#define OPENL 24
#define FG 2
#define NON8 0
#define HMUL 1
#define FCH 1
#define PPK 34
#define RHOOK -1
#define SCHEDBAR 1
#define QH 5
#define XH 3
#define XP 0
#define GSLEEP 32
#define XCH 1
#define MAPPF 1
#define XREL 8
#define WOG 13
#define BREL 1
#define FENCE1 0
#define OWNX 0
#define OWNBAR 0
#define EARLY 1
#define ESPEC 0
#define TESTP 0
#define WOW 1
#define STATP -1
#define WSG 0
#define REPACK 1
#define QPACE 23
#define RDELAY 2000
#define XFIRST 0
#define TLEAD 2
#define TLEAD2 2
#define TLEAD0 2
#define OFIRST 3
#define OSPEC 0
#define FN 3
#define LATE0 0
#define NSPILL 4
#define REGS_C 232
#define REGS_P 40
#define STR2(x) #x
#define STR(x) STR2(x)
constexpr uint32_t SM_X = 0;
constexpr uint32_t XSLOT = 18432;
constexpr uint32_t SM_WOC = SM_X + 3 * XSLOT + 9216;
constexpr uint32_t SM_B = 147456;
constexpr uint32_t BSLOT = 16384;
constexpr uint32_t SM_KEEP = 229376;
constexpr uint32_t SM_WSUM = SM_KEEP + 512;
constexpr uint32_t SM_BAR = SM_KEEP + 2048;
constexpr uint32_t BAR_FULLB = SM_BAR;
constexpr uint32_t BAR_RREADY = SM_BAR + 40;
constexpr uint32_t BAR_CLR = SM_BAR + 56;
constexpr uint32_t BAR_FULLX = SM_BAR + 72;
constexpr uint32_t BAR_EMPTYB = SM_BAR + 144;
constexpr uint32_t BAR_EMPTYX = SM_BAR + 184;
constexpr uint32_t BAR_REDDONE = SM_BAR + 248;
constexpr uint32_t BAR_DONE = SM_BAR + 264;
constexpr uint32_t BAR_WSUM = SM_BAR + 280;
constexpr uint32_t SM_PROG = SM_BAR + 288;
constexpr uint32_t SMEM_BYTES = SM_BAR + 1024;

struct Maps { CUtensorMap x, qm, qc, o, oc, g, u, g3, u3, d, out, outc; };

constexpr int INBOX = 576;
struct Group {
  uint2 sum[4 * 8 * 8];
  uint2 sq[4 * 8 * 8];
  uint32_t pad[512];
  uint32_t flag[512];
  uint4 halo[8 * 160];
  uint4 obox[36 * 128];
  uint4 xbox[36 * 128];
  uint4 inbox[2][8 * INBOX];
};
struct Scratch { Group g[32]; uint4 wq[8][36][432]; uint32_t wsum[640]; };
__device__ __align__(1024) Scratch g_ws;
#define PROF(i)
#define PROFX(i)

#define PROF2(i) PROF(i)

struct Desc { uint32_t lo, hi; };
__device__ __forceinline__ constexpr Desc desc_hi(uint32_t lbo, uint32_t sbo, uint32_t sw) { return Desc{(lbo >> 4) << 16, (sbo >> 4) | sw << 30}; }
__device__ __forceinline__ constexpr Desc operator+(Desc d, uint32_t a) { return Desc{d.lo + a, d.hi}; }

template<int N> __device__ __forceinline__ void wgmma_ss(float (&d)[N / 2], Desc da, Desc db, int sc);
template<> __device__ __forceinline__ void wgmma_ss<192>(float (&d)[96], Desc da, Desc db, int sc) {
  asm volatile("{\n.reg .pred p;\n.reg .b64 a, b;\nsetp.ne.b32 p, %100, 0;\nmov.b64 a, {%96, %97};\nmov.b64 b, {%98, %99};\n"
    "wgmma.mma_async.sync.aligned.m64n192k16.f32.bf16.bf16 {%0,%1,%2,%3,%4,%5,%6,%7,%8,%9,%10,%11,%12,%13,%14,%15,%16,%17,%18,%19,%20,%21,%22,%23,%24,%25,%26,%27,%28,%29,%30,%31,%32,%33,%34,%35,%36,%37,%38,%39,%40,%41,%42,%43,%44,%45,%46,%47,%48,%49,%50,%51,%52,%53,%54,%55,%56,%57,%58,%59,%60,%61,%62,%63,%64,%65,%66,%67,%68,%69,%70,%71,%72,%73,%74,%75,%76,%77,%78,%79,%80,%81,%82,%83,%84,%85,%86,%87,%88,%89,%90,%91,%92,%93,%94,%95}, a, b, p, 1, 1, 0, 1;\n}\n"
    : "+f"(d[0]),"+f"(d[1]),"+f"(d[2]),"+f"(d[3]),"+f"(d[4]),"+f"(d[5]),"+f"(d[6]),"+f"(d[7]),"+f"(d[8]),"+f"(d[9]),"+f"(d[10]),"+f"(d[11]),"+f"(d[12]),"+f"(d[13]),"+f"(d[14]),"+f"(d[15]),"+f"(d[16]),"+f"(d[17]),"+f"(d[18]),"+f"(d[19]),"+f"(d[20]),"+f"(d[21]),"+f"(d[22]),"+f"(d[23]),"+f"(d[24]),"+f"(d[25]),"+f"(d[26]),"+f"(d[27]),"+f"(d[28]),"+f"(d[29]),"+f"(d[30]),"+f"(d[31]),"+f"(d[32]),"+f"(d[33]),"+f"(d[34]),"+f"(d[35]),"+f"(d[36]),"+f"(d[37]),"+f"(d[38]),"+f"(d[39]),"+f"(d[40]),"+f"(d[41]),"+f"(d[42]),"+f"(d[43]),"+f"(d[44]),"+f"(d[45]),"+f"(d[46]),"+f"(d[47]),"+f"(d[48]),"+f"(d[49]),"+f"(d[50]),"+f"(d[51]),"+f"(d[52]),"+f"(d[53]),"+f"(d[54]),"+f"(d[55]),"+f"(d[56]),"+f"(d[57]),"+f"(d[58]),"+f"(d[59]),"+f"(d[60]),"+f"(d[61]),"+f"(d[62]),"+f"(d[63]),"+f"(d[64]),"+f"(d[65]),"+f"(d[66]),"+f"(d[67]),"+f"(d[68]),"+f"(d[69]),"+f"(d[70]),"+f"(d[71]),"+f"(d[72]),"+f"(d[73]),"+f"(d[74]),"+f"(d[75]),"+f"(d[76]),"+f"(d[77]),"+f"(d[78]),"+f"(d[79]),"+f"(d[80]),"+f"(d[81]),"+f"(d[82]),"+f"(d[83]),"+f"(d[84]),"+f"(d[85]),"+f"(d[86]),"+f"(d[87]),"+f"(d[88]),"+f"(d[89]),"+f"(d[90]),"+f"(d[91]),"+f"(d[92]),"+f"(d[93]),"+f"(d[94]),"+f"(d[95]) : "r"(da.lo), "r"(da.hi), "r"(db.lo), "r"(db.hi), "r"(sc));
}
template<> __device__ __forceinline__ void wgmma_ss<256>(float (&d)[128], Desc da, Desc db, int sc) {
  asm volatile("{\n.reg .pred p;\n.reg .b64 a, b;\nsetp.ne.b32 p, %132, 0;\nmov.b64 a, {%128, %129};\nmov.b64 b, {%130, %131};\n"
    "wgmma.mma_async.sync.aligned.m64n256k16.f32.bf16.bf16 {%0,%1,%2,%3,%4,%5,%6,%7,%8,%9,%10,%11,%12,%13,%14,%15,%16,%17,%18,%19,%20,%21,%22,%23,%24,%25,%26,%27,%28,%29,%30,%31,%32,%33,%34,%35,%36,%37,%38,%39,%40,%41,%42,%43,%44,%45,%46,%47,%48,%49,%50,%51,%52,%53,%54,%55,%56,%57,%58,%59,%60,%61,%62,%63,%64,%65,%66,%67,%68,%69,%70,%71,%72,%73,%74,%75,%76,%77,%78,%79,%80,%81,%82,%83,%84,%85,%86,%87,%88,%89,%90,%91,%92,%93,%94,%95,%96,%97,%98,%99,%100,%101,%102,%103,%104,%105,%106,%107,%108,%109,%110,%111,%112,%113,%114,%115,%116,%117,%118,%119,%120,%121,%122,%123,%124,%125,%126,%127}, a, b, p, 1, 1, 0, 1;\n}\n"
    : "+f"(d[0]),"+f"(d[1]),"+f"(d[2]),"+f"(d[3]),"+f"(d[4]),"+f"(d[5]),"+f"(d[6]),"+f"(d[7]),"+f"(d[8]),"+f"(d[9]),"+f"(d[10]),"+f"(d[11]),"+f"(d[12]),"+f"(d[13]),"+f"(d[14]),"+f"(d[15]),"+f"(d[16]),"+f"(d[17]),"+f"(d[18]),"+f"(d[19]),"+f"(d[20]),"+f"(d[21]),"+f"(d[22]),"+f"(d[23]),"+f"(d[24]),"+f"(d[25]),"+f"(d[26]),"+f"(d[27]),"+f"(d[28]),"+f"(d[29]),"+f"(d[30]),"+f"(d[31]),"+f"(d[32]),"+f"(d[33]),"+f"(d[34]),"+f"(d[35]),"+f"(d[36]),"+f"(d[37]),"+f"(d[38]),"+f"(d[39]),"+f"(d[40]),"+f"(d[41]),"+f"(d[42]),"+f"(d[43]),"+f"(d[44]),"+f"(d[45]),"+f"(d[46]),"+f"(d[47]),"+f"(d[48]),"+f"(d[49]),"+f"(d[50]),"+f"(d[51]),"+f"(d[52]),"+f"(d[53]),"+f"(d[54]),"+f"(d[55]),"+f"(d[56]),"+f"(d[57]),"+f"(d[58]),"+f"(d[59]),"+f"(d[60]),"+f"(d[61]),"+f"(d[62]),"+f"(d[63]),"+f"(d[64]),"+f"(d[65]),"+f"(d[66]),"+f"(d[67]),"+f"(d[68]),"+f"(d[69]),"+f"(d[70]),"+f"(d[71]),"+f"(d[72]),"+f"(d[73]),"+f"(d[74]),"+f"(d[75]),"+f"(d[76]),"+f"(d[77]),"+f"(d[78]),"+f"(d[79]),"+f"(d[80]),"+f"(d[81]),"+f"(d[82]),"+f"(d[83]),"+f"(d[84]),"+f"(d[85]),"+f"(d[86]),"+f"(d[87]),"+f"(d[88]),"+f"(d[89]),"+f"(d[90]),"+f"(d[91]),"+f"(d[92]),"+f"(d[93]),"+f"(d[94]),"+f"(d[95]),"+f"(d[96]),"+f"(d[97]),"+f"(d[98]),"+f"(d[99]),"+f"(d[100]),"+f"(d[101]),"+f"(d[102]),"+f"(d[103]),"+f"(d[104]),"+f"(d[105]),"+f"(d[106]),"+f"(d[107]),"+f"(d[108]),"+f"(d[109]),"+f"(d[110]),"+f"(d[111]),"+f"(d[112]),"+f"(d[113]),"+f"(d[114]),"+f"(d[115]),"+f"(d[116]),"+f"(d[117]),"+f"(d[118]),"+f"(d[119]),"+f"(d[120]),"+f"(d[121]),"+f"(d[122]),"+f"(d[123]),"+f"(d[124]),"+f"(d[125]),"+f"(d[126]),"+f"(d[127]) : "r"(da.lo), "r"(da.hi), "r"(db.lo), "r"(db.hi), "r"(sc));
}
template<int N, int ACC> __device__ __forceinline__ void wgmma_rs(float (&d)[N / 2], const uint4& a, Desc db);
template<> __device__ __forceinline__ void wgmma_rs<8, 1>(float (&d)[4], const uint4& a, Desc db) {
  asm volatile("{\n.reg .pred p;\n.reg .b64 b;\nsetp.ne.b32 p, 1, 0;\nmov.b64 b, {%8, %9};\n"
    "wgmma.mma_async.sync.aligned.m64n8k16.f32.bf16.bf16 {%0,%1,%2,%3}, {%4,%5,%6,%7}, b, p, 1, 1, 1;\n}\n"
    : "+f"(d[0]),"+f"(d[1]),"+f"(d[2]),"+f"(d[3]) : "r"(a.x), "r"(a.y), "r"(a.z), "r"(a.w), "r"(db.lo), "r"(db.hi));
}
template<> __device__ __forceinline__ void wgmma_rs<8, 0>(float (&d)[4], const uint4& a, Desc db) {
  asm volatile("{\n.reg .pred p;\n.reg .b64 b;\nsetp.ne.b32 p, 0, 0;\nmov.b64 b, {%8, %9};\n"
    "wgmma.mma_async.sync.aligned.m64n8k16.f32.bf16.bf16 {%0,%1,%2,%3}, {%4,%5,%6,%7}, b, p, 1, 1, 1;\n}\n"
    : "=f"(d[0]),"=f"(d[1]),"=f"(d[2]),"=f"(d[3]) : "r"(a.x), "r"(a.y), "r"(a.z), "r"(a.w), "r"(db.lo), "r"(db.hi));
}
template<> __device__ __forceinline__ void wgmma_rs<24, 1>(float (&d)[12], const uint4& a, Desc db) {
  asm volatile("{\n.reg .pred p;\n.reg .b64 b;\nsetp.ne.b32 p, 1, 0;\nmov.b64 b, {%16, %17};\n"
    "wgmma.mma_async.sync.aligned.m64n24k16.f32.bf16.bf16 {%0,%1,%2,%3,%4,%5,%6,%7,%8,%9,%10,%11}, {%12,%13,%14,%15}, b, p, 1, 1, 1;\n}\n"
    : "+f"(d[0]),"+f"(d[1]),"+f"(d[2]),"+f"(d[3]),"+f"(d[4]),"+f"(d[5]),"+f"(d[6]),"+f"(d[7]),"+f"(d[8]),"+f"(d[9]),"+f"(d[10]),"+f"(d[11]) : "r"(a.x), "r"(a.y), "r"(a.z), "r"(a.w), "r"(db.lo), "r"(db.hi));
}
template<> __device__ __forceinline__ void wgmma_rs<24, 0>(float (&d)[12], const uint4& a, Desc db) {
  asm volatile("{\n.reg .pred p;\n.reg .b64 b;\nsetp.ne.b32 p, 0, 0;\nmov.b64 b, {%16, %17};\n"
    "wgmma.mma_async.sync.aligned.m64n24k16.f32.bf16.bf16 {%0,%1,%2,%3,%4,%5,%6,%7,%8,%9,%10,%11}, {%12,%13,%14,%15}, b, p, 1, 1, 1;\n}\n"
    : "=f"(d[0]),"=f"(d[1]),"=f"(d[2]),"=f"(d[3]),"=f"(d[4]),"=f"(d[5]),"=f"(d[6]),"=f"(d[7]),"=f"(d[8]),"=f"(d[9]),"=f"(d[10]),"=f"(d[11]) : "r"(a.x), "r"(a.y), "r"(a.z), "r"(a.w), "r"(db.lo), "r"(db.hi));
}
template<> __device__ __forceinline__ void wgmma_rs<64, 1>(float (&d)[32], const uint4& a, Desc db) {
  asm volatile("{\n.reg .pred p;\n.reg .b64 b;\nsetp.ne.b32 p, 1, 0;\nmov.b64 b, {%36, %37};\n"
    "wgmma.mma_async.sync.aligned.m64n64k16.f32.bf16.bf16 {%0,%1,%2,%3,%4,%5,%6,%7,%8,%9,%10,%11,%12,%13,%14,%15,%16,%17,%18,%19,%20,%21,%22,%23,%24,%25,%26,%27,%28,%29,%30,%31}, {%32,%33,%34,%35}, b, p, 1, 1, 1;\n}\n"
    : "+f"(d[0]),"+f"(d[1]),"+f"(d[2]),"+f"(d[3]),"+f"(d[4]),"+f"(d[5]),"+f"(d[6]),"+f"(d[7]),"+f"(d[8]),"+f"(d[9]),"+f"(d[10]),"+f"(d[11]),"+f"(d[12]),"+f"(d[13]),"+f"(d[14]),"+f"(d[15]),"+f"(d[16]),"+f"(d[17]),"+f"(d[18]),"+f"(d[19]),"+f"(d[20]),"+f"(d[21]),"+f"(d[22]),"+f"(d[23]),"+f"(d[24]),"+f"(d[25]),"+f"(d[26]),"+f"(d[27]),"+f"(d[28]),"+f"(d[29]),"+f"(d[30]),"+f"(d[31]) : "r"(a.x), "r"(a.y), "r"(a.z), "r"(a.w), "r"(db.lo), "r"(db.hi));
}
template<> __device__ __forceinline__ void wgmma_rs<64, 0>(float (&d)[32], const uint4& a, Desc db) {
  asm volatile("{\n.reg .pred p;\n.reg .b64 b;\nsetp.ne.b32 p, 0, 0;\nmov.b64 b, {%36, %37};\n"
    "wgmma.mma_async.sync.aligned.m64n64k16.f32.bf16.bf16 {%0,%1,%2,%3,%4,%5,%6,%7,%8,%9,%10,%11,%12,%13,%14,%15,%16,%17,%18,%19,%20,%21,%22,%23,%24,%25,%26,%27,%28,%29,%30,%31}, {%32,%33,%34,%35}, b, p, 1, 1, 1;\n}\n"
    : "=f"(d[0]),"=f"(d[1]),"=f"(d[2]),"=f"(d[3]),"=f"(d[4]),"=f"(d[5]),"=f"(d[6]),"=f"(d[7]),"=f"(d[8]),"=f"(d[9]),"=f"(d[10]),"=f"(d[11]),"=f"(d[12]),"=f"(d[13]),"=f"(d[14]),"=f"(d[15]),"=f"(d[16]),"=f"(d[17]),"=f"(d[18]),"=f"(d[19]),"=f"(d[20]),"=f"(d[21]),"=f"(d[22]),"=f"(d[23]),"=f"(d[24]),"=f"(d[25]),"=f"(d[26]),"=f"(d[27]),"=f"(d[28]),"=f"(d[29]),"=f"(d[30]),"=f"(d[31]) : "r"(a.x), "r"(a.y), "r"(a.z), "r"(a.w), "r"(db.lo), "r"(db.hi));
}
template<> __device__ __forceinline__ void wgmma_rs<192, 1>(float (&d)[96], const uint4& a, Desc db) {
  asm volatile("{\n.reg .pred p;\n.reg .b64 b;\nsetp.ne.b32 p, 1, 0;\nmov.b64 b, {%100, %101};\n"
    "wgmma.mma_async.sync.aligned.m64n192k16.f32.bf16.bf16 {%0,%1,%2,%3,%4,%5,%6,%7,%8,%9,%10,%11,%12,%13,%14,%15,%16,%17,%18,%19,%20,%21,%22,%23,%24,%25,%26,%27,%28,%29,%30,%31,%32,%33,%34,%35,%36,%37,%38,%39,%40,%41,%42,%43,%44,%45,%46,%47,%48,%49,%50,%51,%52,%53,%54,%55,%56,%57,%58,%59,%60,%61,%62,%63,%64,%65,%66,%67,%68,%69,%70,%71,%72,%73,%74,%75,%76,%77,%78,%79,%80,%81,%82,%83,%84,%85,%86,%87,%88,%89,%90,%91,%92,%93,%94,%95}, {%96,%97,%98,%99}, b, p, 1, 1, 1;\n}\n"
    : "+f"(d[0]),"+f"(d[1]),"+f"(d[2]),"+f"(d[3]),"+f"(d[4]),"+f"(d[5]),"+f"(d[6]),"+f"(d[7]),"+f"(d[8]),"+f"(d[9]),"+f"(d[10]),"+f"(d[11]),"+f"(d[12]),"+f"(d[13]),"+f"(d[14]),"+f"(d[15]),"+f"(d[16]),"+f"(d[17]),"+f"(d[18]),"+f"(d[19]),"+f"(d[20]),"+f"(d[21]),"+f"(d[22]),"+f"(d[23]),"+f"(d[24]),"+f"(d[25]),"+f"(d[26]),"+f"(d[27]),"+f"(d[28]),"+f"(d[29]),"+f"(d[30]),"+f"(d[31]),"+f"(d[32]),"+f"(d[33]),"+f"(d[34]),"+f"(d[35]),"+f"(d[36]),"+f"(d[37]),"+f"(d[38]),"+f"(d[39]),"+f"(d[40]),"+f"(d[41]),"+f"(d[42]),"+f"(d[43]),"+f"(d[44]),"+f"(d[45]),"+f"(d[46]),"+f"(d[47]),"+f"(d[48]),"+f"(d[49]),"+f"(d[50]),"+f"(d[51]),"+f"(d[52]),"+f"(d[53]),"+f"(d[54]),"+f"(d[55]),"+f"(d[56]),"+f"(d[57]),"+f"(d[58]),"+f"(d[59]),"+f"(d[60]),"+f"(d[61]),"+f"(d[62]),"+f"(d[63]),"+f"(d[64]),"+f"(d[65]),"+f"(d[66]),"+f"(d[67]),"+f"(d[68]),"+f"(d[69]),"+f"(d[70]),"+f"(d[71]),"+f"(d[72]),"+f"(d[73]),"+f"(d[74]),"+f"(d[75]),"+f"(d[76]),"+f"(d[77]),"+f"(d[78]),"+f"(d[79]),"+f"(d[80]),"+f"(d[81]),"+f"(d[82]),"+f"(d[83]),"+f"(d[84]),"+f"(d[85]),"+f"(d[86]),"+f"(d[87]),"+f"(d[88]),"+f"(d[89]),"+f"(d[90]),"+f"(d[91]),"+f"(d[92]),"+f"(d[93]),"+f"(d[94]),"+f"(d[95]) : "r"(a.x), "r"(a.y), "r"(a.z), "r"(a.w), "r"(db.lo), "r"(db.hi));
}
template<> __device__ __forceinline__ void wgmma_rs<192, 0>(float (&d)[96], const uint4& a, Desc db) {
  asm volatile("{\n.reg .pred p;\n.reg .b64 b;\nsetp.ne.b32 p, 0, 0;\nmov.b64 b, {%100, %101};\n"
    "wgmma.mma_async.sync.aligned.m64n192k16.f32.bf16.bf16 {%0,%1,%2,%3,%4,%5,%6,%7,%8,%9,%10,%11,%12,%13,%14,%15,%16,%17,%18,%19,%20,%21,%22,%23,%24,%25,%26,%27,%28,%29,%30,%31,%32,%33,%34,%35,%36,%37,%38,%39,%40,%41,%42,%43,%44,%45,%46,%47,%48,%49,%50,%51,%52,%53,%54,%55,%56,%57,%58,%59,%60,%61,%62,%63,%64,%65,%66,%67,%68,%69,%70,%71,%72,%73,%74,%75,%76,%77,%78,%79,%80,%81,%82,%83,%84,%85,%86,%87,%88,%89,%90,%91,%92,%93,%94,%95}, {%96,%97,%98,%99}, b, p, 1, 1, 1;\n}\n"
    : "=f"(d[0]),"=f"(d[1]),"=f"(d[2]),"=f"(d[3]),"=f"(d[4]),"=f"(d[5]),"=f"(d[6]),"=f"(d[7]),"=f"(d[8]),"=f"(d[9]),"=f"(d[10]),"=f"(d[11]),"=f"(d[12]),"=f"(d[13]),"=f"(d[14]),"=f"(d[15]),"=f"(d[16]),"=f"(d[17]),"=f"(d[18]),"=f"(d[19]),"=f"(d[20]),"=f"(d[21]),"=f"(d[22]),"=f"(d[23]),"=f"(d[24]),"=f"(d[25]),"=f"(d[26]),"=f"(d[27]),"=f"(d[28]),"=f"(d[29]),"=f"(d[30]),"=f"(d[31]),"=f"(d[32]),"=f"(d[33]),"=f"(d[34]),"=f"(d[35]),"=f"(d[36]),"=f"(d[37]),"=f"(d[38]),"=f"(d[39]),"=f"(d[40]),"=f"(d[41]),"=f"(d[42]),"=f"(d[43]),"=f"(d[44]),"=f"(d[45]),"=f"(d[46]),"=f"(d[47]),"=f"(d[48]),"=f"(d[49]),"=f"(d[50]),"=f"(d[51]),"=f"(d[52]),"=f"(d[53]),"=f"(d[54]),"=f"(d[55]),"=f"(d[56]),"=f"(d[57]),"=f"(d[58]),"=f"(d[59]),"=f"(d[60]),"=f"(d[61]),"=f"(d[62]),"=f"(d[63]),"=f"(d[64]),"=f"(d[65]),"=f"(d[66]),"=f"(d[67]),"=f"(d[68]),"=f"(d[69]),"=f"(d[70]),"=f"(d[71]),"=f"(d[72]),"=f"(d[73]),"=f"(d[74]),"=f"(d[75]),"=f"(d[76]),"=f"(d[77]),"=f"(d[78]),"=f"(d[79]),"=f"(d[80]),"=f"(d[81]),"=f"(d[82]),"=f"(d[83]),"=f"(d[84]),"=f"(d[85]),"=f"(d[86]),"=f"(d[87]),"=f"(d[88]),"=f"(d[89]),"=f"(d[90]),"=f"(d[91]),"=f"(d[92]),"=f"(d[93]),"=f"(d[94]),"=f"(d[95]) : "r"(a.x), "r"(a.y), "r"(a.z), "r"(a.w), "r"(db.lo), "r"(db.hi));
}
template<> __device__ __forceinline__ void wgmma_rs<256, 1>(float (&d)[128], const uint4& a, Desc db) {
  asm volatile("{\n.reg .pred p;\n.reg .b64 b;\nsetp.ne.b32 p, 1, 0;\nmov.b64 b, {%132, %133};\n"
    "wgmma.mma_async.sync.aligned.m64n256k16.f32.bf16.bf16 {%0,%1,%2,%3,%4,%5,%6,%7,%8,%9,%10,%11,%12,%13,%14,%15,%16,%17,%18,%19,%20,%21,%22,%23,%24,%25,%26,%27,%28,%29,%30,%31,%32,%33,%34,%35,%36,%37,%38,%39,%40,%41,%42,%43,%44,%45,%46,%47,%48,%49,%50,%51,%52,%53,%54,%55,%56,%57,%58,%59,%60,%61,%62,%63,%64,%65,%66,%67,%68,%69,%70,%71,%72,%73,%74,%75,%76,%77,%78,%79,%80,%81,%82,%83,%84,%85,%86,%87,%88,%89,%90,%91,%92,%93,%94,%95,%96,%97,%98,%99,%100,%101,%102,%103,%104,%105,%106,%107,%108,%109,%110,%111,%112,%113,%114,%115,%116,%117,%118,%119,%120,%121,%122,%123,%124,%125,%126,%127}, {%128,%129,%130,%131}, b, p, 1, 1, 1;\n}\n"
    : "+f"(d[0]),"+f"(d[1]),"+f"(d[2]),"+f"(d[3]),"+f"(d[4]),"+f"(d[5]),"+f"(d[6]),"+f"(d[7]),"+f"(d[8]),"+f"(d[9]),"+f"(d[10]),"+f"(d[11]),"+f"(d[12]),"+f"(d[13]),"+f"(d[14]),"+f"(d[15]),"+f"(d[16]),"+f"(d[17]),"+f"(d[18]),"+f"(d[19]),"+f"(d[20]),"+f"(d[21]),"+f"(d[22]),"+f"(d[23]),"+f"(d[24]),"+f"(d[25]),"+f"(d[26]),"+f"(d[27]),"+f"(d[28]),"+f"(d[29]),"+f"(d[30]),"+f"(d[31]),"+f"(d[32]),"+f"(d[33]),"+f"(d[34]),"+f"(d[35]),"+f"(d[36]),"+f"(d[37]),"+f"(d[38]),"+f"(d[39]),"+f"(d[40]),"+f"(d[41]),"+f"(d[42]),"+f"(d[43]),"+f"(d[44]),"+f"(d[45]),"+f"(d[46]),"+f"(d[47]),"+f"(d[48]),"+f"(d[49]),"+f"(d[50]),"+f"(d[51]),"+f"(d[52]),"+f"(d[53]),"+f"(d[54]),"+f"(d[55]),"+f"(d[56]),"+f"(d[57]),"+f"(d[58]),"+f"(d[59]),"+f"(d[60]),"+f"(d[61]),"+f"(d[62]),"+f"(d[63]),"+f"(d[64]),"+f"(d[65]),"+f"(d[66]),"+f"(d[67]),"+f"(d[68]),"+f"(d[69]),"+f"(d[70]),"+f"(d[71]),"+f"(d[72]),"+f"(d[73]),"+f"(d[74]),"+f"(d[75]),"+f"(d[76]),"+f"(d[77]),"+f"(d[78]),"+f"(d[79]),"+f"(d[80]),"+f"(d[81]),"+f"(d[82]),"+f"(d[83]),"+f"(d[84]),"+f"(d[85]),"+f"(d[86]),"+f"(d[87]),"+f"(d[88]),"+f"(d[89]),"+f"(d[90]),"+f"(d[91]),"+f"(d[92]),"+f"(d[93]),"+f"(d[94]),"+f"(d[95]),"+f"(d[96]),"+f"(d[97]),"+f"(d[98]),"+f"(d[99]),"+f"(d[100]),"+f"(d[101]),"+f"(d[102]),"+f"(d[103]),"+f"(d[104]),"+f"(d[105]),"+f"(d[106]),"+f"(d[107]),"+f"(d[108]),"+f"(d[109]),"+f"(d[110]),"+f"(d[111]),"+f"(d[112]),"+f"(d[113]),"+f"(d[114]),"+f"(d[115]),"+f"(d[116]),"+f"(d[117]),"+f"(d[118]),"+f"(d[119]),"+f"(d[120]),"+f"(d[121]),"+f"(d[122]),"+f"(d[123]),"+f"(d[124]),"+f"(d[125]),"+f"(d[126]),"+f"(d[127]) : "r"(a.x), "r"(a.y), "r"(a.z), "r"(a.w), "r"(db.lo), "r"(db.hi));
}
template<> __device__ __forceinline__ void wgmma_rs<256, 0>(float (&d)[128], const uint4& a, Desc db) {
  asm volatile("{\n.reg .pred p;\n.reg .b64 b;\nsetp.ne.b32 p, 0, 0;\nmov.b64 b, {%132, %133};\n"
    "wgmma.mma_async.sync.aligned.m64n256k16.f32.bf16.bf16 {%0,%1,%2,%3,%4,%5,%6,%7,%8,%9,%10,%11,%12,%13,%14,%15,%16,%17,%18,%19,%20,%21,%22,%23,%24,%25,%26,%27,%28,%29,%30,%31,%32,%33,%34,%35,%36,%37,%38,%39,%40,%41,%42,%43,%44,%45,%46,%47,%48,%49,%50,%51,%52,%53,%54,%55,%56,%57,%58,%59,%60,%61,%62,%63,%64,%65,%66,%67,%68,%69,%70,%71,%72,%73,%74,%75,%76,%77,%78,%79,%80,%81,%82,%83,%84,%85,%86,%87,%88,%89,%90,%91,%92,%93,%94,%95,%96,%97,%98,%99,%100,%101,%102,%103,%104,%105,%106,%107,%108,%109,%110,%111,%112,%113,%114,%115,%116,%117,%118,%119,%120,%121,%122,%123,%124,%125,%126,%127}, {%128,%129,%130,%131}, b, p, 1, 1, 1;\n}\n"
    : "=f"(d[0]),"=f"(d[1]),"=f"(d[2]),"=f"(d[3]),"=f"(d[4]),"=f"(d[5]),"=f"(d[6]),"=f"(d[7]),"=f"(d[8]),"=f"(d[9]),"=f"(d[10]),"=f"(d[11]),"=f"(d[12]),"=f"(d[13]),"=f"(d[14]),"=f"(d[15]),"=f"(d[16]),"=f"(d[17]),"=f"(d[18]),"=f"(d[19]),"=f"(d[20]),"=f"(d[21]),"=f"(d[22]),"=f"(d[23]),"=f"(d[24]),"=f"(d[25]),"=f"(d[26]),"=f"(d[27]),"=f"(d[28]),"=f"(d[29]),"=f"(d[30]),"=f"(d[31]),"=f"(d[32]),"=f"(d[33]),"=f"(d[34]),"=f"(d[35]),"=f"(d[36]),"=f"(d[37]),"=f"(d[38]),"=f"(d[39]),"=f"(d[40]),"=f"(d[41]),"=f"(d[42]),"=f"(d[43]),"=f"(d[44]),"=f"(d[45]),"=f"(d[46]),"=f"(d[47]),"=f"(d[48]),"=f"(d[49]),"=f"(d[50]),"=f"(d[51]),"=f"(d[52]),"=f"(d[53]),"=f"(d[54]),"=f"(d[55]),"=f"(d[56]),"=f"(d[57]),"=f"(d[58]),"=f"(d[59]),"=f"(d[60]),"=f"(d[61]),"=f"(d[62]),"=f"(d[63]),"=f"(d[64]),"=f"(d[65]),"=f"(d[66]),"=f"(d[67]),"=f"(d[68]),"=f"(d[69]),"=f"(d[70]),"=f"(d[71]),"=f"(d[72]),"=f"(d[73]),"=f"(d[74]),"=f"(d[75]),"=f"(d[76]),"=f"(d[77]),"=f"(d[78]),"=f"(d[79]),"=f"(d[80]),"=f"(d[81]),"=f"(d[82]),"=f"(d[83]),"=f"(d[84]),"=f"(d[85]),"=f"(d[86]),"=f"(d[87]),"=f"(d[88]),"=f"(d[89]),"=f"(d[90]),"=f"(d[91]),"=f"(d[92]),"=f"(d[93]),"=f"(d[94]),"=f"(d[95]),"=f"(d[96]),"=f"(d[97]),"=f"(d[98]),"=f"(d[99]),"=f"(d[100]),"=f"(d[101]),"=f"(d[102]),"=f"(d[103]),"=f"(d[104]),"=f"(d[105]),"=f"(d[106]),"=f"(d[107]),"=f"(d[108]),"=f"(d[109]),"=f"(d[110]),"=f"(d[111]),"=f"(d[112]),"=f"(d[113]),"=f"(d[114]),"=f"(d[115]),"=f"(d[116]),"=f"(d[117]),"=f"(d[118]),"=f"(d[119]),"=f"(d[120]),"=f"(d[121]),"=f"(d[122]),"=f"(d[123]),"=f"(d[124]),"=f"(d[125]),"=f"(d[126]),"=f"(d[127]) : "r"(a.x), "r"(a.y), "r"(a.z), "r"(a.w), "r"(db.lo), "r"(db.hi));
}
template<int N> __device__ __forceinline__ void wgmma_ra(float (&d)[N / 2], const uint4& a, Desc db, bool acc) {
  if (acc) wgmma_rs<N, 1>(d, a, db); else wgmma_rs<N, 0>(d, a, db);
}

__device__ __forceinline__ uint32_t smem_u32(const void* p) { return (uint32_t)__cvta_generic_to_shared(p); }
__device__ __forceinline__ void mbar_init(uint32_t bar, uint32_t cnt) { asm volatile("mbarrier.init.shared::cta.b64 [%0], %1;" ::"r"(bar), "r"(cnt)); }
__device__ __forceinline__ void mbar_expect_tx(uint32_t bar, uint32_t bytes) { asm volatile("mbarrier.arrive.expect_tx.shared::cta.b64 _, [%0], %1;" ::"r"(bar), "r"(bytes) : "memory"); }
__device__ __forceinline__ void mbar_arrive(uint32_t bar) { asm volatile("mbarrier.arrive.shared::cta.b64 _, [%0];" ::"r"(bar) : "memory"); }
__device__ __forceinline__ void mbar_arrive_remote(uint32_t rbar) { asm volatile("mbarrier.arrive.shared::cluster.b64 _, [%0];" ::"r"(rbar) : "memory"); }
__device__ __forceinline__ void mbar_wait(uint32_t bar, uint32_t parity) {
  asm volatile(
      "{\n.reg .pred p;\n.reg .u32 c;\nmov.u32 c, 0;\nLAB_WAIT:\nmbarrier.try_wait.parity.shared::cta.b64 p, [%0], %1;\n@p bra DONE;\n"
      "add.u32 c, c, 1;\nsetp.lt.u32 p, c, 1000000;\n@p bra LAB_WAIT;\ntrap;\nDONE:\n}\n" ::"r"(bar), "r"(parity) : "memory");
}
__device__ __forceinline__ void mbar_wait_c(uint32_t bar, uint32_t parity) {
  asm volatile("{\n.reg .pred p;\nLAB_WAIT:\nmbarrier.try_wait.parity.shared::cta.b64 p, [%0], %1;\n@!p bra LAB_WAIT;\n}\n" ::"r"(bar), "r"(parity) : "memory");
}
__device__ __forceinline__ uint32_t late(uint32_t bar, uint32_t v) {
  uint32_t r;
  asm volatile("{\n.reg .pred p;\nmbarrier.test_wait.parity.shared::cta.b64 p, [%1], 0;\nselp.b32 %0, %2, %1, p;\n}\n" : "=r"(r) : "r"(bar), "r"(v) : "memory");
  return r;
}
__device__ __forceinline__ void wtma2d(uint32_t dst, const CUtensorMap* m, int c0, int c1, uint32_t bar, uint64_t pol) {
  asm volatile("cp.async.bulk.tensor.2d.shared::cluster.global.mbarrier::complete_tx::bytes.multicast::cluster.L2::cache_hint [%0], [%1, {%3, %4}], [%2], %5, %6;"
               ::"r"(dst), "l"(m), "r"(bar), "r"(c0), "r"(c1), "h"((uint16_t)3), "l"(pol) : "memory");
}
__device__ __forceinline__ void wtma3d(uint32_t dst, const CUtensorMap* m, int c0, int c1, int c2, uint32_t bar, uint64_t pol) {
  asm volatile("cp.async.bulk.tensor.3d.shared::cluster.global.mbarrier::complete_tx::bytes.multicast::cluster.L2::cache_hint [%0], [%1, {%3, %4, %5}], [%2], %6, %7;"
               ::"r"(dst), "l"(m), "r"(bar), "r"(c0), "r"(c1), "r"(c2), "h"((uint16_t)3), "l"(pol) : "memory");
}
__device__ __forceinline__ void wbulk(uint32_t dst, const void* src, uint32_t bytes, uint32_t bar, uint64_t pol) {
  asm volatile("cp.async.bulk.shared::cluster.global.mbarrier::complete_tx::bytes.multicast::cluster.L2::cache_hint [%0], [%1], %2, [%3], %4, %5;"
               ::"r"(dst), "l"(src), "r"(bytes), "r"(bar), "h"((uint16_t)3), "l"(pol) : "memory");
}
__device__ __forceinline__ void tma3d(uint32_t dst, const CUtensorMap* m, int c0, int c1, int c2, uint32_t bar) {
  asm volatile("cp.async.bulk.tensor.3d.shared::cluster.global.mbarrier::complete_tx::bytes [%0], [%1, {%3, %4, %5}], [%2];"
               ::"r"(dst), "l"(m), "r"(bar), "r"(c0), "r"(c1), "r"(c2) : "memory");
}
__device__ __forceinline__ void tma_store3d(const CUtensorMap* m, uint32_t src, int c0, int c1, int c2) {
  asm volatile("cp.async.bulk.tensor.3d.global.shared::cta.bulk_group [%0, {%2, %3, %4}], [%1];" ::"l"(m), "r"(src), "r"(c0), "r"(c1), "r"(c2) : "memory");
}
__device__ __forceinline__ void prefetch_l2(const void* p, uint32_t bytes) { asm volatile("cp.async.bulk.prefetch.L2.global [%0], %1;" ::"l"(p), "r"(bytes) : "memory"); }
__device__ __forceinline__ uint64_t policy_evict_first() { uint64_t p; asm volatile("createpolicy.fractional.L2::evict_first.b64 %0, 1.0;" : "=l"(p)); return p; }
__device__ __forceinline__ uint64_t policy_evict_normal() { uint64_t p; asm volatile("createpolicy.fractional.L2::evict_normal.b64 %0, 1.0;" : "=l"(p)); return p; }
__device__ __forceinline__ void bulk_commit() { asm volatile("cp.async.bulk.commit_group;" ::: "memory"); }
__device__ __forceinline__ void bulk_wait_all() { asm volatile("cp.async.bulk.wait_group 0;" ::: "memory"); }
__device__ __forceinline__ void fence_async_smem() { asm volatile("fence.proxy.async.shared::cta;" ::: "memory"); }
__device__ __forceinline__ bool elect_one() {
  uint32_t p;
  asm volatile("{\n.reg .pred P;\nelect.sync _|P, 0xffffffff;\nselp.u32 %0, 1, 0, P;\n}\n" : "=r"(p));
  return p;
}
__device__ __forceinline__ void wg_fence() { asm volatile("wgmma.fence.sync.aligned;" ::: "memory"); }
__device__ __forceinline__ void wg_commit() { asm volatile("wgmma.commit_group.sync.aligned;" ::: "memory"); }
template <int n> __device__ __forceinline__ void wg_wait() { asm volatile("wgmma.wait_group.sync.aligned %0;" ::"n"(n) : "memory"); }
__device__ __forceinline__ void wg_bar(int w) { asm volatile("bar.sync %0, 128;" ::"r"(w + 1) : "memory"); }
__device__ __forceinline__ void cluster_sync() { asm volatile("barrier.cluster.arrive.relaxed.aligned;\nbarrier.cluster.wait.aligned;" ::: "memory"); }
__device__ __forceinline__ void fence_gpu() { asm volatile("fence.acq_rel.gpu;" ::: "memory"); }
__device__ __forceinline__ uint32_t ld_relaxed(const uint32_t* p) { uint32_t v; asm volatile("ld.relaxed.gpu.global.u32 %0, [%1];" : "=r"(v) : "l"(p) : "memory"); return v; }
__device__ __forceinline__ uint32_t ld_acquire(const uint32_t* p) { uint32_t v; asm volatile("ld.acquire.gpu.global.u32 %0, [%1];" : "=r"(v) : "l"(p) : "memory"); return v; }
__device__ __forceinline__ uint4 ld_relaxed4(const uint4* p) {
  uint4 v; asm volatile("ld.relaxed.gpu.global.v4.u32 {%0,%1,%2,%3}, [%4];" : "=r"(v.x), "=r"(v.y), "=r"(v.z), "=r"(v.w) : "l"(p) : "memory"); return v;
}
__device__ __forceinline__ uint2 ld_relaxed2(const uint2* p) {
  uint2 v; asm volatile("ld.relaxed.gpu.global.v2.u32 {%0,%1}, [%2];" : "=r"(v.x), "=r"(v.y) : "l"(p) : "memory"); return v;
}
__device__ __forceinline__ void st_relaxed(uint32_t* p, uint32_t a) { asm volatile("st.relaxed.gpu.global.u32 [%0], %1;" ::"l"(p), "r"(a) : "memory"); }
__device__ __forceinline__ void st_relaxed4(uint4* p, uint32_t a, uint32_t b, uint32_t c, uint32_t d) {
  asm volatile("st.relaxed.gpu.global.v4.u32 [%0], {%1,%2,%3,%4};" ::"l"(p), "r"(a), "r"(b), "r"(c), "r"(d) : "memory");
}
__device__ __forceinline__ void st_relaxed2(uint2* p, uint32_t a, uint32_t b) {
  asm volatile("st.relaxed.gpu.global.v2.u32 [%0], {%1,%2};" ::"l"(p), "r"(a), "r"(b) : "memory");
}
__device__ __forceinline__ void red4(uint4* p, uint32_t a, uint32_t b, uint32_t c, uint32_t d) {
  asm volatile("red.relaxed.gpu.global.add.noftz.v4.bf16x2 [%0], {%1,%2,%3,%4};" ::"l"(p), "r"(a), "r"(b), "r"(c), "r"(d) : "memory");
}
__device__ __forceinline__ void red2(uint2* p, uint32_t a, uint32_t b) {
  asm volatile("red.relaxed.gpu.global.add.noftz.v2.bf16x2 [%0], {%1,%2};" ::"l"(p), "r"(a), "r"(b) : "memory");
}
constexpr int SPIN_MAX = 1 << 21;
__device__ __forceinline__ uint32_t pack_bf16(float lo, float hi) { uint32_t r; asm("cvt.rn.bf16x2.f32 %0, %1, %2;" : "=r"(r) : "f"(hi), "f"(lo)); return r; }
__device__ __forceinline__ float bf_lo(uint32_t v) { return __uint_as_float(v << 16); }
__device__ __forceinline__ float bf_hi(uint32_t v) { return __uint_as_float(v & 0xffff0000u); }
__device__ __forceinline__ float2 lds64(uint32_t a) { float2 v; asm volatile("ld.shared.v2.f32 {%0,%1}, [%2];" : "=f"(v.x), "=f"(v.y) : "r"(a)); return v; }
__device__ __forceinline__ uint32_t lds32(uint32_t a) { uint32_t v; asm volatile("ld.shared.b32 %0, [%1];" : "=r"(v) : "r"(a)); return v; }
__device__ __forceinline__ void sts64f(uint32_t a, float x, float y) { asm volatile("st.shared.v2.f32 [%0], {%1,%2};" ::"r"(a), "f"(x), "f"(y) : "memory"); }
__device__ __forceinline__ void sts32(uint32_t a, uint32_t x) { asm volatile("st.volatile.shared.b32 [%0], %1;" ::"r"(a), "r"(x) : "memory"); }
__device__ __forceinline__ void gate(uint32_t a, int need) {
#pragma unroll 1
  for (int it = 0; it < SPIN_MAX; it++) {
    int v; asm volatile("ld.volatile.shared.b32 %0, [%1];" : "=r"(v) : "r"(a) : "memory");
    if (v >= need) break;
    if (GSLEEP) __nanosleep(GSLEEP);
  }
}
__device__ __forceinline__ void sts128(uint32_t a, uint32_t x, uint32_t y, uint32_t z, uint32_t u) { asm volatile("st.shared.v4.b32 [%0], {%1,%2,%3,%4};" ::"r"(a), "r"(x), "r"(y), "r"(z), "r"(u) : "memory"); }
__device__ __forceinline__ uint4 lds128(uint32_t a) { uint4 v; asm volatile("ld.shared.v4.u32 {%0,%1,%2,%3}, [%4];" : "=r"(v.x), "=r"(v.y), "=r"(v.z), "=r"(v.w) : "r"(a) : "memory"); return v; }
__device__ __forceinline__ uint32_t hmul2(uint32_t a, uint32_t b) { uint32_t r; asm("mul.rn.bf16x2 %0, %1, %2;" : "=r"(r) : "r"(a), "r"(b)); return r; }
__device__ __forceinline__ uint32_t hadd2(uint32_t a, uint32_t b) { uint32_t r; asm("add.rn.bf16x2 %0, %1, %2;" : "=r"(r) : "r"(a), "r"(b)); return r; }
__device__ __forceinline__ void stsm4(uint32_t a, uint32_t r0, uint32_t r1, uint32_t r2, uint32_t r3) {
  asm volatile("stmatrix.sync.aligned.m8n8.x4.shared.b16 [%0], {%1,%2,%3,%4};" ::"r"(a), "r"(r0), "r"(r1), "r"(r2), "r"(r3) : "memory");
}
__device__ __forceinline__ void stsm2(uint32_t a, uint32_t r0, uint32_t r1) {
  asm volatile("stmatrix.sync.aligned.m8n8.x2.shared.b16 [%0], {%1,%2};" ::"r"(a), "r"(r0), "r"(r1) : "memory");
}
__device__ __forceinline__ uint4 ldsm4(uint32_t a) {
  uint4 r; asm volatile("ldmatrix.sync.aligned.m8n8.x4.shared.b16 {%0,%1,%2,%3}, [%4];" : "=r"(r.x), "=r"(r.y), "=r"(r.z), "=r"(r.w) : "r"(a) : "memory"); return r;
}
__device__ __forceinline__ uint32_t movm(uint32_t a) { uint32_t r; asm("movmatrix.sync.aligned.m8n8.trans.b16 %0, %1;" : "=r"(r) : "r"(a)); return r; }
__device__ __forceinline__ void mma16816z(float (&d)[4], uint32_t a0, uint32_t a1, uint32_t a2, uint32_t a3, uint32_t b0, uint32_t b1) {
  asm("mma.sync.aligned.m16n8k16.row.col.f32.bf16.bf16.f32 {%0,%1,%2,%3}, {%4,%5,%6,%7}, {%8,%9}, {%10,%10,%10,%10};"
      : "=f"(d[0]), "=f"(d[1]), "=f"(d[2]), "=f"(d[3]) : "r"(a0), "r"(a1), "r"(a2), "r"(a3), "r"(b0), "r"(b1), "f"(0.f));
}
__device__ __forceinline__ void mma16816(float (&d)[4], const uint4& a, uint32_t b0, uint32_t b1) {
  asm("mma.sync.aligned.m16n8k16.row.col.f32.bf16.bf16.f32 {%0,%1,%2,%3}, {%4,%5,%6,%7}, {%8,%9}, {%0,%1,%2,%3};"
      : "+f"(d[0]), "+f"(d[1]), "+f"(d[2]), "+f"(d[3]) : "r"(a.x), "r"(a.y), "r"(a.z), "r"(a.w), "r"(b0), "r"(b1));
}
__device__ __forceinline__ void mma1688(float (&d)[4], uint32_t a0, uint32_t a1, uint32_t b0) {
  asm("mma.sync.aligned.m16n8k8.row.col.f32.bf16.bf16.f32 {%0,%1,%2,%3}, {%4,%5}, {%6}, {%0,%1,%2,%3};"
      : "+f"(d[0]), "+f"(d[1]), "+f"(d[2]), "+f"(d[3]) : "r"(a0), "r"(a1), "r"(b0));
}
__device__ __forceinline__ float quad_sum(float v) { v += __shfl_xor_sync(0xffffffffu, v, 1); v += __shfl_xor_sync(0xffffffffu, v, 2); return v; }
__device__ __forceinline__ float quad_max(float v) { v = fmaxf(v, __shfl_xor_sync(0xffffffffu, v, 1)); v = fmaxf(v, __shfl_xor_sync(0xffffffffu, v, 2)); return v; }
__device__ __forceinline__ float rcp(float x) { float r; asm("rcp.approx.ftz.f32 %0, %1;" : "=f"(r) : "f"(x)); return r; }
__device__ __forceinline__ float rsq(float x) { float r; asm("rsqrt.approx.ftz.f32 %0, %1;" : "=f"(r) : "f"(x)); return r; }
__device__ __forceinline__ float ex2(float x) { float r; asm("ex2.approx.ftz.f32 %0, %1;" : "=f"(r) : "f"(x)); return r; }
__device__ __forceinline__ uint32_t chk(uint32_t acc, uint32_t v, uint32_t tag) { uint32_t r; asm("lop3.b32 %0, %1, %2, %3, 0xF6;" : "=r"(r) : "r"(acc), "r"(v), "r"(tag)); return r; }
__device__ __forceinline__ uint32_t chk2(uint32_t a, uint32_t b, uint32_t tag) { uint32_t r; asm("lop3.b32 %0, %1, %2, %3, 0x7E;" : "=r"(r) : "r"(a), "r"(b), "r"(tag)); return r; }
__device__ __forceinline__ uint32_t tagged(uint32_t v, uint32_t tag) { return (v & ~1u) | tag; }

__device__ __forceinline__ int group_k0(int g, int j) {
  const int h = g >= 9, r = g - 2 - 7 * h;
  return g < 2 ? 64 * j + 32 * g : g < 16 ? 64 * (r + (r >= j)) + 32 * h : 32 * g;
}
__device__ __forceinline__ uint32_t xin_off(int c, int w) { return SM_X + (2 * c + w + (2 * c + w < 9 ? 9 : -9)) * 8192; }
__device__ __forceinline__ uint32_t xin_bar(int c) { return BAR_FULLX + 8 * (c < 8 ? c ^ 4 : c); }
__device__ __forceinline__ constexpr uint32_t qkv_xslot(int g) { return g < 5 || g > 11 ? 2 : (0x5140762u >> (4 * (g - 5))) & 15; }

template <int N> struct IC { static constexpr int v = N; };

struct Cons {
  uint32_t sb;
  uint32_t rem;
  uint32_t sB, mB;
  uint32_t mX;
  bool elect;
  __device__ __forceinline__ void release2(uint32_t bar) const { if (elect) { mbar_arrive(sb + bar); mbar_arrive_remote(rem + bar); } }
  __device__ __forceinline__ uint32_t nextB(uint32_t& prev) {
    mbar_wait_c(sb + BAR_FULLB + sB, mB);
    const uint32_t a = (((sb & 0x3FFFF) + SM_B) >> 4) + sB * (BSLOT / 128);
    prev = sB == 0 ? 32 : sB - 8;
    sB += 8;
    if (sB == 40) { sB = 0; mB ^= 1; }
    return a;
  }
  __device__ __forceinline__ void progress(uint32_t v) const { if (elect) sts32(sb + SM_PROG + (threadIdx.x >> 5), v); }
  __device__ __forceinline__ void releaseLastB() const { release2(BAR_EMPTYB + (sB == 0 ? 32 : sB - 8)); }
};

__device__ __forceinline__ float2 gather_sums(const uint2* a, uint32_t stag) {
  uint2 sa, sc;
  do { sa = ld_relaxed2(a); sc = ld_relaxed2(a + 8); } while (__any_sync(0xffffffffu, chk2(sa.x, sc.x, stag) & 3));
  return make_float2(quad_sum(__uint_as_float(sa.x) + __uint_as_float(sc.x)), quad_sum(__uint_as_float(sa.y) + __uint_as_float(sc.y)));
}

struct Norm {
  float m0, m1;
  uint32_t nm0, nm1;
  float d0, d1;
  uint2 u0, u1;
  __device__ __forceinline__ Norm(float2 sum) : m0(sum.x * (-1.f / 576)), m1(sum.y * (-1.f / 576)), nm0(pack_bf16(m0, m0)), nm1(pack_bf16(m1, m1)), d0(0.f), d1(0.f) {}
  __device__ __forceinline__ uint4 centre(const uint4& a) const { return make_uint4(hadd2(a.x, nm0), hadd2(a.y, nm1), hadd2(a.z, nm0), hadd2(a.w, nm1)); }
  __device__ __forceinline__ void sqr(uint32_t a, uint32_t b) {
    d0 = fmaf(bf_lo(a), bf_lo(a), fmaf(bf_hi(a), bf_hi(a), d0)); d1 = fmaf(bf_lo(b), bf_lo(b), fmaf(bf_hi(b), bf_hi(b), d1));
  }
  __device__ __forceinline__ void send(uint2* a, int t, uint32_t stag) {
    d0 = quad_sum(d0); d1 = quad_sum(d1);
    if ((t & 3) == 0) st_relaxed2(a, (__float_as_uint(d0) & ~3u) | stag, __float_as_uint(d1));
  }
  __device__ __forceinline__ void fetch(const uint2* a) { u0 = ld_relaxed2(a); u1 = ld_relaxed2(a + 8); }
  __device__ __forceinline__ float2 rstd(const uint2* a, uint32_t stag) {
    while (__any_sync(0xffffffffu, chk2(u0.x, u1.x, stag) & 3)) fetch(a);
    const float e0 = bf_lo(nm0) - m0, e1 = bf_lo(nm1) - m1;
    const float v0 = fmaf(quad_sum(__uint_as_float(u0.x) + __uint_as_float(u1.x)), 1.f / 576, -e0 * e0);
    const float v1 = fmaf(quad_sum(__uint_as_float(u0.y) + __uint_as_float(u1.y)), 1.f / 576, -e1 * e1);
    float2 r = make_float2(rsq(fmaxf(v0, 0.f) + 1e-5f), rsq(fmaxf(v1, 0.f) + 1e-5f));
    asm volatile("" : "+f"(r.x), "+f"(r.y));
    return r;
  }
};

template <class Pre, class Mma>
__device__ __forceinline__ float2 ln_gemm_in(Cons& c, Group* G, uint32_t (&p)[18], float2& sum, int w, int st0, int j, int t, Pre&& pre, Mma&& mma) {
  const uint32_t xa = c.sb + (t >> 5) * 2048 + (t & 15) * 128, sw = (((t >> 4) & 1) ^ (t & 7)) * 16;
  float ra[4] = {0.f, 0.f, 0.f, 0.f}, rb[4] = {0.f, 0.f, 0.f, 0.f};
#pragma unroll 1
  for (int cc = 0; cc < 9; cc++) {
    const uint32_t a = xa + xin_off(cc, w);
    mbar_wait_c(c.sb + xin_bar(cc), 0);
    const uint4 u0 = ldsm4(a + sw), u1 = ldsm4(a + (sw ^ 32)), u2 = ldsm4(a + (sw ^ 64)), u3 = ldsm4(a + (sw ^ 96));
    mma16816(ra, u0, 0x3f803f80u, 0x3f803f80u); mma16816(rb, u1, 0x3f803f80u, 0x3f803f80u);
    mma16816(ra, u2, 0x3f803f80u, 0x3f803f80u); mma16816(rb, u3, 0x3f803f80u, 0x3f803f80u);
  }
  sum = make_float2(ra[0] + rb[0], ra[2] + rb[2]);
  pre(0);
  Norm n(sum);
  n.u0 = n.u1 = make_uint2(0, 0);
  auto stats = [&] {
#pragma unroll
    for (int k = 0; k < 5; k++) {
      const uint4 u = ldsm4(xa + (k < 4 ? xin_off(j, w) + (sw ^ (32 * k)) : xin_off(8, w) + ((j ^ (t & 7)) << 4))), e = n.centre(u);
      p[4 * k] = u.x; p[4 * k + 1] = u.y;
      n.sqr(e.x, e.y);
      if (k < 4) { p[4 * k + 2] = u.z; p[4 * k + 3] = u.w; n.sqr(e.z, e.w); }
    }
    n.send(G->sq + st0 + 8 * j, t, 1);
  };
  if (STATP < 0) stats();
  else {
#pragma unroll
    for (int i = 0; i < 18; i++) p[i] = 0;
  }
  pre(1);
  uint4 y0 = ldsm4(xa + xin_off(0, w) + sw), y1 = ldsm4(xa + xin_off(0, w) + (sw ^ 32));
#pragma unroll 1
  for (int cc = 0; cc < 9; cc++) {
#pragma unroll
    for (int i = 0; i < 2; i++) {
      const uint4 f0 = n.centre(y0), f1 = n.centre(y1);
      const uint32_t a = xa + xin_off(min(cc + i, 8), w);
      y0 = ldsm4(a + (sw ^ (64 - 64 * i))); y1 = ldsm4(a + (sw ^ (96 - 64 * i)));
      uint32_t prev;
      const uint32_t bb = c.nextB(prev);
      mma(true, bb, f0, f1);
      if (i == 1) {
        if (STATP >= 0 && cc == STATP * w) stats();
        if (cc == 1) c.progress(3);
        if (cc == 7) n.fetch(G->sq + st0 + 16 * (t & 3));
        if (cc == 8 && w == 0) asm volatile("bar.arrive 6, 256;" ::: "memory");
      }
      wg_wait<1>();
      if (i + cc > 0) c.release2(BAR_EMPTYB + prev);
      if (2 * cc + i >= WOG && 2 * cc + i < WOG + 4) c.release2(BAR_EMPTYX + 32 + 8 * (2 * cc + i - WOG));
    }
  }
  c.mX = 0xff;
  const float2 r = n.rstd(G->sq + st0 + 16 * (t & 3), 1);
  if (w == 1) asm volatile("bar.sync 6, 256;" ::: "memory");
  wg_wait<0>();
  c.releaseLastB();
  c.release2(BAR_EMPTYX + 24);
  return r;
}

template <bool QKV, class Pre, class Mma>
__device__ __forceinline__ float2 ln_gemm(Cons& c, Group* G, const float (&v)[36], uint32_t (&p)[18], float2& sum, int st0, int j, int t,
                                          int layer, uint32_t tag, Pre&& pre, Mma&& mma) {
  constexpr bool known = !QKV && EARLY;
  const uint32_t stag = (2 * layer + (QKV ? 1 : 2)) & 3;
  uint4 x[6][2];
  uint4* src = G->xbox + t;
  asm volatile("" : "+l"(src));
  auto buf = [&](int g) -> uint4 (&)[2] { return x[g < 16 ? (g - 2) % 6 : g - 13]; };
  auto load = [&](int g0) {
#pragma unroll
    for (int g = g0; g < g0 + (g0 < 14 ? 3 : 2); g++) {
      const uint4* a = g < 16 ? src + ((g - 2) % 7 >= j ? 256 : 0) + (2 * ((g - 2) % 7) + 16 * (g >= 9)) * 128 : src + 2 * g * 128;
      buf(g)[0] = ld_relaxed4(a); buf(g)[1] = ld_relaxed4(a + 128);
    }
  };
  auto invalid = [&](int g, uint32_t tag) {
    uint32_t bad = chk(chk(chk2(buf(g)[0].x, buf(g)[1].x, tag), buf(g + 1)[0].x, tag), buf(g + 1)[1].x, tag);
    if (g < 14) bad = chk(chk(bad, buf(g + 2)[0].x, tag), buf(g + 2)[1].x, tag);
    if (g == 16) bad = chk(chk(chk(chk(bad, buf(g)[0].z, tag), buf(g)[1].z, tag), buf(g + 1)[0].z, tag), buf(g + 1)[1].z, tag);
    return __any_sync(0xffffffffu, bad & 1);
  };
  uint4* const d = src + 2 * j * 128;
  const int sq = st0 + 16 * (t & 3);
  if (!known) {
    float s0 = v[0] + v[1], s1 = v[2] + v[3];
#pragma unroll
    for (int i = 1; i < 9; i++) { s0 += v[4 * i] + v[4 * i + 1]; s1 += v[4 * i + 2] + v[4 * i + 3]; }
    s0 = quad_sum(s0); s1 = quad_sum(s1);
    if ((t & 3) == 0) st_relaxed2(G->sum + st0 + 8 * j, (__float_as_uint(s0) & ~3u) | stag, __float_as_uint(s1));
  }
#pragma unroll
  for (int i = 0; i < 18; i++) p[i] = pack_bf16(v[2 * i], v[2 * i + 1]);
#pragma unroll
  for (int i = 0; i < 2; i++) st_relaxed4(d + i * 128, tagged(p[4 * i], tag), p[4 * i + 1], p[4 * i + 2], p[4 * i + 3]);
  pre(0);
  if (!known) {
    sum = gather_sums(G->sum + sq, stag);
    load(2);
  }
  Norm n(sum);
  pre(1);
  const uint32_t* probe = &(G->xbox + (2 * (t & 7) + 1) * 128 + (t | 31))->x;
  uint32_t pv;
  auto inx = [](int g) { return QKV && ((g >= 5 && g < 12) || g == 17); };
  auto use = [](int g) { return QKV ? (g < 5 ? 108 : 101) + g : 18 + g; };
#pragma unroll
  for (int g = 0; g < 18; g++) {
    if (g < 16 ? g % 3 == 2 : g == 16) {
      const uint32_t lt = late(c.sb + BAR_FULLX + 64, tag);
      while (invalid(g, lt)) load(g);
      if (g < 16) load(g < 14 ? g + 3 : 16);
    }
    const uint4 f0 = n.centre(g < 2 ? make_uint4(p[8 * g], p[8 * g + 1], p[8 * g + 2], p[8 * g + 3]) : buf(g)[0]);
    const uint4 f1 = n.centre(g < 2 ? make_uint4(p[8 * g + 4], p[8 * g + 5], p[8 * g + 6], p[8 * g + 7]) : buf(g)[1]);
    if (g == 14) n.fetch(G->sq + sq);
    if (inx(g)) mbar_wait_c(c.sb + BAR_FULLX + 8 * qkv_xslot(g), ((0x34 >> qkv_xslot(g)) & 1) ^ (g == 17));
    else mbar_wait_c(c.sb + BAR_FULLB + 8 * (use(g) % 5), (use(g) / 5) & 1);
    mma(g, ((c.sb & 0x3FFFF) >> 4) + ((inx(g) ? SM_X + qkv_xslot(g) * XSLOT : SM_B + (use(g) % 5) * BSLOT) >> 4), f0, f1);
    if (g < 2) {
      if (known) {
        if (g == 0) {
          pv = ld_relaxed(probe);
        } else {
          const uint32_t lt = late(c.sb + BAR_FULLX + 64, tag);
          while (__any_sync(0xffffffffu, (pv ^ lt) & 1)) pv = ld_relaxed(probe);
          load(2);
        }
      }
      if (g == (known ? 1 : 0)) {
#pragma unroll
        for (int i = 2; i < 4; i++) st_relaxed4(d + (14 + i) * 128, tagged(p[4 * i], tag), p[4 * i + 1], p[4 * i + 2], p[4 * i + 3]);
        st_relaxed2((uint2*)(src + (32 + (j >> 1)) * 128) + (j & 1), tagged(p[16], tag), p[17]);
      }
      n.sqr(f0.x, f0.y); n.sqr(f0.z, f0.w); n.sqr(f1.x, f1.y); n.sqr(f1.z, f1.w);
      if (g == 1) {
        n.sqr(hadd2(p[16], n.nm0), hadd2(p[17], n.nm1));
        n.send(G->sq + st0 + 8 * j, t, stag);
      }
    }
    wg_wait<1>();
    if (g > 0 && !inx(g - 1)) c.release2(BAR_EMPTYB + 8 * (use(g - 1) % 5));
    if (QKV && g < 13) c.progress(33 + g);
    if (QKV && g == WOG - 1) c.release2(BAR_EMPTYX + 8 * qkv_xslot(17));
    if (QKV && g >= WOG && g < WOG + 4) c.release2(BAR_EMPTYX + 32 + 8 * (g - WOG));
  }
  if (QKV) c.mX = 0x34 ^ 0xf3;
  else { c.sB = 8 * (36 % 5); c.mB = (36 / 5) & 1; }
  const float2 r = n.rstd(G->sq + sq, late(c.sb + BAR_FULLX + 64, stag));
  wg_wait<0>();
  if (!QKV) c.release2(BAR_EMPTYB + 8 * (use(17) % 5));
  return r;
}

template <int NB, int OFF>
__device__ __forceinline__ void glu(const float (&a)[128], uint32_t (&h)[144]) {
#pragma unroll
  for (int b = 0; b < 2 * NB; b++) {
    if (HMUL) h[OFF + b] = hmul2(pack_bf16(a[2 * b], a[2 * b + 1]), pack_bf16(a[4 * NB + 2 * b], a[4 * NB + 2 * b + 1]));
    else h[OFF + b] = pack_bf16(a[2 * b] * a[4 * NB + 2 * b], a[2 * b + 1] * a[4 * NB + 2 * b + 1]);
  }
}

__global__ void __cluster_dims__(2, 1, 1) __launch_bounds__(384, 1)
fused_kernel(const __nv_bfloat16* __restrict__ x_in, Group* ws, const char* __restrict__ wqkv,
             const char* __restrict__ wg, const char* __restrict__ wu, uint32_t first, const __grid_constant__ Maps maps,
             const char* __restrict__ wo, const char* __restrict__ wd) {
  extern __shared__ __align__(1024) uint8_t smem_raw[];
  const uint32_t sb = smem_u32(smem_raw);
  const uint32_t bx = blockIdx.x - first;
  if (bx >= NCTA) {
    const int e = blockIdx.x & 3;
    const uint32_t par = ~ld_relaxed(ws->flag + 32) & 1;
    __nanosleep(RDELAY);
#pragma unroll 1
    for (int r = 144 * e + (threadIdx.x >> 3); r < 144 * e + 144; r += 48) {
      const uint4* row = (const uint4*)(wo + r * 1152) + (threadIdx.x & 7);
      float a = 0.f;
#pragma unroll
      for (int i = 0; i < 72; i += 8) {
        const uint4 u = __ldg(row + i);
        a += ((bf_lo(u.x) + bf_hi(u.x)) + (bf_lo(u.y) + bf_hi(u.y))) + ((bf_lo(u.z) + bf_hi(u.z)) + (bf_lo(u.w) + bf_hi(u.w)));
      }
      a = quad_sum(a);
      a += __shfl_xor_sync(0xffffffffu, a, 4);
      if ((threadIdx.x & 7) == 0) st_relaxed(((Scratch*)ws)->wsum + r, tagged(__float_as_uint(a), par));
    }
    const int cc = threadIdx.x % 54, r0 = threadIdx.x / 54, part = cc / 18, jj = 2 * e + (cc % 18) / 9, c9 = cc % 9;
    if (r0 < 6) {
#pragma unroll 4
      for (int k = r0; k < 576; k += 6) {
        const uint4 u = __ldg((const uint4*)(wqkv + k * 3456 + part * 1152 + 144 * jj) + c9);
        ((Scratch*)ws)->wq[jj][k >> 4][c9 < 8 ? part * 128 + (k & 15) * 8 + (c9 ^ (k & 7)) : 384 + part * 16 + (k & 15)] = u;
      }
    }
    fence_gpu();
    __syncthreads();
    if (threadIdx.x == 0) st_relaxed(((Scratch*)ws)->wsum + 608 + e, par);
    return;
  }
  if (threadIdx.x == 0) asm volatile("prefetch.tensormap [%0];" ::"l"(&maps.x) : "memory");
  const int warp = __shfl_sync(0xffffffffu, threadIdx.x >> 5, 0);
  const int lane = threadIdx.x & 31;
  const int rank = blockIdx.x & 1;
  if (elect_one()) {
    if (warp >= 8) {
#pragma unroll
      for (int i = 0; i < 9; i++) mbar_init(sb + SM_BAR + 72 * (warp - 8) + 8 * i, warp < 10 ? 1 : 4);
      sts32(sb + SM_PROG + 4 * (warp - 8), 0);
      asm volatile("fence.mbarrier_init.release.cluster;" ::: "memory");
    } else if (warp == 1 || warp == 2) {
      asm volatile("prefetch.tensormap [%0];" ::"l"(&maps.x + warp) : "memory");
    } else if (warp == 3) {
      if (PFMODE & 1) prefetch_l2((const char*)x_in + bx * 18432, 18432);
    } else if (warp == 4) {
      if (PFMODE & 2) prefetch_l2(wqkv + bx * (15552 / PFQ), 15552 / PFQ);
    }
  }
  __syncwarp();
  asm volatile("barrier.cluster.arrive.relaxed.aligned;" ::: "memory");
  if (warp == 8) PROFX(53);
  int lb = bx;
  if (GPCMAP) {
    const int cl = bx >> 1, u = cl - 36;
    lb = (cl < 4 ? cl : cl < 36 ? 8 * ((cl - 4) & 7) + ((cl - 4) >> 3) + (((cl - 4) & 7) ? 0 : 4) : 8 * (1 + u % 7) + 4 + u / 7) * 2 + rank;
  }
#define CTA_J(b) (((b) >> 1) & 7)
#define CTA_RB(b) ((((b) >> 4) << 1) | ((b) & 1))
  const int j = CTA_J(lb), rb = CTA_RB(lb);

  PROF(23);
  if (warp >= 8) {
    asm volatile("setmaxnreg.dec.sync.aligned.u32 " STR(REGS_P) ";");
    auto x_chunk = [&](int cc) {
      mbar_expect_tx(sb + xin_bar(cc), 16384);
      tma3d(sb + xin_off(cc, 0), &maps.x, 64 * cc, 0, 64 * rb, sb + xin_bar(cc));
      tma3d(sb + xin_off(cc, 1), &maps.x, 64 * cc, 1, 64 * rb, sb + xin_bar(cc));
    };
    if (warp == 9 && elect_one()) {
      fence_async_smem();
#pragma unroll 1
      for (int i = 0; i < 9; i++) x_chunk(i);
    }
    __syncwarp();
    if (warp == 9) PROFX(54);
    asm volatile("barrier.cluster.wait.aligned;" ::: "memory");
    if (warp == 8) PROFX(56);
    const uint64_t pol = W_POLICY(), pola = A_POLICY();
    uint4 (* const wq)[432] = ((Scratch*)ws)->wq[j];
    const uint32_t par = ~ld_relaxed(ws[2 * rb].flag + 32 + 32 * j) & 1;
    auto qkv_group = [&](bool copy, int k, uint32_t dst, uint32_t bar) {
      if (copy) {
        wbulk(dst + rank * 8192, wq[(k >> 4) + rank], 6912, bar, pol);
      } else {
        wtma3d(dst + rank * 8192, &maps.qm, 72 * j, k + 16 * rank, 0, bar, pola);
        wtma3d(dst + rank * 8192 + 6144, &maps.qc, 72 * j + 64, k + 16 * rank, 0, bar, pola);
      }
    };
    auto repacked = [&] {
#pragma unroll 1
      for (int it = 0; it < SPIN_MAX; it++)
        if (ld_acquire(((Scratch*)ws)->wsum + 608 + (j >> 1)) == par) break;
      asm volatile("fence.proxy.async.global;" ::: "memory");
    };
    const int ktab = group_k0(lane, j);
    auto qkv_gate = [&](int g) { if (g >= 8) gate(sb + SM_PROG, 33 + ((g - 8) * QPACE >> 4)); };
    if (warp == 8) {
      uint32_t s = 0, ph = 1;
      auto slot = [&](uint32_t bytes, auto&& issue) {
        const uint32_t bar = sb + BAR_FULLB + 8 * s;
        mbar_wait(sb + BAR_EMPTYB + 8 * s, ph);
        if (elect_one()) {
          mbar_expect_tx(bar, bytes);
          issue(sb + SM_B + s * BSLOT, bar);
        }
        if (++s == 5) { s = 0; ph ^= 1; }
      };
#pragma unroll 1
      for (int layer = 0; layer < NLAYERS; layer++) {
        if (layer) repacked();
#pragma unroll 1
        for (int g = 0; g < 18 - layer; g += layer && g == 4 ? 8 : 1) {
          const int k = layer ? __shfl_sync(0xffffffffu, ktab, g) : 32 * g;
          if (layer) qkv_gate(g);
          else if (g == QD) mbar_wait(sb + xin_bar(XH), 0);
          slot(2 * 6912, [&](uint32_t dst, uint32_t bar) { qkv_group(layer, k, dst, bar); });
        }
        if (!FCH) {
          gate(sb + SM_PROG, 32 * layer + 20);
          gate(sb + SM_PROG + 4, 32 * layer + 20);
        }
#pragma unroll 1
        for (int t = 0; t < 5; t++) {
          const CUtensorMap* m = &maps.g + (t < 3 ? rank : 2 + rank);
          asm volatile("" : "+l"(m));
          const int c2 = t < 3 ? 9 * j + 2 * t : 18 * j + 3 + 3 * t;
          const uint32_t half = t < 3 ? 8192 : 6144;
          auto tile = [&](int g) {
            const int k = __shfl_sync(0xffffffffu, ktab, g);
            slot(2 * half, [&](uint32_t dst, uint32_t bar) { wtma3d(dst + rank * half, m, 0, k, c2, bar, pol); });
          };
          int g = 0;
          if (t == 0) {
#pragma unroll 1
            for (; g < 5; g++) {
              mbar_wait(sb + BAR_FULLB + 8 * (s < FCH ? s + 5 - FCH : s - FCH), s < FCH ? ph : ph ^ 1);
              if (FG >= 0 && g == FN) gate(sb + SM_PROG + 4, 32 * layer + 20);
              tile(g);
            }
          }
#pragma unroll 1
          for (; g < 18; g++) tile(g);
        }
      }
    } else if (warp == 9) {
      uint32_t mE = 0;
      auto acquire = [&](uint32_t s) { mbar_wait(sb + BAR_EMPTYX + 8 * s, (mE >> s) & 1); mE ^= 1u << s; };
      auto landed = [&](uint32_t s) { mbar_wait(sb + BAR_FULLX + 8 * s, (mE >> s) & 1); };
      auto slot = [&](uint32_t s, const CUtensorMap* m, int col, int row, uint64_t pol) {
        acquire(s);
        if (elect_one()) {
          mbar_expect_tx(sb + BAR_FULLX + 8 * s, XSLOT);
          wtma2d(sb + SM_X + s * XSLOT + rank * 9216, m, col, row + 72 * rank, sb + BAR_FULLX + 8 * s, pol);
        }
      };
#pragma unroll 1
      for (int layer = 0; layer < NLAYERS; layer++) {
        if (layer) repacked();
#pragma unroll 1
        for (int g = 5; g < 18 * layer; g += g == 11 ? 6 : 1) {
          const uint32_t s = qkv_xslot(g);
          const int k = __shfl_sync(0xffffffffu, ktab, g);
          if (g < 12) qkv_gate(g);
          acquire(s);
          if (elect_one()) {
            mbar_expect_tx(sb + BAR_FULLX + 8 * s, 2 * 6912);
            qkv_group(true, k, sb + SM_X + s * XSLOT, sb + BAR_FULLX + 8 * s);
          }
          if (XCH & 1) landed(s);
        }
#pragma unroll 1
        for (int i = 0; i < 4; i++) { slot(4 + i, &maps.o, 64 * j, 144 * i, pola); if (XCH & 2) landed(4 + i); }
        acquire(3);
        if (elect_one()) {
          mbar_expect_tx(sb + BAR_FULLX + 24, 9216);
          wtma2d(sb + SM_WOC + rank * 4608, &maps.oc, 512 + 8 * j, 288 * rank, sb + BAR_FULLX + 24, pola);
          wtma2d(sb + SM_WOC + rank * 4608 + 2304, &maps.oc, 512 + 8 * j, 288 * rank + 144, sb + BAR_FULLX + 24, pola);
        }
#pragma unroll 1
        for (int u = 0; u < 36; u++) {
          const uint32_t s = 4 * (u & 1) + ((u >> 1) & 3);
          slot(s, &maps.d, u < 4 ? 512 : 64 * ((j + (u >> 2)) & 7), 576 * j + 144 * (u & 3), pol);
          if ((XCH & 4) && u < 3) landed(s);
        }
      }
    } else {
      const int w = warp - 10, grp = 2 * rb + w;
      if (PFMODE & 4) {
        mbar_wait(sb + xin_bar(XP), 0);
        if (lane == 0) prefetch_l2(wqkv + (2 * bx + w) * 7776, 7776);
      }
      if (EARLY) {
        gate(sb + SM_PROG, 3);
        if (w == 1) {
          uint32_t u[3];
#pragma unroll 1
          for (int it = 0; it < SPIN_MAX; it++) {
#pragma unroll
            for (int k = 0; k < 3; k++) u[k] = ld_relaxed(((Scratch*)ws)->wsum + 72 * j + min(lane + 32 * k, 71));
            if (!__any_sync(0xffffffffu, chk(chk2(u[0], u[1], par), u[2], par) & 1)) break;
            __nanosleep(300);
          }
#pragma unroll
          for (int k = 0; k < 3; k++) {
            const float f = __uint_as_float(u[k]);
            if (lane + 32 * k < 80) sts128(sb + SM_WSUM + 16 * (lane + 32 * k), pack_bf16(f, f - bf_lo(pack_bf16(f, 0.f))), 0, 0, 0);
          }
          fence_async_smem();
          __syncwarp();
          if (lane < 4) mbar_arrive(sb + BAR_WSUM);
          PROFX(57);
        }
      }
      gate(sb + SM_PROG, 3);
      if (w == 0) PROFX(58);
      auto prefetch_gu = [&](int l0, int n) {
#pragma unroll 1
        for (int i = lane; i < 36 * n; i += 32) {
          asm volatile("prefetch.global.L2 [%0];" ::"l"((w ? wu : wg) + (size_t)(36 * rb + i / n) * 9216 + 1152 * j + 128 * (l0 + i % n)));
          __nanosleep(PFSLEEP);
        }
      };
      auto clear = [&](uint4* p, int n) {
#pragma unroll 1
        for (int i = lane; i < n; i += 64) { st_relaxed4(p + i, 0, 0, 0, 0); st_relaxed4(p + i + 32, 0, 0, 0, 0); __nanosleep(CLRSLEEP); }
      };
      auto exchange = [&](uint32_t v, uint32_t bar) {
        if (FENCE1) { if (lane == 0) fence_gpu(); } else fence_gpu();
        __syncwarp();
        if (w == 0 && v != 1) PROFX(64 + 58 - 2 * v);
        if (lane == 0) st_relaxed(ws[grp].flag + j, v);
#pragma unroll 1
        for (int it = 0; it < SPIN_MAX; it++) {
          const uint32_t f = ld_relaxed(ws[grp].flag + (lane & 7));
          if (__all_sync(0xffffffffu, v ? f >= v : f == 0)) break;
        }
        if (lane == 0) mbar_arrive(sb + bar + 8 * w);
      };
      if (MAPPF && w == 0 && lane < 9) asm volatile("prefetch.tensormap [%0];" ::"l"(&maps.o + lane) : "memory");
#pragma unroll 1
      for (int layer = 0; layer < NLAYERS; layer++) {
        gate(sb + SM_PROG, 32 * layer + 3);
        if (PFF & 1) prefetch_gu(0, 2);
        gate(sb + SM_PROG, 32 * layer + 22);
        if (PFF & 2) prefetch_gu(2, 2);
        if (layer == 0) {
          clear(ws[grp].inbox[0] + 2 * j * INBOX, 2 * INBOX);
          exchange(1, BAR_CLR);
          if (w == 0) PROFX(59);
        }
        if (PFF & 2) prefetch_gu(4, 2);
        if (PFF & 4) prefetch_gu(6, 3);
#pragma unroll 1
        for (int i = lane; i < ((PFF & 8) ? 162 : 0); i += 32) {
          asm volatile("prefetch.global.L2 [%0];" ::"l"(wd + (size_t)(576 * j + 36 * rb + 18 * w) * 1152 + 128 * i));
          __nanosleep(PFSLEEP);
        }
        if (w == 0 && layer == 0) PROFX(60);
        mbar_wait(sb + BAR_REDDONE + 8 * w, layer);
        if (w == 0) PROFX(64 + 53 + 4 * layer);
        exchange(2 - 2 * layer, BAR_RREADY);
        if (w == 0) PROFX(64 + 56 + 4 * layer);
      }
      mbar_wait(sb + BAR_DONE + 8 * w, 0);
    }
    __syncwarp();
    cluster_sync();
  } else {
    asm volatile("setmaxnreg.inc.sync.aligned.u32 " STR(REGS_C) ";");
#define THREAD_IDS()                                                                   \
    int tid_ = threadIdx.x, bid_ = lb;                                                  \
    asm volatile("" : "+r"(tid_), "+r"(bid_));                                          \
    const int w = warp >> 2, wp = warp & 3;                                             \
    const int lane = tid_ & 31, t = tid_ & 127, g = lane >> 2, q = lane & 3;           \
    const int j = CTA_J(bid_), rb = CTA_RB(bid_), grp = 2 * rb + w;                    \
    const int st0 = wp * 64 + g;                         \
    Group* const G = ws + grp;                                                         \
    const uint32_t dsb = (sb & 0x3FFFF) >> 4;                                          \
    (void)t; (void)g; (void)q; (void)grp; (void)j; (void)st0; (void)dsb; (void)G
    Cons c;
    c.sb = sb; c.sB = 0; c.mB = 0; c.mX = 0; c.elect = (threadIdx.x & 127) == 0;
    asm volatile("mapa.shared::cluster.u32 %0, %1, %2;" : "=r"(c.rem) : "r"(sb), "r"(rank ^ 1));
    float v[36], a1[96], a2[12];
    float2 sum, rs;
    uint32_t res[18], xtag;
    auto qkv_mma = [&](bool acc, uint32_t bb, const uint4& f0, const uint4& f1) {
      wg_fence();
      wgmma_ra<192>(a1, f0, desc_hi(2048, 1024, 1) + bb, acc);
      wgmma_ra<24>(a2, f0, desc_hi(128, 256, 0) + (bb + 384), acc);
      wgmma_ra<192>(a1, f1, desc_hi(2048, 1024, 1) + (bb + 512), true);
      wgmma_ra<24>(a2, f1, desc_hi(128, 256, 0) + (bb + 896), true);
      wg_commit();
    };
    {
      THREAD_IDS();
      if (OPEN) {
        if (q == 0) { st_relaxed2(G->sum + st0 + 8 * j, 0, 0); st_relaxed2(G->sq + st0 + 8 * j, 0, 0); }
        if (wp == 3) {
#pragma unroll
          for (int i = 0; i < 5; i++) st_relaxed4(G->halo + j * 160 + lane + i * 32, 0, 0, 0, 0);
        }
        if (lane >= OPENL) st_relaxed4(G->obox + (8 * WPROBE + j) * 128 + t, 0, 0, 0, 0);
      }
      xtag = __shfl_sync(0xffffffffu, ~ld_relaxed(G->flag + 32 + 32 * j) & 1, 0);
      if (OPEN && EARLY && lane >= OPENL) st_relaxed4(G->xbox + (2 * j + 1) * 128 + t, xtag ^ 1, 0, 0, 0);
      asm volatile("barrier.cluster.wait.aligned;" ::: "memory");
      PROF(0);
#pragma unroll
      for (int i = 0; i < 96; i++) asm volatile("mov.b32 %0, 0;" : "=f"(a1[i]));
#pragma unroll
      for (int i = 0; i < 12; i++) asm volatile("mov.b32 %0, 0;" : "=f"(a2[i]));
      PROF(1);
      rs = ln_gemm_in(c, G, res, sum, w, st0, j, t, [&](int i) { PROF(2 + i); if (i) PROF(4); }, qkv_mma);
    }
#pragma unroll 1
    for (int layer = 0;; layer++) {
      const uint32_t tag = layer ^ 1;
      const int pb = 1 + layer * 30;
      uint4 own[5];
      {
        THREAD_IDS();
        PROF(pb + 4);
        uint32_t kv[3][18];
        auto cvt = [&](int b, float r) {
#pragma unroll
          for (int cc = 0; cc < 18; cc++) {
            const float* a = (cc == 8 ? a2 + 4 : cc == 17 ? a2 + 8 : cc < 8 ? a1 + 32 + 4 * cc : a1 + 28 + 4 * cc) + 2 * (b - 1);
            const uint32_t u = pack_bf16(a[0] * r, a[1] * r);
            kv[b][cc] = cc < 9 ? u : movm(u);
          }
        };
        cvt(2, rs.y);
        const uint32_t msg = sb + SM_X + (w ? 3 * XSLOT : 24576) + wp * 2304 + lane * 16;
        if (wp == 3) {
          uint4* hp = G->halo + j * 160 + lane;
#pragma unroll
          for (int i = 0; i < 4; i++) st_relaxed4(hp + i * 32, tagged(kv[2][4 * i], tag), kv[2][4 * i + 1], kv[2][4 * i + 2], kv[2][4 * i + 3]);
          st_relaxed2((uint2*)(hp + 128), tagged(kv[2][16], tag), kv[2][17]);
        } else {
#pragma unroll
          for (int i = 0; i < 4; i++) sts128(msg + i * 512, kv[2][4 * i], kv[2][4 * i + 1], kv[2][4 * i + 2], kv[2][4 * i + 3]);
          sts64f(msg + 2048 - lane * 8, __uint_as_float(kv[2][16]), __uint_as_float(kv[2][17]));
        }
        cvt(1, rs.x);
        uint32_t Q[4][6];
#pragma unroll
        for (int h = 0; h < 4; h++)
#pragma unroll
          for (int i = 0; i < 6; i++) {
            const float* a = 4 * h + i < 16 ? a1 + 8 * h + 2 * i : a2 + 8 * h + 2 * i - 32;
            const uint32_t u = pack_bf16(a[0], a[1]);
            Q[h][i] = i < 2 ? (q >= h ? u : 0) : i < 4 ? u : (q <= h ? u : 0);
          }
        const bool lo0 = 2 * q > g, lo1 = 2 * q + 1 > g;
        const uint32_t M = (lo0 ? 0xffffu : 0u) | (lo1 ? 0xffff0000u : 0u);
        auto scores = [&](int h, int b, float (&s)[4]) {
          mma16816z(s, Q[h][0], Q[h][1], Q[h][2], Q[h][3], kv[b][2 * h], kv[b][2 * h + 1]);
          mma1688(s, Q[h][4], Q[h][5], kv[b][2 * h + 2]);
        };
        auto softmax = [&](float (&l)[4][2], float r, uint32_t (&P)[4]) {
          const float sl = r * (0.23570226039551584f * 1.4426950408889634f);
          float m[4];
#pragma unroll
          for (int h = 0; h < 4; h++) { m[h] = fmaxf(l[h][0], l[h][1]); m[h] = fmaxf(m[h], __shfl_xor_sync(0xffffffffu, m[h], 1)); }
#pragma unroll
          for (int h = 0; h < 4; h++) m[h] = fmaxf(m[h], __shfl_xor_sync(0xffffffffu, m[h], 2)) * sl;
#pragma unroll
          for (int h = 0; h < 4; h++) {
            l[h][0] = ex2(fmaf(l[h][0], sl, -m[h])); l[h][1] = ex2(fmaf(l[h][1], sl, -m[h]));
            m[h] = l[h][0] + l[h][1]; m[h] += __shfl_xor_sync(0xffffffffu, m[h], 1);
          }
#pragma unroll
          for (int h = 0; h < 4; h++) { m[h] = rcp(m[h] + __shfl_xor_sync(0xffffffffu, m[h], 2)); P[h] = pack_bf16(l[h][0] * m[h], l[h][1] * m[h]); }
        };
        const bool remote = wp == 0 && rb > 0;
        const uint4* hp = (G - 2)->halo + j * 160 + lane;
        auto halo = [&] {
#pragma unroll
          for (int i = 0; i < 4; i++) { const uint4 u = ld_relaxed4(hp + i * 32); kv[0][4 * i] = u.x; kv[0][4 * i + 1] = u.y; kv[0][4 * i + 2] = u.z; kv[0][4 * i + 3] = u.w; }
          const uint2 u = ld_relaxed2((const uint2*)(hp + 128));
          kv[0][16] = u.x; kv[0][17] = u.y;
        };
#pragma unroll
        for (int i = 0; i < 18; i++) kv[0][i] = 0;
        if (remote) halo();
        float l0[4][2], l1[4][2];
#pragma unroll
        for (int h = 0; h < 4; h++) {
          float s1[4], s2[4];
          scores(h, 1, s1); scores(h, 2, s2);
          l0[h][0] = s1[0]; l0[h][1] = s1[1];
          l1[h][0] = lo0 ? s1[2] : s2[2]; l1[h][1] = lo1 ? s1[3] : s2[3];
        }
        uint32_t P0[4], P1[4];
        softmax(l1, rs.y, P1);
        if (remote) {
          while (__any_sync(0xffffffffu, chk(chk2(kv[0][0], kv[0][4], tag) | chk2(kv[0][8], kv[0][12], tag), kv[0][16], tag) & 1)) halo();
        }
        if (FG < 0) c.progress(32 * layer + 20);
        wg_bar(w);
        if (wp > 0) {
          const uint32_t from = msg - 2304;
#pragma unroll
          for (int i = 0; i < 4; i++) { const uint4 u = lds128(from + i * 512); kv[0][4 * i] = u.x; kv[0][4 * i + 1] = u.y; kv[0][4 * i + 2] = u.z; kv[0][4 * i + 3] = u.w; }
          const float2 u = lds64(from + 2048 - lane * 8);
          kv[0][16] = __float_as_uint(u.x); kv[0][17] = __float_as_uint(u.y);
        }
        PROF(pb + 5);
        const bool first = (rb == 0 && wp == 0);
#pragma unroll
        for (int h = 0; h < 4; h++) {
          float s0[4];
          scores(h, 0, s0);
          if (first) s0[0] = s0[1] = -INFINITY;
          l0[h][0] = lo0 ? s0[0] : l0[h][0]; l0[h][1] = lo1 ? s0[1] : l0[h][1];
        }
        softmax(l0, rs.x, P0);
        uint4* ob = G->obox + t;
        uint32_t car0 = 0, car1 = 0;
#pragma unroll
        for (int h = 0; h < 4; h++) {
          float o[3][4];
#pragma unroll
          for (int i = 0; i < 3; i++) {
            mma16816z(o[i], P0[h] & ~M, P1[h] & M, 0u, P1[h] & ~M, kv[1][9 + 2 * h + i], kv[2][9 + 2 * h + i]);
            mma1688(o[i], P0[h] & M, 0u, kv[0][9 + 2 * h + i]);
          }
          const uint32_t o0 = q < h ? car0 : pack_bf16(o[0][0], o[0][1]), o1 = q < h ? car1 : pack_bf16(o[0][2], o[0][3]);
          own[h] = make_uint4(o0 | 1, o1, pack_bf16(o[1][0], o[1][1]), pack_bf16(o[1][2], o[1][3]));
          if (h < OFIRST) st_relaxed4(ob + (8 * h + j) * 128, own[h].x, own[h].y, own[h].z, own[h].w);
          car0 = pack_bf16(o[2][0], o[2][1]); car1 = pack_bf16(o[2][2], o[2][3]);
        }
        car0 = tagged(car0, tag);
        own[4] = make_uint4(car0, car1, 0, 0);
        PROF(pb + 6);
      }
      {
        THREAD_IDS();
        uint4* src = G->obox + t;
        asm volatile("" : "+l"(src));
        uint2 sa, sc;
        uint4 x[32];
        const uint4* from[7];
#pragma unroll
        for (int r = 0; r < 7; r++) { from[r] = src + (r >= j ? 128 : 0); asm volatile("" : "+l"(from[r])); }
        auto load = [&](int i) { x[i] = ld_relaxed4(i < 28 ? from[i % 7] + (8 * (i / 7) + i % 7) * 128 : src + (i + 4) * 128); };
        const uint32_t* probe = &(G->obox + (8 * WPROBE + (lane & 7)) * 128 + (t | 31))->x;
        uint32_t pv = ld_relaxed(probe);
#pragma unroll
        for (int i = 3; i < 8; i++) mbar_wait_c(sb + BAR_FULLX + 8 * i, (c.mX >> i) & 1);
        c.mX ^= 0xf8;
        if (EARLY) mbar_wait_c(sb + BAR_WSUM, 0);
        while (__any_sync(0xffffffffu, ~pv & 1)) pv = ld_relaxed(probe);
        if (layer) PROF(24); else PROF(25);
        if (WOBAR && w == 1) asm volatile("bar.sync 7, 256;" ::: "memory");
#pragma unroll
        for (int i = 0; i < WB1; i++) load(i);
        if (WOBAR && w == 0) asm volatile("bar.arrive 7, 256;" ::: "memory");
#pragma unroll
        for (int h = OFIRST; h < 4; h++) st_relaxed4(src + (8 * h + j) * 128, own[h].x, own[h].y, own[h].z, own[h].w);
        st_relaxed2((uint2*)(src + (32 + (j >> 1)) * 128) + (j & 1), own[4].x, own[4].y);
        if (layer) PROF(26); else PROF(27);
        float a[32], a8[4];
        auto step = [&](const uint4& f, uint32_t r0, int rs, bool acc) {
          wgmma_ra<64>(a, f, desc_hi(0, rs * 128, 1) + (dsb + ((SM_X + 4 * XSLOT) >> 4) + r0 * 8), acc);
          wgmma_ra<8>(a8, f, desc_hi(rs * 16, 0, 0) + (dsb + (SM_WOC >> 4) + r0), acc);
        };
        if (OWNBAR) asm volatile("bar.sync 4, 256;" ::: "memory");
        float e[4];
        wg_fence();
        if (EARLY) {
#pragma unroll
          for (int i = 0; i < 5; i++) wgmma_ra<8>(e, own[i], desc_hi(128, 0, 0) + (dsb + (SM_WSUM >> 4) + 16 * i), i > 0);
          wg_commit();
        }
#pragma unroll
        for (int i = 0; i < 4; i++) step(own[i], 72 * j + 16 * i, 8, i > 0);
        wg_commit();
        if (EARLY) {
          wg_wait<1>();
          if (q == 0) st_relaxed2(G->sum + st0 + 8 * j, (__float_as_uint(e[0] + e[1]) & ~3u) | ((2 * layer + 2) & 3), __float_as_uint(e[2] + e[3]));
        }
        if (layer) PROF(28); else PROF(29);
        auto batch = [&](auto e0, auto e1, auto e2, int b) {
          constexpr int E0 = decltype(e0)::v, E1 = decltype(e1)::v, E2 = decltype(e2)::v;
          const uint32_t one = (LATE0 || E0 > 0) && E1 > E0 ? late(sb + BAR_FULLX + 64, 1) : 1;
          while (E1 > E0) {
            uint32_t bad = 0;
#pragma unroll
            for (int i = E0; i < E1; i++) bad = i < 28 ? chk(bad, x[i].x, one) : chk(chk(bad, x[i].x, tag), x[i].z, tag);
            if (!__any_sync(0xffffffffu, bad & 1)) break;
#pragma unroll
            for (int i = E0; i < E1; i++) load(i);
          }
          if (b == 0) PROF(pb + 7);
          if (b == FG) c.progress(32 * layer + 20);
          if (b > 0 && E2 > E1) wg_wait<WOW>();
#pragma unroll
          for (int i = E1; i < E2; i++) load(i);
          if (EARLY && b == 1) { sa = ld_relaxed2(G->sum + st0 + 16 * q); sc = ld_relaxed2(G->sum + st0 + 16 * q + 8); }
          if (E1 > E0) {
            wg_fence();
#pragma unroll
            for (int i = E0; i < E1; i++) {
              if (i < 28) step(x[i], 72 * (i % 7) + (i % 7 >= j ? 72 : 0) + 16 * (i / 7), 8, true);
              else step(x[i], 144 * (i - 28) + 64, 72, true);
            }
            wg_commit();
          }
        };
        batch(IC<0>(), IC<WB1>(), IC<WB2>(), 0);
        batch(IC<WB1>(), IC<WB2>(), IC<WB3>(), 1);
        batch(IC<WB2>(), IC<WB3>(), IC<32>(), 2);
        batch(IC<WB3>(), IC<32>(), IC<32>(), 3);
        if (EARLY) {
          float2 e = make_float2(quad_sum(__uint_as_float(sa.x) + __uint_as_float(sc.x)), quad_sum(__uint_as_float(sa.y) + __uint_as_float(sc.y)));
          if (__any_sync(0xffffffffu, chk2(sa.x, sc.x, (2 * layer + 2) & 3) & 3)) e = gather_sums(G->sum + st0 + 16 * q, (2 * layer + 2) & 3);
          sum.x += e.x; sum.y += e.y;
        }
        wg_wait<0>();
        if (w == 0) asm volatile("bar.arrive 3, 256;" ::: "memory");
        PROF(pb + 8);
#pragma unroll
        for (int i = 0; i < 18; i++) {
          v[2 * i] = bf_lo(res[i]) + (i < 16 ? a[2 * i] : a8[2 * i - 32]);
          v[2 * i + 1] = bf_hi(res[i]) + (i < 16 ? a[2 * i + 1] : a8[2 * i - 31]);
        }
      }
      uint32_t lsb;
      uint32_t h[144];
      {
        THREAD_IDS();
        float a[128];
        const uint32_t xd = sb + SM_X + w * 4 * XSLOT + (lane >> 4) * 1024 + (16 * wp + (lane & 15)) * 16;
        const float2 rs = ln_gemm<false>(c, G, v, res, sum, st0, j, t, layer, xtag,
          [&](int i) {
            if (i == 0) {
              lsb = ((res[0] & 1) | (res[4] & 1) << 1 | (res[8] & 1) << 2 | (res[12] & 1) << 3 | (res[16] & 1) << 4) ^ (xtag * 31);
              if (w == 1) asm volatile("bar.sync 3, 256;" ::: "memory");
            }
            PROF(pb + 9 + i);
          },
          [&](int gi, uint32_t bb, const uint4& f0, const uint4& f1) {
            if (gi == 0) PROF(pb + 11);
            if (TLEAD0 && gi == 18 - TLEAD0 && w == 1) asm volatile("bar.sync 5, 256;" ::: "memory");
            wg_fence();
            wgmma_ra<256>(a, f0, desc_hi(4096, 1024, 1) + bb, gi > 0);
            wgmma_ra<256>(a, f1, desc_hi(4096, 1024, 1) + (bb + 128), true);
            wg_commit();
            if (TLEAD0 && gi == 17 && w == 0) asm volatile("bar.arrive 5, 256;" ::: "memory");
            stsm4(xd + gi * 4096, f0.x, f0.y, f0.z, f0.w);
            stsm4(xd + gi * 4096 + 2048, f1.x, f1.y, f1.z, f1.w);
            if (gi == 17) { fence_async_smem(); wg_bar(w); }
          });
        sts64f(sb + SM_KEEP + (tid_ >> 2) * 8, rs.x * rs.x, rs.y * rs.y);
        c.progress(32 * layer + 22);
        PROF2(pb + 12);
        glu<16, 0>(a, h);
        const Desc da0 = desc_hi(1024, 128, 0) + (dsb + ((SM_X + w * 4 * XSLOT) >> 4));
        auto tile = [&](auto wide, auto last) {
          const uint32_t xe = BAR_EMPTYX + 32 * (t & 1) + 4 * (t & 6);
          auto group = [&](int gi) {
            uint32_t prev;
            const uint32_t bb = c.nextB(prev);
            const Desc da = da0 + gi * 256;
            wg_fence();
            if (wide()) {
              wgmma_ss<256>(a, da, desc_hi(4096, 1024, 1) + bb, gi);
              wgmma_ss<256>(a, da + 128, desc_hi(4096, 1024, 1) + (bb + 128), 1);
            } else {
              wgmma_ss<192>(*(float(*)[96])a, da, desc_hi(2048, 512, 2) + bb, gi);
              wgmma_ss<192>(*(float(*)[96])a, da + 128, desc_hi(2048, 512, 2) + (bb + 64), 1);
            }
            wg_commit();
            if (gi == 17 && w == 0) asm volatile("bar.arrive 5, 256;" ::: "memory");
            wg_wait<1>();
            if (gi > 0 && !(last() && gi > 13)) c.release2(BAR_EMPTYB + prev);
            if (last() && gi >= XREL && !((gi ^ XREL) & 1)) c.release2(BAR_EMPTYX + 16 * ((gi - XREL) & 2) + 2 * ((gi - XREL) & 12));
          };
          int gi = 0, end = w ? 18 - (wide() ? TLEAD2 : TLEAD) : 18;
#pragma unroll 1
          while (true) {
#pragma unroll 1
            for (; gi < end; gi++) group(gi);
            if (end == 18) break;
            asm volatile("bar.sync 5, 256;" ::: "memory");
            end = 18;
          }
          wg_wait<0>();
          if (!last()) c.releaseLastB();
          if (last() && t >= (19 - XREL) / 2 && t < 8) { mbar_arrive(sb + xe); mbar_arrive_remote(c.rem + xe); }
        };
        auto yes = [] { return true; };
        auto no = [] { return false; };
        tile(yes, no); PROF2(pb + 13); glu<16, 32>(a, h);
        tile(yes, no); PROF2(pb + 14); glu<16, 64>(a, h);
        tile(no, no); PROF2(pb + 15); glu<12, 96>(a, h);
        const uint32_t hole = sb + SM_B + 12288 + tid_ * 16;
#pragma unroll
        for (int i = 0; i < NSPILL; i++) sts128(hole + i * BSLOT, h[96 + 4 * i], h[97 + 4 * i], h[98 + 4 * i], h[99 + 4 * i]);
        if (w == 1) asm volatile("bar.arrive 8, 256;" ::: "memory");
        tile(no, yes); PROF2(pb + 16); glu<12, 120>(a, h);
#pragma unroll
        for (int i = 0; i < NSPILL; i++) { const uint4 u = lds128(hole + i * BSLOT); h[96 + 4 * i] = u.x; h[97 + 4 * i] = u.y; h[98 + 4 * i] = u.z; h[99 + 4 * i] = u.w; }
      }
      {
        THREAD_IDS();
        float d[32];
        uint4* gt = G->obox + t;
        asm volatile("" : "+l"(gt));
        uint4* const ib = gt + 2 * 4608 + layer * 8 * INBOX;
        auto pass = [&](uint32_t s0, bool last, auto&& hook) {
          const Desc db = desc_hi(0, 1024, 1) + (dsb + (SM_X >> 4) + s0 * (XSLOT >> 4));
          mbar_wait_c(sb + BAR_FULLX + 8 * s0, (c.mX >> s0) & 1);
          if (RHOOK < 0) hook();
          asm volatile("bar.sync %0, 256;" ::"r"(8 + w) : "memory");
#pragma unroll
          for (int i = 0; i < 4; i++) {
            const int si = 4 * (i & 1) + (i >> 1);
            if (i > 0) mbar_wait_c(sb + BAR_FULLX + 8 * (s0 + si), (c.mX >> (s0 + si)) & 1);
            wg_fence();
#pragma unroll
            for (int k = 0; k < 9; k++) {
              const uint32_t* hk = h + 36 * i + 4 * k;
              wgmma_ra<64>(d, make_uint4(hk[0], hk[1], hk[2], hk[3]), db + (si * (XSLOT >> 4) + k * 128), last || i + k > 0);
              if (9 * i + k == PPK && !(last && w == 1)) asm volatile("bar.arrive %0, 256;" ::"r"(9 - w) : "memory");
            }
            wg_commit();
            if (i > 0) { wg_wait<1>(); c.release2(BAR_EMPTYX + 8 * (s0 + 4 * ((i - 1) & 1) + ((i - 1) >> 1))); }
            if (i == RHOOK) hook();
          }
          c.mX ^= 0x33u << s0;
        };
        PROF2(pb + 17);
#pragma unroll 1
        for (int p = 0; p < 8; p++) {
          const uint32_t s0 = 2 * (p & 1);
          pass(s0, false, [] {});
          wg_wait<0>();
          c.release2(BAR_EMPTYX + 8 * (s0 + 5));
          uint32_t pk[16];
#pragma unroll
          for (int i = 0; i < 16; i++) pk[i] = pack_bf16(d[2 * i], d[2 * i + 1]);
          if (p >= BREL && p < BREL + 5) {
            const uint32_t o = c.sB + 8 * (p - BREL);
            c.release2(BAR_EMPTYB + (o < 40 ? o : o - 40));
          }
          uint4* const dst = ib + ((j + p) & 7) * INBOX;
          if (p == 0) {
            mbar_wait_c(sb + BAR_CLR + 8 * w, 0);
#pragma unroll
            for (int k = 0; k < 8; k++) red2((uint2*)(ib + k * INBOX + 512) - t, pk[2 * k], pk[2 * k + 1]);
          } else if (p < 7) {
#pragma unroll
            for (int k = 0; k < 4; k++) red4(dst + k * 128, pk[4 * k], pk[4 * k + 1], pk[4 * k + 2], pk[4 * k + 3]);
            if (p == 6) { __syncwarp(); if (lane == 0) mbar_arrive(sb + BAR_REDDONE + 8 * w); }
          } else {
#pragma unroll
            for (int k = 0; k < 4; k++) st_relaxed4(gt + ((j + 7) & 7) * 128 + k * 1024, pk[4 * k] & ~1u, pk[4 * k + 1], pk[4 * k + 2], pk[4 * k + 3]);
          }
        }
        PROF2(pb + 18);
        const uint4 *in = ib + j * INBOX, *pin = gt + j * 128;
        const uint2* in9 = (const uint2*)(in + 512) - t;
        asm volatile("" : "+l"(in), "+l"(pin), "+l"(in9));
        const float2 r2 = lds64(sb + SM_KEEP + (tid_ >> 2) * 8);
        uint2 X9;
        {
          uint4 X[4];
          const uint4* box = gt + 4608;
#pragma unroll
          for (int k = 0; k < 4; k++) X[k] = ld_relaxed4(box + 256 * j + ((k & 1) + 8 * (k & 2)) * 128);
          X9 = ld_relaxed2((const uint2*)(box + (32 + (j >> 1)) * 128) + (j & 1));
          const float i0 = rcp(r2.x), i1 = rcp(r2.y);
#pragma unroll
          for (int k = 0; k < 4; k++) {
            float* e = d + 8 * k;
            X[k].x ^= (lsb >> k) & 1;
            e[0] = bf_lo(X[k].x) * i0; e[1] = bf_hi(X[k].x) * i0; e[2] = bf_lo(X[k].y) * i1; e[3] = bf_hi(X[k].y) * i1;
            e[4] = bf_lo(X[k].z) * i0; e[5] = bf_hi(X[k].z) * i0; e[6] = bf_lo(X[k].w) * i1; e[7] = bf_hi(X[k].w) * i1;
          }
        }
        uint4 R[4], P[4];
        uint2 R9;
        PROF2(pb + 19);
        pass(0, true, [&] {
          mbar_wait_c(sb + BAR_RREADY + 8 * w, layer);
#pragma unroll
          for (int k = 0; k < 4; k++) R[k] = ld_relaxed4(in + k * 128);
          R9 = ld_relaxed2(in9);
#pragma unroll
          for (int k = 0; k < 4; k++) P[k] = ld_relaxed4(pin + k * 1024);
        });
        const uint32_t zero = late(sb + BAR_FULLX + 64, 0);
        while (__any_sync(0xffffffffu, (chk2(P[0].x, P[1].x, zero) | chk2(P[2].x, P[3].x, zero)) & 1)) {
#pragma unroll
          for (int k = 0; k < 4; k++) P[k] = ld_relaxed4(pin + k * 1024);
        }
#pragma unroll
        for (int k = 0; k < 4; k++) {
          const uint32_t u[4] = {hadd2(R[k].x, P[k].x), hadd2(R[k].y, P[k].y), hadd2(R[k].z, P[k].z), hadd2(R[k].w, P[k].w)};
#pragma unroll
          for (int i = 0; i < 4; i++) { v[8 * k + 2 * i] = bf_lo(u[i]); v[8 * k + 2 * i + 1] = bf_hi(u[i]); }
        }
        X9.x = chk(zero, X9.x, lsb >> 4);
        v[32] = fmaf(bf_lo(R9.x), r2.x, bf_lo(X9.x)); v[33] = fmaf(bf_hi(R9.x), r2.x, bf_hi(X9.x));
        v[34] = fmaf(bf_lo(R9.y), r2.y, bf_lo(X9.y)); v[35] = fmaf(bf_hi(R9.y), r2.y, bf_hi(X9.y));
        PROF2(pb + 20);
        wg_wait<0>();
        c.release2(BAR_EMPTYX + 40);
        PROF2(pb + 21);
#pragma unroll
        for (int i = 0; i < 32; i++) v[i] = (v[i] + d[i]) * (i & 2 ? r2.y : r2.x);
      }
      if (layer == NLAYERS - 1) break;
      {
        THREAD_IDS();
        PROF(31);
        rs = ln_gemm<true>(c, G, v, res, sum, st0, j, t, 1, xtag ^ 1, [&](int i) { PROF(32 + i); if (i) PROF(34); }, qkv_mma);
      }
    }
    {
      THREAD_IDS();
      const uint32_t stg = sb + SM_B + warp * 4096;
      const uint32_t sd = stg + (lane & 15) * 128;
#pragma unroll
      for (int i = 0; i < 4; i++)
        stsm4(sd + (((2 * i + (lane >> 4)) ^ (lane & 7)) << 4), pack_bf16(v[8 * i], v[8 * i + 1]), pack_bf16(v[8 * i + 2], v[8 * i + 3]),
              pack_bf16(v[8 * i + 4], v[8 * i + 5]), pack_bf16(v[8 * i + 6], v[8 * i + 7]));
      stsm2(stg + 2048 + (lane & 15) * 16, pack_bf16(v[32], v[33]), pack_bf16(v[34], v[35]));
      fence_async_smem();
      __syncwarp();
      if (lane == 0) {
        tma_store3d(&maps.out, stg, 64 * j, w, 64 * rb + 16 * wp);
        tma_store3d(&maps.outc, stg + 2048, 512 + 8 * j, w, 64 * rb + 16 * wp);
        bulk_commit();
        if (wp == 0) st_relaxed(G->flag + 32 + 32 * j, xtag);
        bulk_wait_all();
        mbar_arrive(sb + BAR_DONE + 8 * w);
      }
      PROF(61);
    }
    __syncwarp();
    cluster_sync();
  }
}

typedef CUresult (*EncFn)(CUtensorMap*, CUtensorMapDataType, cuuint32_t, void*, const cuuint64_t*, const cuuint64_t*, const cuuint32_t*,
                          const cuuint32_t*, CUtensorMapInterleave, CUtensorMapSwizzle, CUtensorMapL2promotion, CUtensorMapFloatOOBfill);

void make_map(EncFn enc, CUtensorMap* m, const void* p, int rank, uint64_t d0, uint64_t d1, uint64_t d2, uint64_t s1, uint64_t s2, uint32_t b0,
              uint32_t b1, uint32_t b2, CUtensorMapSwizzle sw) {
  cuuint64_t gd[3] = {d0, d1, d2};
  cuuint64_t gs[2] = {s1, s2};
  cuuint32_t bd[3] = {b0, b1, b2};
  cuuint32_t es[3] = {1, 1, 1};
  enc(m, CU_TENSOR_MAP_DATA_TYPE_BFLOAT16, rank, const_cast<void*>(p), gd, gs, bd, es, CU_TENSOR_MAP_INTERLEAVE_NONE, sw,
      CU_TENSOR_MAP_L2_PROMOTION_L2_128B, CU_TENSOR_MAP_FLOAT_OOB_FILL_NONE);
}

}

extern "C" void kernel_launch(void* const* d_in, const int* in_sizes, int n_in, void* d_out, int out_size) {
  const __nv_bfloat16* x = (const __nv_bfloat16*)d_in[0];
  const char *wqkv = (const char*)d_in[1], *wo = (const char*)d_in[2], *wg = (const char*)d_in[4], *wu = (const char*)d_in[5], *wd = (const char*)d_in[6];
  static EncFn enc = nullptr;
  static uint32_t first = 0;
  static Group* ws = nullptr;
  if (!enc) {
    cudaDriverEntryPointQueryResult qr;
    cudaGetDriverEntryPoint("cuTensorMapEncodeTiled", (void**)&enc, cudaEnableDefault, &qr);
    cudaGetSymbolAddress((void**)&ws, g_ws);
    cudaFuncSetAttribute(fused_kernel, cudaFuncAttributeMaxDynamicSharedMemorySize, SMEM_BYTES);
    cudaLaunchConfig_t cfg = {};
    cfg.gridDim = NCTA + 4; cfg.blockDim = 384; cfg.dynamicSmemBytes = SMEM_BYTES;
    int clusters = 0;
    if (XFIRST || cudaOccupancyMaxActiveClusters(&clusters, fused_kernel, &cfg) != cudaSuccess || 2 * clusters < NCTA + 4) first = 4;
    cudaGetLastError();
  }
  const CUtensorMapSwizzle S0 = CU_TENSOR_MAP_SWIZZLE_NONE, S64 = CU_TENSOR_MAP_SWIZZLE_64B, S128 = CU_TENSOR_MAP_SWIZZLE_128B;
  Maps m;
  make_map(enc, &m.x, x, 3, 576, 2, 1024, 1152, 2304, 64, 1, 64, S128);
  make_map(enc, &m.qm, wqkv, 3, 576, 576, 3, 3456, 1152, 64, 16, 3, S128);
  make_map(enc, &m.qc, wqkv, 3, 576, 576, 3, 3456, 1152, 8, 16, 3, S0);
  make_map(enc, &m.o, wo, 2, 576, 576, 1, 1152, 0, 64, 72, 1, S128);
  make_map(enc, &m.oc, wo, 2, 576, 576, 1, 1152, 0, 8, 144, 1, S0);
  make_map(enc, &m.g, wg, 3, 64, 576, 72, 9216, 128, 64, 32, 2, S128);
  make_map(enc, &m.u, wu, 3, 64, 576, 72, 9216, 128, 64, 32, 2, S128);
  make_map(enc, &m.g3, wg, 3, 32, 576, 144, 9216, 64, 32, 32, 3, S64);
  make_map(enc, &m.u3, wu, 3, 32, 576, 144, 9216, 64, 32, 32, 3, S64);
  make_map(enc, &m.d, wd, 2, 576, 4608, 1, 1152, 0, 64, 72, 1, S128);
  make_map(enc, &m.out, d_out, 3, 576, 2, 1024, 1152, 2304, 64, 1, 16, S128);
  make_map(enc, &m.outc, d_out, 3, 576, 2, 1024, 1152, 2304, 8, 1, 16, S0);
  fused_kernel<<<NCTA + 4, 384, SMEM_BYTES>>>(x, ws, wqkv, wg, wu, first, m, wo, wd);
}
```

```cpp
#include <cuda_runtime.h>
#include <cuda_bf16.h>
#include <cuda.h>
#include <stdint.h>
#include <stddef.h>

namespace {

constexpr int D_ = 576;
constexpr int NCTA = 128;
#define NLAYERS 2
#define W_POLICY policy_evict_first
#define A_POLICY policy_evict_normal
#define OPEN 1
#define PFMODE 5
#define WWIN 4
#define WOREL -1
#define WB1 11
#define WB2 21
#define WB3 32
#define WPROBE 1
#define WPROBE2 0
#define SPEC 2
#define POLLFIRST 0
#define SUMFIRST 1
#define EARLYPOLL 1
#define LEAD 0
#define ATTBAR 0
#define GL 18
#define WOBAR 1
#define QD 0
#define QG 4
#define PFQ 1
#define XDELAY 0
#define WOH 1
#define PFSLEEP 700
#define GPCMAP 1
#define PFF 1
#define REDN 1
#define CLRSLEEP 300
#define OPENL 24
#define FG 2
#define NON8 0
#define HMUL 1
#define FCH 1
#define PPK 34
#define RHOOK -1
#define SCHEDBAR 1
#define QH 5
#define XH 3
#define XP 0
#define GSLEEP 32
#define XCH 1
#define MAPPF 1
#define XREL 8
#define WOG 13
#define BREL 1
#define FENCE1 0
#define OWNX 0
#define OWNBAR 0
#define EARLY 1
#define ESPEC 0
#define TESTP 0
#define WOW 1
#define STATP -1
#define WSG 0
#define REPACK 1
#define QPACE 23
#define RDELAY 1000
#define XFIRST 0
#define TLEAD 2
#define TLEAD2 2
#define TLEAD0 2
#define OFIRST 3
#define OSPEC 0
#define FN 3
#define LATE0 0
#define SUMB 1
#define NSPILL 4
#define REGS_C 232
#define REGS_P 40
#define STR2(x) #x
#define STR(x) STR2(x)
constexpr uint32_t SM_X = 0;
constexpr uint32_t XSLOT = 18432;
__host__ __device__ constexpr uint32_t xslot(uint32_t s) { return SM_X + (s ^ 4) * XSLOT; }
constexpr uint32_t SM_WOC = xslot(3) + 8192;
constexpr uint32_t SM_B = 147456;
constexpr uint32_t BSLOT = 16384;
constexpr uint32_t SM_KEEP = 229376;
constexpr uint32_t SM_WSUM = SM_KEEP + 512;
constexpr uint32_t SM_BAR = SM_KEEP + 2048;
constexpr uint32_t BAR_FULLB = SM_BAR;
constexpr uint32_t BAR_RREADY = SM_BAR + 40;
constexpr uint32_t BAR_CLR = SM_BAR + 56;
constexpr uint32_t BAR_FULLX = SM_BAR + 72;
constexpr uint32_t BAR_EMPTYB = SM_BAR + 144;
constexpr uint32_t BAR_EMPTYX = SM_BAR + 184;
constexpr uint32_t BAR_REDDONE = SM_BAR + 248;
constexpr uint32_t BAR_DONE = SM_BAR + 264;
constexpr uint32_t SM_PROG = SM_BAR + 288;
constexpr uint32_t SMEM_BYTES = SM_BAR + 1024;

struct Maps { CUtensorMap x, qm, qc, o, g, u, g3, u3, d, out, outc; };

constexpr int INBOX = 576;
struct Group {
  uint2 sum[4 * 8 * 8];
  uint2 sq[4 * 8 * 8];
  uint32_t pad[512];
  uint32_t flag[512];
  uint4 halo[8 * 160];
  uint4 obox[36 * 128];
  uint4 xbox[36 * 128];
  uint4 inbox[2][8 * INBOX];
};
struct Scratch { Group g[32]; uint4 wq[8][36][432]; uint4 woc[8][720]; uint32_t done[64]; };
__device__ __align__(1024) Scratch g_ws;
#define PROF(i)
#define PROFX(i)

#define PROF2(i) PROF(i)

struct Desc { uint32_t lo, hi; };
__device__ __forceinline__ constexpr Desc desc_hi(uint32_t lbo, uint32_t sbo, uint32_t sw) { return Desc{(lbo >> 4) << 16, (sbo >> 4) | sw << 30}; }
__device__ __forceinline__ constexpr Desc operator+(Desc d, uint32_t a) { return Desc{d.lo + a, d.hi}; }

template<int N> __device__ __forceinline__ void wgmma_ss(float (&d)[N / 2], Desc da, Desc db, int sc);
template<> __device__ __forceinline__ void wgmma_ss<192>(float (&d)[96], Desc da, Desc db, int sc) {
  asm volatile("{\n.reg .pred p;\n.reg .b64 a, b;\nsetp.ne.b32 p, %100, 0;\nmov.b64 a, {%96, %97};\nmov.b64 b, {%98, %99};\n"
    "wgmma.mma_async.sync.aligned.m64n192k16.f32.bf16.bf16 {%0,%1,%2,%3,%4,%5,%6,%7,%8,%9,%10,%11,%12,%13,%14,%15,%16,%17,%18,%19,%20,%21,%22,%23,%24,%25,%26,%27,%28,%29,%30,%31,%32,%33,%34,%35,%36,%37,%38,%39,%40,%41,%42,%43,%44,%45,%46,%47,%48,%49,%50,%51,%52,%53,%54,%55,%56,%57,%58,%59,%60,%61,%62,%63,%64,%65,%66,%67,%68,%69,%70,%71,%72,%73,%74,%75,%76,%77,%78,%79,%80,%81,%82,%83,%84,%85,%86,%87,%88,%89,%90,%91,%92,%93,%94,%95}, a, b, p, 1, 1, 0, 1;\n}\n"
    : "+f"(d[0]),"+f"(d[1]),"+f"(d[2]),"+f"(d[3]),"+f"(d[4]),"+f"(d[5]),"+f"(d[6]),"+f"(d[7]),"+f"(d[8]),"+f"(d[9]),"+f"(d[10]),"+f"(d[11]),"+f"(d[12]),"+f"(d[13]),"+f"(d[14]),"+f"(d[15]),"+f"(d[16]),"+f"(d[17]),"+f"(d[18]),"+f"(d[19]),"+f"(d[20]),"+f"(d[21]),"+f"(d[22]),"+f"(d[23]),"+f"(d[24]),"+f"(d[25]),"+f"(d[26]),"+f"(d[27]),"+f"(d[28]),"+f"(d[29]),"+f"(d[30]),"+f"(d[31]),"+f"(d[32]),"+f"(d[33]),"+f"(d[34]),"+f"(d[35]),"+f"(d[36]),"+f"(d[37]),"+f"(d[38]),"+f"(d[39]),"+f"(d[40]),"+f"(d[41]),"+f"(d[42]),"+f"(d[43]),"+f"(d[44]),"+f"(d[45]),"+f"(d[46]),"+f"(d[47]),"+f"(d[48]),"+f"(d[49]),"+f"(d[50]),"+f"(d[51]),"+f"(d[52]),"+f"(d[53]),"+f"(d[54]),"+f"(d[55]),"+f"(d[56]),"+f"(d[57]),"+f"(d[58]),"+f"(d[59]),"+f"(d[60]),"+f"(d[61]),"+f"(d[62]),"+f"(d[63]),"+f"(d[64]),"+f"(d[65]),"+f"(d[66]),"+f"(d[67]),"+f"(d[68]),"+f"(d[69]),"+f"(d[70]),"+f"(d[71]),"+f"(d[72]),"+f"(d[73]),"+f"(d[74]),"+f"(d[75]),"+f"(d[76]),"+f"(d[77]),"+f"(d[78]),"+f"(d[79]),"+f"(d[80]),"+f"(d[81]),"+f"(d[82]),"+f"(d[83]),"+f"(d[84]),"+f"(d[85]),"+f"(d[86]),"+f"(d[87]),"+f"(d[88]),"+f"(d[89]),"+f"(d[90]),"+f"(d[91]),"+f"(d[92]),"+f"(d[93]),"+f"(d[94]),"+f"(d[95]) : "r"(da.lo), "r"(da.hi), "r"(db.lo), "r"(db.hi), "r"(sc));
}
template<> __device__ __forceinline__ void wgmma_ss<256>(float (&d)[128], Desc da, Desc db, int sc) {
  asm volatile("{\n.reg .pred p;\n.reg .b64 a, b;\nsetp.ne.b32 p, %132, 0;\nmov.b64 a, {%128, %129};\nmov.b64 b, {%130, %131};\n"
    "wgmma.mma_async.sync.aligned.m64n256k16.f32.bf16.bf16 {%0,%1,%2,%3,%4,%5,%6,%7,%8,%9,%10,%11,%12,%13,%14,%15,%16,%17,%18,%19,%20,%21,%22,%23,%24,%25,%26,%27,%28,%29,%30,%31,%32,%33,%34,%35,%36,%37,%38,%39,%40,%41,%42,%43,%44,%45,%46,%47,%48,%49,%50,%51,%52,%53,%54,%55,%56,%57,%58,%59,%60,%61,%62,%63,%64,%65,%66,%67,%68,%69,%70,%71,%72,%73,%74,%75,%76,%77,%78,%79,%80,%81,%82,%83,%84,%85,%86,%87,%88,%89,%90,%91,%92,%93,%94,%95,%96,%97,%98,%99,%100,%101,%102,%103,%104,%105,%106,%107,%108,%109,%110,%111,%112,%113,%114,%115,%116,%117,%118,%119,%120,%121,%122,%123,%124,%125,%126,%127}, a, b, p, 1, 1, 0, 1;\n}\n"
    : "+f"(d[0]),"+f"(d[1]),"+f"(d[2]),"+f"(d[3]),"+f"(d[4]),"+f"(d[5]),"+f"(d[6]),"+f"(d[7]),"+f"(d[8]),"+f"(d[9]),"+f"(d[10]),"+f"(d[11]),"+f"(d[12]),"+f"(d[13]),"+f"(d[14]),"+f"(d[15]),"+f"(d[16]),"+f"(d[17]),"+f"(d[18]),"+f"(d[19]),"+f"(d[20]),"+f"(d[21]),"+f"(d[22]),"+f"(d[23]),"+f"(d[24]),"+f"(d[25]),"+f"(d[26]),"+f"(d[27]),"+f"(d[28]),"+f"(d[29]),"+f"(d[30]),"+f"(d[31]),"+f"(d[32]),"+f"(d[33]),"+f"(d[34]),"+f"(d[35]),"+f"(d[36]),"+f"(d[37]),"+f"(d[38]),"+f"(d[39]),"+f"(d[40]),"+f"(d[41]),"+f"(d[42]),"+f"(d[43]),"+f"(d[44]),"+f"(d[45]),"+f"(d[46]),"+f"(d[47]),"+f"(d[48]),"+f"(d[49]),"+f"(d[50]),"+f"(d[51]),"+f"(d[52]),"+f"(d[53]),"+f"(d[54]),"+f"(d[55]),"+f"(d[56]),"+f"(d[57]),"+f"(d[58]),"+f"(d[59]),"+f"(d[60]),"+f"(d[61]),"+f"(d[62]),"+f"(d[63]),"+f"(d[64]),"+f"(d[65]),"+f"(d[66]),"+f"(d[67]),"+f"(d[68]),"+f"(d[69]),"+f"(d[70]),"+f"(d[71]),"+f"(d[72]),"+f"(d[73]),"+f"(d[74]),"+f"(d[75]),"+f"(d[76]),"+f"(d[77]),"+f"(d[78]),"+f"(d[79]),"+f"(d[80]),"+f"(d[81]),"+f"(d[82]),"+f"(d[83]),"+f"(d[84]),"+f"(d[85]),"+f"(d[86]),"+f"(d[87]),"+f"(d[88]),"+f"(d[89]),"+f"(d[90]),"+f"(d[91]),"+f"(d[92]),"+f"(d[93]),"+f"(d[94]),"+f"(d[95]),"+f"(d[96]),"+f"(d[97]),"+f"(d[98]),"+f"(d[99]),"+f"(d[100]),"+f"(d[101]),"+f"(d[102]),"+f"(d[103]),"+f"(d[104]),"+f"(d[105]),"+f"(d[106]),"+f"(d[107]),"+f"(d[108]),"+f"(d[109]),"+f"(d[110]),"+f"(d[111]),"+f"(d[112]),"+f"(d[113]),"+f"(d[114]),"+f"(d[115]),"+f"(d[116]),"+f"(d[117]),"+f"(d[118]),"+f"(d[119]),"+f"(d[120]),"+f"(d[121]),"+f"(d[122]),"+f"(d[123]),"+f"(d[124]),"+f"(d[125]),"+f"(d[126]),"+f"(d[127]) : "r"(da.lo), "r"(da.hi), "r"(db.lo), "r"(db.hi), "r"(sc));
}
template<int N, int ACC> __device__ __forceinline__ void wgmma_rs(float (&d)[N / 2], const uint4& a, Desc db);
template<> __device__ __forceinline__ void wgmma_rs<8, 1>(float (&d)[4], const uint4& a, Desc db) {
  asm volatile("{\n.reg .pred p;\n.reg .b64 b;\nsetp.ne.b32 p, 1, 0;\nmov.b64 b, {%8, %9};\n"
    "wgmma.mma_async.sync.aligned.m64n8k16.f32.bf16.bf16 {%0,%1,%2,%3}, {%4,%5,%6,%7}, b, p, 1, 1, 1;\n}\n"
    : "+f"(d[0]),"+f"(d[1]),"+f"(d[2]),"+f"(d[3]) : "r"(a.x), "r"(a.y), "r"(a.z), "r"(a.w), "r"(db.lo), "r"(db.hi));
}
template<> __device__ __forceinline__ void wgmma_rs<8, 0>(float (&d)[4], const uint4& a, Desc db) {
  asm volatile("{\n.reg .pred p;\n.reg .b64 b;\nsetp.ne.b32 p, 0, 0;\nmov.b64 b, {%8, %9};\n"
    "wgmma.mma_async.sync.aligned.m64n8k16.f32.bf16.bf16 {%0,%1,%2,%3}, {%4,%5,%6,%7}, b, p, 1, 1, 1;\n}\n"
    : "=f"(d[0]),"=f"(d[1]),"=f"(d[2]),"=f"(d[3]) : "r"(a.x), "r"(a.y), "r"(a.z), "r"(a.w), "r"(db.lo), "r"(db.hi));
}
template<> __device__ __forceinline__ void wgmma_rs<24, 1>(float (&d)[12], const uint4& a, Desc db) {
  asm volatile("{\n.reg .pred p;\n.reg .b64 b;\nsetp.ne.b32 p, 1, 0;\nmov.b64 b, {%16, %17};\n"
    "wgmma.mma_async.sync.aligned.m64n24k16.f32.bf16.bf16 {%0,%1,%2,%3,%4,%5,%6,%7,%8,%9,%10,%11}, {%12,%13,%14,%15}, b, p, 1, 1, 1;\n}\n"
    : "+f"(d[0]),"+f"(d[1]),"+f"(d[2]),"+f"(d[3]),"+f"(d[4]),"+f"(d[5]),"+f"(d[6]),"+f"(d[7]),"+f"(d[8]),"+f"(d[9]),"+f"(d[10]),"+f"(d[11]) : "r"(a.x), "r"(a.y), "r"(a.z), "r"(a.w), "r"(db.lo), "r"(db.hi));
}
template<> __device__ __forceinline__ void wgmma_rs<24, 0>(float (&d)[12], const uint4& a, Desc db) {
  asm volatile("{\n.reg .pred p;\n.reg .b64 b;\nsetp.ne.b32 p, 0, 0;\nmov.b64 b, {%16, %17};\n"
    "wgmma.mma_async.sync.aligned.m64n24k16.f32.bf16.bf16 {%0,%1,%2,%3,%4,%5,%6,%7,%8,%9,%10,%11}, {%12,%13,%14,%15}, b, p, 1, 1, 1;\n}\n"
    : "=f"(d[0]),"=f"(d[1]),"=f"(d[2]),"=f"(d[3]),"=f"(d[4]),"=f"(d[5]),"=f"(d[6]),"=f"(d[7]),"=f"(d[8]),"=f"(d[9]),"=f"(d[10]),"=f"(d[11]) : "r"(a.x), "r"(a.y), "r"(a.z), "r"(a.w), "r"(db.lo), "r"(db.hi));
}
template<> __device__ __forceinline__ void wgmma_rs<64, 1>(float (&d)[32], const uint4& a, Desc db) {
  asm volatile("{\n.reg .pred p;\n.reg .b64 b;\nsetp.ne.b32 p, 1, 0;\nmov.b64 b, {%36, %37};\n"
    "wgmma.mma_async.sync.aligned.m64n64k16.f32.bf16.bf16 {%0,%1,%2,%3,%4,%5,%6,%7,%8,%9,%10,%11,%12,%13,%14,%15,%16,%17,%18,%19,%20,%21,%22,%23,%24,%25,%26,%27,%28,%29,%30,%31}, {%32,%33,%34,%35}, b, p, 1, 1, 1;\n}\n"
    : "+f"(d[0]),"+f"(d[1]),"+f"(d[2]),"+f"(d[3]),"+f"(d[4]),"+f"(d[5]),"+f"(d[6]),"+f"(d[7]),"+f"(d[8]),"+f"(d[9]),"+f"(d[10]),"+f"(d[11]),"+f"(d[12]),"+f"(d[13]),"+f"(d[14]),"+f"(d[15]),"+f"(d[16]),"+f"(d[17]),"+f"(d[18]),"+f"(d[19]),"+f"(d[20]),"+f"(d[21]),"+f"(d[22]),"+f"(d[23]),"+f"(d[24]),"+f"(d[25]),"+f"(d[26]),"+f"(d[27]),"+f"(d[28]),"+f"(d[29]),"+f"(d[30]),"+f"(d[31]) : "r"(a.x), "r"(a.y), "r"(a.z), "r"(a.w), "r"(db.lo), "r"(db.hi));
}
template<> __device__ __forceinline__ void wgmma_rs<64, 0>(float (&d)[32], const uint4& a, Desc db) {
  asm volatile("{\n.reg .pred p;\n.reg .b64 b;\nsetp.ne.b32 p, 0, 0;\nmov.b64 b, {%36, %37};\n"
    "wgmma.mma_async.sync.aligned.m64n64k16.f32.bf16.bf16 {%0,%1,%2,%3,%4,%5,%6,%7,%8,%9,%10,%11,%12,%13,%14,%15,%16,%17,%18,%19,%20,%21,%22,%23,%24,%25,%26,%27,%28,%29,%30,%31}, {%32,%33,%34,%35}, b, p, 1, 1, 1;\n}\n"
    : "=f"(d[0]),"=f"(d[1]),"=f"(d[2]),"=f"(d[3]),"=f"(d[4]),"=f"(d[5]),"=f"(d[6]),"=f"(d[7]),"=f"(d[8]),"=f"(d[9]),"=f"(d[10]),"=f"(d[11]),"=f"(d[12]),"=f"(d[13]),"=f"(d[14]),"=f"(d[15]),"=f"(d[16]),"=f"(d[17]),"=f"(d[18]),"=f"(d[19]),"=f"(d[20]),"=f"(d[21]),"=f"(d[22]),"=f"(d[23]),"=f"(d[24]),"=f"(d[25]),"=f"(d[26]),"=f"(d[27]),"=f"(d[28]),"=f"(d[29]),"=f"(d[30]),"=f"(d[31]) : "r"(a.x), "r"(a.y), "r"(a.z), "r"(a.w), "r"(db.lo), "r"(db.hi));
}
template<> __device__ __forceinline__ void wgmma_rs<72, 1>(float (&d)[36], const uint4& a, Desc db) {
  asm volatile("{\n.reg .pred p;\n.reg .b64 b;\nsetp.ne.b32 p, 1, 0;\nmov.b64 b, {%40, %41};\n"
    "wgmma.mma_async.sync.aligned.m64n72k16.f32.bf16.bf16 {%0,%1,%2,%3,%4,%5,%6,%7,%8,%9,%10,%11,%12,%13,%14,%15,%16,%17,%18,%19,%20,%21,%22,%23,%24,%25,%26,%27,%28,%29,%30,%31,%32,%33,%34,%35}, {%36,%37,%38,%39}, b, p, 1, 1, 1;\n}\n"
    : "+f"(d[0]),"+f"(d[1]),"+f"(d[2]),"+f"(d[3]),"+f"(d[4]),"+f"(d[5]),"+f"(d[6]),"+f"(d[7]),"+f"(d[8]),"+f"(d[9]),"+f"(d[10]),"+f"(d[11]),"+f"(d[12]),"+f"(d[13]),"+f"(d[14]),"+f"(d[15]),"+f"(d[16]),"+f"(d[17]),"+f"(d[18]),"+f"(d[19]),"+f"(d[20]),"+f"(d[21]),"+f"(d[22]),"+f"(d[23]),"+f"(d[24]),"+f"(d[25]),"+f"(d[26]),"+f"(d[27]),"+f"(d[28]),"+f"(d[29]),"+f"(d[30]),"+f"(d[31]),"+f"(d[32]),"+f"(d[33]),"+f"(d[34]),"+f"(d[35]) : "r"(a.x), "r"(a.y), "r"(a.z), "r"(a.w), "r"(db.lo), "r"(db.hi));
}
template<> __device__ __forceinline__ void wgmma_rs<72, 0>(float (&d)[36], const uint4& a, Desc db) {
  asm volatile("{\n.reg .pred p;\n.reg .b64 b;\nsetp.ne.b32 p, 0, 0;\nmov.b64 b, {%40, %41};\n"
    "wgmma.mma_async.sync.aligned.m64n72k16.f32.bf16.bf16 {%0,%1,%2,%3,%4,%5,%6,%7,%8,%9,%10,%11,%12,%13,%14,%15,%16,%17,%18,%19,%20,%21,%22,%23,%24,%25,%26,%27,%28,%29,%30,%31,%32,%33,%34,%35}, {%36,%37,%38,%39}, b, p, 1, 1, 1;\n}\n"
    : "=f"(d[0]),"=f"(d[1]),"=f"(d[2]),"=f"(d[3]),"=f"(d[4]),"=f"(d[5]),"=f"(d[6]),"=f"(d[7]),"=f"(d[8]),"=f"(d[9]),"=f"(d[10]),"=f"(d[11]),"=f"(d[12]),"=f"(d[13]),"=f"(d[14]),"=f"(d[15]),"=f"(d[16]),"=f"(d[17]),"=f"(d[18]),"=f"(d[19]),"=f"(d[20]),"=f"(d[21]),"=f"(d[22]),"=f"(d[23]),"=f"(d[24]),"=f"(d[25]),"=f"(d[26]),"=f"(d[27]),"=f"(d[28]),"=f"(d[29]),"=f"(d[30]),"=f"(d[31]),"=f"(d[32]),"=f"(d[33]),"=f"(d[34]),"=f"(d[35]) : "r"(a.x), "r"(a.y), "r"(a.z), "r"(a.w), "r"(db.lo), "r"(db.hi));
}
template<> __device__ __forceinline__ void wgmma_rs<192, 1>(float (&d)[96], const uint4& a, Desc db) {
  asm volatile("{\n.reg .pred p;\n.reg .b64 b;\nsetp.ne.b32 p, 1, 0;\nmov.b64 b, {%100, %101};\n"
    "wgmma.mma_async.sync.aligned.m64n192k16.f32.bf16.bf16 {%0,%1,%2,%3,%4,%5,%6,%7,%8,%9,%10,%11,%12,%13,%14,%15,%16,%17,%18,%19,%20,%21,%22,%23,%24,%25,%26,%27,%28,%29,%30,%31,%32,%33,%34,%35,%36,%37,%38,%39,%40,%41,%42,%43,%44,%45,%46,%47,%48,%49,%50,%51,%52,%53,%54,%55,%56,%57,%58,%59,%60,%61,%62,%63,%64,%65,%66,%67,%68,%69,%70,%71,%72,%73,%74,%75,%76,%77,%78,%79,%80,%81,%82,%83,%84,%85,%86,%87,%88,%89,%90,%91,%92,%93,%94,%95}, {%96,%97,%98,%99}, b, p, 1, 1, 1;\n}\n"
    : "+f"(d[0]),"+f"(d[1]),"+f"(d[2]),"+f"(d[3]),"+f"(d[4]),"+f"(d[5]),"+f"(d[6]),"+f"(d[7]),"+f"(d[8]),"+f"(d[9]),"+f"(d[10]),"+f"(d[11]),"+f"(d[12]),"+f"(d[13]),"+f"(d[14]),"+f"(d[15]),"+f"(d[16]),"+f"(d[17]),"+f"(d[18]),"+f"(d[19]),"+f"(d[20]),"+f"(d[21]),"+f"(d[22]),"+f"(d[23]),"+f"(d[24]),"+f"(d[25]),"+f"(d[26]),"+f"(d[27]),"+f"(d[28]),"+f"(d[29]),"+f"(d[30]),"+f"(d[31]),"+f"(d[32]),"+f"(d[33]),"+f"(d[34]),"+f"(d[35]),"+f"(d[36]),"+f"(d[37]),"+f"(d[38]),"+f"(d[39]),"+f"(d[40]),"+f"(d[41]),"+f"(d[42]),"+f"(d[43]),"+f"(d[44]),"+f"(d[45]),"+f"(d[46]),"+f"(d[47]),"+f"(d[48]),"+f"(d[49]),"+f"(d[50]),"+f"(d[51]),"+f"(d[52]),"+f"(d[53]),"+f"(d[54]),"+f"(d[55]),"+f"(d[56]),"+f"(d[57]),"+f"(d[58]),"+f"(d[59]),"+f"(d[60]),"+f"(d[61]),"+f"(d[62]),"+f"(d[63]),"+f"(d[64]),"+f"(d[65]),"+f"(d[66]),"+f"(d[67]),"+f"(d[68]),"+f"(d[69]),"+f"(d[70]),"+f"(d[71]),"+f"(d[72]),"+f"(d[73]),"+f"(d[74]),"+f"(d[75]),"+f"(d[76]),"+f"(d[77]),"+f"(d[78]),"+f"(d[79]),"+f"(d[80]),"+f"(d[81]),"+f"(d[82]),"+f"(d[83]),"+f"(d[84]),"+f"(d[85]),"+f"(d[86]),"+f"(d[87]),"+f"(d[88]),"+f"(d[89]),"+f"(d[90]),"+f"(d[91]),"+f"(d[92]),"+f"(d[93]),"+f"(d[94]),"+f"(d[95]) : "r"(a.x), "r"(a.y), "r"(a.z), "r"(a.w), "r"(db.lo), "r"(db.hi));
}
template<> __device__ __forceinline__ void wgmma_rs<192, 0>(float (&d)[96], const uint4& a, Desc db) {
  asm volatile("{\n.reg .pred p;\n.reg .b64 b;\nsetp.ne.b32 p, 0, 0;\nmov.b64 b, {%100, %101};\n"
    "wgmma.mma_async.sync.aligned.m64n192k16.f32.bf16.bf16 {%0,%1,%2,%3,%4,%5,%6,%7,%8,%9,%10,%11,%12,%13,%14,%15,%16,%17,%18,%19,%20,%21,%22,%23,%24,%25,%26,%27,%28,%29,%30,%31,%32,%33,%34,%35,%36,%37,%38,%39,%40,%41,%42,%43,%44,%45,%46,%47,%48,%49,%50,%51,%52,%53,%54,%55,%56,%57,%58,%59,%60,%61,%62,%63,%64,%65,%66,%67,%68,%69,%70,%71,%72,%73,%74,%75,%76,%77,%78,%79,%80,%81,%82,%83,%84,%85,%86,%87,%88,%89,%90,%91,%92,%93,%94,%95}, {%96,%97,%98,%99}, b, p, 1, 1, 1;\n}\n"
    : "=f"(d[0]),"=f"(d[1]),"=f"(d[2]),"=f"(d[3]),"=f"(d[4]),"=f"(d[5]),"=f"(d[6]),"=f"(d[7]),"=f"(d[8]),"=f"(d[9]),"=f"(d[10]),"=f"(d[11]),"=f"(d[12]),"=f"(d[13]),"=f"(d[14]),"=f"(d[15]),"=f"(d[16]),"=f"(d[17]),"=f"(d[18]),"=f"(d[19]),"=f"(d[20]),"=f"(d[21]),"=f"(d[22]),"=f"(d[23]),"=f"(d[24]),"=f"(d[25]),"=f"(d[26]),"=f"(d[27]),"=f"(d[28]),"=f"(d[29]),"=f"(d[30]),"=f"(d[31]),"=f"(d[32]),"=f"(d[33]),"=f"(d[34]),"=f"(d[35]),"=f"(d[36]),"=f"(d[37]),"=f"(d[38]),"=f"(d[39]),"=f"(d[40]),"=f"(d[41]),"=f"(d[42]),"=f"(d[43]),"=f"(d[44]),"=f"(d[45]),"=f"(d[46]),"=f"(d[47]),"=f"(d[48]),"=f"(d[49]),"=f"(d[50]),"=f"(d[51]),"=f"(d[52]),"=f"(d[53]),"=f"(d[54]),"=f"(d[55]),"=f"(d[56]),"=f"(d[57]),"=f"(d[58]),"=f"(d[59]),"=f"(d[60]),"=f"(d[61]),"=f"(d[62]),"=f"(d[63]),"=f"(d[64]),"=f"(d[65]),"=f"(d[66]),"=f"(d[67]),"=f"(d[68]),"=f"(d[69]),"=f"(d[70]),"=f"(d[71]),"=f"(d[72]),"=f"(d[73]),"=f"(d[74]),"=f"(d[75]),"=f"(d[76]),"=f"(d[77]),"=f"(d[78]),"=f"(d[79]),"=f"(d[80]),"=f"(d[81]),"=f"(d[82]),"=f"(d[83]),"=f"(d[84]),"=f"(d[85]),"=f"(d[86]),"=f"(d[87]),"=f"(d[88]),"=f"(d[89]),"=f"(d[90]),"=f"(d[91]),"=f"(d[92]),"=f"(d[93]),"=f"(d[94]),"=f"(d[95]) : "r"(a.x), "r"(a.y), "r"(a.z), "r"(a.w), "r"(db.lo), "r"(db.hi));
}
template<> __device__ __forceinline__ void wgmma_rs<256, 1>(float (&d)[128], const uint4& a, Desc db) {
  asm volatile("{\n.reg .pred p;\n.reg .b64 b;\nsetp.ne.b32 p, 1, 0;\nmov.b64 b, {%132, %133};\n"
    "wgmma.mma_async.sync.aligned.m64n256k16.f32.bf16.bf16 {%0,%1,%2,%3,%4,%5,%6,%7,%8,%9,%10,%11,%12,%13,%14,%15,%16,%17,%18,%19,%20,%21,%22,%23,%24,%25,%26,%27,%28,%29,%30,%31,%32,%33,%34,%35,%36,%37,%38,%39,%40,%41,%42,%43,%44,%45,%46,%47,%48,%49,%50,%51,%52,%53,%54,%55,%56,%57,%58,%59,%60,%61,%62,%63,%64,%65,%66,%67,%68,%69,%70,%71,%72,%73,%74,%75,%76,%77,%78,%79,%80,%81,%82,%83,%84,%85,%86,%87,%88,%89,%90,%91,%92,%93,%94,%95,%96,%97,%98,%99,%100,%101,%102,%103,%104,%105,%106,%107,%108,%109,%110,%111,%112,%113,%114,%115,%116,%117,%118,%119,%120,%121,%122,%123,%124,%125,%126,%127}, {%128,%129,%130,%131}, b, p, 1, 1, 1;\n}\n"
    : "+f"(d[0]),"+f"(d[1]),"+f"(d[2]),"+f"(d[3]),"+f"(d[4]),"+f"(d[5]),"+f"(d[6]),"+f"(d[7]),"+f"(d[8]),"+f"(d[9]),"+f"(d[10]),"+f"(d[11]),"+f"(d[12]),"+f"(d[13]),"+f"(d[14]),"+f"(d[15]),"+f"(d[16]),"+f"(d[17]),"+f"(d[18]),"+f"(d[19]),"+f"(d[20]),"+f"(d[21]),"+f"(d[22]),"+f"(d[23]),"+f"(d[24]),"+f"(d[25]),"+f"(d[26]),"+f"(d[27]),"+f"(d[28]),"+f"(d[29]),"+f"(d[30]),"+f"(d[31]),"+f"(d[32]),"+f"(d[33]),"+f"(d[34]),"+f"(d[35]),"+f"(d[36]),"+f"(d[37]),"+f"(d[38]),"+f"(d[39]),"+f"(d[40]),"+f"(d[41]),"+f"(d[42]),"+f"(d[43]),"+f"(d[44]),"+f"(d[45]),"+f"(d[46]),"+f"(d[47]),"+f"(d[48]),"+f"(d[49]),"+f"(d[50]),"+f"(d[51]),"+f"(d[52]),"+f"(d[53]),"+f"(d[54]),"+f"(d[55]),"+f"(d[56]),"+f"(d[57]),"+f"(d[58]),"+f"(d[59]),"+f"(d[60]),"+f"(d[61]),"+f"(d[62]),"+f"(d[63]),"+f"(d[64]),"+f"(d[65]),"+f"(d[66]),"+f"(d[67]),"+f"(d[68]),"+f"(d[69]),"+f"(d[70]),"+f"(d[71]),"+f"(d[72]),"+f"(d[73]),"+f"(d[74]),"+f"(d[75]),"+f"(d[76]),"+f"(d[77]),"+f"(d[78]),"+f"(d[79]),"+f"(d[80]),"+f"(d[81]),"+f"(d[82]),"+f"(d[83]),"+f"(d[84]),"+f"(d[85]),"+f"(d[86]),"+f"(d[87]),"+f"(d[88]),"+f"(d[89]),"+f"(d[90]),"+f"(d[91]),"+f"(d[92]),"+f"(d[93]),"+f"(d[94]),"+f"(d[95]),"+f"(d[96]),"+f"(d[97]),"+f"(d[98]),"+f"(d[99]),"+f"(d[100]),"+f"(d[101]),"+f"(d[102]),"+f"(d[103]),"+f"(d[104]),"+f"(d[105]),"+f"(d[106]),"+f"(d[107]),"+f"(d[108]),"+f"(d[109]),"+f"(d[110]),"+f"(d[111]),"+f"(d[112]),"+f"(d[113]),"+f"(d[114]),"+f"(d[115]),"+f"(d[116]),"+f"(d[117]),"+f"(d[118]),"+f"(d[119]),"+f"(d[120]),"+f"(d[121]),"+f"(d[122]),"+f"(d[123]),"+f"(d[124]),"+f"(d[125]),"+f"(d[126]),"+f"(d[127]) : "r"(a.x), "r"(a.y), "r"(a.z), "r"(a.w), "r"(db.lo), "r"(db.hi));
}
template<> __device__ __forceinline__ void wgmma_rs<256, 0>(float (&d)[128], const uint4& a, Desc db) {
  asm volatile("{\n.reg .pred p;\n.reg .b64 b;\nsetp.ne.b32 p, 0, 0;\nmov.b64 b, {%132, %133};\n"
    "wgmma.mma_async.sync.aligned.m64n256k16.f32.bf16.bf16 {%0,%1,%2,%3,%4,%5,%6,%7,%8,%9,%10,%11,%12,%13,%14,%15,%16,%17,%18,%19,%20,%21,%22,%23,%24,%25,%26,%27,%28,%29,%30,%31,%32,%33,%34,%35,%36,%37,%38,%39,%40,%41,%42,%43,%44,%45,%46,%47,%48,%49,%50,%51,%52,%53,%54,%55,%56,%57,%58,%59,%60,%61,%62,%63,%64,%65,%66,%67,%68,%69,%70,%71,%72,%73,%74,%75,%76,%77,%78,%79,%80,%81,%82,%83,%84,%85,%86,%87,%88,%89,%90,%91,%92,%93,%94,%95,%96,%97,%98,%99,%100,%101,%102,%103,%104,%105,%106,%107,%108,%109,%110,%111,%112,%113,%114,%115,%116,%117,%118,%119,%120,%121,%122,%123,%124,%125,%126,%127}, {%128,%129,%130,%131}, b, p, 1, 1, 1;\n}\n"
    : "=f"(d[0]),"=f"(d[1]),"=f"(d[2]),"=f"(d[3]),"=f"(d[4]),"=f"(d[5]),"=f"(d[6]),"=f"(d[7]),"=f"(d[8]),"=f"(d[9]),"=f"(d[10]),"=f"(d[11]),"=f"(d[12]),"=f"(d[13]),"=f"(d[14]),"=f"(d[15]),"=f"(d[16]),"=f"(d[17]),"=f"(d[18]),"=f"(d[19]),"=f"(d[20]),"=f"(d[21]),"=f"(d[22]),"=f"(d[23]),"=f"(d[24]),"=f"(d[25]),"=f"(d[26]),"=f"(d[27]),"=f"(d[28]),"=f"(d[29]),"=f"(d[30]),"=f"(d[31]),"=f"(d[32]),"=f"(d[33]),"=f"(d[34]),"=f"(d[35]),"=f"(d[36]),"=f"(d[37]),"=f"(d[38]),"=f"(d[39]),"=f"(d[40]),"=f"(d[41]),"=f"(d[42]),"=f"(d[43]),"=f"(d[44]),"=f"(d[45]),"=f"(d[46]),"=f"(d[47]),"=f"(d[48]),"=f"(d[49]),"=f"(d[50]),"=f"(d[51]),"=f"(d[52]),"=f"(d[53]),"=f"(d[54]),"=f"(d[55]),"=f"(d[56]),"=f"(d[57]),"=f"(d[58]),"=f"(d[59]),"=f"(d[60]),"=f"(d[61]),"=f"(d[62]),"=f"(d[63]),"=f"(d[64]),"=f"(d[65]),"=f"(d[66]),"=f"(d[67]),"=f"(d[68]),"=f"(d[69]),"=f"(d[70]),"=f"(d[71]),"=f"(d[72]),"=f"(d[73]),"=f"(d[74]),"=f"(d[75]),"=f"(d[76]),"=f"(d[77]),"=f"(d[78]),"=f"(d[79]),"=f"(d[80]),"=f"(d[81]),"=f"(d[82]),"=f"(d[83]),"=f"(d[84]),"=f"(d[85]),"=f"(d[86]),"=f"(d[87]),"=f"(d[88]),"=f"(d[89]),"=f"(d[90]),"=f"(d[91]),"=f"(d[92]),"=f"(d[93]),"=f"(d[94]),"=f"(d[95]),"=f"(d[96]),"=f"(d[97]),"=f"(d[98]),"=f"(d[99]),"=f"(d[100]),"=f"(d[101]),"=f"(d[102]),"=f"(d[103]),"=f"(d[104]),"=f"(d[105]),"=f"(d[106]),"=f"(d[107]),"=f"(d[108]),"=f"(d[109]),"=f"(d[110]),"=f"(d[111]),"=f"(d[112]),"=f"(d[113]),"=f"(d[114]),"=f"(d[115]),"=f"(d[116]),"=f"(d[117]),"=f"(d[118]),"=f"(d[119]),"=f"(d[120]),"=f"(d[121]),"=f"(d[122]),"=f"(d[123]),"=f"(d[124]),"=f"(d[125]),"=f"(d[126]),"=f"(d[127]) : "r"(a.x), "r"(a.y), "r"(a.z), "r"(a.w), "r"(db.lo), "r"(db.hi));
}
template<int N> __device__ __forceinline__ void wgmma_ra(float (&d)[N / 2], const uint4& a, Desc db, bool acc) {
  if (acc) wgmma_rs<N, 1>(d, a, db); else wgmma_rs<N, 0>(d, a, db);
}

__device__ __forceinline__ uint32_t smem_u32(const void* p) { return (uint32_t)__cvta_generic_to_shared(p); }
__device__ __forceinline__ void mbar_init(uint32_t bar, uint32_t cnt) { asm volatile("mbarrier.init.shared::cta.b64 [%0], %1;" ::"r"(bar), "r"(cnt)); }
__device__ __forceinline__ void mbar_expect_tx(uint32_t bar, uint32_t bytes) { asm volatile("mbarrier.arrive.expect_tx.shared::cta.b64 _, [%0], %1;" ::"r"(bar), "r"(bytes) : "memory"); }
__device__ __forceinline__ void mbar_arrive(uint32_t bar) { asm volatile("mbarrier.arrive.shared::cta.b64 _, [%0];" ::"r"(bar) : "memory"); }
__device__ __forceinline__ void mbar_arrive_remote(uint32_t rbar) { asm volatile("mbarrier.arrive.shared::cluster.b64 _, [%0];" ::"r"(rbar) : "memory"); }
__device__ __forceinline__ void mbar_wait(uint32_t bar, uint32_t parity) {
  asm volatile(
      "{\n.reg .pred p;\n.reg .u32 c;\nmov.u32 c, 0;\nLAB_WAIT:\nmbarrier.try_wait.parity.shared::cta.b64 p, [%0], %1;\n@p bra DONE;\n"
      "add.u32 c, c, 1;\nsetp.lt.u32 p, c, 1000000;\n@p bra LAB_WAIT;\ntrap;\nDONE:\n}\n" ::"r"(bar), "r"(parity) : "memory");
}
__device__ __forceinline__ void mbar_wait_c(uint32_t bar, uint32_t parity) {
  asm volatile("{\n.reg .pred p;\nLAB_WAIT:\nmbarrier.try_wait.parity.shared::cta.b64 p, [%0], %1;\n@!p bra LAB_WAIT;\n}\n" ::"r"(bar), "r"(parity) : "memory");
}
__device__ __forceinline__ uint32_t late(uint32_t bar, uint32_t v) {
  uint32_t r;
  asm volatile("{\n.reg .pred p;\nmbarrier.test_wait.parity.shared::cta.b64 p, [%1], 0;\nselp.b32 %0, %2, %1, p;\n}\n" : "=r"(r) : "r"(bar), "r"(v) : "memory");
  return r;
}
__device__ __forceinline__ void wtma2d(uint32_t dst, const CUtensorMap* m, int c0, int c1, uint32_t bar, uint64_t pol) {
  asm volatile("cp.async.bulk.tensor.2d.shared::cluster.global.mbarrier::complete_tx::bytes.multicast::cluster.L2::cache_hint [%0], [%1, {%3, %4}], [%2], %5, %6;"
               ::"r"(dst), "l"(m), "r"(bar), "r"(c0), "r"(c1), "h"((uint16_t)3), "l"(pol) : "memory");
}
__device__ __forceinline__ void wtma3d(uint32_t dst, const CUtensorMap* m, int c0, int c1, int c2, uint32_t bar, uint64_t pol) {
  asm volatile("cp.async.bulk.tensor.3d.shared::cluster.global.mbarrier::complete_tx::bytes.multicast::cluster.L2::cache_hint [%0], [%1, {%3, %4, %5}], [%2], %6, %7;"
               ::"r"(dst), "l"(m), "r"(bar), "r"(c0), "r"(c1), "r"(c2), "h"((uint16_t)3), "l"(pol) : "memory");
}
__device__ __forceinline__ void wbulk(uint32_t dst, const void* src, uint32_t bytes, uint32_t bar, uint64_t pol) {
  asm volatile("cp.async.bulk.shared::cluster.global.mbarrier::complete_tx::bytes.multicast::cluster.L2::cache_hint [%0], [%1], %2, [%3], %4, %5;"
               ::"r"(dst), "l"(src), "r"(bytes), "r"(bar), "h"((uint16_t)3), "l"(pol) : "memory");
}
__device__ __forceinline__ void tma3d(uint32_t dst, const CUtensorMap* m, int c0, int c1, int c2, uint32_t bar) {
  asm volatile("cp.async.bulk.tensor.3d.shared::cluster.global.mbarrier::complete_tx::bytes [%0], [%1, {%3, %4, %5}], [%2];"
               ::"r"(dst), "l"(m), "r"(bar), "r"(c0), "r"(c1), "r"(c2) : "memory");
}
__device__ __forceinline__ void tma_store3d(const CUtensorMap* m, uint32_t src, int c0, int c1, int c2) {
  asm volatile("cp.async.bulk.tensor.3d.global.shared::cta.bulk_group [%0, {%2, %3, %4}], [%1];" ::"l"(m), "r"(src), "r"(c0), "r"(c1), "r"(c2) : "memory");
}
__device__ __forceinline__ void prefetch_l2(const void* p, uint32_t bytes) { asm volatile("cp.async.bulk.prefetch.L2.global [%0], %1;" ::"l"(p), "r"(bytes) : "memory"); }
__device__ __forceinline__ uint64_t policy_evict_first() { uint64_t p; asm volatile("createpolicy.fractional.L2::evict_first.b64 %0, 1.0;" : "=l"(p)); return p; }
__device__ __forceinline__ uint64_t policy_evict_normal() { uint64_t p; asm volatile("createpolicy.fractional.L2::evict_normal.b64 %0, 1.0;" : "=l"(p)); return p; }
__device__ __forceinline__ void bulk_commit() { asm volatile("cp.async.bulk.commit_group;" ::: "memory"); }
__device__ __forceinline__ void bulk_wait_all() { asm volatile("cp.async.bulk.wait_group 0;" ::: "memory"); }
__device__ __forceinline__ void fence_async_smem() { asm volatile("fence.proxy.async.shared::cta;" ::: "memory"); }
__device__ __forceinline__ bool elect_one() {
  uint32_t p;
  asm volatile("{\n.reg .pred P;\nelect.sync _|P, 0xffffffff;\nselp.u32 %0, 1, 0, P;\n}\n" : "=r"(p));
  return p;
}
__device__ __forceinline__ void wg_fence() { asm volatile("wgmma.fence.sync.aligned;" ::: "memory"); }
__device__ __forceinline__ void wg_commit() { asm volatile("wgmma.commit_group.sync.aligned;" ::: "memory"); }
template <int n> __device__ __forceinline__ void wg_wait() { asm volatile("wgmma.wait_group.sync.aligned %0;" ::"n"(n) : "memory"); }
__device__ __forceinline__ void wg_bar(int w) { asm volatile("bar.sync %0, 128;" ::"r"(w + 1) : "memory"); }
__device__ __forceinline__ void cluster_sync() { asm volatile("barrier.cluster.arrive.relaxed.aligned;\nbarrier.cluster.wait.aligned;" ::: "memory"); }
__device__ __forceinline__ void fence_gpu() { asm volatile("fence.acq_rel.gpu;" ::: "memory"); }
__device__ __forceinline__ uint32_t ld_relaxed(const uint32_t* p) { uint32_t v; asm volatile("ld.relaxed.gpu.global.u32 %0, [%1];" : "=r"(v) : "l"(p) : "memory"); return v; }
__device__ __forceinline__ uint32_t ld_acquire(const uint32_t* p) { uint32_t v; asm volatile("ld.acquire.gpu.global.u32 %0, [%1];" : "=r"(v) : "l"(p) : "memory"); return v; }
__device__ __forceinline__ uint4 ld_relaxed4(const uint4* p) {
  uint4 v; asm volatile("ld.relaxed.gpu.global.v4.u32 {%0,%1,%2,%3}, [%4];" : "=r"(v.x), "=r"(v.y), "=r"(v.z), "=r"(v.w) : "l"(p) : "memory"); return v;
}
__device__ __forceinline__ uint2 ld_relaxed2(const uint2* p) {
  uint2 v; asm volatile("ld.relaxed.gpu.global.v2.u32 {%0,%1}, [%2];" : "=r"(v.x), "=r"(v.y) : "l"(p) : "memory"); return v;
}
__device__ __forceinline__ void st_relaxed(uint32_t* p, uint32_t a) { asm volatile("st.relaxed.gpu.global.u32 [%0], %1;" ::"l"(p), "r"(a) : "memory"); }
__device__ __forceinline__ void st_relaxed4(uint4* p, uint32_t a, uint32_t b, uint32_t c, uint32_t d) {
  asm volatile("st.relaxed.gpu.global.v4.u32 [%0], {%1,%2,%3,%4};" ::"l"(p), "r"(a), "r"(b), "r"(c), "r"(d) : "memory");
}
__device__ __forceinline__ void st_relaxed2(uint2* p, uint32_t a, uint32_t b) {
  asm volatile("st.relaxed.gpu.global.v2.u32 [%0], {%1,%2};" ::"l"(p), "r"(a), "r"(b) : "memory");
}
__device__ __forceinline__ void red4(uint4* p, uint32_t a, uint32_t b, uint32_t c, uint32_t d) {
  asm volatile("red.relaxed.gpu.global.add.noftz.v4.bf16x2 [%0], {%1,%2,%3,%4};" ::"l"(p), "r"(a), "r"(b), "r"(c), "r"(d) : "memory");
}
__device__ __forceinline__ void red2(uint2* p, uint32_t a, uint32_t b) {
  asm volatile("red.relaxed.gpu.global.add.noftz.v2.bf16x2 [%0], {%1,%2};" ::"l"(p), "r"(a), "r"(b) : "memory");
}
constexpr int SPIN_MAX = 1 << 21;
__device__ __forceinline__ uint32_t pack_bf16(float lo, float hi) { uint32_t r; asm("cvt.rn.bf16x2.f32 %0, %1, %2;" : "=r"(r) : "f"(hi), "f"(lo)); return r; }
__device__ __forceinline__ float bf_lo(uint32_t v) { return __uint_as_float(v << 16); }
__device__ __forceinline__ float bf_hi(uint32_t v) { return __uint_as_float(v & 0xffff0000u); }
__device__ __forceinline__ float2 lds64(uint32_t a) { float2 v; asm volatile("ld.shared.v2.f32 {%0,%1}, [%2];" : "=f"(v.x), "=f"(v.y) : "r"(a)); return v; }
__device__ __forceinline__ uint32_t lds32(uint32_t a) { uint32_t v; asm volatile("ld.shared.b32 %0, [%1];" : "=r"(v) : "r"(a)); return v; }
__device__ __forceinline__ void sts64f(uint32_t a, float x, float y) { asm volatile("st.shared.v2.f32 [%0], {%1,%2};" ::"r"(a), "f"(x), "f"(y) : "memory"); }
__device__ __forceinline__ void sts32(uint32_t a, uint32_t x) { asm volatile("st.volatile.shared.b32 [%0], %1;" ::"r"(a), "r"(x) : "memory"); }
__device__ __forceinline__ void gate(uint32_t a, int need) {
#pragma unroll 1
  for (int it = 0; it < SPIN_MAX; it++) {
    int v; asm volatile("ld.volatile.shared.b32 %0, [%1];" : "=r"(v) : "r"(a) : "memory");
    if (v >= need) break;
    if (GSLEEP) __nanosleep(GSLEEP);
  }
}
__device__ __forceinline__ void sts128(uint32_t a, uint32_t x, uint32_t y, uint32_t z, uint32_t u) { asm volatile("st.shared.v4.b32 [%0], {%1,%2,%3,%4};" ::"r"(a), "r"(x), "r"(y), "r"(z), "r"(u) : "memory"); }
__device__ __forceinline__ uint4 lds128(uint32_t a) { uint4 v; asm volatile("ld.shared.v4.u32 {%0,%1,%2,%3}, [%4];" : "=r"(v.x), "=r"(v.y), "=r"(v.z), "=r"(v.w) : "r"(a) : "memory"); return v; }
__device__ __forceinline__ uint32_t hmul2(uint32_t a, uint32_t b) { uint32_t r; asm("mul.rn.bf16x2 %0, %1, %2;" : "=r"(r) : "r"(a), "r"(b)); return r; }
__device__ __forceinline__ uint32_t hadd2(uint32_t a, uint32_t b) { uint32_t r; asm("add.rn.bf16x2 %0, %1, %2;" : "=r"(r) : "r"(a), "r"(b)); return r; }
__device__ __forceinline__ void stsm4(uint32_t a, uint32_t r0, uint32_t r1, uint32_t r2, uint32_t r3) {
  asm volatile("stmatrix.sync.aligned.m8n8.x4.shared.b16 [%0], {%1,%2,%3,%4};" ::"r"(a), "r"(r0), "r"(r1), "r"(r2), "r"(r3) : "memory");
}
__device__ __forceinline__ void stsm2(uint32_t a, uint32_t r0, uint32_t r1) {
  asm volatile("stmatrix.sync.aligned.m8n8.x2.shared.b16 [%0], {%1,%2};" ::"r"(a), "r"(r0), "r"(r1) : "memory");
}
__device__ __forceinline__ uint4 ldsm4(uint32_t a) {
  uint4 r; asm volatile("ldmatrix.sync.aligned.m8n8.x4.shared.b16 {%0,%1,%2,%3}, [%4];" : "=r"(r.x), "=r"(r.y), "=r"(r.z), "=r"(r.w) : "r"(a) : "memory"); return r;
}
__device__ __forceinline__ uint32_t movm(uint32_t a) { uint32_t r; asm("movmatrix.sync.aligned.m8n8.trans.b16 %0, %1;" : "=r"(r) : "r"(a)); return r; }
__device__ __forceinline__ void mma16816z(float (&d)[4], uint32_t a0, uint32_t a1, uint32_t a2, uint32_t a3, uint32_t b0, uint32_t b1) {
  asm("mma.sync.aligned.m16n8k16.row.col.f32.bf16.bf16.f32 {%0,%1,%2,%3}, {%4,%5,%6,%7}, {%8,%9}, {%10,%10,%10,%10};"
      : "=f"(d[0]), "=f"(d[1]), "=f"(d[2]), "=f"(d[3]) : "r"(a0), "r"(a1), "r"(a2), "r"(a3), "r"(b0), "r"(b1), "f"(0.f));
}
__device__ __forceinline__ void mma16816(float (&d)[4], const uint4& a, uint32_t b0, uint32_t b1) {
  asm("mma.sync.aligned.m16n8k16.row.col.f32.bf16.bf16.f32 {%0,%1,%2,%3}, {%4,%5,%6,%7}, {%8,%9}, {%0,%1,%2,%3};"
      : "+f"(d[0]), "+f"(d[1]), "+f"(d[2]), "+f"(d[3]) : "r"(a.x), "r"(a.y), "r"(a.z), "r"(a.w), "r"(b0), "r"(b1));
}
__device__ __forceinline__ void mma1688(float (&d)[4], uint32_t a0, uint32_t a1, uint32_t b0) {
  asm("mma.sync.aligned.m16n8k8.row.col.f32.bf16.bf16.f32 {%0,%1,%2,%3}, {%4,%5}, {%6}, {%0,%1,%2,%3};"
      : "+f"(d[0]), "+f"(d[1]), "+f"(d[2]), "+f"(d[3]) : "r"(a0), "r"(a1), "r"(b0));
}
__device__ __forceinline__ float quad_sum(float v) { v += __shfl_xor_sync(0xffffffffu, v, 1); v += __shfl_xor_sync(0xffffffffu, v, 2); return v; }
__device__ __forceinline__ float quad_max(float v) { v = fmaxf(v, __shfl_xor_sync(0xffffffffu, v, 1)); v = fmaxf(v, __shfl_xor_sync(0xffffffffu, v, 2)); return v; }
__device__ __forceinline__ float rcp(float x) { float r; asm("rcp.approx.ftz.f32 %0, %1;" : "=f"(r) : "f"(x)); return r; }
__device__ __forceinline__ float rsq(float x) { float r; asm("rsqrt.approx.ftz.f32 %0, %1;" : "=f"(r) : "f"(x)); return r; }
__device__ __forceinline__ float ex2(float x) { float r; asm("ex2.approx.ftz.f32 %0, %1;" : "=f"(r) : "f"(x)); return r; }
__device__ __forceinline__ uint32_t chk(uint32_t acc, uint32_t v, uint32_t tag) { uint32_t r; asm("lop3.b32 %0, %1, %2, %3, 0xF6;" : "=r"(r) : "r"(acc), "r"(v), "r"(tag)); return r; }
__device__ __forceinline__ uint32_t chk2(uint32_t a, uint32_t b, uint32_t tag) { uint32_t r; asm("lop3.b32 %0, %1, %2, %3, 0x7E;" : "=r"(r) : "r"(a), "r"(b), "r"(tag)); return r; }
__device__ __forceinline__ uint32_t tagged(uint32_t v, uint32_t tag) { return (v & ~1u) | tag; }

__device__ __forceinline__ int group_k0(int g, int j) {
  const int h = g >= 9, r = g - 2 - 7 * h;
  return g < 2 ? 64 * j + 32 * g : g < 16 ? 64 * (r + (r >= j)) + 32 * h : 32 * g;
}
__device__ __forceinline__ uint32_t xin_off(int c, int w) { return SM_X + (2 * c + w) * 8192; }
__device__ __forceinline__ uint32_t xin_bar(int c) { return BAR_FULLX + 8 * (c < 8 ? c ^ 4 : c); }
__device__ __forceinline__ constexpr uint32_t qkv_xslot(int g) { return g < 5 || g > 11 ? 2 : (0x5140762u >> (4 * (g - 5))) & 15; }

template <int N> struct IC { static constexpr int v = N; };

struct Cons {
  uint32_t sb;
  uint32_t rem;
  uint32_t sB, mB;
  uint32_t mX;
  bool elect;
  __device__ __forceinline__ void release2(uint32_t bar) const { if (elect) { mbar_arrive(sb + bar); mbar_arrive_remote(rem + bar); } }
  __device__ __forceinline__ uint32_t nextB(uint32_t& prev) {
    mbar_wait_c(sb + BAR_FULLB + sB, mB);
    const uint32_t a = (((sb & 0x3FFFF) + SM_B) >> 4) + sB * (BSLOT / 128);
    prev = sB == 0 ? 32 : sB - 8;
    sB += 8;
    if (sB == 40) { sB = 0; mB ^= 1; }
    return a;
  }
  __device__ __forceinline__ void progress(uint32_t v) const { if (elect) sts32(sb + SM_PROG + (threadIdx.x >> 5), v); }
  __device__ __forceinline__ void releaseLastB() const { release2(BAR_EMPTYB + (sB == 0 ? 32 : sB - 8)); }
};

__device__ __forceinline__ float2 gather_sums(const uint2* a, uint32_t stag) {
  uint2 sa, sc;
  do { sa = ld_relaxed2(a); sc = ld_relaxed2(a + 8); } while (__any_sync(0xffffffffu, chk2(sa.x, sc.x, stag) & 3));
  return make_float2(quad_sum(__uint_as_float(sa.x) + __uint_as_float(sc.x)), quad_sum(__uint_as_float(sa.y) + __uint_as_float(sc.y)));
}

struct Norm {
  float m0, m1;
  uint32_t nm0, nm1;
  float d0, d1;
  uint2 u0, u1;
  __device__ __forceinline__ Norm(float2 sum) : m0(sum.x * (-1.f / 576)), m1(sum.y * (-1.f / 576)), nm0(pack_bf16(m0, m0)), nm1(pack_bf16(m1, m1)), d0(0.f), d1(0.f) {}
  __device__ __forceinline__ uint4 centre(const uint4& a) const { return make_uint4(hadd2(a.x, nm0), hadd2(a.y, nm1), hadd2(a.z, nm0), hadd2(a.w, nm1)); }
  __device__ __forceinline__ void sqr(uint32_t a, uint32_t b) {
    d0 = fmaf(bf_lo(a), bf_lo(a), fmaf(bf_hi(a), bf_hi(a), d0)); d1 = fmaf(bf_lo(b), bf_lo(b), fmaf(bf_hi(b), bf_hi(b), d1));
  }
  __device__ __forceinline__ void send(uint2* a, int t, uint32_t stag) {
    d0 = quad_sum(d0); d1 = quad_sum(d1);
    if ((t & 3) == 0) st_relaxed2(a, (__float_as_uint(d0) & ~3u) | stag, __float_as_uint(d1));
  }
  __device__ __forceinline__ void fetch(const uint2* a) { u0 = ld_relaxed2(a); u1 = ld_relaxed2(a + 8); }
  __device__ __forceinline__ float2 rstd(const uint2* a, uint32_t stag) {
    while (__any_sync(0xffffffffu, chk2(u0.x, u1.x, stag) & 3)) fetch(a);
    const float e0 = bf_lo(nm0) - m0, e1 = bf_lo(nm1) - m1;
    const float v0 = fmaf(quad_sum(__uint_as_float(u0.x) + __uint_as_float(u1.x)), 1.f / 576, -e0 * e0);
    const float v1 = fmaf(quad_sum(__uint_as_float(u0.y) + __uint_as_float(u1.y)), 1.f / 576, -e1 * e1);
    float2 r = make_float2(rsq(fmaxf(v0, 0.f) + 1e-5f), rsq(fmaxf(v1, 0.f) + 1e-5f));
    asm volatile("" : "+f"(r.x), "+f"(r.y));
    return r;
  }
};

template <class Pre, class Mma>
__device__ __forceinline__ float2 ln_gemm_in(Cons& c, Group* G, uint32_t (&p)[18], float2& sum, int w, int st0, int j, int t, Pre&& pre, Mma&& mma) {
  const uint32_t xa = c.sb + (t >> 5) * 2048 + (t & 15) * 128, sw = (((t >> 4) & 1) ^ (t & 7)) * 16;
  float ra[4] = {0.f, 0.f, 0.f, 0.f}, rb[4] = {0.f, 0.f, 0.f, 0.f};
#pragma unroll 1
  for (int cc = 0; cc < 9; cc++) {
    const uint32_t a = xa + xin_off(cc, w);
    mbar_wait_c(c.sb + xin_bar(cc), 0);
    const uint4 u0 = ldsm4(a + sw), u1 = ldsm4(a + (sw ^ 32)), u2 = ldsm4(a + (sw ^ 64)), u3 = ldsm4(a + (sw ^ 96));
    mma16816(ra, u0, 0x3f803f80u, 0x3f803f80u); mma16816(rb, u1, 0x3f803f80u, 0x3f803f80u);
    mma16816(ra, u2, 0x3f803f80u, 0x3f803f80u); mma16816(rb, u3, 0x3f803f80u, 0x3f803f80u);
  }
  sum = make_float2(ra[0] + rb[0], ra[2] + rb[2]);
  pre(0);
  Norm n(sum);
  n.u0 = n.u1 = make_uint2(0, 0);
  auto stats = [&] {
#pragma unroll
    for (int k = 0; k < 5; k++) {
      const uint4 u = ldsm4(xa + (k < 4 ? xin_off(j, w) + (sw ^ (32 * k)) : xin_off(8, w) + ((j ^ (t & 7)) << 4))), e = n.centre(u);
      p[4 * k] = u.x; p[4 * k + 1] = u.y;
      n.sqr(e.x, e.y);
      if (k < 4) { p[4 * k + 2] = u.z; p[4 * k + 3] = u.w; n.sqr(e.z, e.w); }
    }
    n.send(G->sq + st0 + 8 * j, t, 1);
  };
  if (STATP < 0) stats();
  else {
#pragma unroll
    for (int i = 0; i < 18; i++) p[i] = 0;
  }
  pre(1);
  uint4 y0 = ldsm4(xa + xin_off(0, w) + sw), y1 = ldsm4(xa + xin_off(0, w) + (sw ^ 32));
#pragma unroll 1
  for (int cc = 0; cc < 9; cc++) {
#pragma unroll
    for (int i = 0; i < 2; i++) {
      const uint4 f0 = n.centre(y0), f1 = n.centre(y1);
      const uint32_t a = xa + xin_off(min(cc + i, 8), w);
      y0 = ldsm4(a + (sw ^ (64 - 64 * i))); y1 = ldsm4(a + (sw ^ (96 - 64 * i)));
      uint32_t prev;
      const uint32_t bb = c.nextB(prev);
      mma(true, bb, f0, f1);
      if (i == 1) {
        if (STATP >= 0 && cc == STATP * w) stats();
        if (cc == 1) c.progress(3);
        if (cc == 7) n.fetch(G->sq + st0 + 16 * (t & 3));
        if (cc == 8 && w == 0) asm volatile("bar.arrive 6, 256;" ::: "memory");
      }
      wg_wait<1>();
      if (i + cc > 0) c.release2(BAR_EMPTYB + prev);
      if (2 * cc + i >= WOG && 2 * cc + i < WOG + 4) c.release2(BAR_EMPTYX + 32 + 8 * (2 * cc + i - WOG));
    }
  }
  c.mX = 0xff;
  const float2 r = n.rstd(G->sq + st0 + 16 * (t & 3), 1);
  if (w == 1) asm volatile("bar.sync 6, 256;" ::: "memory");
  wg_wait<0>();
  c.releaseLastB();
  c.release2(BAR_EMPTYX + 24);
  return r;
}

template <bool QKV, class Pre, class Mma>
__device__ __forceinline__ float2 ln_gemm(Cons& c, Group* G, const float (&v)[36], uint32_t (&p)[18], float2& sum, int st0, int j, int t,
                                          int layer, uint32_t tag, Pre&& pre, Mma&& mma) {
  constexpr bool known = !QKV && EARLY;
  const uint32_t stag = (2 * layer + (QKV ? 1 : 2)) & 3;
  uint4 x[6][2];
  uint4* src = G->xbox + t;
  asm volatile("" : "+l"(src));
  auto buf = [&](int g) -> uint4 (&)[2] { return x[g < 16 ? (g - 2) % 6 : g - 13]; };
  auto load = [&](int g0) {
#pragma unroll
    for (int g = g0; g < g0 + (g0 < 14 ? 3 : 2); g++) {
      const uint4* a = g < 16 ? src + ((g - 2) % 7 >= j ? 256 : 0) + (2 * ((g - 2) % 7) + 16 * (g >= 9)) * 128 : src + 2 * g * 128;
      buf(g)[0] = ld_relaxed4(a); buf(g)[1] = ld_relaxed4(a + 128);
    }
  };
  auto invalid = [&](int g, uint32_t tag) {
    uint32_t bad = chk(chk(chk2(buf(g)[0].x, buf(g)[1].x, tag), buf(g + 1)[0].x, tag), buf(g + 1)[1].x, tag);
    if (g < 14) bad = chk(chk(bad, buf(g + 2)[0].x, tag), buf(g + 2)[1].x, tag);
    if (g == 16) bad = chk(chk(chk(chk(bad, buf(g)[0].z, tag), buf(g)[1].z, tag), buf(g + 1)[0].z, tag), buf(g + 1)[1].z, tag);
    return __any_sync(0xffffffffu, bad & 1);
  };
  uint4* const d = src + 2 * j * 128;
  const int sq = st0 + 16 * (t & 3);
  if (!known) {
    float s0 = v[0] + v[1], s1 = v[2] + v[3];
#pragma unroll
    for (int i = 1; i < 9; i++) { s0 += v[4 * i] + v[4 * i + 1]; s1 += v[4 * i + 2] + v[4 * i + 3]; }
    s0 = quad_sum(s0); s1 = quad_sum(s1);
    if ((t & 3) == 0) st_relaxed2(G->sum + st0 + 8 * j, (__float_as_uint(s0) & ~3u) | stag, __float_as_uint(s1));
  }
#pragma unroll
  for (int i = 0; i < 18; i++) p[i] = pack_bf16(v[2 * i], v[2 * i + 1]);
#pragma unroll
  for (int i = 0; i < 2; i++) st_relaxed4(d + i * 128, tagged(p[4 * i], tag), p[4 * i + 1], p[4 * i + 2], p[4 * i + 3]);
  pre(0);
  if (!known) {
    sum = gather_sums(G->sum + sq, stag);
    load(2);
  }
  Norm n(sum);
  pre(1);
  const uint32_t* probe = &(G->xbox + (2 * (t & 7) + 1) * 128 + (t | 31))->x;
  uint32_t pv;
  auto inx = [](int g) { return QKV && ((g >= 5 && g < 12) || g == 17); };
  auto use = [](int g) { return QKV ? (g < 5 ? 108 : 101) + g : 18 + g; };
#pragma unroll
  for (int g = 0; g < 18; g++) {
    if (g < 16 ? g % 3 == 2 : g == 16) {
      const uint32_t lt = late(c.sb + BAR_FULLX + 64, tag);
      while (invalid(g, lt)) load(g);
      if (g < 16) load(g < 14 ? g + 3 : 16);
    }
    const uint4 f0 = n.centre(g < 2 ? make_uint4(p[8 * g], p[8 * g + 1], p[8 * g + 2], p[8 * g + 3]) : buf(g)[0]);
    const uint4 f1 = n.centre(g < 2 ? make_uint4(p[8 * g + 4], p[8 * g + 5], p[8 * g + 6], p[8 * g + 7]) : buf(g)[1]);
    if (g == 14) n.fetch(G->sq + sq);
    if (inx(g)) mbar_wait_c(c.sb + BAR_FULLX + 8 * qkv_xslot(g), ((0x34 >> qkv_xslot(g)) & 1) ^ (g == 17));
    else mbar_wait_c(c.sb + BAR_FULLB + 8 * (use(g) % 5), (use(g) / 5) & 1);
    mma(g, ((c.sb & 0x3FFFF) >> 4) + ((inx(g) ? xslot(qkv_xslot(g)) : SM_B + (use(g) % 5) * BSLOT) >> 4), f0, f1);
    if (g < 2) {
      if (known) {
        if (g == 0) {
          pv = ld_relaxed(probe);
        } else {
          const uint32_t lt = late(c.sb + BAR_FULLX + 64, tag);
          while (__any_sync(0xffffffffu, (pv ^ lt) & 1)) pv = ld_relaxed(probe);
          load(2);
        }
      }
      if (g == (known ? 1 : 0)) {
#pragma unroll
        for (int i = 2; i < 4; i++) st_relaxed4(d + (14 + i) * 128, tagged(p[4 * i], tag), p[4 * i + 1], p[4 * i + 2], p[4 * i + 3]);
        st_relaxed2((uint2*)(src + (32 + (j >> 1)) * 128) + (j & 1), tagged(p[16], tag), p[17]);
      }
      n.sqr(f0.x, f0.y); n.sqr(f0.z, f0.w); n.sqr(f1.x, f1.y); n.sqr(f1.z, f1.w);
      if (g == 1) {
        n.sqr(hadd2(p[16], n.nm0), hadd2(p[17], n.nm1));
        n.send(G->sq + st0 + 8 * j, t, stag);
      }
    }
    wg_wait<1>();
    if (g > 0 && !inx(g - 1)) c.release2(BAR_EMPTYB + 8 * (use(g - 1) % 5));
    if (QKV && g < 13) c.progress(33 + g);
    if (QKV && g == WOG - 1) c.release2(BAR_EMPTYX + 8 * qkv_xslot(17));
    if (QKV && g >= WOG && g < WOG + 4) c.release2(BAR_EMPTYX + 32 + 8 * (g - WOG));
  }
  if (QKV) c.mX = 0x34 ^ 0xf3;
  else { c.sB = 8 * (36 % 5); c.mB = (36 / 5) & 1; }
  const float2 r = n.rstd(G->sq + sq, late(c.sb + BAR_FULLX + 64, stag));
  wg_wait<0>();
  if (!QKV) c.release2(BAR_EMPTYB + 8 * (use(17) % 5));
  return r;
}

template <int NB, int OFF>
__device__ __forceinline__ void glu(const float (&a)[128], uint32_t (&h)[144]) {
#pragma unroll
  for (int b = 0; b < 2 * NB; b++) {
    if (HMUL) h[OFF + b] = hmul2(pack_bf16(a[2 * b], a[2 * b + 1]), pack_bf16(a[4 * NB + 2 * b], a[4 * NB + 2 * b + 1]));
    else h[OFF + b] = pack_bf16(a[2 * b] * a[4 * NB + 2 * b], a[2 * b + 1] * a[4 * NB + 2 * b + 1]);
  }
}

__global__ void __cluster_dims__(2, 1, 1) __launch_bounds__(384, 1)
fused_kernel(const __nv_bfloat16* __restrict__ x_in, Group* ws, const char* __restrict__ wqkv,
             const char* __restrict__ wg, const char* __restrict__ wu, uint32_t first, const __grid_constant__ Maps maps,
             const char* __restrict__ wo, const char* __restrict__ wd) {
  extern __shared__ __align__(1024) uint8_t smem_raw[];
  const uint32_t sb = smem_u32(smem_raw);
  const uint32_t bx = blockIdx.x - first;
  if (bx >= NCTA) {
    const int e = blockIdx.x & 3;
    const uint32_t par = ~ld_relaxed(ws->flag + 32) & 1;
    __nanosleep(RDELAY);
    if (threadIdx.x < 16) prefetch_l2(wo + (144 * e + 9 * threadIdx.x) * 1152, 9 * 1152);
#pragma unroll 1
    for (int r = threadIdx.x >> 3; r < 144; r += 48) {
      const uint4* row = (const uint4*)(wo + (144 * e + r) * 1152) + (threadIdx.x & 7);
      float a = 0.f;
      uint4 u;
#pragma unroll
      for (int i = 0; i < 72; i += 8) {
        u = __ldg(row + i);
        a += ((bf_lo(u.x) + bf_hi(u.x)) + (bf_lo(u.y) + bf_hi(u.y))) + ((bf_lo(u.z) + bf_hi(u.z)) + (bf_lo(u.w) + bf_hi(u.w)));
      }
      const int h = r >= 72, k = r - 72 * h;
      ((Scratch*)ws)->woc[threadIdx.x & 7][k < 64 ? 64 + 8 * k + ((2 * e + h) ^ (k & 7)) : 576 * h + 8 * (k & 7) + (e ^ (k & 7))] = u;
      a = quad_sum(a);
      a += __shfl_xor_sync(0xffffffffu, a, 4);
      if ((threadIdx.x & 7) == 0) ((Scratch*)ws)->woc[2 * e + h][640 + k] = make_uint4(pack_bf16(a, a - bf_lo(pack_bf16(a, 0.f))), 0, 0, 0);
    }
    fence_gpu();
    __syncthreads();
    if (threadIdx.x == 0) st_relaxed(((Scratch*)ws)->done + e, par);
    const int cc = threadIdx.x % 54, r0 = threadIdx.x / 54, part = cc / 18, jj = 2 * e + (cc % 18) / 9, c9 = cc % 9;
    if (r0 < 6) {
#pragma unroll 4
      for (int k = r0; k < 576; k += 6) {
        const uint4 u = __ldg((const uint4*)(wqkv + k * 3456 + part * 1152 + 144 * jj) + c9);
        ((Scratch*)ws)->wq[jj][k >> 4][c9 < 8 ? part * 128 + (k & 15) * 8 + (c9 ^ (k & 7)) : 384 + part * 16 + (k & 15)] = u;
      }
    }
    fence_gpu();
    __syncthreads();
    if (threadIdx.x == 0) st_relaxed(((Scratch*)ws)->done + 32 + e, par);
    return;
  }
  if (threadIdx.x == 0) asm volatile("prefetch.tensormap [%0];" ::"l"(&maps.x) : "memory");
  const int warp = __shfl_sync(0xffffffffu, threadIdx.x >> 5, 0);
  const int lane = threadIdx.x & 31;
  const int rank = blockIdx.x & 1;
  if (elect_one()) {
    if (warp >= 8) {
#pragma unroll
      for (int i = 0; i < 9; i++) mbar_init(sb + SM_BAR + 72 * (warp - 8) + 8 * i, warp < 10 ? 1 : 4);
      sts32(sb + SM_PROG + 4 * (warp - 8), 0);
      asm volatile("fence.mbarrier_init.release.cluster;" ::: "memory");
    } else if (warp == 1 || warp == 2) {
      asm volatile("prefetch.tensormap [%0];" ::"l"(&maps.x + warp) : "memory");
    } else if (warp == 3) {
      if (PFMODE & 1) prefetch_l2((const char*)x_in + bx * 18432, 18432);
    } else if (warp == 4) {
      if (PFMODE & 2) prefetch_l2(wqkv + bx * (15552 / PFQ), 15552 / PFQ);
    }
  }
  __syncwarp();
  asm volatile("barrier.cluster.arrive.relaxed.aligned;" ::: "memory");
  if (warp == 8) PROFX(53);
  int lb = bx;
  if (GPCMAP) {
    const int cl = bx >> 1, u = cl - 36;
    lb = (cl < 4 ? cl : cl < 36 ? 8 * ((cl - 4) & 7) + ((cl - 4) >> 3) + (((cl - 4) & 7) ? 0 : 4) : 8 * (1 + u % 7) + 4 + u / 7) * 2 + rank;
  }
#define CTA_J(b) (((b) >> 1) & 7)
#define CTA_RB(b) ((((b) >> 4) << 1) | ((b) & 1))
  const int j = CTA_J(lb), rb = CTA_RB(lb);

  PROF(23);
  if (warp >= 8) {
    asm volatile("setmaxnreg.dec.sync.aligned.u32 " STR(REGS_P) ";");
    auto x_chunk = [&](int cc) {
      mbar_expect_tx(sb + xin_bar(cc), 16384);
      tma3d(sb + xin_off(cc, 0), &maps.x, 64 * cc, 0, 64 * rb, sb + xin_bar(cc));
      tma3d(sb + xin_off(cc, 1), &maps.x, 64 * cc, 1, 64 * rb, sb + xin_bar(cc));
    };
    if (warp == 9 && elect_one()) {
      fence_async_smem();
#pragma unroll 1
      for (int i = 0; i < 9; i++) x_chunk(i);
    }
    __syncwarp();
    if (warp == 9) PROFX(54);
    asm volatile("barrier.cluster.wait.aligned;" ::: "memory");
    if (warp == 8) PROFX(56);
    const uint64_t pol = W_POLICY(), pola = A_POLICY();
    uint4 (* const wq)[432] = ((Scratch*)ws)->wq[j];
    const uint32_t par = ~ld_relaxed(ws[2 * rb].flag + 32 + 32 * j) & 1;
    auto qkv_group = [&](bool copy, int k, uint32_t dst, uint32_t bar) {
      if (copy) {
        wbulk(dst + rank * 8192, wq[(k >> 4) + rank], 6912, bar, pol);
      } else {
        wtma3d(dst + rank * 8192, &maps.qm, 72 * j, k + 16 * rank, 0, bar, pola);
        wtma3d(dst + rank * 8192 + 6144, &maps.qc, 72 * j + 64, k + 16 * rank, 0, bar, pola);
      }
    };
    auto chore = [&](int i) {
#pragma unroll 1
      for (int it = 0; it < SPIN_MAX; it++)
        if (__all_sync(0xffffffffu, ld_acquire(((Scratch*)ws)->done + i) == par)) break;
      asm volatile("fence.proxy.async.global;" ::: "memory");
    };
    const int ktab = group_k0(lane, j);
    auto qkv_gate = [&](int g) { if (g >= 8) gate(sb + SM_PROG, 33 + ((g - 8) * QPACE >> 4)); };
    if (warp == 8) {
      uint32_t s = 0, ph = 1;
      auto slot = [&](uint32_t bytes, auto&& issue) {
        const uint32_t bar = sb + BAR_FULLB + 8 * s;
        mbar_wait(sb + BAR_EMPTYB + 8 * s, ph);
        if (elect_one()) {
          mbar_expect_tx(bar, bytes);
          issue(sb + SM_B + s * BSLOT, bar);
        }
        if (++s == 5) { s = 0; ph ^= 1; }
      };
#pragma unroll 1
      for (int layer = 0; layer < NLAYERS; layer++) {
        if (layer) chore(32 + (j >> 1));
#pragma unroll 1
        for (int g = 0; g < 18 - layer; g += layer && g == 4 ? 8 : 1) {
          const int k = layer ? __shfl_sync(0xffffffffu, ktab, g) : 32 * g;
          if (layer) qkv_gate(g);
          else if (g == QD) mbar_wait(sb + xin_bar(XH), 0);
          slot(2 * 6912, [&](uint32_t dst, uint32_t bar) { qkv_group(layer, k, dst, bar); });
        }
        if (!FCH) {
          gate(sb + SM_PROG, 32 * layer + 20);
          gate(sb + SM_PROG + 4, 32 * layer + 20);
        }
#pragma unroll 1
        for (int t = 0; t < 5; t++) {
          const CUtensorMap* m = &maps.g + (t < 3 ? rank : 2 + rank);
          asm volatile("" : "+l"(m));
          const int c2 = t < 3 ? 9 * j + 2 * t : 18 * j + 3 + 3 * t;
          const uint32_t half = t < 3 ? 8192 : 6144;
          auto tile = [&](int g) {
            const int k = __shfl_sync(0xffffffffu, ktab, g);
            slot(2 * half, [&](uint32_t dst, uint32_t bar) { wtma3d(dst + rank * half, m, 0, k, c2, bar, pol); });
          };
          int g = 0;
          if (t == 0) {
#pragma unroll 1
            for (; g < 5; g++) {
              mbar_wait(sb + BAR_FULLB + 8 * (s < FCH ? s + 5 - FCH : s - FCH), s < FCH ? ph : ph ^ 1);
              if (FG >= 0 && g == FN) gate(sb + SM_PROG + 4, 32 * layer + 20);
              tile(g);
            }
          }
#pragma unroll 1
          for (; g < 18; g++) tile(g);
        }
      }
    } else if (warp == 9) {
      uint32_t mE = 0;
      auto acquire = [&](uint32_t s) { mbar_wait(sb + BAR_EMPTYX + 8 * s, (mE >> s) & 1); mE ^= 1u << s; };
      auto landed = [&](uint32_t s) { mbar_wait(sb + BAR_FULLX + 8 * s, (mE >> s) & 1); };
      auto slot = [&](uint32_t s, const CUtensorMap* m, int col, int row, uint64_t pol) {
        acquire(s);
        if (elect_one()) {
          mbar_expect_tx(sb + BAR_FULLX + 8 * s, XSLOT);
          wtma2d(sb + xslot(s) + rank * 9216, m, col, row + 72 * rank, sb + BAR_FULLX + 8 * s, pol);
        }
      };
#pragma unroll 1
      for (int layer = 0; layer < NLAYERS; layer++) {
        if (layer) chore(32 + (j >> 1));
#pragma unroll 1
        for (int g = 5; g < 18 * layer; g += g == 11 ? 6 : 1) {
          const uint32_t s = qkv_xslot(g);
          const int k = __shfl_sync(0xffffffffu, ktab, g);
          if (g < 12) qkv_gate(g);
          acquire(s);
          if (elect_one()) {
            mbar_expect_tx(sb + BAR_FULLX + 8 * s, 2 * 6912);
            qkv_group(true, k, sb + xslot(s), sb + BAR_FULLX + 8 * s);
          }
          if (XCH & 1) landed(s);
        }
#pragma unroll 1
        for (int i = 0; i < 4; i++) { slot(4 + i, &maps.o, 64 * j, 144 * i, pola); if (XCH & 2) landed(4 + i); }
        if (layer == 0) { chore(lane & 3); PROFX(57); }
        acquire(3);
        if (elect_one()) {
          mbar_expect_tx(sb + BAR_FULLX + 24, 10240 + 1280);
          wbulk(sb + SM_WOC + rank * 5120, ((Scratch*)ws)->woc[j] + rank * 320, 5120, sb + BAR_FULLX + 24, pola);
          wbulk(sb + SM_WSUM + rank * 640, ((Scratch*)ws)->woc[j] + 640 + rank * 40, 640, sb + BAR_FULLX + 24, pola);
        }
#pragma unroll 1
        for (int u = 0; u < 36; u++) {
          const uint32_t s = 4 * (u & 1) + ((u >> 1) & 3);
          slot(s, &maps.d, u < 4 ? 512 : 64 * ((j + (u >> 2)) & 7), 576 * j + 144 * (u & 3), pol);
          if ((XCH & 4) && u < 3) landed(s);
        }
      }
    } else {
      const int w = warp - 10, grp = 2 * rb + w;
      if (PFMODE & 4) {
        mbar_wait(sb + xin_bar(XP), 0);
        if (lane == 0) prefetch_l2(wqkv + (2 * bx + w) * 7776, 7776);
      }
      gate(sb + SM_PROG, 3);
      if (w == 0) PROFX(58);
      auto prefetch_gu = [&](int l0, int n) {
#pragma unroll 1
        for (int i = lane; i < 36 * n; i += 32) {
          asm volatile("prefetch.global.L2 [%0];" ::"l"((w ? wu : wg) + (size_t)(36 * rb + i / n) * 9216 + 1152 * j + 128 * (l0 + i % n)));
          __nanosleep(PFSLEEP);
        }
      };
      auto clear = [&](uint4* p, int n) {
#pragma unroll 1
        for (int i = lane; i < n; i += 64) { st_relaxed4(p + i, 0, 0, 0, 0); st_relaxed4(p + i + 32, 0, 0, 0, 0); __nanosleep(CLRSLEEP); }
      };
      auto exchange = [&](uint32_t v, uint32_t bar) {
        if (FENCE1) { if (lane == 0) fence_gpu(); } else fence_gpu();
        __syncwarp();
        if (w == 0 && v != 1) PROFX(64 + 58 - 2 * v);
        if (lane == 0) st_relaxed(ws[grp].flag + j, v);
#pragma unroll 1
        for (int it = 0; it < SPIN_MAX; it++) {
          const uint32_t f = ld_relaxed(ws[grp].flag + (lane & 7));
          if (__all_sync(0xffffffffu, v ? f >= v : f == 0)) break;
        }
        if (lane == 0) mbar_arrive(sb + bar + 8 * w);
      };
      if (MAPPF && w == 0 && lane < 8) asm volatile("prefetch.tensormap [%0];" ::"l"(&maps.o + lane) : "memory");
#pragma unroll 1
      for (int layer = 0; layer < NLAYERS; layer++) {
        gate(sb + SM_PROG, 32 * layer + 3);
        if (PFF & 1) prefetch_gu(0, 2);
        gate(sb + SM_PROG, 32 * layer + 22);
        if (PFF & 2) prefetch_gu(2, 2);
        if (layer == 0) {
          clear(ws[grp].inbox[0] + 2 * j * INBOX, 2 * INBOX);
          exchange(1, BAR_CLR);
          if (w == 0) PROFX(59);
        }
        if (PFF & 2) prefetch_gu(4, 2);
        if (PFF & 4) prefetch_gu(6, 3);
#pragma unroll 1
        for (int i = lane; i < ((PFF & 8) ? 162 : 0); i += 32) {
          asm volatile("prefetch.global.L2 [%0];" ::"l"(wd + (size_t)(576 * j + 36 * rb + 18 * w) * 1152 + 128 * i));
          __nanosleep(PFSLEEP);
        }
        if (w == 0 && layer == 0) PROFX(60);
        mbar_wait(sb + BAR_REDDONE + 8 * w, layer);
        if (w == 0) PROFX(64 + 53 + 4 * layer);
        exchange(2 - 2 * layer, BAR_RREADY);
        if (w == 0) PROFX(64 + 56 + 4 * layer);
      }
      mbar_wait(sb + BAR_DONE + 8 * w, 0);
    }
    __syncwarp();
    cluster_sync();
  } else {
    asm volatile("setmaxnreg.inc.sync.aligned.u32 " STR(REGS_C) ";");
#define THREAD_IDS()                                                                   \
    int tid_ = threadIdx.x, bid_ = lb;                                                  \
    asm volatile("" : "+r"(tid_), "+r"(bid_));                                          \
    const int w = warp >> 2, wp = warp & 3;                                             \
    const int lane = tid_ & 31, t = tid_ & 127, g = lane >> 2, q = lane & 3;           \
    const int j = CTA_J(bid_), rb = CTA_RB(bid_), grp = 2 * rb + w;                    \
    const int st0 = wp * 64 + g;                         \
    Group* const G = ws + grp;                                                         \
    const uint32_t dsb = (sb & 0x3FFFF) >> 4;                                          \
    (void)t; (void)g; (void)q; (void)grp; (void)j; (void)st0; (void)dsb; (void)G
    Cons c;
    c.sb = sb; c.sB = 0; c.mB = 0; c.mX = 0; c.elect = (threadIdx.x & 127) == 0;
    asm volatile("mapa.shared::cluster.u32 %0, %1, %2;" : "=r"(c.rem) : "r"(sb), "r"(rank ^ 1));
    float v[36], a1[96], a2[12];
    float2 sum, rs;
    uint32_t res[18], xtag;
    auto qkv_mma = [&](bool acc, uint32_t bb, const uint4& f0, const uint4& f1) {
      wg_fence();
      wgmma_ra<192>(a1, f0, desc_hi(2048, 1024, 1) + bb, acc);
      wgmma_ra<24>(a2, f0, desc_hi(128, 256, 0) + (bb + 384), acc);
      wgmma_ra<192>(a1, f1, desc_hi(2048, 1024, 1) + (bb + 512), true);
      wgmma_ra<24>(a2, f1, desc_hi(128, 256, 0) + (bb + 896), true);
      wg_commit();
    };
    {
      THREAD_IDS();
      if (OPEN) {
        if (q == 0) { st_relaxed2(G->sum + st0 + 8 * j, 0, 0); st_relaxed2(G->sq + st0 + 8 * j, 0, 0); }
        if (wp == 3) {
#pragma unroll
          for (int i = 0; i < 5; i++) st_relaxed4(G->halo + j * 160 + lane + i * 32, 0, 0, 0, 0);
        }
        if (lane >= OPENL) st_relaxed4(G->obox + (8 * WPROBE + j) * 128 + t, 0, 0, 0, 0);
      }
      xtag = __shfl_sync(0xffffffffu, ~ld_relaxed(G->flag + 32 + 32 * j) & 1, 0);
      if (OPEN && EARLY && lane >= OPENL) st_relaxed4(G->xbox + (2 * j + 1) * 128 + t, xtag ^ 1, 0, 0, 0);
      asm volatile("barrier.cluster.wait.aligned;" ::: "memory");
      PROF(0);
#pragma unroll
      for (int i = 0; i < 96; i++) asm volatile("mov.b32 %0, 0;" : "=f"(a1[i]));
#pragma unroll
      for (int i = 0; i < 12; i++) asm volatile("mov.b32 %0, 0;" : "=f"(a2[i]));
      PROF(1);
      rs = ln_gemm_in(c, G, res, sum, w, st0, j, t, [&](int i) { PROF(2 + i); if (i) PROF(4); }, qkv_mma);
    }
#pragma unroll 1
    for (int layer = 0;; layer++) {
      const uint32_t tag = layer ^ 1;
      const int pb = 1 + layer * 30;
      uint4 own[5];
      {
        THREAD_IDS();
        PROF(pb + 4);
        uint32_t kv[3][18];
        auto cvt = [&](int b, float r) {
#pragma unroll
          for (int cc = 0; cc < 18; cc++) {
            const float* a = (cc == 8 ? a2 + 4 : cc == 17 ? a2 + 8 : cc < 8 ? a1 + 32 + 4 * cc : a1 + 28 + 4 * cc) + 2 * (b - 1);
            const uint32_t u = pack_bf16(a[0] * r, a[1] * r);
            kv[b][cc] = cc < 9 ? u : movm(u);
          }
        };
        cvt(2, rs.y);
        const uint32_t msg = sb + (w ? xslot(3) : xslot(0) + 24576) + wp * 2304 + lane * 16;
        if (wp == 3) {
          uint4* hp = G->halo + j * 160 + lane;
#pragma unroll
          for (int i = 0; i < 4; i++) st_relaxed4(hp + i * 32, tagged(kv[2][4 * i], tag), kv[2][4 * i + 1], kv[2][4 * i + 2], kv[2][4 * i + 3]);
          st_relaxed2((uint2*)(hp + 128), tagged(kv[2][16], tag), kv[2][17]);
        } else {
#pragma unroll
          for (int i = 0; i < 4; i++) sts128(msg + i * 512, kv[2][4 * i], kv[2][4 * i + 1], kv[2][4 * i + 2], kv[2][4 * i + 3]);
          sts64f(msg + 2048 - lane * 8, __uint_as_float(kv[2][16]), __uint_as_float(kv[2][17]));
        }
        cvt(1, rs.x);
        uint32_t Q[4][6];
#pragma unroll
        for (int h = 0; h < 4; h++)
#pragma unroll
          for (int i = 0; i < 6; i++) {
            const float* a = 4 * h + i < 16 ? a1 + 8 * h + 2 * i : a2 + 8 * h + 2 * i - 32;
            const uint32_t u = pack_bf16(a[0], a[1]);
            Q[h][i] = i < 2 ? (q >= h ? u : 0) : i < 4 ? u : (q <= h ? u : 0);
          }
        const bool lo0 = 2 * q > g, lo1 = 2 * q + 1 > g;
        const uint32_t M = (lo0 ? 0xffffu : 0u) | (lo1 ? 0xffff0000u : 0u);
        auto scores = [&](int h, int b, float (&s)[4]) {
          mma16816z(s, Q[h][0], Q[h][1], Q[h][2], Q[h][3], kv[b][2 * h], kv[b][2 * h + 1]);
          mma1688(s, Q[h][4], Q[h][5], kv[b][2 * h + 2]);
        };
        auto softmax = [&](float (&l)[4][2], float r, uint32_t (&P)[4]) {
          const float sl = r * (0.23570226039551584f * 1.4426950408889634f);
          float m[4];
#pragma unroll
          for (int h = 0; h < 4; h++) { m[h] = fmaxf(l[h][0], l[h][1]); m[h] = fmaxf(m[h], __shfl_xor_sync(0xffffffffu, m[h], 1)); }
#pragma unroll
          for (int h = 0; h < 4; h++) m[h] = fmaxf(m[h], __shfl_xor_sync(0xffffffffu, m[h], 2)) * sl;
#pragma unroll
          for (int h = 0; h < 4; h++) {
            l[h][0] = ex2(fmaf(l[h][0], sl, -m[h])); l[h][1] = ex2(fmaf(l[h][1], sl, -m[h]));
            m[h] = l[h][0] + l[h][1]; m[h] += __shfl_xor_sync(0xffffffffu, m[h], 1);
          }
#pragma unroll
          for (int h = 0; h < 4; h++) { m[h] = rcp(m[h] + __shfl_xor_sync(0xffffffffu, m[h], 2)); P[h] = pack_bf16(l[h][0] * m[h], l[h][1] * m[h]); }
        };
        const bool remote = wp == 0 && rb > 0;
        const uint4* hp = (G - 2)->halo + j * 160 + lane;
        auto halo = [&] {
#pragma unroll
          for (int i = 0; i < 4; i++) { const uint4 u = ld_relaxed4(hp + i * 32); kv[0][4 * i] = u.x; kv[0][4 * i + 1] = u.y; kv[0][4 * i + 2] = u.z; kv[0][4 * i + 3] = u.w; }
          const uint2 u = ld_relaxed2((const uint2*)(hp + 128));
          kv[0][16] = u.x; kv[0][17] = u.y;
        };
#pragma unroll
        for (int i = 0; i < 18; i++) kv[0][i] = 0;
        if (remote) halo();
        float l0[4][2], l1[4][2];
#pragma unroll
        for (int h = 0; h < 4; h++) {
          float s1[4], s2[4];
          scores(h, 1, s1); scores(h, 2, s2);
          l0[h][0] = s1[0]; l0[h][1] = s1[1];
          l1[h][0] = lo0 ? s1[2] : s2[2]; l1[h][1] = lo1 ? s1[3] : s2[3];
        }
        uint32_t P0[4], P1[4];
        softmax(l1, rs.y, P1);
        if (remote) {
          while (__any_sync(0xffffffffu, chk(chk2(kv[0][0], kv[0][4], tag) | chk2(kv[0][8], kv[0][12], tag), kv[0][16], tag) & 1)) halo();
        }
        if (FG < 0) c.progress(32 * layer + 20);
        wg_bar(w);
        if (wp > 0) {
          const uint32_t from = msg - 2304;
#pragma unroll
          for (int i = 0; i < 4; i++) { const uint4 u = lds128(from + i * 512); kv[0][4 * i] = u.x; kv[0][4 * i + 1] = u.y; kv[0][4 * i + 2] = u.z; kv[0][4 * i + 3] = u.w; }
          const float2 u = lds64(from + 2048 - lane * 8);
          kv[0][16] = __float_as_uint(u.x); kv[0][17] = __float_as_uint(u.y);
        }
        PROF(pb + 5);
        const bool first = (rb == 0 && wp == 0);
#pragma unroll
        for (int h = 0; h < 4; h++) {
          float s0[4];
          scores(h, 0, s0);
          if (first) s0[0] = s0[1] = -INFINITY;
          l0[h][0] = lo0 ? s0[0] : l0[h][0]; l0[h][1] = lo1 ? s0[1] : l0[h][1];
        }
        softmax(l0, rs.x, P0);
        uint4* ob = G->obox + t;
        uint32_t car0 = 0, car1 = 0;
#pragma unroll
        for (int h = 0; h < 4; h++) {
          float o[3][4];
#pragma unroll
          for (int i = 0; i < 3; i++) {
            mma16816z(o[i], P0[h] & ~M, P1[h] & M, 0u, P1[h] & ~M, kv[1][9 + 2 * h + i], kv[2][9 + 2 * h + i]);
            mma1688(o[i], P0[h] & M, 0u, kv[0][9 + 2 * h + i]);
          }
          const uint32_t o0 = q < h ? car0 : pack_bf16(o[0][0], o[0][1]), o1 = q < h ? car1 : pack_bf16(o[0][2], o[0][3]);
          own[h] = make_uint4(o0 | 1, o1, pack_bf16(o[1][0], o[1][1]), pack_bf16(o[1][2], o[1][3]));
          if (h < OFIRST) st_relaxed4(ob + (8 * h + j) * 128, own[h].x, own[h].y, own[h].z, own[h].w);
          car0 = pack_bf16(o[2][0], o[2][1]); car1 = pack_bf16(o[2][2], o[2][3]);
        }
        car0 = tagged(car0, tag);
        own[4] = make_uint4(car0, car1, 0, 0);
        PROF(pb + 6);
      }
      {
        THREAD_IDS();
        uint4* src = G->obox + t;
        asm volatile("" : "+l"(src));
        uint2 sa, sc;
        uint4 x[32];
        const uint4* from[7];
#pragma unroll
        for (int r = 0; r < 7; r++) { from[r] = src + (r >= j ? 128 : 0); asm volatile("" : "+l"(from[r])); }
        auto load = [&](int i) { x[i] = ld_relaxed4(i < 28 ? from[i % 7] + (8 * (i / 7) + i % 7) * 128 : src + (i + 4) * 128); };
        const uint32_t* probe = &(G->obox + (8 * WPROBE + (lane & 7)) * 128 + (t | 31))->x;
        uint32_t pv = ld_relaxed(probe);
#pragma unroll
        for (int i = 3; i < 8; i++) mbar_wait_c(sb + BAR_FULLX + 8 * i, (c.mX >> i) & 1);
        c.mX ^= 0xf8;
        while (__any_sync(0xffffffffu, ~pv & 1)) pv = ld_relaxed(probe);
        if (layer) PROF(24); else PROF(25);
        if (WOBAR && w == 1) asm volatile("bar.sync 7, 256;" ::: "memory");
#pragma unroll
        for (int i = 0; i < WB1; i++) load(i);
        if (WOBAR && w == 0) asm volatile("bar.arrive 7, 256;" ::: "memory");
#pragma unroll
        for (int h = OFIRST; h < 4; h++) st_relaxed4(src + (8 * h + j) * 128, own[h].x, own[h].y, own[h].z, own[h].w);
        st_relaxed2((uint2*)(src + (32 + (j >> 1)) * 128) + (j & 1), own[4].x, own[4].y);
        if (layer) PROF(26); else PROF(27);
        float a[36];
        auto step = [&](const uint4& f, uint32_t s, int i, bool acc) {
          const uint32_t r = (xslot(4) >> 4) + (i < 4 ? 72 * s + 16 * i : 144 * s + 64) * 8, c = (SM_WOC >> 4) + (i < 4 ? 64 + 128 * i : 0) + s;
          wgmma_ra<72>(a, f, desc_hi(0, i < 4 ? 1024 : 9216, 1) + (dsb + r + ((c - r) << 16)), acc);
        };
        if (OWNBAR) asm volatile("bar.sync 4, 256;" ::: "memory");
        float e[4];
        wg_fence();
        if (EARLY) {
#pragma unroll
          for (int i = 0; i < 5; i++) wgmma_ra<8>(e, own[i], desc_hi(128, 0, 0) + (dsb + (SM_WSUM >> 4) + 16 * i), i > 0);
          wg_commit();
        }
#pragma unroll
        for (int i = 0; i < 4; i++) step(own[i], j, i, i > 0);
        wg_commit();
        if (layer) PROF(28); else PROF(29);
        auto batch = [&](auto e0, auto e1, auto e2, int b) {
          constexpr int E0 = decltype(e0)::v, E1 = decltype(e1)::v, E2 = decltype(e2)::v;
          const uint32_t one = (LATE0 || E0 > 0) && E1 > E0 ? late(sb + BAR_FULLX + 64, 1) : 1;
          while (E1 > E0) {
            uint32_t bad = 0;
#pragma unroll
            for (int i = E0; i < E1; i++) bad = i < 28 ? chk(bad, x[i].x, one) : chk(chk(bad, x[i].x, tag), x[i].z, tag);
            if (!__any_sync(0xffffffffu, bad & 1)) break;
#pragma unroll
            for (int i = E0; i < E1; i++) load(i);
          }
          if (b == 0) PROF(pb + 7);
          if (b == FG) c.progress(32 * layer + 20);
          if (b > 0 && E2 > E1) wg_wait<WOW>();
#pragma unroll
          for (int i = E1; i < E2; i++) load(i);
          if (EARLY && b == 0) {
            wg_wait<1>();
            if (q == 0) st_relaxed2(G->sum + st0 + 8 * j, (__float_as_uint(e[0] + e[1]) & ~3u) | ((2 * layer + 2) & 3), __float_as_uint(e[2] + e[3]));
          }
          if (EARLY && b == SUMB) { sa = ld_relaxed2(G->sum + st0 + 16 * q); sc = ld_relaxed2(G->sum + st0 + 16 * q + 8); }
          if (E1 > E0) {
            wg_fence();
#pragma unroll
            for (int i = E0; i < E1; i++) {
              step(x[i], i % 7 + (i < 28 && i % 7 >= j), i / 7, true);
            }
            wg_commit();
          }
        };
        batch(IC<0>(), IC<WB1>(), IC<WB2>(), 0);
        batch(IC<WB1>(), IC<WB2>(), IC<WB3>(), 1);
        batch(IC<WB2>(), IC<WB3>(), IC<32>(), 2);
        batch(IC<WB3>(), IC<32>(), IC<32>(), 3);
        if (EARLY) {
          float2 e = make_float2(quad_sum(__uint_as_float(sa.x) + __uint_as_float(sc.x)), quad_sum(__uint_as_float(sa.y) + __uint_as_float(sc.y)));
          if (__any_sync(0xffffffffu, chk2(sa.x, sc.x, (2 * layer + 2) & 3) & 3)) e = gather_sums(G->sum + st0 + 16 * q, (2 * layer + 2) & 3);
          sum.x += e.x; sum.y += e.y;
        }
        wg_wait<0>();
        if (w == 0) asm volatile("bar.arrive 3, 256;" ::: "memory");
        PROF(pb + 8);
#pragma unroll
        for (int i = 0; i < 18; i++) {
          v[2 * i] = bf_lo(res[i]) + a[2 * i];
          v[2 * i + 1] = bf_hi(res[i]) + a[2 * i + 1];
        }
      }
      uint32_t lsb;
      uint32_t h[144];
      {
        THREAD_IDS();
        float a[128];
        const uint32_t xd = sb + xslot(4 * w) + (lane >> 4) * 1024 + (16 * wp + (lane & 15)) * 16;
        const float2 rs = ln_gemm<false>(c, G, v, res, sum, st0, j, t, layer, xtag,
          [&](int i) {
            if (i == 0) {
              lsb = ((res[0] & 1) | (res[4] & 1) << 1 | (res[8] & 1) << 2 | (res[12] & 1) << 3 | (res[16] & 1) << 4) ^ (xtag * 31);
              if (w == 1) asm volatile("bar.sync 3, 256;" ::: "memory");
            }
            PROF(pb + 9 + i);
          },
          [&](int gi, uint32_t bb, const uint4& f0, const uint4& f1) {
            if (gi == 0) PROF(pb + 11);
            if (TLEAD0 && gi == 18 - TLEAD0 && w == 1) asm volatile("bar.sync 5, 256;" ::: "memory");
            wg_fence();
            wgmma_ra<256>(a, f0, desc_hi(4096, 1024, 1) + bb, gi > 0);
            wgmma_ra<256>(a, f1, desc_hi(4096, 1024, 1) + (bb + 128), true);
            wg_commit();
            if (TLEAD0 && gi == 17 && w == 0) asm volatile("bar.arrive 5, 256;" ::: "memory");
            stsm4(xd + gi * 4096, f0.x, f0.y, f0.z, f0.w);
            stsm4(xd + gi * 4096 + 2048, f1.x, f1.y, f1.z, f1.w);
            if (gi == 17) { fence_async_smem(); wg_bar(w); }
          });
        sts64f(sb + SM_KEEP + (tid_ >> 2) * 8, rs.x * rs.x, rs.y * rs.y);
        c.progress(32 * layer + 22);
        PROF2(pb + 12);
        glu<16, 0>(a, h);
        const Desc da0 = desc_hi(1024, 128, 0) + (dsb + (xslot(4 * w) >> 4));
        auto tile = [&](auto wide, auto last) {
          const uint32_t xe = BAR_EMPTYX + 32 * (t & 1) + 4 * (t & 6);
          auto group = [&](int gi) {
            uint32_t prev;
            const uint32_t bb = c.nextB(prev);
            const Desc da = da0 + gi * 256;
            wg_fence();
            if (wide()) {
              wgmma_ss<256>(a, da, desc_hi(4096, 1024, 1) + bb, gi);
              wgmma_ss<256>(a, da + 128, desc_hi(4096, 1024, 1) + (bb + 128), 1);
            } else {
              wgmma_ss<192>(*(float(*)[96])a, da, desc_hi(2048, 512, 2) + bb, gi);
              wgmma_ss<192>(*(float(*)[96])a, da + 128, desc_hi(2048, 512, 2) + (bb + 64), 1);
            }
            wg_commit();
            if (gi == 17 && w == 0) asm volatile("bar.arrive 5, 256;" ::: "memory");
            wg_wait<1>();
            if (gi > 0 && !(last() && gi > 13)) c.release2(BAR_EMPTYB + prev);
            if (last() && gi >= XREL && !((gi ^ XREL) & 1)) c.release2(BAR_EMPTYX + 16 * ((gi - XREL) & 2) + 2 * ((gi - XREL) & 12));
          };
          int gi = 0, end = w ? 18 - (wide() ? TLEAD2 : TLEAD) : 18;
#pragma unroll 1
          while (true) {
#pragma unroll 1
            for (; gi < end; gi++) group(gi);
            if (end == 18) break;
            asm volatile("bar.sync 5, 256;" ::: "memory");
            end = 18;
          }
          wg_wait<0>();
          if (!last()) c.releaseLastB();
          if (last() && t >= (19 - XREL) / 2 && t < 8) { mbar_arrive(sb + xe); mbar_arrive_remote(c.rem + xe); }
        };
        auto yes = [] { return true; };
        auto no = [] { return false; };
        tile(yes, no); PROF2(pb + 13); glu<16, 32>(a, h);
        tile(yes, no); PROF2(pb + 14); glu<16, 64>(a, h);
        tile(no, no); PROF2(pb + 15); glu<12, 96>(a, h);
        const uint32_t hole = sb + SM_B + 12288 + tid_ * 16;
#pragma unroll
        for (int i = 0; i < NSPILL; i++) sts128(hole + i * BSLOT, h[96 + 4 * i], h[97 + 4 * i], h[98 + 4 * i], h[99 + 4 * i]);
        if (w == 1) asm volatile("bar.arrive 8, 256;" ::: "memory");
        tile(no, yes); PROF2(pb + 16); glu<12, 120>(a, h);
#pragma unroll
        for (int i = 0; i < NSPILL; i++) { const uint4 u = lds128(hole + i * BSLOT); h[96 + 4 * i] = u.x; h[97 + 4 * i] = u.y; h[98 + 4 * i] = u.z; h[99 + 4 * i] = u.w; }
      }
      {
        THREAD_IDS();
        float d[32];
        uint4* gt = G->obox + t;
        asm volatile("" : "+l"(gt));
        uint4* const ib = gt + 2 * 4608 + layer * 8 * INBOX;
        auto pass = [&](uint32_t s0, bool last, auto&& hook) {
          const Desc db = desc_hi(0, 1024, 1) + (dsb + s0 * (XSLOT >> 4));
          mbar_wait_c(sb + BAR_FULLX + 8 * s0, (c.mX >> s0) & 1);
          if (RHOOK < 0) hook();
          asm volatile("bar.sync %0, 256;" ::"r"(8 + w) : "memory");
#pragma unroll
          for (int i = 0; i < 4; i++) {
            const int si = 4 * (i & 1) + (i >> 1);
            if (i > 0) mbar_wait_c(sb + BAR_FULLX + 8 * (s0 + si), (c.mX >> (s0 + si)) & 1);
            wg_fence();
#pragma unroll
            for (int k = 0; k < 9; k++) {
              const uint32_t* hk = h + 36 * i + 4 * k;
              wgmma_ra<64>(d, make_uint4(hk[0], hk[1], hk[2], hk[3]), db + ((xslot(si) >> 4) + k * 128), last || i + k > 0);
              if (9 * i + k == PPK && !(last && w == 1)) asm volatile("bar.arrive %0, 256;" ::"r"(9 - w) : "memory");
            }
            wg_commit();
            if (i > 0) { wg_wait<1>(); c.release2(BAR_EMPTYX + 8 * (s0 + 4 * ((i - 1) & 1) + ((i - 1) >> 1))); }
            if (i == RHOOK) hook();
          }
          c.mX ^= 0x33u << s0;
        };
        PROF2(pb + 17);
#pragma unroll 1
        for (int p = 0; p < 8; p++) {
          const uint32_t s0 = 2 * (p & 1);
          pass(s0, false, [] {});
          wg_wait<0>();
          c.release2(BAR_EMPTYX + 8 * (s0 + 5));
          uint32_t pk[16];
#pragma unroll
          for (int i = 0; i < 16; i++) pk[i] = pack_bf16(d[2 * i], d[2 * i + 1]);
          if (p >= BREL && p < BREL + 5) {
            const uint32_t o = c.sB + 8 * (p - BREL);
            c.release2(BAR_EMPTYB + (o < 40 ? o : o - 40));
          }
          uint4* const dst = ib + ((j + p) & 7) * INBOX;
          if (p == 0) {
            mbar_wait_c(sb + BAR_CLR + 8 * w, 0);
#pragma unroll
            for (int k = 0; k < 8; k++) red2((uint2*)(ib + k * INBOX + 512) - t, pk[2 * k], pk[2 * k + 1]);
          } else if (p < 7) {
#pragma unroll
            for (int k = 0; k < 4; k++) red4(dst + k * 128, pk[4 * k], pk[4 * k + 1], pk[4 * k + 2], pk[4 * k + 3]);
            if (p == 6) { __syncwarp(); if (lane == 0) mbar_arrive(sb + BAR_REDDONE + 8 * w); }
          } else {
#pragma unroll
            for (int k = 0; k < 4; k++) st_relaxed4(gt + ((j + 7) & 7) * 128 + k * 1024, pk[4 * k] & ~1u, pk[4 * k + 1], pk[4 * k + 2], pk[4 * k + 3]);
          }
        }
        PROF2(pb + 18);
        const uint4 *in = ib + j * INBOX, *pin = gt + j * 128;
        const uint2* in9 = (const uint2*)(in + 512) - t;
        asm volatile("" : "+l"(in), "+l"(pin), "+l"(in9));
        const float2 r2 = lds64(sb + SM_KEEP + (tid_ >> 2) * 8);
        uint2 X9;
        {
          uint4 X[4];
          const uint4* box = gt + 4608;
#pragma unroll
          for (int k = 0; k < 4; k++) X[k] = ld_relaxed4(box + 256 * j + ((k & 1) + 8 * (k & 2)) * 128);
          X9 = ld_relaxed2((const uint2*)(box + (32 + (j >> 1)) * 128) + (j & 1));
          const float i0 = rcp(r2.x), i1 = rcp(r2.y);
#pragma unroll
          for (int k = 0; k < 4; k++) {
            float* e = d + 8 * k;
            X[k].x ^= (lsb >> k) & 1;
            e[0] = bf_lo(X[k].x) * i0; e[1] = bf_hi(X[k].x) * i0; e[2] = bf_lo(X[k].y) * i1; e[3] = bf_hi(X[k].y) * i1;
            e[4] = bf_lo(X[k].z) * i0; e[5] = bf_hi(X[k].z) * i0; e[6] = bf_lo(X[k].w) * i1; e[7] = bf_hi(X[k].w) * i1;
          }
        }
        uint4 R[4], P[4];
        uint2 R9;
        PROF2(pb + 19);
        pass(0, true, [&] {
          mbar_wait_c(sb + BAR_RREADY + 8 * w, layer);
#pragma unroll
          for (int k = 0; k < 4; k++) R[k] = ld_relaxed4(in + k * 128);
          R9 = ld_relaxed2(in9);
#pragma unroll
          for (int k = 0; k < 4; k++) P[k] = ld_relaxed4(pin + k * 1024);
        });
        const uint32_t zero = late(sb + BAR_FULLX + 64, 0);
        while (__any_sync(0xffffffffu, (chk2(P[0].x, P[1].x, zero) | chk2(P[2].x, P[3].x, zero)) & 1)) {
#pragma unroll
          for (int k = 0; k < 4; k++) P[k] = ld_relaxed4(pin + k * 1024);
        }
#pragma unroll
        for (int k = 0; k < 4; k++) {
          const uint32_t u[4] = {hadd2(R[k].x, P[k].x), hadd2(R[k].y, P[k].y), hadd2(R[k].z, P[k].z), hadd2(R[k].w, P[k].w)};
#pragma unroll
          for (int i = 0; i < 4; i++) { v[8 * k + 2 * i] = bf_lo(u[i]); v[8 * k + 2 * i + 1] = bf_hi(u[i]); }
        }
        X9.x = chk(zero, X9.x, lsb >> 4);
        v[32] = fmaf(bf_lo(R9.x), r2.x, bf_lo(X9.x)); v[33] = fmaf(bf_hi(R9.x), r2.x, bf_hi(X9.x));
        v[34] = fmaf(bf_lo(R9.y), r2.y, bf_lo(X9.y)); v[35] = fmaf(bf_hi(R9.y), r2.y, bf_hi(X9.y));
        PROF2(pb + 20);
        wg_wait<0>();
        c.release2(BAR_EMPTYX + 40);
        PROF2(pb + 21);
#pragma unroll
        for (int i = 0; i < 32; i++) v[i] = (v[i] + d[i]) * (i & 2 ? r2.y : r2.x);
      }
      if (layer == NLAYERS - 1) break;
      {
        THREAD_IDS();
        PROF(31);
        rs = ln_gemm<true>(c, G, v, res, sum, st0, j, t, 1, xtag ^ 1, [&](int i) { PROF(32 + i); if (i) PROF(34); }, qkv_mma);
      }
    }
    {
      THREAD_IDS();
      const uint32_t stg = sb + SM_B + warp * 4096;
      const uint32_t sd = stg + (lane & 15) * 128;
#pragma unroll
      for (int i = 0; i < 4; i++)
        stsm4(sd + (((2 * i + (lane >> 4)) ^ (lane & 7)) << 4), pack_bf16(v[8 * i], v[8 * i + 1]), pack_bf16(v[8 * i + 2], v[8 * i + 3]),
              pack_bf16(v[8 * i + 4], v[8 * i + 5]), pack_bf16(v[8 * i + 6], v[8 * i + 7]));
      stsm2(stg + 2048 + (lane & 15) * 16, pack_bf16(v[32], v[33]), pack_bf16(v[34], v[35]));
      fence_async_smem();
      __syncwarp();
      if (lane == 0) {
        tma_store3d(&maps.out, stg, 64 * j, w, 64 * rb + 16 * wp);
        tma_store3d(&maps.outc, stg + 2048, 512 + 8 * j, w, 64 * rb + 16 * wp);
        bulk_commit();
        if (wp == 0) st_relaxed(G->flag + 32 + 32 * j, xtag);
        bulk_wait_all();
        mbar_arrive(sb + BAR_DONE + 8 * w);
      }
      PROF(61);
    }
    __syncwarp();
    cluster_sync();
  }
}

typedef CUresult (*EncFn)(CUtensorMap*, CUtensorMapDataType, cuuint32_t, void*, const cuuint64_t*, const cuuint64_t*, const cuuint32_t*,
                          const cuuint32_t*, CUtensorMapInterleave, CUtensorMapSwizzle, CUtensorMapL2promotion, CUtensorMapFloatOOBfill);

void make_map(EncFn enc, CUtensorMap* m, const void* p, int rank, uint64_t d0, uint64_t d1, uint64_t d2, uint64_t s1, uint64_t s2, uint32_t b0,
              uint32_t b1, uint32_t b2, CUtensorMapSwizzle sw) {
  cuuint64_t gd[3] = {d0, d1, d2};
  cuuint64_t gs[2] = {s1, s2};
  cuuint32_t bd[3] = {b0, b1, b2};
  cuuint32_t es[3] = {1, 1, 1};
  enc(m, CU_TENSOR_MAP_DATA_TYPE_BFLOAT16, rank, const_cast<void*>(p), gd, gs, bd, es, CU_TENSOR_MAP_INTERLEAVE_NONE, sw,
      CU_TENSOR_MAP_L2_PROMOTION_L2_128B, CU_TENSOR_MAP_FLOAT_OOB_FILL_NONE);
}

}

extern "C" void kernel_launch(void* const* d_in, const int* in_sizes, int n_in, void* d_out, int out_size) {
  const __nv_bfloat16* x = (const __nv_bfloat16*)d_in[0];
  const char *wqkv = (const char*)d_in[1], *wo = (const char*)d_in[2], *wg = (const char*)d_in[4], *wu = (const char*)d_in[5], *wd = (const char*)d_in[6];
  static EncFn enc = nullptr;
  static uint32_t first = 0;
  static Group* ws = nullptr;
  if (!enc) {
    cudaDriverEntryPointQueryResult qr;
    cudaGetDriverEntryPoint("cuTensorMapEncodeTiled", (void**)&enc, cudaEnableDefault, &qr);
    cudaGetSymbolAddress((void**)&ws, g_ws);
    cudaFuncSetAttribute(fused_kernel, cudaFuncAttributeMaxDynamicSharedMemorySize, SMEM_BYTES);
    cudaLaunchConfig_t cfg = {};
    cfg.gridDim = NCTA + 4; cfg.blockDim = 384; cfg.dynamicSmemBytes = SMEM_BYTES;
    int clusters = 0;
    if (XFIRST || cudaOccupancyMaxActiveClusters(&clusters, fused_kernel, &cfg) != cudaSuccess || 2 * clusters < NCTA + 4) first = 4;
    cudaGetLastError();
  }
  const CUtensorMapSwizzle S0 = CU_TENSOR_MAP_SWIZZLE_NONE, S64 = CU_TENSOR_MAP_SWIZZLE_64B, S128 = CU_TENSOR_MAP_SWIZZLE_128B;
  Maps m;
  make_map(enc, &m.x, x, 3, 576, 2, 1024, 1152, 2304, 64, 1, 64, S128);
  make_map(enc, &m.qm, wqkv, 3, 576, 576, 3, 3456, 1152, 64, 16, 3, S128);
  make_map(enc, &m.qc, wqkv, 3, 576, 576, 3, 3456, 1152, 8, 16, 3, S0);
  make_map(enc, &m.o, wo, 2, 576, 576, 1, 1152, 0, 64, 72, 1, S128);
  make_map(enc, &m.g, wg, 3, 64, 576, 72, 9216, 128, 64, 32, 2, S128);
  make_map(enc, &m.u, wu, 3, 64, 576, 72, 9216, 128, 64, 32, 2, S128);
  make_map(enc, &m.g3, wg, 3, 32, 576, 144, 9216, 64, 32, 32, 3, S64);
  make_map(enc, &m.u3, wu, 3, 32, 576, 144, 9216, 64, 32, 32, 3, S64);
  make_map(enc, &m.d, wd, 2, 576, 4608, 1, 1152, 0, 64, 72, 1, S128);
  make_map(enc, &m.out, d_out, 3, 576, 2, 1024, 1152, 2304, 64, 1, 16, S128);
  make_map(enc, &m.outc, d_out, 3, 576, 2, 1024, 1152, 2304, 8, 1, 16, S0);
  fused_kernel<<<NCTA + 4, 384, SMEM_BYTES>>>(x, ws, wqkv, wg, wu, first, m, wo, wd);
}
```

```cpp
#include <cuda_runtime.h>
#include <cuda_bf16.h>
#include <cuda.h>
#include <stdint.h>
#include <stddef.h>

namespace {

constexpr int D_ = 576;
constexpr int NCTA = 128;
#define NLAYERS 2
#define W_POLICY policy_evict_first
#define A_POLICY policy_evict_normal
#define OPEN 1
#define PFMODE 5
#define WWIN 4
#define WOREL -1
#define WB1 11
#define WB2 21
#define WB3 32
#define WPROBE 1
#define WPROBE2 0
#define SPEC 2
#define POLLFIRST 0
#define SUMFIRST 1
#define EARLYPOLL 1
#define LEAD 0
#define ATTBAR 0
#define GL 18
#define WOBAR 1
#define QD 0
#define QG 4
#define PFQ 1
#define XDELAY 0
#define WOH 1
#define PFSLEEP 700
#define GPCMAP 1
#define PFF 1
#define REDN 1
#define CLRSLEEP 300
#define OPENL 24
#define FG 1
#define NON8 0
#define HMUL 1
#define FCH 1
#define PPK 34
#define RHOOK -1
#define SCHEDBAR 1
#define QH 5
#define XH 3
#define XP 0
#define GSLEEP 32
#define XCH 1
#define MAPPF 1
#define XREL 8
#define WOG 13
#define BREL 1
#define FENCE1 0
#define OWNX 0
#define OWNBAR 0
#define EARLY 1
#define ESPEC 0
#define TESTP 0
#define WOW 1
#define STATP -1
#define WSG 0
#define REPACK 1
#define QPACE 23
#define RDELAY 1000
#define XFIRST 0
#define TLEAD 2
#define TLEAD2 2
#define TLEAD0 2
#define OFIRST 3
#define OSPEC 0
#define FN 3
#define LATE0 0
#define SUMB 2
#define XPM 3
#define NSPILL 4
#define REGS_C 232
#define REGS_P 40
#define STR2(x) #x
#define STR(x) STR2(x)
constexpr uint32_t SM_X = 0;
constexpr uint32_t XSLOT = 18432;
__host__ __device__ constexpr uint32_t xslot(uint32_t s) { return SM_X + (s ^ 4) * XSLOT; }
constexpr uint32_t SM_WOC = xslot(3) + 8192;
constexpr uint32_t SM_B = 147456;
constexpr uint32_t BSLOT = 16384;
constexpr uint32_t SM_KEEP = 229376;
constexpr uint32_t SM_WSUM = SM_KEEP + 512;
constexpr uint32_t SM_BAR = SM_KEEP + 2048;
constexpr uint32_t BAR_FULLB = SM_BAR;
constexpr uint32_t BAR_RREADY = SM_BAR + 40;
constexpr uint32_t BAR_CLR = SM_BAR + 56;
constexpr uint32_t BAR_FULLX = SM_BAR + 72;
constexpr uint32_t BAR_EMPTYB = SM_BAR + 144;
constexpr uint32_t BAR_EMPTYX = SM_BAR + 184;
constexpr uint32_t BAR_REDDONE = SM_BAR + 248;
constexpr uint32_t BAR_DONE = SM_BAR + 264;
constexpr uint32_t SM_PROG = SM_BAR + 288;
constexpr uint32_t SMEM_BYTES = SM_BAR + 1024;

struct Maps { CUtensorMap x, qm, qc, o, g, u, g3, u3, d, out, outc; };

constexpr int INBOX = 576;
struct Group {
  uint2 sum[4 * 8 * 8];
  uint2 sq[4 * 8 * 8];
  uint32_t pad[512];
  uint32_t flag[512];
  uint4 halo[8 * 160];
  uint4 obox[36 * 128];
  uint4 xbox[36 * 128];
  uint4 inbox[2][8 * INBOX];
};
struct Scratch { Group g[32]; uint4 wq[8][36][432]; uint4 woc[8][720]; uint32_t done[64]; };
__device__ __align__(1024) Scratch g_ws;
#define PROF(i)
#define PROFX(i)

#define PROF2(i) PROF(i)

struct Desc { uint32_t lo, hi; };
__device__ __forceinline__ constexpr Desc desc_hi(uint32_t lbo, uint32_t sbo, uint32_t sw) { return Desc{(lbo >> 4) << 16, (sbo >> 4) | sw << 30}; }
__device__ __forceinline__ constexpr Desc operator+(Desc d, uint32_t a) { return Desc{d.lo + a, d.hi}; }

template<int N> __device__ __forceinline__ void wgmma_ss(float (&d)[N / 2], Desc da, Desc db, int sc);
template<> __device__ __forceinline__ void wgmma_ss<192>(float (&d)[96], Desc da, Desc db, int sc) {
  asm volatile("{\n.reg .pred p;\n.reg .b64 a, b;\nsetp.ne.b32 p, %100, 0;\nmov.b64 a, {%96, %97};\nmov.b64 b, {%98, %99};\n"
    "wgmma.mma_async.sync.aligned.m64n192k16.f32.bf16.bf16 {%0,%1,%2,%3,%4,%5,%6,%7,%8,%9,%10,%11,%12,%13,%14,%15,%16,%17,%18,%19,%20,%21,%22,%23,%24,%25,%26,%27,%28,%29,%30,%31,%32,%33,%34,%35,%36,%37,%38,%39,%40,%41,%42,%43,%44,%45,%46,%47,%48,%49,%50,%51,%52,%53,%54,%55,%56,%57,%58,%59,%60,%61,%62,%63,%64,%65,%66,%67,%68,%69,%70,%71,%72,%73,%74,%75,%76,%77,%78,%79,%80,%81,%82,%83,%84,%85,%86,%87,%88,%89,%90,%91,%92,%93,%94,%95}, a, b, p, 1, 1, 0, 1;\n}\n"
    : "+f"(d[0]),"+f"(d[1]),"+f"(d[2]),"+f"(d[3]),"+f"(d[4]),"+f"(d[5]),"+f"(d[6]),"+f"(d[7]),"+f"(d[8]),"+f"(d[9]),"+f"(d[10]),"+f"(d[11]),"+f"(d[12]),"+f"(d[13]),"+f"(d[14]),"+f"(d[15]),"+f"(d[16]),"+f"(d[17]),"+f"(d[18]),"+f"(d[19]),"+f"(d[20]),"+f"(d[21]),"+f"(d[22]),"+f"(d[23]),"+f"(d[24]),"+f"(d[25]),"+f"(d[26]),"+f"(d[27]),"+f"(d[28]),"+f"(d[29]),"+f"(d[30]),"+f"(d[31]),"+f"(d[32]),"+f"(d[33]),"+f"(d[34]),"+f"(d[35]),"+f"(d[36]),"+f"(d[37]),"+f"(d[38]),"+f"(d[39]),"+f"(d[40]),"+f"(d[41]),"+f"(d[42]),"+f"(d[43]),"+f"(d[44]),"+f"(d[45]),"+f"(d[46]),"+f"(d[47]),"+f"(d[48]),"+f"(d[49]),"+f"(d[50]),"+f"(d[51]),"+f"(d[52]),"+f"(d[53]),"+f"(d[54]),"+f"(d[55]),"+f"(d[56]),"+f"(d[57]),"+f"(d[58]),"+f"(d[59]),"+f"(d[60]),"+f"(d[61]),"+f"(d[62]),"+f"(d[63]),"+f"(d[64]),"+f"(d[65]),"+f"(d[66]),"+f"(d[67]),"+f"(d[68]),"+f"(d[69]),"+f"(d[70]),"+f"(d[71]),"+f"(d[72]),"+f"(d[73]),"+f"(d[74]),"+f"(d[75]),"+f"(d[76]),"+f"(d[77]),"+f"(d[78]),"+f"(d[79]),"+f"(d[80]),"+f"(d[81]),"+f"(d[82]),"+f"(d[83]),"+f"(d[84]),"+f"(d[85]),"+f"(d[86]),"+f"(d[87]),"+f"(d[88]),"+f"(d[89]),"+f"(d[90]),"+f"(d[91]),"+f"(d[92]),"+f"(d[93]),"+f"(d[94]),"+f"(d[95]) : "r"(da.lo), "r"(da.hi), "r"(db.lo), "r"(db.hi), "r"(sc));
}
template<> __device__ __forceinline__ void wgmma_ss<256>(float (&d)[128], Desc da, Desc db, int sc) {
  asm volatile("{\n.reg .pred p;\n.reg .b64 a, b;\nsetp.ne.b32 p, %132, 0;\nmov.b64 a, {%128, %129};\nmov.b64 b, {%130, %131};\n"
    "wgmma.mma_async.sync.aligned.m64n256k16.f32.bf16.bf16 {%0,%1,%2,%3,%4,%5,%6,%7,%8,%9,%10,%11,%12,%13,%14,%15,%16,%17,%18,%19,%20,%21,%22,%23,%24,%25,%26,%27,%28,%29,%30,%31,%32,%33,%34,%35,%36,%37,%38,%39,%40,%41,%42,%43,%44,%45,%46,%47,%48,%49,%50,%51,%52,%53,%54,%55,%56,%57,%58,%59,%60,%61,%62,%63,%64,%65,%66,%67,%68,%69,%70,%71,%72,%73,%74,%75,%76,%77,%78,%79,%80,%81,%82,%83,%84,%85,%86,%87,%88,%89,%90,%91,%92,%93,%94,%95,%96,%97,%98,%99,%100,%101,%102,%103,%104,%105,%106,%107,%108,%109,%110,%111,%112,%113,%114,%115,%116,%117,%118,%119,%120,%121,%122,%123,%124,%125,%126,%127}, a, b, p, 1, 1, 0, 1;\n}\n"
    : "+f"(d[0]),"+f"(d[1]),"+f"(d[2]),"+f"(d[3]),"+f"(d[4]),"+f"(d[5]),"+f"(d[6]),"+f"(d[7]),"+f"(d[8]),"+f"(d[9]),"+f"(d[10]),"+f"(d[11]),"+f"(d[12]),"+f"(d[13]),"+f"(d[14]),"+f"(d[15]),"+f"(d[16]),"+f"(d[17]),"+f"(d[18]),"+f"(d[19]),"+f"(d[20]),"+f"(d[21]),"+f"(d[22]),"+f"(d[23]),"+f"(d[24]),"+f"(d[25]),"+f"(d[26]),"+f"(d[27]),"+f"(d[28]),"+f"(d[29]),"+f"(d[30]),"+f"(d[31]),"+f"(d[32]),"+f"(d[33]),"+f"(d[34]),"+f"(d[35]),"+f"(d[36]),"+f"(d[37]),"+f"(d[38]),"+f"(d[39]),"+f"(d[40]),"+f"(d[41]),"+f"(d[42]),"+f"(d[43]),"+f"(d[44]),"+f"(d[45]),"+f"(d[46]),"+f"(d[47]),"+f"(d[48]),"+f"(d[49]),"+f"(d[50]),"+f"(d[51]),"+f"(d[52]),"+f"(d[53]),"+f"(d[54]),"+f"(d[55]),"+f"(d[56]),"+f"(d[57]),"+f"(d[58]),"+f"(d[59]),"+f"(d[60]),"+f"(d[61]),"+f"(d[62]),"+f"(d[63]),"+f"(d[64]),"+f"(d[65]),"+f"(d[66]),"+f"(d[67]),"+f"(d[68]),"+f"(d[69]),"+f"(d[70]),"+f"(d[71]),"+f"(d[72]),"+f"(d[73]),"+f"(d[74]),"+f"(d[75]),"+f"(d[76]),"+f"(d[77]),"+f"(d[78]),"+f"(d[79]),"+f"(d[80]),"+f"(d[81]),"+f"(d[82]),"+f"(d[83]),"+f"(d[84]),"+f"(d[85]),"+f"(d[86]),"+f"(d[87]),"+f"(d[88]),"+f"(d[89]),"+f"(d[90]),"+f"(d[91]),"+f"(d[92]),"+f"(d[93]),"+f"(d[94]),"+f"(d[95]),"+f"(d[96]),"+f"(d[97]),"+f"(d[98]),"+f"(d[99]),"+f"(d[100]),"+f"(d[101]),"+f"(d[102]),"+f"(d[103]),"+f"(d[104]),"+f"(d[105]),"+f"(d[106]),"+f"(d[107]),"+f"(d[108]),"+f"(d[109]),"+f"(d[110]),"+f"(d[111]),"+f"(d[112]),"+f"(d[113]),"+f"(d[114]),"+f"(d[115]),"+f"(d[116]),"+f"(d[117]),"+f"(d[118]),"+f"(d[119]),"+f"(d[120]),"+f"(d[121]),"+f"(d[122]),"+f"(d[123]),"+f"(d[124]),"+f"(d[125]),"+f"(d[126]),"+f"(d[127]) : "r"(da.lo), "r"(da.hi), "r"(db.lo), "r"(db.hi), "r"(sc));
}
template<int N, int ACC> __device__ __forceinline__ void wgmma_rs(float (&d)[N / 2], const uint4& a, Desc db);
template<> __device__ __forceinline__ void wgmma_rs<8, 1>(float (&d)[4], const uint4& a, Desc db) {
  asm volatile("{\n.reg .pred p;\n.reg .b64 b;\nsetp.ne.b32 p, 1, 0;\nmov.b64 b, {%8, %9};\n"
    "wgmma.mma_async.sync.aligned.m64n8k16.f32.bf16.bf16 {%0,%1,%2,%3}, {%4,%5,%6,%7}, b, p, 1, 1, 1;\n}\n"
    : "+f"(d[0]),"+f"(d[1]),"+f"(d[2]),"+f"(d[3]) : "r"(a.x), "r"(a.y), "r"(a.z), "r"(a.w), "r"(db.lo), "r"(db.hi));
}
template<> __device__ __forceinline__ void wgmma_rs<8, 0>(float (&d)[4], const uint4& a, Desc db) {
  asm volatile("{\n.reg .pred p;\n.reg .b64 b;\nsetp.ne.b32 p, 0, 0;\nmov.b64 b, {%8, %9};\n"
    "wgmma.mma_async.sync.aligned.m64n8k16.f32.bf16.bf16 {%0,%1,%2,%3}, {%4,%5,%6,%7}, b, p, 1, 1, 1;\n}\n"
    : "=f"(d[0]),"=f"(d[1]),"=f"(d[2]),"=f"(d[3]) : "r"(a.x), "r"(a.y), "r"(a.z), "r"(a.w), "r"(db.lo), "r"(db.hi));
}
template<> __device__ __forceinline__ void wgmma_rs<24, 1>(float (&d)[12], const uint4& a, Desc db) {
  asm volatile("{\n.reg .pred p;\n.reg .b64 b;\nsetp.ne.b32 p, 1, 0;\nmov.b64 b, {%16, %17};\n"
    "wgmma.mma_async.sync.aligned.m64n24k16.f32.bf16.bf16 {%0,%1,%2,%3,%4,%5,%6,%7,%8,%9,%10,%11}, {%12,%13,%14,%15}, b, p, 1, 1, 1;\n}\n"
    : "+f"(d[0]),"+f"(d[1]),"+f"(d[2]),"+f"(d[3]),"+f"(d[4]),"+f"(d[5]),"+f"(d[6]),"+f"(d[7]),"+f"(d[8]),"+f"(d[9]),"+f"(d[10]),"+f"(d[11]) : "r"(a.x), "r"(a.y), "r"(a.z), "r"(a.w), "r"(db.lo), "r"(db.hi));
}
template<> __device__ __forceinline__ void wgmma_rs<24, 0>(float (&d)[12], const uint4& a, Desc db) {
  asm volatile("{\n.reg .pred p;\n.reg .b64 b;\nsetp.ne.b32 p, 0, 0;\nmov.b64 b, {%16, %17};\n"
    "wgmma.mma_async.sync.aligned.m64n24k16.f32.bf16.bf16 {%0,%1,%2,%3,%4,%5,%6,%7,%8,%9,%10,%11}, {%12,%13,%14,%15}, b, p, 1, 1, 1;\n}\n"
    : "=f"(d[0]),"=f"(d[1]),"=f"(d[2]),"=f"(d[3]),"=f"(d[4]),"=f"(d[5]),"=f"(d[6]),"=f"(d[7]),"=f"(d[8]),"=f"(d[9]),"=f"(d[10]),"=f"(d[11]) : "r"(a.x), "r"(a.y), "r"(a.z), "r"(a.w), "r"(db.lo), "r"(db.hi));
}
template<> __device__ __forceinline__ void wgmma_rs<64, 1>(float (&d)[32], const uint4& a, Desc db) {
  asm volatile("{\n.reg .pred p;\n.reg .b64 b;\nsetp.ne.b32 p, 1, 0;\nmov.b64 b, {%36, %37};\n"
    "wgmma.mma_async.sync.aligned.m64n64k16.f32.bf16.bf16 {%0,%1,%2,%3,%4,%5,%6,%7,%8,%9,%10,%11,%12,%13,%14,%15,%16,%17,%18,%19,%20,%21,%22,%23,%24,%25,%26,%27,%28,%29,%30,%31}, {%32,%33,%34,%35}, b, p, 1, 1, 1;\n}\n"
    : "+f"(d[0]),"+f"(d[1]),"+f"(d[2]),"+f"(d[3]),"+f"(d[4]),"+f"(d[5]),"+f"(d[6]),"+f"(d[7]),"+f"(d[8]),"+f"(d[9]),"+f"(d[10]),"+f"(d[11]),"+f"(d[12]),"+f"(d[13]),"+f"(d[14]),"+f"(d[15]),"+f"(d[16]),"+f"(d[17]),"+f"(d[18]),"+f"(d[19]),"+f"(d[20]),"+f"(d[21]),"+f"(d[22]),"+f"(d[23]),"+f"(d[24]),"+f"(d[25]),"+f"(d[26]),"+f"(d[27]),"+f"(d[28]),"+f"(d[29]),"+f"(d[30]),"+f"(d[31]) : "r"(a.x), "r"(a.y), "r"(a.z), "r"(a.w), "r"(db.lo), "r"(db.hi));
}
template<> __device__ __forceinline__ void wgmma_rs<64, 0>(float (&d)[32], const uint4& a, Desc db) {
  asm volatile("{\n.reg .pred p;\n.reg .b64 b;\nsetp.ne.b32 p, 0, 0;\nmov.b64 b, {%36, %37};\n"
    "wgmma.mma_async.sync.aligned.m64n64k16.f32.bf16.bf16 {%0,%1,%2,%3,%4,%5,%6,%7,%8,%9,%10,%11,%12,%13,%14,%15,%16,%17,%18,%19,%20,%21,%22,%23,%24,%25,%26,%27,%28,%29,%30,%31}, {%32,%33,%34,%35}, b, p, 1, 1, 1;\n}\n"
    : "=f"(d[0]),"=f"(d[1]),"=f"(d[2]),"=f"(d[3]),"=f"(d[4]),"=f"(d[5]),"=f"(d[6]),"=f"(d[7]),"=f"(d[8]),"=f"(d[9]),"=f"(d[10]),"=f"(d[11]),"=f"(d[12]),"=f"(d[13]),"=f"(d[14]),"=f"(d[15]),"=f"(d[16]),"=f"(d[17]),"=f"(d[18]),"=f"(d[19]),"=f"(d[20]),"=f"(d[21]),"=f"(d[22]),"=f"(d[23]),"=f"(d[24]),"=f"(d[25]),"=f"(d[26]),"=f"(d[27]),"=f"(d[28]),"=f"(d[29]),"=f"(d[30]),"=f"(d[31]) : "r"(a.x), "r"(a.y), "r"(a.z), "r"(a.w), "r"(db.lo), "r"(db.hi));
}
template<> __device__ __forceinline__ void wgmma_rs<72, 1>(float (&d)[36], const uint4& a, Desc db) {
  asm volatile("{\n.reg .pred p;\n.reg .b64 b;\nsetp.ne.b32 p, 1, 0;\nmov.b64 b, {%40, %41};\n"
    "wgmma.mma_async.sync.aligned.m64n72k16.f32.bf16.bf16 {%0,%1,%2,%3,%4,%5,%6,%7,%8,%9,%10,%11,%12,%13,%14,%15,%16,%17,%18,%19,%20,%21,%22,%23,%24,%25,%26,%27,%28,%29,%30,%31,%32,%33,%34,%35}, {%36,%37,%38,%39}, b, p, 1, 1, 1;\n}\n"
    : "+f"(d[0]),"+f"(d[1]),"+f"(d[2]),"+f"(d[3]),"+f"(d[4]),"+f"(d[5]),"+f"(d[6]),"+f"(d[7]),"+f"(d[8]),"+f"(d[9]),"+f"(d[10]),"+f"(d[11]),"+f"(d[12]),"+f"(d[13]),"+f"(d[14]),"+f"(d[15]),"+f"(d[16]),"+f"(d[17]),"+f"(d[18]),"+f"(d[19]),"+f"(d[20]),"+f"(d[21]),"+f"(d[22]),"+f"(d[23]),"+f"(d[24]),"+f"(d[25]),"+f"(d[26]),"+f"(d[27]),"+f"(d[28]),"+f"(d[29]),"+f"(d[30]),"+f"(d[31]),"+f"(d[32]),"+f"(d[33]),"+f"(d[34]),"+f"(d[35]) : "r"(a.x), "r"(a.y), "r"(a.z), "r"(a.w), "r"(db.lo), "r"(db.hi));
}
template<> __device__ __forceinline__ void wgmma_rs<72, 0>(float (&d)[36], const uint4& a, Desc db) {
  asm volatile("{\n.reg .pred p;\n.reg .b64 b;\nsetp.ne.b32 p, 0, 0;\nmov.b64 b, {%40, %41};\n"
    "wgmma.mma_async.sync.aligned.m64n72k16.f32.bf16.bf16 {%0,%1,%2,%3,%4,%5,%6,%7,%8,%9,%10,%11,%12,%13,%14,%15,%16,%17,%18,%19,%20,%21,%22,%23,%24,%25,%26,%27,%28,%29,%30,%31,%32,%33,%34,%35}, {%36,%37,%38,%39}, b, p, 1, 1, 1;\n}\n"
    : "=f"(d[0]),"=f"(d[1]),"=f"(d[2]),"=f"(d[3]),"=f"(d[4]),"=f"(d[5]),"=f"(d[6]),"=f"(d[7]),"=f"(d[8]),"=f"(d[9]),"=f"(d[10]),"=f"(d[11]),"=f"(d[12]),"=f"(d[13]),"=f"(d[14]),"=f"(d[15]),"=f"(d[16]),"=f"(d[17]),"=f"(d[18]),"=f"(d[19]),"=f"(d[20]),"=f"(d[21]),"=f"(d[22]),"=f"(d[23]),"=f"(d[24]),"=f"(d[25]),"=f"(d[26]),"=f"(d[27]),"=f"(d[28]),"=f"(d[29]),"=f"(d[30]),"=f"(d[31]),"=f"(d[32]),"=f"(d[33]),"=f"(d[34]),"=f"(d[35]) : "r"(a.x), "r"(a.y), "r"(a.z), "r"(a.w), "r"(db.lo), "r"(db.hi));
}
template<> __device__ __forceinline__ void wgmma_rs<192, 1>(float (&d)[96], const uint4& a, Desc db) {
  asm volatile("{\n.reg .pred p;\n.reg .b64 b;\nsetp.ne.b32 p, 1, 0;\nmov.b64 b, {%100, %101};\n"
    "wgmma.mma_async.sync.aligned.m64n192k16.f32.bf16.bf16 {%0,%1,%2,%3,%4,%5,%6,%7,%8,%9,%10,%11,%12,%13,%14,%15,%16,%17,%18,%19,%20,%21,%22,%23,%24,%25,%26,%27,%28,%29,%30,%31,%32,%33,%34,%35,%36,%37,%38,%39,%40,%41,%42,%43,%44,%45,%46,%47,%48,%49,%50,%51,%52,%53,%54,%55,%56,%57,%58,%59,%60,%61,%62,%63,%64,%65,%66,%67,%68,%69,%70,%71,%72,%73,%74,%75,%76,%77,%78,%79,%80,%81,%82,%83,%84,%85,%86,%87,%88,%89,%90,%91,%92,%93,%94,%95}, {%96,%97,%98,%99}, b, p, 1, 1, 1;\n}\n"
    : "+f"(d[0]),"+f"(d[1]),"+f"(d[2]),"+f"(d[3]),"+f"(d[4]),"+f"(d[5]),"+f"(d[6]),"+f"(d[7]),"+f"(d[8]),"+f"(d[9]),"+f"(d[10]),"+f"(d[11]),"+f"(d[12]),"+f"(d[13]),"+f"(d[14]),"+f"(d[15]),"+f"(d[16]),"+f"(d[17]),"+f"(d[18]),"+f"(d[19]),"+f"(d[20]),"+f"(d[21]),"+f"(d[22]),"+f"(d[23]),"+f"(d[24]),"+f"(d[25]),"+f"(d[26]),"+f"(d[27]),"+f"(d[28]),"+f"(d[29]),"+f"(d[30]),"+f"(d[31]),"+f"(d[32]),"+f"(d[33]),"+f"(d[34]),"+f"(d[35]),"+f"(d[36]),"+f"(d[37]),"+f"(d[38]),"+f"(d[39]),"+f"(d[40]),"+f"(d[41]),"+f"(d[42]),"+f"(d[43]),"+f"(d[44]),"+f"(d[45]),"+f"(d[46]),"+f"(d[47]),"+f"(d[48]),"+f"(d[49]),"+f"(d[50]),"+f"(d[51]),"+f"(d[52]),"+f"(d[53]),"+f"(d[54]),"+f"(d[55]),"+f"(d[56]),"+f"(d[57]),"+f"(d[58]),"+f"(d[59]),"+f"(d[60]),"+f"(d[61]),"+f"(d[62]),"+f"(d[63]),"+f"(d[64]),"+f"(d[65]),"+f"(d[66]),"+f"(d[67]),"+f"(d[68]),"+f"(d[69]),"+f"(d[70]),"+f"(d[71]),"+f"(d[72]),"+f"(d[73]),"+f"(d[74]),"+f"(d[75]),"+f"(d[76]),"+f"(d[77]),"+f"(d[78]),"+f"(d[79]),"+f"(d[80]),"+f"(d[81]),"+f"(d[82]),"+f"(d[83]),"+f"(d[84]),"+f"(d[85]),"+f"(d[86]),"+f"(d[87]),"+f"(d[88]),"+f"(d[89]),"+f"(d[90]),"+f"(d[91]),"+f"(d[92]),"+f"(d[93]),"+f"(d[94]),"+f"(d[95]) : "r"(a.x), "r"(a.y), "r"(a.z), "r"(a.w), "r"(db.lo), "r"(db.hi));
}
template<> __device__ __forceinline__ void wgmma_rs<192, 0>(float (&d)[96], const uint4& a, Desc db) {
  asm volatile("{\n.reg .pred p;\n.reg .b64 b;\nsetp.ne.b32 p, 0, 0;\nmov.b64 b, {%100, %101};\n"
    "wgmma.mma_async.sync.aligned.m64n192k16.f32.bf16.bf16 {%0,%1,%2,%3,%4,%5,%6,%7,%8,%9,%10,%11,%12,%13,%14,%15,%16,%17,%18,%19,%20,%21,%22,%23,%24,%25,%26,%27,%28,%29,%30,%31,%32,%33,%34,%35,%36,%37,%38,%39,%40,%41,%42,%43,%44,%45,%46,%47,%48,%49,%50,%51,%52,%53,%54,%55,%56,%57,%58,%59,%60,%61,%62,%63,%64,%65,%66,%67,%68,%69,%70,%71,%72,%73,%74,%75,%76,%77,%78,%79,%80,%81,%82,%83,%84,%85,%86,%87,%88,%89,%90,%91,%92,%93,%94,%95}, {%96,%97,%98,%99}, b, p, 1, 1, 1;\n}\n"
    : "=f"(d[0]),"=f"(d[1]),"=f"(d[2]),"=f"(d[3]),"=f"(d[4]),"=f"(d[5]),"=f"(d[6]),"=f"(d[7]),"=f"(d[8]),"=f"(d[9]),"=f"(d[10]),"=f"(d[11]),"=f"(d[12]),"=f"(d[13]),"=f"(d[14]),"=f"(d[15]),"=f"(d[16]),"=f"(d[17]),"=f"(d[18]),"=f"(d[19]),"=f"(d[20]),"=f"(d[21]),"=f"(d[22]),"=f"(d[23]),"=f"(d[24]),"=f"(d[25]),"=f"(d[26]),"=f"(d[27]),"=f"(d[28]),"=f"(d[29]),"=f"(d[30]),"=f"(d[31]),"=f"(d[32]),"=f"(d[33]),"=f"(d[34]),"=f"(d[35]),"=f"(d[36]),"=f"(d[37]),"=f"(d[38]),"=f"(d[39]),"=f"(d[40]),"=f"(d[41]),"=f"(d[42]),"=f"(d[43]),"=f"(d[44]),"=f"(d[45]),"=f"(d[46]),"=f"(d[47]),"=f"(d[48]),"=f"(d[49]),"=f"(d[50]),"=f"(d[51]),"=f"(d[52]),"=f"(d[53]),"=f"(d[54]),"=f"(d[55]),"=f"(d[56]),"=f"(d[57]),"=f"(d[58]),"=f"(d[59]),"=f"(d[60]),"=f"(d[61]),"=f"(d[62]),"=f"(d[63]),"=f"(d[64]),"=f"(d[65]),"=f"(d[66]),"=f"(d[67]),"=f"(d[68]),"=f"(d[69]),"=f"(d[70]),"=f"(d[71]),"=f"(d[72]),"=f"(d[73]),"=f"(d[74]),"=f"(d[75]),"=f"(d[76]),"=f"(d[77]),"=f"(d[78]),"=f"(d[79]),"=f"(d[80]),"=f"(d[81]),"=f"(d[82]),"=f"(d[83]),"=f"(d[84]),"=f"(d[85]),"=f"(d[86]),"=f"(d[87]),"=f"(d[88]),"=f"(d[89]),"=f"(d[90]),"=f"(d[91]),"=f"(d[92]),"=f"(d[93]),"=f"(d[94]),"=f"(d[95]) : "r"(a.x), "r"(a.y), "r"(a.z), "r"(a.w), "r"(db.lo), "r"(db.hi));
}
template<> __device__ __forceinline__ void wgmma_rs<256, 1>(float (&d)[128], const uint4& a, Desc db) {
  asm volatile("{\n.reg .pred p;\n.reg .b64 b;\nsetp.ne.b32 p, 1, 0;\nmov.b64 b, {%132, %133};\n"
    "wgmma.mma_async.sync.aligned.m64n256k16.f32.bf16.bf16 {%0,%1,%2,%3,%4,%5,%6,%7,%8,%9,%10,%11,%12,%13,%14,%15,%16,%17,%18,%19,%20,%21,%22,%23,%24,%25,%26,%27,%28,%29,%30,%31,%32,%33,%34,%35,%36,%37,%38,%39,%40,%41,%42,%43,%44,%45,%46,%47,%48,%49,%50,%51,%52,%53,%54,%55,%56,%57,%58,%59,%60,%61,%62,%63,%64,%65,%66,%67,%68,%69,%70,%71,%72,%73,%74,%75,%76,%77,%78,%79,%80,%81,%82,%83,%84,%85,%86,%87,%88,%89,%90,%91,%92,%93,%94,%95,%96,%97,%98,%99,%100,%101,%102,%103,%104,%105,%106,%107,%108,%109,%110,%111,%112,%113,%114,%115,%116,%117,%118,%119,%120,%121,%122,%123,%124,%125,%126,%127}, {%128,%129,%130,%131}, b, p, 1, 1, 1;\n}\n"
    : "+f"(d[0]),"+f"(d[1]),"+f"(d[2]),"+f"(d[3]),"+f"(d[4]),"+f"(d[5]),"+f"(d[6]),"+f"(d[7]),"+f"(d[8]),"+f"(d[9]),"+f"(d[10]),"+f"(d[11]),"+f"(d[12]),"+f"(d[13]),"+f"(d[14]),"+f"(d[15]),"+f"(d[16]),"+f"(d[17]),"+f"(d[18]),"+f"(d[19]),"+f"(d[20]),"+f"(d[21]),"+f"(d[22]),"+f"(d[23]),"+f"(d[24]),"+f"(d[25]),"+f"(d[26]),"+f"(d[27]),"+f"(d[28]),"+f"(d[29]),"+f"(d[30]),"+f"(d[31]),"+f"(d[32]),"+f"(d[33]),"+f"(d[34]),"+f"(d[35]),"+f"(d[36]),"+f"(d[37]),"+f"(d[38]),"+f"(d[39]),"+f"(d[40]),"+f"(d[41]),"+f"(d[42]),"+f"(d[43]),"+f"(d[44]),"+f"(d[45]),"+f"(d[46]),"+f"(d[47]),"+f"(d[48]),"+f"(d[49]),"+f"(d[50]),"+f"(d[51]),"+f"(d[52]),"+f"(d[53]),"+f"(d[54]),"+f"(d[55]),"+f"(d[56]),"+f"(d[57]),"+f"(d[58]),"+f"(d[59]),"+f"(d[60]),"+f"(d[61]),"+f"(d[62]),"+f"(d[63]),"+f"(d[64]),"+f"(d[65]),"+f"(d[66]),"+f"(d[67]),"+f"(d[68]),"+f"(d[69]),"+f"(d[70]),"+f"(d[71]),"+f"(d[72]),"+f"(d[73]),"+f"(d[74]),"+f"(d[75]),"+f"(d[76]),"+f"(d[77]),"+f"(d[78]),"+f"(d[79]),"+f"(d[80]),"+f"(d[81]),"+f"(d[82]),"+f"(d[83]),"+f"(d[84]),"+f"(d[85]),"+f"(d[86]),"+f"(d[87]),"+f"(d[88]),"+f"(d[89]),"+f"(d[90]),"+f"(d[91]),"+f"(d[92]),"+f"(d[93]),"+f"(d[94]),"+f"(d[95]),"+f"(d[96]),"+f"(d[97]),"+f"(d[98]),"+f"(d[99]),"+f"(d[100]),"+f"(d[101]),"+f"(d[102]),"+f"(d[103]),"+f"(d[104]),"+f"(d[105]),"+f"(d[106]),"+f"(d[107]),"+f"(d[108]),"+f"(d[109]),"+f"(d[110]),"+f"(d[111]),"+f"(d[112]),"+f"(d[113]),"+f"(d[114]),"+f"(d[115]),"+f"(d[116]),"+f"(d[117]),"+f"(d[118]),"+f"(d[119]),"+f"(d[120]),"+f"(d[121]),"+f"(d[122]),"+f"(d[123]),"+f"(d[124]),"+f"(d[125]),"+f"(d[126]),"+f"(d[127]) : "r"(a.x), "r"(a.y), "r"(a.z), "r"(a.w), "r"(db.lo), "r"(db.hi));
}
template<> __device__ __forceinline__ void wgmma_rs<256, 0>(float (&d)[128], const uint4& a, Desc db) {
  asm volatile("{\n.reg .pred p;\n.reg .b64 b;\nsetp.ne.b32 p, 0, 0;\nmov.b64 b, {%132, %133};\n"
    "wgmma.mma_async.sync.aligned.m64n256k16.f32.bf16.bf16 {%0,%1,%2,%3,%4,%5,%6,%7,%8,%9,%10,%11,%12,%13,%14,%15,%16,%17,%18,%19,%20,%21,%22,%23,%24,%25,%26,%27,%28,%29,%30,%31,%32,%33,%34,%35,%36,%37,%38,%39,%40,%41,%42,%43,%44,%45,%46,%47,%48,%49,%50,%51,%52,%53,%54,%55,%56,%57,%58,%59,%60,%61,%62,%63,%64,%65,%66,%67,%68,%69,%70,%71,%72,%73,%74,%75,%76,%77,%78,%79,%80,%81,%82,%83,%84,%85,%86,%87,%88,%89,%90,%91,%92,%93,%94,%95,%96,%97,%98,%99,%100,%101,%102,%103,%104,%105,%106,%107,%108,%109,%110,%111,%112,%113,%114,%115,%116,%117,%118,%119,%120,%121,%122,%123,%124,%125,%126,%127}, {%128,%129,%130,%131}, b, p, 1, 1, 1;\n}\n"
    : "=f"(d[0]),"=f"(d[1]),"=f"(d[2]),"=f"(d[3]),"=f"(d[4]),"=f"(d[5]),"=f"(d[6]),"=f"(d[7]),"=f"(d[8]),"=f"(d[9]),"=f"(d[10]),"=f"(d[11]),"=f"(d[12]),"=f"(d[13]),"=f"(d[14]),"=f"(d[15]),"=f"(d[16]),"=f"(d[17]),"=f"(d[18]),"=f"(d[19]),"=f"(d[20]),"=f"(d[21]),"=f"(d[22]),"=f"(d[23]),"=f"(d[24]),"=f"(d[25]),"=f"(d[26]),"=f"(d[27]),"=f"(d[28]),"=f"(d[29]),"=f"(d[30]),"=f"(d[31]),"=f"(d[32]),"=f"(d[33]),"=f"(d[34]),"=f"(d[35]),"=f"(d[36]),"=f"(d[37]),"=f"(d[38]),"=f"(d[39]),"=f"(d[40]),"=f"(d[41]),"=f"(d[42]),"=f"(d[43]),"=f"(d[44]),"=f"(d[45]),"=f"(d[46]),"=f"(d[47]),"=f"(d[48]),"=f"(d[49]),"=f"(d[50]),"=f"(d[51]),"=f"(d[52]),"=f"(d[53]),"=f"(d[54]),"=f"(d[55]),"=f"(d[56]),"=f"(d[57]),"=f"(d[58]),"=f"(d[59]),"=f"(d[60]),"=f"(d[61]),"=f"(d[62]),"=f"(d[63]),"=f"(d[64]),"=f"(d[65]),"=f"(d[66]),"=f"(d[67]),"=f"(d[68]),"=f"(d[69]),"=f"(d[70]),"=f"(d[71]),"=f"(d[72]),"=f"(d[73]),"=f"(d[74]),"=f"(d[75]),"=f"(d[76]),"=f"(d[77]),"=f"(d[78]),"=f"(d[79]),"=f"(d[80]),"=f"(d[81]),"=f"(d[82]),"=f"(d[83]),"=f"(d[84]),"=f"(d[85]),"=f"(d[86]),"=f"(d[87]),"=f"(d[88]),"=f"(d[89]),"=f"(d[90]),"=f"(d[91]),"=f"(d[92]),"=f"(d[93]),"=f"(d[94]),"=f"(d[95]),"=f"(d[96]),"=f"(d[97]),"=f"(d[98]),"=f"(d[99]),"=f"(d[100]),"=f"(d[101]),"=f"(d[102]),"=f"(d[103]),"=f"(d[104]),"=f"(d[105]),"=f"(d[106]),"=f"(d[107]),"=f"(d[108]),"=f"(d[109]),"=f"(d[110]),"=f"(d[111]),"=f"(d[112]),"=f"(d[113]),"=f"(d[114]),"=f"(d[115]),"=f"(d[116]),"=f"(d[117]),"=f"(d[118]),"=f"(d[119]),"=f"(d[120]),"=f"(d[121]),"=f"(d[122]),"=f"(d[123]),"=f"(d[124]),"=f"(d[125]),"=f"(d[126]),"=f"(d[127]) : "r"(a.x), "r"(a.y), "r"(a.z), "r"(a.w), "r"(db.lo), "r"(db.hi));
}
template<int N> __device__ __forceinline__ void wgmma_ra(float (&d)[N / 2], const uint4& a, Desc db, bool acc) {
  if (acc) wgmma_rs<N, 1>(d, a, db); else wgmma_rs<N, 0>(d, a, db);
}

__device__ __forceinline__ uint32_t smem_u32(const void* p) { return (uint32_t)__cvta_generic_to_shared(p); }
__device__ __forceinline__ void mbar_init(uint32_t bar, uint32_t cnt) { asm volatile("mbarrier.init.shared::cta.b64 [%0], %1;" ::"r"(bar), "r"(cnt)); }
__device__ __forceinline__ void mbar_expect_tx(uint32_t bar, uint32_t bytes) { asm volatile("mbarrier.arrive.expect_tx.shared::cta.b64 _, [%0], %1;" ::"r"(bar), "r"(bytes) : "memory"); }
__device__ __forceinline__ void mbar_arrive(uint32_t bar) { asm volatile("mbarrier.arrive.shared::cta.b64 _, [%0];" ::"r"(bar) : "memory"); }
__device__ __forceinline__ void mbar_arrive_remote(uint32_t rbar) { asm volatile("mbarrier.arrive.shared::cluster.b64 _, [%0];" ::"r"(rbar) : "memory"); }
__device__ __forceinline__ void mbar_wait(uint32_t bar, uint32_t parity) {
  asm volatile(
      "{\n.reg .pred p;\n.reg .u32 c;\nmov.u32 c, 0;\nLAB_WAIT:\nmbarrier.try_wait.parity.shared::cta.b64 p, [%0], %1;\n@p bra DONE;\n"
      "add.u32 c, c, 1;\nsetp.lt.u32 p, c, 1000000;\n@p bra LAB_WAIT;\ntrap;\nDONE:\n}\n" ::"r"(bar), "r"(parity) : "memory");
}
__device__ __forceinline__ void mbar_wait_c(uint32_t bar, uint32_t parity) {
  asm volatile("{\n.reg .pred p;\nLAB_WAIT:\nmbarrier.try_wait.parity.shared::cta.b64 p, [%0], %1;\n@!p bra LAB_WAIT;\n}\n" ::"r"(bar), "r"(parity) : "memory");
}
__device__ __forceinline__ uint32_t late(uint32_t bar, uint32_t v) {
  uint32_t r;
  asm volatile("{\n.reg .pred p;\nmbarrier.test_wait.parity.shared::cta.b64 p, [%1], 0;\nselp.b32 %0, %2, %1, p;\n}\n" : "=r"(r) : "r"(bar), "r"(v) : "memory");
  return r;
}
__device__ __forceinline__ void wtma2d(uint32_t dst, const CUtensorMap* m, int c0, int c1, uint32_t bar, uint64_t pol) {
  asm volatile("cp.async.bulk.tensor.2d.shared::cluster.global.mbarrier::complete_tx::bytes.multicast::cluster.L2::cache_hint [%0], [%1, {%3, %4}], [%2], %5, %6;"
               ::"r"(dst), "l"(m), "r"(bar), "r"(c0), "r"(c1), "h"((uint16_t)3), "l"(pol) : "memory");
}
__device__ __forceinline__ void wtma3d(uint32_t dst, const CUtensorMap* m, int c0, int c1, int c2, uint32_t bar, uint64_t pol) {
  asm volatile("cp.async.bulk.tensor.3d.shared::cluster.global.mbarrier::complete_tx::bytes.multicast::cluster.L2::cache_hint [%0], [%1, {%3, %4, %5}], [%2], %6, %7;"
               ::"r"(dst), "l"(m), "r"(bar), "r"(c0), "r"(c1), "r"(c2), "h"((uint16_t)3), "l"(pol) : "memory");
}
__device__ __forceinline__ void wbulk(uint32_t dst, const void* src, uint32_t bytes, uint32_t bar, uint64_t pol) {
  asm volatile("cp.async.bulk.shared::cluster.global.mbarrier::complete_tx::bytes.multicast::cluster.L2::cache_hint [%0], [%1], %2, [%3], %4, %5;"
               ::"r"(dst), "l"(src), "r"(bytes), "r"(bar), "h"((uint16_t)3), "l"(pol) : "memory");
}
__device__ __forceinline__ void tma3d(uint32_t dst, const CUtensorMap* m, int c0, int c1, int c2, uint32_t bar) {
  asm volatile("cp.async.bulk.tensor.3d.shared::cluster.global.mbarrier::complete_tx::bytes [%0], [%1, {%3, %4, %5}], [%2];"
               ::"r"(dst), "l"(m), "r"(bar), "r"(c0), "r"(c1), "r"(c2) : "memory");
}
__device__ __forceinline__ void tma_store3d(const CUtensorMap* m, uint32_t src, int c0, int c1, int c2) {
  asm volatile("cp.async.bulk.tensor.3d.global.shared::cta.bulk_group [%0, {%2, %3, %4}], [%1];" ::"l"(m), "r"(src), "r"(c0), "r"(c1), "r"(c2) : "memory");
}
__device__ __forceinline__ void prefetch_l2(const void* p, uint32_t bytes) { asm volatile("cp.async.bulk.prefetch.L2.global [%0], %1;" ::"l"(p), "r"(bytes) : "memory"); }
__device__ __forceinline__ uint64_t policy_evict_first() { uint64_t p; asm volatile("createpolicy.fractional.L2::evict_first.b64 %0, 1.0;" : "=l"(p)); return p; }
__device__ __forceinline__ uint64_t policy_evict_normal() { uint64_t p; asm volatile("createpolicy.fractional.L2::evict_normal.b64 %0, 1.0;" : "=l"(p)); return p; }
__device__ __forceinline__ void bulk_commit() { asm volatile("cp.async.bulk.commit_group;" ::: "memory"); }
__device__ __forceinline__ void bulk_wait_read() { asm volatile("cp.async.bulk.wait_group.read 0;" ::: "memory"); }
__device__ __forceinline__ void fence_async_smem() { asm volatile("fence.proxy.async.shared::cta;" ::: "memory"); }
__device__ __forceinline__ bool elect_one() {
  uint32_t p;
  asm volatile("{\n.reg .pred P;\nelect.sync _|P, 0xffffffff;\nselp.u32 %0, 1, 0, P;\n}\n" : "=r"(p));
  return p;
}
__device__ __forceinline__ void wg_fence() { asm volatile("wgmma.fence.sync.aligned;" ::: "memory"); }
__device__ __forceinline__ void wg_commit() { asm volatile("wgmma.commit_group.sync.aligned;" ::: "memory"); }
template <int n> __device__ __forceinline__ void wg_wait() { asm volatile("wgmma.wait_group.sync.aligned %0;" ::"n"(n) : "memory"); }
__device__ __forceinline__ void wg_bar(int w) { asm volatile("bar.sync %0, 128;" ::"r"(w + 1) : "memory"); }
__device__ __forceinline__ void fence_gpu() { asm volatile("fence.acq_rel.gpu;" ::: "memory"); }
__device__ __forceinline__ uint32_t ld_relaxed(const uint32_t* p) { uint32_t v; asm volatile("ld.relaxed.gpu.global.u32 %0, [%1];" : "=r"(v) : "l"(p) : "memory"); return v; }
__device__ __forceinline__ uint32_t ld_acquire(const uint32_t* p) { uint32_t v; asm volatile("ld.acquire.gpu.global.u32 %0, [%1];" : "=r"(v) : "l"(p) : "memory"); return v; }
__device__ __forceinline__ uint4 ld_relaxed4(const uint4* p) {
  uint4 v; asm volatile("ld.relaxed.gpu.global.v4.u32 {%0,%1,%2,%3}, [%4];" : "=r"(v.x), "=r"(v.y), "=r"(v.z), "=r"(v.w) : "l"(p) : "memory"); return v;
}
__device__ __forceinline__ uint2 ld_relaxed2(const uint2* p) {
  uint2 v; asm volatile("ld.relaxed.gpu.global.v2.u32 {%0,%1}, [%2];" : "=r"(v.x), "=r"(v.y) : "l"(p) : "memory"); return v;
}
__device__ __forceinline__ void st_relaxed(uint32_t* p, uint32_t a) { asm volatile("st.relaxed.gpu.global.u32 [%0], %1;" ::"l"(p), "r"(a) : "memory"); }
__device__ __forceinline__ void st_relaxed4(uint4* p, uint32_t a, uint32_t b, uint32_t c, uint32_t d) {
  asm volatile("st.relaxed.gpu.global.v4.u32 [%0], {%1,%2,%3,%4};" ::"l"(p), "r"(a), "r"(b), "r"(c), "r"(d) : "memory");
}
__device__ __forceinline__ void st_relaxed2(uint2* p, uint32_t a, uint32_t b) {
  asm volatile("st.relaxed.gpu.global.v2.u32 [%0], {%1,%2};" ::"l"(p), "r"(a), "r"(b) : "memory");
}
__device__ __forceinline__ void red4(uint4* p, uint32_t a, uint32_t b, uint32_t c, uint32_t d) {
  asm volatile("red.relaxed.gpu.global.add.noftz.v4.bf16x2 [%0], {%1,%2,%3,%4};" ::"l"(p), "r"(a), "r"(b), "r"(c), "r"(d) : "memory");
}
__device__ __forceinline__ void red2(uint2* p, uint32_t a, uint32_t b) {
  asm volatile("red.relaxed.gpu.global.add.noftz.v2.bf16x2 [%0], {%1,%2};" ::"l"(p), "r"(a), "r"(b) : "memory");
}
constexpr int SPIN_MAX = 1 << 21;
__device__ __forceinline__ uint32_t pack_bf16(float lo, float hi) { uint32_t r; asm("cvt.rn.bf16x2.f32 %0, %1, %2;" : "=r"(r) : "f"(hi), "f"(lo)); return r; }
__device__ __forceinline__ float bf_lo(uint32_t v) { return __uint_as_float(v << 16); }
__device__ __forceinline__ float bf_hi(uint32_t v) { return __uint_as_float(v & 0xffff0000u); }
__device__ __forceinline__ float2 lds64(uint32_t a) { float2 v; asm volatile("ld.shared.v2.f32 {%0,%1}, [%2];" : "=f"(v.x), "=f"(v.y) : "r"(a)); return v; }
__device__ __forceinline__ uint32_t lds32(uint32_t a) { uint32_t v; asm volatile("ld.shared.b32 %0, [%1];" : "=r"(v) : "r"(a)); return v; }
__device__ __forceinline__ void sts64f(uint32_t a, float x, float y) { asm volatile("st.shared.v2.f32 [%0], {%1,%2};" ::"r"(a), "f"(x), "f"(y) : "memory"); }
__device__ __forceinline__ void sts32(uint32_t a, uint32_t x) { asm volatile("st.volatile.shared.b32 [%0], %1;" ::"r"(a), "r"(x) : "memory"); }
__device__ __forceinline__ void gate(uint32_t a, int need) {
#pragma unroll 1
  for (int it = 0; it < SPIN_MAX; it++) {
    int v; asm volatile("ld.volatile.shared.b32 %0, [%1];" : "=r"(v) : "r"(a) : "memory");
    if (v >= need) break;
    if (GSLEEP) __nanosleep(GSLEEP);
  }
}
__device__ __forceinline__ void sts128(uint32_t a, uint32_t x, uint32_t y, uint32_t z, uint32_t u) { asm volatile("st.shared.v4.b32 [%0], {%1,%2,%3,%4};" ::"r"(a), "r"(x), "r"(y), "r"(z), "r"(u) : "memory"); }
__device__ __forceinline__ uint4 lds128(uint32_t a) { uint4 v; asm volatile("ld.shared.v4.u32 {%0,%1,%2,%3}, [%4];" : "=r"(v.x), "=r"(v.y), "=r"(v.z), "=r"(v.w) : "r"(a) : "memory"); return v; }
__device__ __forceinline__ uint32_t hmul2(uint32_t a, uint32_t b) { uint32_t r; asm("mul.rn.bf16x2 %0, %1, %2;" : "=r"(r) : "r"(a), "r"(b)); return r; }
__device__ __forceinline__ uint32_t hadd2(uint32_t a, uint32_t b) { uint32_t r; asm("add.rn.bf16x2 %0, %1, %2;" : "=r"(r) : "r"(a), "r"(b)); return r; }
__device__ __forceinline__ void stsm4(uint32_t a, uint32_t r0, uint32_t r1, uint32_t r2, uint32_t r3) {
  asm volatile("stmatrix.sync.aligned.m8n8.x4.shared.b16 [%0], {%1,%2,%3,%4};" ::"r"(a), "r"(r0), "r"(r1), "r"(r2), "r"(r3) : "memory");
}
__device__ __forceinline__ void stsm2(uint32_t a, uint32_t r0, uint32_t r1) {
  asm volatile("stmatrix.sync.aligned.m8n8.x2.shared.b16 [%0], {%1,%2};" ::"r"(a), "r"(r0), "r"(r1) : "memory");
}
__device__ __forceinline__ uint4 ldsm4(uint32_t a) {
  uint4 r; asm volatile("ldmatrix.sync.aligned.m8n8.x4.shared.b16 {%0,%1,%2,%3}, [%4];" : "=r"(r.x), "=r"(r.y), "=r"(r.z), "=r"(r.w) : "r"(a) : "memory"); return r;
}
__device__ __forceinline__ uint32_t movm(uint32_t a) { uint32_t r; asm("movmatrix.sync.aligned.m8n8.trans.b16 %0, %1;" : "=r"(r) : "r"(a)); return r; }
__device__ __forceinline__ void mma16816z(float (&d)[4], uint32_t a0, uint32_t a1, uint32_t a2, uint32_t a3, uint32_t b0, uint32_t b1) {
  asm("mma.sync.aligned.m16n8k16.row.col.f32.bf16.bf16.f32 {%0,%1,%2,%3}, {%4,%5,%6,%7}, {%8,%9}, {%10,%10,%10,%10};"
      : "=f"(d[0]), "=f"(d[1]), "=f"(d[2]), "=f"(d[3]) : "r"(a0), "r"(a1), "r"(a2), "r"(a3), "r"(b0), "r"(b1), "f"(0.f));
}
__device__ __forceinline__ void mma16816(float (&d)[4], const uint4& a, uint32_t b0, uint32_t b1) {
  asm("mma.sync.aligned.m16n8k16.row.col.f32.bf16.bf16.f32 {%0,%1,%2,%3}, {%4,%5,%6,%7}, {%8,%9}, {%0,%1,%2,%3};"
      : "+f"(d[0]), "+f"(d[1]), "+f"(d[2]), "+f"(d[3]) : "r"(a.x), "r"(a.y), "r"(a.z), "r"(a.w), "r"(b0), "r"(b1));
}
__device__ __forceinline__ void mma1688(float (&d)[4], uint32_t a0, uint32_t a1, uint32_t b0) {
  asm("mma.sync.aligned.m16n8k8.row.col.f32.bf16.bf16.f32 {%0,%1,%2,%3}, {%4,%5}, {%6}, {%0,%1,%2,%3};"
      : "+f"(d[0]), "+f"(d[1]), "+f"(d[2]), "+f"(d[3]) : "r"(a0), "r"(a1), "r"(b0));
}
__device__ __forceinline__ float quad_sum(float v) { v += __shfl_xor_sync(0xffffffffu, v, 1); v += __shfl_xor_sync(0xffffffffu, v, 2); return v; }
__device__ __forceinline__ float quad_max(float v) { v = fmaxf(v, __shfl_xor_sync(0xffffffffu, v, 1)); v = fmaxf(v, __shfl_xor_sync(0xffffffffu, v, 2)); return v; }
__device__ __forceinline__ float rcp(float x) { float r; asm("rcp.approx.ftz.f32 %0, %1;" : "=f"(r) : "f"(x)); return r; }
__device__ __forceinline__ float rsq(float x) { float r; asm("rsqrt.approx.ftz.f32 %0, %1;" : "=f"(r) : "f"(x)); return r; }
__device__ __forceinline__ float ex2(float x) { float r; asm("ex2.approx.ftz.f32 %0, %1;" : "=f"(r) : "f"(x)); return r; }
__device__ __forceinline__ uint32_t chk(uint32_t acc, uint32_t v, uint32_t tag) { uint32_t r; asm("lop3.b32 %0, %1, %2, %3, 0xF6;" : "=r"(r) : "r"(acc), "r"(v), "r"(tag)); return r; }
__device__ __forceinline__ uint32_t chk2(uint32_t a, uint32_t b, uint32_t tag) { uint32_t r; asm("lop3.b32 %0, %1, %2, %3, 0x7E;" : "=r"(r) : "r"(a), "r"(b), "r"(tag)); return r; }
__device__ __forceinline__ uint32_t tagged(uint32_t v, uint32_t tag) { return (v & ~1u) | tag; }

__device__ __forceinline__ int group_k0(int g, int j) {
  const int h = g >= 9, r = g - 2 - 7 * h;
  return g < 2 ? 64 * j + 32 * g : g < 16 ? 64 * (r + (r >= j)) + 32 * h : 32 * g;
}
__device__ __forceinline__ uint32_t xin_off(int c, int w) { return SM_X + (2 * c + w) * 8192; }
__device__ __forceinline__ uint32_t xin_bar(int c) { return BAR_FULLX + 8 * (c < 8 ? c ^ 4 : c); }
__device__ __forceinline__ constexpr uint32_t qkv_xslot(int g) { return g < 5 || g > 11 ? 2 : (0x5140762u >> (4 * (g - 5))) & 15; }

template <int N> struct IC { static constexpr int v = N; };

struct Cons {
  uint32_t sb;
  uint32_t rem;
  uint32_t sB, mB;
  uint32_t mX;
  bool elect;
  __device__ __forceinline__ void release2(uint32_t bar) const { if (elect) { mbar_arrive(sb + bar); mbar_arrive_remote(rem + bar); } }
  __device__ __forceinline__ uint32_t nextB(uint32_t& prev) {
    mbar_wait_c(sb + BAR_FULLB + sB, mB);
    const uint32_t a = (((sb & 0x3FFFF) + SM_B) >> 4) + sB * (BSLOT / 128);
    prev = sB == 0 ? 32 : sB - 8;
    sB += 8;
    if (sB == 40) { sB = 0; mB ^= 1; }
    return a;
  }
  __device__ __forceinline__ void progress(uint32_t v) const { if (elect) sts32(sb + SM_PROG + (threadIdx.x >> 5), v); }
  __device__ __forceinline__ void releaseLastB() const { release2(BAR_EMPTYB + (sB == 0 ? 32 : sB - 8)); }
};

__device__ __forceinline__ float2 gather_sums(const uint2* a, uint32_t stag) {
  uint2 sa, sc;
  do { sa = ld_relaxed2(a); sc = ld_relaxed2(a + 8); } while (__any_sync(0xffffffffu, chk2(sa.x, sc.x, stag) & 3));
  return make_float2(quad_sum(__uint_as_float(sa.x) + __uint_as_float(sc.x)), quad_sum(__uint_as_float(sa.y) + __uint_as_float(sc.y)));
}

struct Norm {
  float m0, m1;
  uint32_t nm0, nm1;
  float d0, d1;
  uint2 u0, u1;
  __device__ __forceinline__ Norm(float2 sum) : m0(sum.x * (-1.f / 576)), m1(sum.y * (-1.f / 576)), nm0(pack_bf16(m0, m0)), nm1(pack_bf16(m1, m1)), d0(0.f), d1(0.f) {}
  __device__ __forceinline__ uint4 centre(const uint4& a) const { return make_uint4(hadd2(a.x, nm0), hadd2(a.y, nm1), hadd2(a.z, nm0), hadd2(a.w, nm1)); }
  __device__ __forceinline__ void sqr(uint32_t a, uint32_t b) {
    d0 = fmaf(bf_lo(a), bf_lo(a), fmaf(bf_hi(a), bf_hi(a), d0)); d1 = fmaf(bf_lo(b), bf_lo(b), fmaf(bf_hi(b), bf_hi(b), d1));
  }
  __device__ __forceinline__ void send(uint2* a, int t, uint32_t stag) {
    d0 = quad_sum(d0); d1 = quad_sum(d1);
    if ((t & 3) == 0) st_relaxed2(a, (__float_as_uint(d0) & ~3u) | stag, __float_as_uint(d1));
  }
  __device__ __forceinline__ void fetch(const uint2* a) { u0 = ld_relaxed2(a); u1 = ld_relaxed2(a + 8); }
  __device__ __forceinline__ float2 rstd(const uint2* a, uint32_t stag) {
    while (__any_sync(0xffffffffu, chk2(u0.x, u1.x, stag) & 3)) fetch(a);
    const float e0 = bf_lo(nm0) - m0, e1 = bf_lo(nm1) - m1;
    const float v0 = fmaf(quad_sum(__uint_as_float(u0.x) + __uint_as_float(u1.x)), 1.f / 576, -e0 * e0);
    const float v1 = fmaf(quad_sum(__uint_as_float(u0.y) + __uint_as_float(u1.y)), 1.f / 576, -e1 * e1);
    float2 r = make_float2(rsq(fmaxf(v0, 0.f) + 1e-5f), rsq(fmaxf(v1, 0.f) + 1e-5f));
    asm volatile("" : "+f"(r.x), "+f"(r.y));
    return r;
  }
};

template <class Pre, class Mma>
__device__ __forceinline__ float2 ln_gemm_in(Cons& c, Group* G, uint32_t (&p)[18], float2& sum, int w, int st0, int j, int t, Pre&& pre, Mma&& mma) {
  const uint32_t xa = c.sb + (t >> 5) * 2048 + (t & 15) * 128, sw = (((t >> 4) & 1) ^ (t & 7)) * 16;
  float ra[4] = {0.f, 0.f, 0.f, 0.f}, rb[4] = {0.f, 0.f, 0.f, 0.f};
#pragma unroll 1
  for (int cc = 0; cc < 9; cc++) {
    const uint32_t a = xa + xin_off(cc, w);
    mbar_wait_c(c.sb + xin_bar(cc), 0);
    const uint4 u0 = ldsm4(a + sw), u1 = ldsm4(a + (sw ^ 32)), u2 = ldsm4(a + (sw ^ 64)), u3 = ldsm4(a + (sw ^ 96));
    mma16816(ra, u0, 0x3f803f80u, 0x3f803f80u); mma16816(rb, u1, 0x3f803f80u, 0x3f803f80u);
    mma16816(ra, u2, 0x3f803f80u, 0x3f803f80u); mma16816(rb, u3, 0x3f803f80u, 0x3f803f80u);
  }
  sum = make_float2(ra[0] + rb[0], ra[2] + rb[2]);
  pre(0);
  Norm n(sum);
  n.u0 = n.u1 = make_uint2(0, 0);
  auto stats = [&] {
#pragma unroll
    for (int k = 0; k < 5; k++) {
      const uint4 u = ldsm4(xa + (k < 4 ? xin_off(j, w) + (sw ^ (32 * k)) : xin_off(8, w) + ((j ^ (t & 7)) << 4))), e = n.centre(u);
      p[4 * k] = u.x; p[4 * k + 1] = u.y;
      n.sqr(e.x, e.y);
      if (k < 4) { p[4 * k + 2] = u.z; p[4 * k + 3] = u.w; n.sqr(e.z, e.w); }
    }
    n.send(G->sq + st0 + 8 * j, t, 1);
  };
  if (STATP < 0) stats();
  else {
#pragma unroll
    for (int i = 0; i < 18; i++) p[i] = 0;
  }
  pre(1);
  uint4 y0 = ldsm4(xa + xin_off(0, w) + sw), y1 = ldsm4(xa + xin_off(0, w) + (sw ^ 32));
#pragma unroll 1
  for (int cc = 0; cc < 9; cc++) {
#pragma unroll
    for (int i = 0; i < 2; i++) {
      const uint4 f0 = n.centre(y0), f1 = n.centre(y1);
      const uint32_t a = xa + xin_off(min(cc + i, 8), w);
      y0 = ldsm4(a + (sw ^ (64 - 64 * i))); y1 = ldsm4(a + (sw ^ (96 - 64 * i)));
      uint32_t prev;
      const uint32_t bb = c.nextB(prev);
      mma(true, bb, f0, f1);
      if (i == 1) {
        if (STATP >= 0 && cc == STATP * w) stats();
        if (cc == 1) c.progress(3);
        if (cc == 7) n.fetch(G->sq + st0 + 16 * (t & 3));
        if (cc == 8 && w == 0) asm volatile("bar.arrive 6, 256;" ::: "memory");
      }
      wg_wait<1>();
      if (i + cc > 0) c.release2(BAR_EMPTYB + prev);
      if (2 * cc + i >= WOG && 2 * cc + i < WOG + 4) c.release2(BAR_EMPTYX + 32 + 8 * (2 * cc + i - WOG));
    }
  }
  c.mX = 0xff;
  const float2 r = n.rstd(G->sq + st0 + 16 * (t & 3), 1);
  if (w == 1) asm volatile("bar.sync 6, 256;" ::: "memory");
  wg_wait<0>();
  c.releaseLastB();
  c.release2(BAR_EMPTYX + 24);
  return r;
}

template <bool QKV, class Pre, class Mma>
__device__ __forceinline__ float2 ln_gemm(Cons& c, Group* G, const float (&v)[36], uint32_t (&p)[18], float2& sum, int st0, int j, int t,
                                          int layer, uint32_t tag, Pre&& pre, Mma&& mma) {
  constexpr bool known = !QKV && EARLY;
  const uint32_t stag = (2 * layer + (QKV ? 1 : 2)) & 3;
  uint4 x[6][2];
  uint4* src = G->xbox + t;
  asm volatile("" : "+l"(src));
  auto buf = [&](int g) -> uint4 (&)[2] { return x[g < 16 ? (g - 2) % 6 : g - 13]; };
  auto load = [&](int g0) {
#pragma unroll
    for (int g = g0; g < g0 + (g0 < 14 ? 3 : 2); g++) {
      const uint4* a = g < 16 ? src + ((g - 2) % 7 >= j ? 256 : 0) + (2 * ((g - 2) % 7) + 16 * (g >= 9)) * 128 : src + 2 * g * 128;
      buf(g)[0] = ld_relaxed4(a); buf(g)[1] = ld_relaxed4(a + 128);
    }
  };
  auto invalid = [&](int g, uint32_t tag) {
    uint32_t bad = chk(chk(chk2(buf(g)[0].x, buf(g)[1].x, tag), buf(g + 1)[0].x, tag), buf(g + 1)[1].x, tag);
    if (g < 14) bad = chk(chk(bad, buf(g + 2)[0].x, tag), buf(g + 2)[1].x, tag);
    if (g == 16) bad = chk(chk(chk(chk(bad, buf(g)[0].z, tag), buf(g)[1].z, tag), buf(g + 1)[0].z, tag), buf(g + 1)[1].z, tag);
    return __any_sync(0xffffffffu, bad & 1);
  };
  uint4* const d = src + 2 * j * 128;
  const int sq = st0 + 16 * (t & 3);
  if (!known) {
    float s0 = v[0] + v[1], s1 = v[2] + v[3];
#pragma unroll
    for (int i = 1; i < 9; i++) { s0 += v[4 * i] + v[4 * i + 1]; s1 += v[4 * i + 2] + v[4 * i + 3]; }
    s0 = quad_sum(s0); s1 = quad_sum(s1);
    if ((t & 3) == 0) st_relaxed2(G->sum + st0 + 8 * j, (__float_as_uint(s0) & ~3u) | stag, __float_as_uint(s1));
  }
#pragma unroll
  for (int i = 0; i < 18; i++) p[i] = pack_bf16(v[2 * i], v[2 * i + 1]);
#pragma unroll
  for (int i = 0; i < 2; i++) st_relaxed4(d + i * 128, tagged(p[4 * i], tag), p[4 * i + 1], p[4 * i + 2], p[4 * i + 3]);
  pre(0);
  if (!known) {
    sum = gather_sums(G->sum + sq, stag);
    load(2);
  }
  Norm n(sum);
  pre(1);
  const uint32_t* probe = &(G->xbox + (2 * (t & XPM) + 1) * 128 + (t | 31))->x;
  uint32_t pv;
  auto inx = [](int g) { return QKV && ((g >= 5 && g < 12) || g == 17); };
  auto use = [](int g) { return QKV ? (g < 5 ? 108 : 101) + g : 18 + g; };
#pragma unroll
  for (int g = 0; g < 18; g++) {
    if (g < 16 ? g % 3 == 2 : g == 16) {
      const uint32_t lt = late(c.sb + BAR_FULLX + 64, tag);
      while (invalid(g, lt)) load(g);
      if (g < 16) load(g < 14 ? g + 3 : 16);
    }
    const uint4 f0 = n.centre(g < 2 ? make_uint4(p[8 * g], p[8 * g + 1], p[8 * g + 2], p[8 * g + 3]) : buf(g)[0]);
    const uint4 f1 = n.centre(g < 2 ? make_uint4(p[8 * g + 4], p[8 * g + 5], p[8 * g + 6], p[8 * g + 7]) : buf(g)[1]);
    if (g == 14) n.fetch(G->sq + sq);
    if (inx(g)) mbar_wait_c(c.sb + BAR_FULLX + 8 * qkv_xslot(g), ((0x34 >> qkv_xslot(g)) & 1) ^ (g == 17));
    else mbar_wait_c(c.sb + BAR_FULLB + 8 * (use(g) % 5), (use(g) / 5) & 1);
    mma(g, ((c.sb & 0x3FFFF) >> 4) + ((inx(g) ? xslot(qkv_xslot(g)) : SM_B + (use(g) % 5) * BSLOT) >> 4), f0, f1);
    if (g == 1) { wg_wait<1>(); c.release2(BAR_EMPTYB + 8 * (use(0) % 5)); }
    if (g < 2) {
      if (known) {
        if (g == 0) {
          pv = tag;
          if (!ESPEC || layer == 0) pv = ld_relaxed(probe);
        } else {
          const uint32_t lt = late(c.sb + BAR_FULLX + 64, tag);
          while (__any_sync(0xffffffffu, (pv ^ lt) & 1)) pv = ld_relaxed(probe);
          load(2);
        }
      }
      if (g == (known ? 1 : 0)) {
#pragma unroll
        for (int i = 2; i < 4; i++) st_relaxed4(d + (14 + i) * 128, tagged(p[4 * i], tag), p[4 * i + 1], p[4 * i + 2], p[4 * i + 3]);
        st_relaxed2((uint2*)(src + (32 + (j >> 1)) * 128) + (j & 1), tagged(p[16], tag), p[17]);
      }
      n.sqr(f0.x, f0.y); n.sqr(f0.z, f0.w); n.sqr(f1.x, f1.y); n.sqr(f1.z, f1.w);
      if (g == 1) {
        n.sqr(hadd2(p[16], n.nm0), hadd2(p[17], n.nm1));
        n.send(G->sq + st0 + 8 * j, t, stag);
      }
    }
    if (g == 1 && !QKV) { wg_wait<0>(); c.release2(BAR_EMPTYB + 8 * (use(1) % 5)); }
    else wg_wait<1>();
    if (g > (QKV ? 1 : 2) && !inx(g - 1)) c.release2(BAR_EMPTYB + 8 * (use(g - 1) % 5));
    if (QKV && g < 13) c.progress(33 + g);
    if (QKV && g == WOG - 1) c.release2(BAR_EMPTYX + 8 * qkv_xslot(17));
    if (QKV && g >= WOG && g < WOG + 4) c.release2(BAR_EMPTYX + 32 + 8 * (g - WOG));
  }
  if (QKV) c.mX = 0x34 ^ 0xf3;
  else { c.sB = 8 * (36 % 5); c.mB = (36 / 5) & 1; }
  const float2 r = n.rstd(G->sq + sq, late(c.sb + BAR_FULLX + 64, stag));
  wg_wait<0>();
  if (!QKV) c.release2(BAR_EMPTYB + 8 * (use(17) % 5));
  return r;
}

template <int NB, int OFF>
__device__ __forceinline__ void glu(const float (&a)[128], uint32_t (&h)[144]) {
#pragma unroll
  for (int b = 0; b < 2 * NB; b++) {
    if (HMUL) h[OFF + b] = hmul2(pack_bf16(a[2 * b], a[2 * b + 1]), pack_bf16(a[4 * NB + 2 * b], a[4 * NB + 2 * b + 1]));
    else h[OFF + b] = pack_bf16(a[2 * b] * a[4 * NB + 2 * b], a[2 * b + 1] * a[4 * NB + 2 * b + 1]);
  }
}

__global__ void __cluster_dims__(2, 1, 1) __launch_bounds__(384, 1)
fused_kernel(const __nv_bfloat16* __restrict__ x_in, Group* ws, const char* __restrict__ wqkv,
             const char* __restrict__ wg, const char* __restrict__ wu, uint32_t first, const __grid_constant__ Maps maps,
             const char* __restrict__ wo, const char* __restrict__ wd) {
  extern __shared__ __align__(1024) uint8_t smem_raw[];
  const uint32_t sb = smem_u32(smem_raw);
  const uint32_t bx = blockIdx.x - first;
  if (bx >= NCTA) {
    const int e = blockIdx.x & 3;
    const uint32_t par = ~ld_relaxed(ws->flag + 32) & 1;
    __nanosleep(RDELAY);
    if (threadIdx.x < 16) prefetch_l2(wo + (144 * e + 9 * threadIdx.x) * 1152, 9 * 1152);
#pragma unroll 1
    for (int r = threadIdx.x >> 3; r < 144; r += 48) {
      const uint4* row = (const uint4*)(wo + (144 * e + r) * 1152) + (threadIdx.x & 7);
      float a = 0.f;
      uint4 u;
#pragma unroll
      for (int i = 0; i < 72; i += 8) {
        u = __ldg(row + i);
        a += ((bf_lo(u.x) + bf_hi(u.x)) + (bf_lo(u.y) + bf_hi(u.y))) + ((bf_lo(u.z) + bf_hi(u.z)) + (bf_lo(u.w) + bf_hi(u.w)));
      }
      const int h = r >= 72, k = r - 72 * h;
      ((Scratch*)ws)->woc[threadIdx.x & 7][k < 64 ? 64 + 8 * k + ((2 * e + h) ^ (k & 7)) : 576 * h + 8 * (k & 7) + (e ^ (k & 7))] = u;
      a = quad_sum(a);
      a += __shfl_xor_sync(0xffffffffu, a, 4);
      if ((threadIdx.x & 7) == 0) ((Scratch*)ws)->woc[2 * e + h][640 + k] = make_uint4(pack_bf16(a, a - bf_lo(pack_bf16(a, 0.f))), 0, 0, 0);
    }
    fence_gpu();
    __syncthreads();
    if (threadIdx.x == 0) st_relaxed(((Scratch*)ws)->done + e, par);
    const int cc = threadIdx.x % 54, r0 = threadIdx.x / 54, part = cc / 18, jj = 2 * e + (cc % 18) / 9, c9 = cc % 9;
    if (r0 < 6) {
#pragma unroll 4
      for (int k = r0; k < 576; k += 6) {
        const uint4 u = __ldg((const uint4*)(wqkv + k * 3456 + part * 1152 + 144 * jj) + c9);
        ((Scratch*)ws)->wq[jj][k >> 4][c9 < 8 ? part * 128 + (k & 15) * 8 + (c9 ^ (k & 7)) : 384 + part * 16 + (k & 15)] = u;
      }
    }
    fence_gpu();
    __syncthreads();
    if (threadIdx.x == 0) st_relaxed(((Scratch*)ws)->done + 32 + e, par);
    return;
  }
  if (threadIdx.x == 0) asm volatile("prefetch.tensormap [%0];" ::"l"(&maps.x) : "memory");
  const int warp = __shfl_sync(0xffffffffu, threadIdx.x >> 5, 0);
  const int lane = threadIdx.x & 31;
  const int rank = blockIdx.x & 1;
  if (elect_one()) {
    if (warp >= 8) {
#pragma unroll
      for (int i = 0; i < 9; i++) mbar_init(sb + SM_BAR + 72 * (warp - 8) + 8 * i, warp < 10 ? 1 : 4);
      sts32(sb + SM_PROG + 4 * (warp - 8), 0);
      asm volatile("fence.mbarrier_init.release.cluster;" ::: "memory");
    } else if (warp == 1 || warp == 2) {
      asm volatile("prefetch.tensormap [%0];" ::"l"(&maps.x + warp) : "memory");
    } else if (warp == 3) {
      if (PFMODE & 1) prefetch_l2((const char*)x_in + bx * 18432, 18432);
    } else if (warp == 4) {
      if (PFMODE & 2) prefetch_l2(wqkv + bx * (15552 / PFQ), 15552 / PFQ);
    }
  }
  __syncwarp();
  asm volatile("barrier.cluster.arrive.relaxed.aligned;" ::: "memory");
  if (warp == 8) PROFX(53);
  int lb = bx;
  if (GPCMAP) {
    const int cl = bx >> 1, u = cl - 36;
    lb = (cl < 4 ? cl : cl < 36 ? 8 * ((cl - 4) & 7) + ((cl - 4) >> 3) + (((cl - 4) & 7) ? 0 : 4) : 8 * (1 + u % 7) + 4 + u / 7) * 2 + rank;
  }
#define CTA_J(b) (((b) >> 1) & 7)
#define CTA_RB(b) ((((b) >> 4) << 1) | ((b) & 1))
  const int j = CTA_J(lb), rb = CTA_RB(lb);

  PROF(23);
  if (warp >= 8) {
    asm volatile("setmaxnreg.dec.sync.aligned.u32 " STR(REGS_P) ";");
    auto x_chunk = [&](int cc) {
      mbar_expect_tx(sb + xin_bar(cc), 16384);
      tma3d(sb + xin_off(cc, 0), &maps.x, 64 * cc, 0, 64 * rb, sb + xin_bar(cc));
      tma3d(sb + xin_off(cc, 1), &maps.x, 64 * cc, 1, 64 * rb, sb + xin_bar(cc));
    };
    if (warp == 9 && elect_one()) {
      fence_async_smem();
#pragma unroll 1
      for (int i = 0; i < 9; i++) x_chunk(i);
    }
    __syncwarp();
    if (warp == 9) PROFX(54);
    asm volatile("barrier.cluster.wait.aligned;" ::: "memory");
    if (warp == 8) PROFX(56);
    const uint64_t pol = W_POLICY(), pola = A_POLICY();
    uint4 (* const wq)[432] = ((Scratch*)ws)->wq[j];
    const uint32_t par = ~ld_relaxed(ws[2 * rb].flag + 32 + 32 * j) & 1;
    auto qkv_group = [&](bool copy, int k, uint32_t dst, uint32_t bar) {
      if (copy) {
        wbulk(dst + rank * 8192, wq[(k >> 4) + rank], 6912, bar, pol);
      } else {
        wtma3d(dst + rank * 8192, &maps.qm, 72 * j, k + 16 * rank, 0, bar, pola);
        wtma3d(dst + rank * 8192 + 6144, &maps.qc, 72 * j + 64, k + 16 * rank, 0, bar, pola);
      }
    };
    auto chore = [&](int i) {
#pragma unroll 1
      for (int it = 0; it < SPIN_MAX; it++)
        if (__all_sync(0xffffffffu, ld_acquire(((Scratch*)ws)->done + i) == par)) break;
      asm volatile("fence.proxy.async.global;" ::: "memory");
    };
    const int ktab = group_k0(lane, j);
    auto qkv_gate = [&](int g) { if (g >= 8) gate(sb + SM_PROG, 33 + ((g - 8) * QPACE >> 4)); };
    if (warp == 8) {
      uint32_t s = 0, ph = 1;
      auto slot = [&](uint32_t bytes, auto&& issue) {
        const uint32_t bar = sb + BAR_FULLB + 8 * s;
        mbar_wait(sb + BAR_EMPTYB + 8 * s, ph);
        if (elect_one()) {
          mbar_expect_tx(bar, bytes);
          issue(sb + SM_B + s * BSLOT, bar);
        }
        if (++s == 5) { s = 0; ph ^= 1; }
      };
#pragma unroll 1
      for (int layer = 0; layer < NLAYERS; layer++) {
        if (layer) chore(32 + (j >> 1));
#pragma unroll 1
        for (int g = 0; g < 18 - layer; g += layer && g == 4 ? 8 : 1) {
          const int k = layer ? __shfl_sync(0xffffffffu, ktab, g) : 32 * g;
          if (layer) qkv_gate(g);
          else if (g == QD) mbar_wait(sb + xin_bar(XH), 0);
          slot(2 * 6912, [&](uint32_t dst, uint32_t bar) { qkv_group(layer, k, dst, bar); });
        }
        if (!FCH) {
          gate(sb + SM_PROG, 32 * layer + 20);
          gate(sb + SM_PROG + 4, 32 * layer + 20);
        }
#pragma unroll 1
        for (int t = 0; t < 5; t++) {
          const CUtensorMap* m = &maps.g + (t < 3 ? rank : 2 + rank);
          asm volatile("" : "+l"(m));
          const int c2 = t < 3 ? 9 * j + 2 * t : 18 * j + 3 + 3 * t;
          const uint32_t half = t < 3 ? 8192 : 6144;
          auto tile = [&](int g) {
            const int k = __shfl_sync(0xffffffffu, ktab, g);
            slot(2 * half, [&](uint32_t dst, uint32_t bar) { wtma3d(dst + rank * half, m, 0, k, c2, bar, pol); });
          };
          int g = 0;
          if (t == 0) {
#pragma unroll 1
            for (; g < 5; g++) {
              mbar_wait(sb + BAR_FULLB + 8 * (s < FCH ? s + 5 - FCH : s - FCH), s < FCH ? ph : ph ^ 1);
              if (FG >= 0 && g == FN) gate(sb + SM_PROG + 4, 32 * layer + 20);
              tile(g);
            }
          }
#pragma unroll 1
          for (; g < 18; g++) tile(g);
        }
      }
    } else if (warp == 9) {
      uint32_t mE = 0;
      auto acquire = [&](uint32_t s) { mbar_wait(sb + BAR_EMPTYX + 8 * s, (mE >> s) & 1); mE ^= 1u << s; };
      auto landed = [&](uint32_t s) { mbar_wait(sb + BAR_FULLX + 8 * s, (mE >> s) & 1); };
      auto slot = [&](uint32_t s, const CUtensorMap* m, int col, int row, uint64_t pol) {
        acquire(s);
        if (elect_one()) {
          mbar_expect_tx(sb + BAR_FULLX + 8 * s, XSLOT);
          wtma2d(sb + xslot(s) + rank * 9216, m, col, row + 72 * rank, sb + BAR_FULLX + 8 * s, pol);
        }
      };
#pragma unroll 1
      for (int layer = 0; layer < NLAYERS; layer++) {
        if (layer) chore(32 + (j >> 1));
#pragma unroll 1
        for (int g = 5; g < 18 * layer; g += g == 11 ? 6 : 1) {
          const uint32_t s = qkv_xslot(g);
          const int k = __shfl_sync(0xffffffffu, ktab, g);
          if (g < 12) qkv_gate(g);
          acquire(s);
          if (elect_one()) {
            mbar_expect_tx(sb + BAR_FULLX + 8 * s, 2 * 6912);
            qkv_group(true, k, sb + xslot(s), sb + BAR_FULLX + 8 * s);
          }
          if (XCH & 1) landed(s);
        }
#pragma unroll 1
        for (int i = 0; i < 4; i++) { slot(4 + i, &maps.o, 64 * j, 144 * i, pola); if (XCH & 2) landed(4 + i); }
        if (layer == 0) { chore(lane & 3); PROFX(57); }
        acquire(3);
        if (elect_one()) {
          mbar_expect_tx(sb + BAR_FULLX + 24, 10240 + 1280);
          wbulk(sb + SM_WOC + rank * 5120, ((Scratch*)ws)->woc[j] + rank * 320, 5120, sb + BAR_FULLX + 24, pola);
          wbulk(sb + SM_WSUM + rank * 640, ((Scratch*)ws)->woc[j] + 640 + rank * 40, 640, sb + BAR_FULLX + 24, pola);
        }
#pragma unroll 1
        for (int u = 0; u < 36; u++) {
          const uint32_t s = 4 * (u & 1) + ((u >> 1) & 3);
          slot(s, &maps.d, u < 4 ? 512 : 64 * ((j + (u >> 2)) & 7), 576 * j + 144 * (u & 3), pol);
          if ((XCH & 4) && u < 3) landed(s);
        }
      }
    } else {
      const int w = warp - 10, grp = 2 * rb + w;
      if (PFMODE & 4) {
        mbar_wait(sb + xin_bar(XP), 0);
        if (lane == 0) prefetch_l2(wqkv + (2 * bx + w) * 7776, 7776);
      }
      gate(sb + SM_PROG, 3);
      if (w == 0) PROFX(58);
      auto prefetch_gu = [&](int l0, int n) {
#pragma unroll 1
        for (int i = lane; i < 36 * n; i += 32) {
          asm volatile("prefetch.global.L2 [%0];" ::"l"((w ? wu : wg) + (size_t)(36 * rb + i / n) * 9216 + 1152 * j + 128 * (l0 + i % n)));
          __nanosleep(PFSLEEP);
        }
      };
      auto clear = [&](uint4* p, int n) {
#pragma unroll 1
        for (int i = lane; i < n; i += 64) { st_relaxed4(p + i, 0, 0, 0, 0); st_relaxed4(p + i + 32, 0, 0, 0, 0); __nanosleep(CLRSLEEP); }
      };
      auto exchange = [&](uint32_t v, uint32_t bar) {
        if (FENCE1) { if (lane == 0) fence_gpu(); } else fence_gpu();
        __syncwarp();
        if (w == 0 && v != 1) PROFX(64 + 58 - 2 * v);
        if (lane == 0) st_relaxed(ws[grp].flag + j, v);
#pragma unroll 1
        for (int it = 0; it < SPIN_MAX; it++) {
          const uint32_t f = ld_relaxed(ws[grp].flag + (lane & 7));
          if (__all_sync(0xffffffffu, v ? f >= v : f == 0)) break;
        }
        if (lane == 0) mbar_arrive(sb + bar + 8 * w);
      };
      if (MAPPF && w == 0 && lane < 8) asm volatile("prefetch.tensormap [%0];" ::"l"(&maps.o + lane) : "memory");
#pragma unroll 1
      for (int layer = 0; layer < NLAYERS; layer++) {
        gate(sb + SM_PROG, 32 * layer + 3);
        if (PFF & 1) prefetch_gu(0, 2);
        gate(sb + SM_PROG, 32 * layer + 22);
        if (PFF & 2) prefetch_gu(2, 2);
        if (layer == 0) {
          clear(ws[grp].inbox[0] + 2 * j * INBOX, 2 * INBOX);
          exchange(1, BAR_CLR);
          if (w == 0) PROFX(59);
        }
        if (PFF & 2) prefetch_gu(4, 2);
        if (PFF & 4) prefetch_gu(6, 3);
#pragma unroll 1
        for (int i = lane; i < ((PFF & 8) ? 162 : 0); i += 32) {
          asm volatile("prefetch.global.L2 [%0];" ::"l"(wd + (size_t)(576 * j + 36 * rb + 18 * w) * 1152 + 128 * i));
          __nanosleep(PFSLEEP);
        }
        if (w == 0 && layer == 0) PROFX(60);
        mbar_wait(sb + BAR_REDDONE + 8 * w, layer);
        if (w == 0) PROFX(64 + 53 + 4 * layer);
        exchange(2 - 2 * layer, BAR_RREADY);
        if (w == 0) PROFX(64 + 56 + 4 * layer);
      }
      mbar_wait(sb + BAR_DONE + 8 * w, 0);
    }
  } else {
    asm volatile("setmaxnreg.inc.sync.aligned.u32 " STR(REGS_C) ";");
#define THREAD_IDS()                                                                   \
    int tid_ = threadIdx.x, bid_ = lb;                                                  \
    asm volatile("" : "+r"(tid_), "+r"(bid_));                                          \
    const int w = warp >> 2, wp = warp & 3;                                             \
    const int lane = tid_ & 31, t = tid_ & 127, g = lane >> 2, q = lane & 3;           \
    const int j = CTA_J(bid_), rb = CTA_RB(bid_), grp = 2 * rb + w;                    \
    const int st0 = wp * 64 + g;                         \
    Group* const G = ws + grp;                                                         \
    const uint32_t dsb = (sb & 0x3FFFF) >> 4;                                          \
    (void)t; (void)g; (void)q; (void)grp; (void)j; (void)st0; (void)dsb; (void)G
    Cons c;
    c.sb = sb; c.sB = 0; c.mB = 0; c.mX = 0; c.elect = (threadIdx.x & 127) == 0;
    asm volatile("mapa.shared::cluster.u32 %0, %1, %2;" : "=r"(c.rem) : "r"(sb), "r"(rank ^ 1));
    float v[36], a1[96], a2[12];
    float2 sum, rs;
    uint32_t res[18], xtag;
    auto qkv_mma = [&](bool acc, uint32_t bb, const uint4& f0, const uint4& f1) {
      wg_fence();
      wgmma_ra<192>(a1, f0, desc_hi(2048, 1024, 1) + bb, acc);
      wgmma_ra<24>(a2, f0, desc_hi(128, 256, 0) + (bb + 384), acc);
      wgmma_ra<192>(a1, f1, desc_hi(2048, 1024, 1) + (bb + 512), true);
      wgmma_ra<24>(a2, f1, desc_hi(128, 256, 0) + (bb + 896), true);
      wg_commit();
    };
    {
      THREAD_IDS();
      if (OPEN) {
        if (q == 0) { st_relaxed2(G->sum + st0 + 8 * j, 0, 0); st_relaxed2(G->sq + st0 + 8 * j, 0, 0); }
        if (wp == 3) {
#pragma unroll
          for (int i = 0; i < 5; i++) st_relaxed4(G->halo + j * 160 + lane + i * 32, 0, 0, 0, 0);
        }
        if (lane >= OPENL) st_relaxed4(G->obox + (8 * WPROBE + j) * 128 + t, 0, 0, 0, 0);
      }
      xtag = __shfl_sync(0xffffffffu, ~ld_relaxed(G->flag + 32 + 32 * j) & 1, 0);
      if (OPEN && EARLY && lane >= OPENL) st_relaxed4(G->xbox + (2 * j + 1) * 128 + t, xtag ^ 1, 0, 0, 0);
      asm volatile("barrier.cluster.wait.aligned;" ::: "memory");
      PROF(0);
#pragma unroll
      for (int i = 0; i < 96; i++) asm volatile("mov.b32 %0, 0;" : "=f"(a1[i]));
#pragma unroll
      for (int i = 0; i < 12; i++) asm volatile("mov.b32 %0, 0;" : "=f"(a2[i]));
      PROF(1);
      rs = ln_gemm_in(c, G, res, sum, w, st0, j, t, [&](int i) { PROF(2 + i); if (i) PROF(4); }, qkv_mma);
    }
#pragma unroll 1
    for (int layer = 0;; layer++) {
      const uint32_t tag = layer ^ 1;
      const int pb = 1 + layer * 30;
      uint4 own[5];
      {
        THREAD_IDS();
        PROF(pb + 4);
        uint32_t kv[3][18];
        auto cvt = [&](int b, float r) {
#pragma unroll
          for (int cc = 0; cc < 18; cc++) {
            const float* a = (cc == 8 ? a2 + 4 : cc == 17 ? a2 + 8 : cc < 8 ? a1 + 32 + 4 * cc : a1 + 28 + 4 * cc) + 2 * (b - 1);
            const uint32_t u = pack_bf16(a[0] * r, a[1] * r);
            kv[b][cc] = cc < 9 ? u : movm(u);
          }
        };
        cvt(2, rs.y);
        const uint32_t msg = sb + (w ? xslot(3) : xslot(0) + 24576) + wp * 2304 + lane * 16;
        if (wp == 3) {
          uint4* hp = G->halo + j * 160 + lane;
#pragma unroll
          for (int i = 0; i < 4; i++) st_relaxed4(hp + i * 32, tagged(kv[2][4 * i], tag), kv[2][4 * i + 1], kv[2][4 * i + 2], kv[2][4 * i + 3]);
          st_relaxed2((uint2*)(hp + 128), tagged(kv[2][16], tag), kv[2][17]);
        } else {
#pragma unroll
          for (int i = 0; i < 4; i++) sts128(msg + i * 512, kv[2][4 * i], kv[2][4 * i + 1], kv[2][4 * i + 2], kv[2][4 * i + 3]);
          sts64f(msg + 2048 - lane * 8, __uint_as_float(kv[2][16]), __uint_as_float(kv[2][17]));
        }
        cvt(1, rs.x);
        uint32_t Q[4][6];
#pragma unroll
        for (int h = 0; h < 4; h++)
#pragma unroll
          for (int i = 0; i < 6; i++) {
            const float* a = 4 * h + i < 16 ? a1 + 8 * h + 2 * i : a2 + 8 * h + 2 * i - 32;
            const uint32_t u = pack_bf16(a[0], a[1]);
            Q[h][i] = i < 2 ? (q >= h ? u : 0) : i < 4 ? u : (q <= h ? u : 0);
          }
        const bool lo0 = 2 * q > g, lo1 = 2 * q + 1 > g;
        const uint32_t M = (lo0 ? 0xffffu : 0u) | (lo1 ? 0xffff0000u : 0u);
        auto scores = [&](int h, int b, float (&s)[4]) {
          mma16816z(s, Q[h][0], Q[h][1], Q[h][2], Q[h][3], kv[b][2 * h], kv[b][2 * h + 1]);
          mma1688(s, Q[h][4], Q[h][5], kv[b][2 * h + 2]);
        };
        auto softmax = [&](float (&l)[4][2], float r, uint32_t (&P)[4]) {
          const float sl = r * (0.23570226039551584f * 1.4426950408889634f);
          float m[4];
#pragma unroll
          for (int h = 0; h < 4; h++) { m[h] = fmaxf(l[h][0], l[h][1]); m[h] = fmaxf(m[h], __shfl_xor_sync(0xffffffffu, m[h], 1)); }
#pragma unroll
          for (int h = 0; h < 4; h++) m[h] = fmaxf(m[h], __shfl_xor_sync(0xffffffffu, m[h], 2)) * sl;
#pragma unroll
          for (int h = 0; h < 4; h++) {
            l[h][0] = ex2(fmaf(l[h][0], sl, -m[h])); l[h][1] = ex2(fmaf(l[h][1], sl, -m[h]));
            m[h] = l[h][0] + l[h][1]; m[h] += __shfl_xor_sync(0xffffffffu, m[h], 1);
          }
#pragma unroll
          for (int h = 0; h < 4; h++) { m[h] = rcp(m[h] + __shfl_xor_sync(0xffffffffu, m[h], 2)); P[h] = pack_bf16(l[h][0] * m[h], l[h][1] * m[h]); }
        };
        const bool remote = wp == 0 && rb > 0;
        const uint4* hp = (G - 2)->halo + j * 160 + lane;
        auto halo = [&] {
#pragma unroll
          for (int i = 0; i < 4; i++) { const uint4 u = ld_relaxed4(hp + i * 32); kv[0][4 * i] = u.x; kv[0][4 * i + 1] = u.y; kv[0][4 * i + 2] = u.z; kv[0][4 * i + 3] = u.w; }
          const uint2 u = ld_relaxed2((const uint2*)(hp + 128));
          kv[0][16] = u.x; kv[0][17] = u.y;
        };
#pragma unroll
        for (int i = 0; i < 18; i++) kv[0][i] = 0;
        if (remote) halo();
        float l0[4][2], l1[4][2];
#pragma unroll
        for (int h = 0; h < 4; h++) {
          float s1[4], s2[4];
          scores(h, 1, s1); scores(h, 2, s2);
          l0[h][0] = s1[0]; l0[h][1] = s1[1];
          l1[h][0] = lo0 ? s1[2] : s2[2]; l1[h][1] = lo1 ? s1[3] : s2[3];
        }
        uint32_t P0[4], P1[4];
        softmax(l1, rs.y, P1);
        if (remote) {
          while (__any_sync(0xffffffffu, chk(chk2(kv[0][0], kv[0][4], tag) | chk2(kv[0][8], kv[0][12], tag), kv[0][16], tag) & 1)) halo();
        }
        if (FG < 0) c.progress(32 * layer + 20);
        wg_bar(w);
        if (wp > 0) {
          const uint32_t from = msg - 2304;
#pragma unroll
          for (int i = 0; i < 4; i++) { const uint4 u = lds128(from + i * 512); kv[0][4 * i] = u.x; kv[0][4 * i + 1] = u.y; kv[0][4 * i + 2] = u.z; kv[0][4 * i + 3] = u.w; }
          const float2 u = lds64(from + 2048 - lane * 8);
          kv[0][16] = __float_as_uint(u.x); kv[0][17] = __float_as_uint(u.y);
        }
        PROF(pb + 5);
        const bool first = (rb == 0 && wp == 0);
#pragma unroll
        for (int h = 0; h < 4; h++) {
          float s0[4];
          scores(h, 0, s0);
          if (first) s0[0] = s0[1] = -INFINITY;
          l0[h][0] = lo0 ? s0[0] : l0[h][0]; l0[h][1] = lo1 ? s0[1] : l0[h][1];
        }
        softmax(l0, rs.x, P0);
        uint4* ob = G->obox + t;
        uint32_t car0 = 0, car1 = 0;
#pragma unroll
        for (int h = 0; h < 4; h++) {
          float o[3][4];
#pragma unroll
          for (int i = 0; i < 3; i++) {
            mma16816z(o[i], P0[h] & ~M, P1[h] & M, 0u, P1[h] & ~M, kv[1][9 + 2 * h + i], kv[2][9 + 2 * h + i]);
            mma1688(o[i], P0[h] & M, 0u, kv[0][9 + 2 * h + i]);
          }
          const uint32_t o0 = q < h ? car0 : pack_bf16(o[0][0], o[0][1]), o1 = q < h ? car1 : pack_bf16(o[0][2], o[0][3]);
          own[h] = make_uint4(o0 | 1, o1, pack_bf16(o[1][0], o[1][1]), pack_bf16(o[1][2], o[1][3]));
          if (h < OFIRST) st_relaxed4(ob + (8 * h + j) * 128, own[h].x, own[h].y, own[h].z, own[h].w);
          car0 = pack_bf16(o[2][0], o[2][1]); car1 = pack_bf16(o[2][2], o[2][3]);
        }
        car0 = tagged(car0, tag);
        own[4] = make_uint4(car0, car1, 0, 0);
        PROF(pb + 6);
      }
      uint2 sa, sc;
      {
        THREAD_IDS();
        uint4* src = G->obox + t;
        asm volatile("" : "+l"(src));
        uint4 x[32];
        const uint4* from[7];
#pragma unroll
        for (int r = 0; r < 7; r++) { from[r] = src + (r >= j ? 128 : 0); asm volatile("" : "+l"(from[r])); }
        auto load = [&](int i) { x[i] = ld_relaxed4(i < 28 ? from[i % 7] + (8 * (i / 7) + i % 7) * 128 : src + (i + 4) * 128); };
        const uint32_t* probe = &(G->obox + (8 * WPROBE + (lane & 7)) * 128 + (t | 31))->x;
        uint32_t pv = ld_relaxed(probe);
#pragma unroll
        for (int i = 3; i < 8; i++) mbar_wait_c(sb + BAR_FULLX + 8 * i, (c.mX >> i) & 1);
        c.mX ^= 0xf8;
        while (__any_sync(0xffffffffu, ~pv & 1)) pv = ld_relaxed(probe);
        if (layer) PROF(24); else PROF(25);
        if (WOBAR && w == 1) asm volatile("bar.sync 7, 256;" ::: "memory");
#pragma unroll
        for (int i = 0; i < WB1; i++) load(i);
        if (WOBAR && w == 0) asm volatile("bar.arrive 7, 256;" ::: "memory");
#pragma unroll
        for (int h = OFIRST; h < 4; h++) st_relaxed4(src + (8 * h + j) * 128, own[h].x, own[h].y, own[h].z, own[h].w);
        st_relaxed2((uint2*)(src + (32 + (j >> 1)) * 128) + (j & 1), own[4].x, own[4].y);
        if (layer) PROF(26); else PROF(27);
        float a[36];
        auto step = [&](const uint4& f, uint32_t s, int i, bool acc) {
          const uint32_t r = (xslot(4) >> 4) + (i < 4 ? 72 * s + 16 * i : 144 * s + 64) * 8, c = (SM_WOC >> 4) + (i < 4 ? 64 + 128 * i : 0) + s;
          wgmma_ra<72>(a, f, desc_hi(0, i < 4 ? 1024 : 9216, 1) + (dsb + r + ((c - r) << 16)), acc);
        };
        if (OWNBAR) asm volatile("bar.sync 4, 256;" ::: "memory");
        float e[4];
        wg_fence();
        if (EARLY) {
#pragma unroll
          for (int i = 0; i < 5; i++) wgmma_ra<8>(e, own[i], desc_hi(128, 0, 0) + (dsb + (SM_WSUM >> 4) + 16 * i), i > 0);
          wg_commit();
        }
#pragma unroll
        for (int i = 0; i < 4; i++) step(own[i], j, i, i > 0);
        wg_commit();
        if (layer) PROF(28); else PROF(29);
        auto batch = [&](auto e0, auto e1, auto e2, int b) {
          constexpr int E0 = decltype(e0)::v, E1 = decltype(e1)::v, E2 = decltype(e2)::v;
          const uint32_t one = (LATE0 || E0 > 0) && E1 > E0 ? late(sb + BAR_FULLX + 64, 1) : 1;
          while (E1 > E0) {
            uint32_t bad = 0;
#pragma unroll
            for (int i = E0; i < E1; i++) bad = i < 28 ? chk(bad, x[i].x, one) : chk(chk(bad, x[i].x, tag), x[i].z, tag);
            if (!__any_sync(0xffffffffu, bad & 1)) break;
#pragma unroll
            for (int i = E0; i < E1; i++) load(i);
          }
          if (b == 0) PROF(pb + 7);
          if (b == FG) c.progress(32 * layer + 20);
          if (b > 0 && E2 > E1) wg_wait<WOW>();
#pragma unroll
          for (int i = E1; i < E2; i++) load(i);
          if (EARLY && b == 0) {
            wg_wait<1>();
            if (q == 0) st_relaxed2(G->sum + st0 + 8 * j, (__float_as_uint(e[0] + e[1]) & ~3u) | ((2 * layer + 2) & 3), __float_as_uint(e[2] + e[3]));
          }
          if (EARLY && b == SUMB) { sa = ld_relaxed2(G->sum + st0 + 16 * q); sc = ld_relaxed2(G->sum + st0 + 16 * q + 8); }
          if (E1 > E0) {
            wg_fence();
#pragma unroll
            for (int i = E0; i < E1; i++) {
              step(x[i], i % 7 + (i < 28 && i % 7 >= j), i / 7, true);
            }
            wg_commit();
          }
        };
        batch(IC<0>(), IC<WB1>(), IC<WB2>(), 0);
        batch(IC<WB1>(), IC<WB2>(), IC<WB3>(), 1);
        batch(IC<WB2>(), IC<WB3>(), IC<32>(), 2);
        batch(IC<WB3>(), IC<32>(), IC<32>(), 3);
        wg_wait<0>();
        if (w == 0) asm volatile("bar.arrive 3, 256;" ::: "memory");
        PROF(pb + 8);
#pragma unroll
        for (int i = 0; i < 18; i++) {
          v[2 * i] = bf_lo(res[i]) + a[2 * i];
          v[2 * i + 1] = bf_hi(res[i]) + a[2 * i + 1];
        }
      }
      uint32_t lsb;
      uint32_t h[144];
      {
        THREAD_IDS();
        float a[128];
        const uint32_t xd = sb + xslot(4 * w) + (lane >> 4) * 1024 + (16 * wp + (lane & 15)) * 16;
        const float2 rs = ln_gemm<false>(c, G, v, res, sum, st0, j, t, layer, xtag,
          [&](int i) {
            if (i == 0) {
              lsb = ((res[0] & 1) | (res[4] & 1) << 1 | (res[8] & 1) << 2 | (res[12] & 1) << 3 | (res[16] & 1) << 4) ^ (xtag * 31);
              if (EARLY) {
                const uint32_t st = late(sb + BAR_FULLX + 64, (2 * layer + 2) & 3);
                while (__any_sync(0xffffffffu, chk2(sa.x, sc.x, st) & 3)) { sa = ld_relaxed2(G->sum + st0 + 16 * q); sc = ld_relaxed2(G->sum + st0 + 16 * q + 8); }
                sum.x += quad_sum(__uint_as_float(sa.x) + __uint_as_float(sc.x)); sum.y += quad_sum(__uint_as_float(sa.y) + __uint_as_float(sc.y));
              }
              if (w == 1) asm volatile("bar.sync 3, 256;" ::: "memory");
            }
            PROF(pb + 9 + i);
          },
          [&](int gi, uint32_t bb, const uint4& f0, const uint4& f1) {
            if (gi == 0) PROF(pb + 11);
            if (TLEAD0 && gi == 18 - TLEAD0 && w == 1) asm volatile("bar.sync 5, 256;" ::: "memory");
            wg_fence();
            wgmma_ra<256>(a, f0, desc_hi(4096, 1024, 1) + bb, gi > 0);
            wgmma_ra<256>(a, f1, desc_hi(4096, 1024, 1) + (bb + 128), true);
            wg_commit();
            if (TLEAD0 && gi == 17 && w == 0) asm volatile("bar.arrive 5, 256;" ::: "memory");
            stsm4(xd + gi * 4096, f0.x, f0.y, f0.z, f0.w);
            stsm4(xd + gi * 4096 + 2048, f1.x, f1.y, f1.z, f1.w);
            if (gi == 17) { fence_async_smem(); wg_bar(w); }
          });
        sts64f(sb + SM_KEEP + (tid_ >> 2) * 8, rs.x * rs.x, rs.y * rs.y);
        c.progress(32 * layer + 22);
        PROF2(pb + 12);
        glu<16, 0>(a, h);
        const Desc da0 = desc_hi(1024, 128, 0) + (dsb + (xslot(4 * w) >> 4));
        auto tile = [&](auto wide, auto last) {
          const uint32_t xe = BAR_EMPTYX + 32 * (t & 1) + 4 * (t & 6);
          auto group = [&](int gi) {
            uint32_t prev;
            const uint32_t bb = c.nextB(prev);
            const Desc da = da0 + gi * 256;
            wg_fence();
            if (wide()) {
              wgmma_ss<256>(a, da, desc_hi(4096, 1024, 1) + bb, gi);
              wgmma_ss<256>(a, da + 128, desc_hi(4096, 1024, 1) + (bb + 128), 1);
            } else {
              wgmma_ss<192>(*(float(*)[96])a, da, desc_hi(2048, 512, 2) + bb, gi);
              wgmma_ss<192>(*(float(*)[96])a, da + 128, desc_hi(2048, 512, 2) + (bb + 64), 1);
            }
            wg_commit();
            if (gi == 17 && w == 0) asm volatile("bar.arrive 5, 256;" ::: "memory");
            wg_wait<1>();
            if (gi > 0 && !(last() && gi > 13)) c.release2(BAR_EMPTYB + prev);
            if (last() && gi >= XREL && !((gi ^ XREL) & 1)) c.release2(BAR_EMPTYX + 16 * ((gi - XREL) & 2) + 2 * ((gi - XREL) & 12));
          };
          int gi = 0, end = w ? 18 - (wide() ? TLEAD2 : TLEAD) : 18;
#pragma unroll 1
          while (true) {
#pragma unroll 1
            for (; gi < end; gi++) group(gi);
            if (end == 18) break;
            asm volatile("bar.sync 5, 256;" ::: "memory");
            end = 18;
          }
          wg_wait<0>();
          if (!last()) c.releaseLastB();
          if (last() && t >= (19 - XREL) / 2 && t < 8) { mbar_arrive(sb + xe); mbar_arrive_remote(c.rem + xe); }
        };
        auto yes = [] { return true; };
        auto no = [] { return false; };
        tile(yes, no); PROF2(pb + 13); glu<16, 32>(a, h);
        tile(yes, no); PROF2(pb + 14); glu<16, 64>(a, h);
        tile(no, no); PROF2(pb + 15); glu<12, 96>(a, h);
        const uint32_t hole = sb + SM_B + 12288 + tid_ * 16;
#pragma unroll
        for (int i = 0; i < NSPILL; i++) sts128(hole + i * BSLOT, h[96 + 4 * i], h[97 + 4 * i], h[98 + 4 * i], h[99 + 4 * i]);
        if (w == 1) asm volatile("bar.arrive 8, 256;" ::: "memory");
        tile(no, yes); PROF2(pb + 16); glu<12, 120>(a, h);
#pragma unroll
        for (int i = 0; i < NSPILL; i++) { const uint4 u = lds128(hole + i * BSLOT); h[96 + 4 * i] = u.x; h[97 + 4 * i] = u.y; h[98 + 4 * i] = u.z; h[99 + 4 * i] = u.w; }
      }
      {
        THREAD_IDS();
        float d[32];
        uint4* gt = G->obox + t;
        asm volatile("" : "+l"(gt));
        uint4* const ib = gt + 2 * 4608 + layer * 8 * INBOX;
        auto pass = [&](uint32_t s0, bool last, auto&& hook) {
          const Desc db = desc_hi(0, 1024, 1) + (dsb + s0 * (XSLOT >> 4));
          mbar_wait_c(sb + BAR_FULLX + 8 * s0, (c.mX >> s0) & 1);
          if (RHOOK < 0) hook();
          asm volatile("bar.sync %0, 256;" ::"r"(8 + w) : "memory");
#pragma unroll
          for (int i = 0; i < 4; i++) {
            const int si = 4 * (i & 1) + (i >> 1);
            if (i > 0) mbar_wait_c(sb + BAR_FULLX + 8 * (s0 + si), (c.mX >> (s0 + si)) & 1);
            wg_fence();
#pragma unroll
            for (int k = 0; k < 9; k++) {
              const uint32_t* hk = h + 36 * i + 4 * k;
              wgmma_ra<64>(d, make_uint4(hk[0], hk[1], hk[2], hk[3]), db + ((xslot(si) >> 4) + k * 128), last || i + k > 0);
              if (9 * i + k == PPK && !(last && w == 1)) asm volatile("bar.arrive %0, 256;" ::"r"(9 - w) : "memory");
            }
            wg_commit();
            if (i > 0) { wg_wait<1>(); c.release2(BAR_EMPTYX + 8 * (s0 + 4 * ((i - 1) & 1) + ((i - 1) >> 1))); }
            if (i == RHOOK) hook();
          }
          c.mX ^= 0x33u << s0;
        };
        PROF2(pb + 17);
#pragma unroll 1
        for (int p = 0; p < 8; p++) {
          const uint32_t s0 = 2 * (p & 1);
          pass(s0, false, [] {});
          wg_wait<0>();
          c.release2(BAR_EMPTYX + 8 * (s0 + 5));
          if (p == 6 && layer == NLAYERS - 1) c.elect = false;
          uint32_t pk[16];
#pragma unroll
          for (int i = 0; i < 16; i++) pk[i] = pack_bf16(d[2 * i], d[2 * i + 1]);
          if (p >= BREL && p < BREL + 5 && layer < NLAYERS - 1) {
            const uint32_t o = c.sB + 8 * (p - BREL);
            c.release2(BAR_EMPTYB + (o < 40 ? o : o - 40));
          }
          uint4* const dst = ib + ((j + p) & 7) * INBOX;
          if (p == 0) {
            mbar_wait_c(sb + BAR_CLR + 8 * w, 0);
#pragma unroll
            for (int k = 0; k < 8; k++) red2((uint2*)(ib + k * INBOX + 512) - t, pk[2 * k], pk[2 * k + 1]);
          } else if (p < 7) {
#pragma unroll
            for (int k = 0; k < 4; k++) red4(dst + k * 128, pk[4 * k], pk[4 * k + 1], pk[4 * k + 2], pk[4 * k + 3]);
            if (p == 6) { __syncwarp(); if (lane == 0) mbar_arrive(sb + BAR_REDDONE + 8 * w); }
          } else {
#pragma unroll
            for (int k = 0; k < 4; k++) st_relaxed4(gt + ((j + 7) & 7) * 128 + k * 1024, pk[4 * k] & ~1u, pk[4 * k + 1], pk[4 * k + 2], pk[4 * k + 3]);
          }
        }
        PROF2(pb + 18);
        const uint4 *in = ib + j * INBOX, *pin = gt + j * 128;
        const uint2* in9 = (const uint2*)(in + 512) - t;
        asm volatile("" : "+l"(in), "+l"(pin), "+l"(in9));
        const float2 r2 = lds64(sb + SM_KEEP + (tid_ >> 2) * 8);
        uint2 X9;
        {
          uint4 X[4];
          const uint4* box = gt + 4608;
#pragma unroll
          for (int k = 0; k < 4; k++) X[k] = ld_relaxed4(box + 256 * j + ((k & 1) + 8 * (k & 2)) * 128);
          X9 = ld_relaxed2((const uint2*)(box + (32 + (j >> 1)) * 128) + (j & 1));
          const float i0 = rcp(r2.x), i1 = rcp(r2.y);
#pragma unroll
          for (int k = 0; k < 4; k++) {
            float* e = d + 8 * k;
            X[k].x ^= (lsb >> k) & 1;
            e[0] = bf_lo(X[k].x) * i0; e[1] = bf_hi(X[k].x) * i0; e[2] = bf_lo(X[k].y) * i1; e[3] = bf_hi(X[k].y) * i1;
            e[4] = bf_lo(X[k].z) * i0; e[5] = bf_hi(X[k].z) * i0; e[6] = bf_lo(X[k].w) * i1; e[7] = bf_hi(X[k].w) * i1;
          }
        }
        uint4 R[4], P[4];
        uint2 R9;
        PROF2(pb + 19);
        pass(0, true, [&] {
          mbar_wait_c(sb + BAR_RREADY + 8 * w, layer);
#pragma unroll
          for (int k = 0; k < 4; k++) R[k] = ld_relaxed4(in + k * 128);
          R9 = ld_relaxed2(in9);
#pragma unroll
          for (int k = 0; k < 4; k++) P[k] = ld_relaxed4(pin + k * 1024);
        });
        const uint32_t zero = late(sb + BAR_FULLX + 64, 0);
        while (__any_sync(0xffffffffu, (chk2(P[0].x, P[1].x, zero) | chk2(P[2].x, P[3].x, zero)) & 1)) {
#pragma unroll
          for (int k = 0; k < 4; k++) P[k] = ld_relaxed4(pin + k * 1024);
        }
#pragma unroll
        for (int k = 0; k < 4; k++) {
          const uint32_t u[4] = {hadd2(R[k].x, P[k].x), hadd2(R[k].y, P[k].y), hadd2(R[k].z, P[k].z), hadd2(R[k].w, P[k].w)};
#pragma unroll
          for (int i = 0; i < 4; i++) { v[8 * k + 2 * i] = bf_lo(u[i]); v[8 * k + 2 * i + 1] = bf_hi(u[i]); }
        }
        X9.x = chk(zero, X9.x, lsb >> 4);
        v[32] = fmaf(bf_lo(R9.x), r2.x, bf_lo(X9.x)); v[33] = fmaf(bf_hi(R9.x), r2.x, bf_hi(X9.x));
        v[34] = fmaf(bf_lo(R9.y), r2.y, bf_lo(X9.y)); v[35] = fmaf(bf_hi(R9.y), r2.y, bf_hi(X9.y));
        PROF2(pb + 20);
        wg_wait<0>();
        c.release2(BAR_EMPTYX + 40);
        PROF2(pb + 21);
#pragma unroll
        for (int i = 0; i < 32; i++) v[i] = (v[i] + d[i]) * (i & 2 ? r2.y : r2.x);
      }
      if (layer == NLAYERS - 1) break;
      {
        THREAD_IDS();
        PROF(31);
        rs = ln_gemm<true>(c, G, v, res, sum, st0, j, t, 1, xtag ^ 1, [&](int i) { PROF(32 + i); if (i) PROF(34); }, qkv_mma);
      }
    }
    {
      THREAD_IDS();
      const uint32_t stg = sb + SM_B + warp * 4096;
      const uint32_t sd = stg + (lane & 15) * 128;
#pragma unroll
      for (int i = 0; i < 4; i++)
        stsm4(sd + (((2 * i + (lane >> 4)) ^ (lane & 7)) << 4), pack_bf16(v[8 * i], v[8 * i + 1]), pack_bf16(v[8 * i + 2], v[8 * i + 3]),
              pack_bf16(v[8 * i + 4], v[8 * i + 5]), pack_bf16(v[8 * i + 6], v[8 * i + 7]));
      stsm2(stg + 2048 + (lane & 15) * 16, pack_bf16(v[32], v[33]), pack_bf16(v[34], v[35]));
      fence_async_smem();
      __syncwarp();
      if (lane == 0) {
        tma_store3d(&maps.out, stg, 64 * j, w, 64 * rb + 16 * wp);
        tma_store3d(&maps.outc, stg + 2048, 512 + 8 * j, w, 64 * rb + 16 * wp);
        bulk_commit();
        if (wp == 0) st_relaxed(G->flag + 32 + 32 * j, xtag);
        bulk_wait_read();
        mbar_arrive(sb + BAR_DONE + 8 * w);
      }
      PROF(61);
    }
  }
}

typedef CUresult (*EncFn)(CUtensorMap*, CUtensorMapDataType, cuuint32_t, void*, const cuuint64_t*, const cuuint64_t*, const cuuint32_t*,
                          const cuuint32_t*, CUtensorMapInterleave, CUtensorMapSwizzle, CUtensorMapL2promotion, CUtensorMapFloatOOBfill);

void make_map(EncFn enc, CUtensorMap* m, const void* p, int rank, uint64_t d0, uint64_t d1, uint64_t d2, uint64_t s1, uint64_t s2, uint32_t b0,
              uint32_t b1, uint32_t b2, CUtensorMapSwizzle sw) {
  cuuint64_t gd[3] = {d0, d1, d2};
  cuuint64_t gs[2] = {s1, s2};
  cuuint32_t bd[3] = {b0, b1, b2};
  cuuint32_t es[3] = {1, 1, 1};
  enc(m, CU_TENSOR_MAP_DATA_TYPE_BFLOAT16, rank, const_cast<void*>(p), gd, gs, bd, es, CU_TENSOR_MAP_INTERLEAVE_NONE, sw,
      CU_TENSOR_MAP_L2_PROMOTION_L2_128B, CU_TENSOR_MAP_FLOAT_OOB_FILL_NONE);
}

}

extern "C" void kernel_launch(void* const* d_in, const int* in_sizes, int n_in, void* d_out, int out_size) {
  const __nv_bfloat16* x = (const __nv_bfloat16*)d_in[0];
  const char *wqkv = (const char*)d_in[1], *wo = (const char*)d_in[2], *wg = (const char*)d_in[4], *wu = (const char*)d_in[5], *wd = (const char*)d_in[6];
  static EncFn enc = nullptr;
  static uint32_t first = 0;
  static Group* ws = nullptr;
  if (!enc) {
    cudaDriverEntryPointQueryResult qr;
    cudaGetDriverEntryPoint("cuTensorMapEncodeTiled", (void**)&enc, cudaEnableDefault, &qr);
    cudaGetSymbolAddress((void**)&ws, g_ws);
    cudaFuncSetAttribute(fused_kernel, cudaFuncAttributeMaxDynamicSharedMemorySize, SMEM_BYTES);
    cudaLaunchConfig_t cfg = {};
    cfg.gridDim = NCTA + 4; cfg.blockDim = 384; cfg.dynamicSmemBytes = SMEM_BYTES;
    int clusters = 0;
    if (XFIRST || cudaOccupancyMaxActiveClusters(&clusters, fused_kernel, &cfg) != cudaSuccess || 2 * clusters < NCTA + 4) first = 4;
    cudaGetLastError();
  }
  const CUtensorMapSwizzle S0 = CU_TENSOR_MAP_SWIZZLE_NONE, S64 = CU_TENSOR_MAP_SWIZZLE_64B, S128 = CU_TENSOR_MAP_SWIZZLE_128B;
  Maps m;
  make_map(enc, &m.x, x, 3, 576, 2, 1024, 1152, 2304, 64, 1, 64, S128);
  make_map(enc, &m.qm, wqkv, 3, 576, 576, 3, 3456, 1152, 64, 16, 3, S128);
  make_map(enc, &m.qc, wqkv, 3, 576, 576, 3, 3456, 1152, 8, 16, 3, S0);
  make_map(enc, &m.o, wo, 2, 576, 576, 1, 1152, 0, 64, 72, 1, S128);
  make_map(enc, &m.g, wg, 3, 64, 576, 72, 9216, 128, 64, 32, 2, S128);
  make_map(enc, &m.u, wu, 3, 64, 576, 72, 9216, 128, 64, 32, 2, S128);
  make_map(enc, &m.g3, wg, 3, 32, 576, 144, 9216, 64, 32, 32, 3, S64);
  make_map(enc, &m.u3, wu, 3, 32, 576, 144, 9216, 64, 32, 32, 3, S64);
  make_map(enc, &m.d, wd, 2, 576, 4608, 1, 1152, 0, 64, 72, 1, S128);
  make_map(enc, &m.out, d_out, 3, 576, 2, 1024, 1152, 2304, 64, 1, 16, S128);
  make_map(enc, &m.outc, d_out, 3, 576, 2, 1024, 1152, 2304, 8, 1, 16, S0);
  fused_kernel<<<NCTA + 4, 384, SMEM_BYTES>>>(x, ws, wqkv, wg, wu, first, m, wo, wd);
}
```

```cpp
#include <cuda_runtime.h>
#include <cuda_bf16.h>
#include <cuda.h>
#include <stdint.h>
#include <stddef.h>

namespace {

constexpr int D_ = 576;
constexpr int NCTA = 128;
#define NLAYERS 2
#define W_POLICY policy_evict_first
#define A_POLICY policy_evict_normal
#define OPEN 1
#define PFMODE 5
#define WWIN 4
#define WOREL -1
#define WB1 11
#define WB2 21
#define WB3 32
#define WPROBE 1
#define WPROBE2 0
#define SPEC 2
#define POLLFIRST 0
#define SUMFIRST 1
#define EARLYPOLL 1
#define LEAD 0
#define ATTBAR 0
#define GL 18
#define WOBAR 1
#define QD 0
#define QG 4
#define PFQ 1
#define XDELAY 0
#define WOH 1
#define PFSLEEP 700
#define GPCMAP 1
#define PFF 1
#define REDN 1
#define CLRSLEEP 300
#define OPENL 24
#define FG 1
#define NON8 0
#define HMUL 1
#define FCH 1
#define PPK 35
#define RHOOK -1
#define SCHEDBAR 1
#define QH 5
#define XH 3
#define XP 0
#define GSLEEP 32
#define XCH 1
#define MAPPF 1
#define XREL 8
#define WOG 13
#define BREL 1
#define FENCE1 0
#define OWNX 0
#define OWNBAR 0
#define EARLY 1
#define ESPEC 0
#define TESTP 0
#define WOW 1
#define STATP -1
#define WSG 0
#define REPACK 1
#define QPACE 23
#define RDELAY 1000
#define XFIRST 0
#define TLEAD 2
#define TLEAD2 2
#define TLEAD0 2
#define OFIRST 3
#define OSPEC 0
#define FN 3
#define LATE0 0
#define SUMB 2
#define XPM 3
#define HALOH 0
#define NSPILL 4
#define REGS_C 232
#define REGS_P 40
#define STR2(x) #x
#define STR(x) STR2(x)
constexpr uint32_t SM_X = 0;
constexpr uint32_t XSLOT = 18432;
__host__ __device__ constexpr uint32_t xslot(uint32_t s) { return SM_X + (s ^ 4) * XSLOT; }
constexpr uint32_t SM_WOC = xslot(3) + 8192;
constexpr uint32_t SM_B = 147456;
constexpr uint32_t BSLOT = 16384;
constexpr uint32_t SM_KEEP = 229376;
constexpr uint32_t SM_WSUM = SM_KEEP + 512;
constexpr uint32_t SM_BAR = SM_KEEP + 2048;
constexpr uint32_t BAR_FULLB = SM_BAR;
constexpr uint32_t BAR_RREADY = SM_BAR + 40;
constexpr uint32_t BAR_CLR = SM_BAR + 56;
constexpr uint32_t BAR_FULLX = SM_BAR + 72;
constexpr uint32_t BAR_EMPTYB = SM_BAR + 144;
constexpr uint32_t BAR_EMPTYX = SM_BAR + 184;
constexpr uint32_t BAR_REDDONE = SM_BAR + 248;
constexpr uint32_t BAR_DONE = SM_BAR + 264;
constexpr uint32_t SM_PROG = SM_BAR + 288;
constexpr uint32_t SMEM_BYTES = SM_BAR + 1024;

struct Maps { CUtensorMap x, qm, qc, o, g, u, g3, u3, d; };

constexpr int INBOX = 576;
struct Group {
  uint2 sum[4 * 8 * 8];
  uint2 sq[4 * 8 * 8];
  uint32_t pad[512];
  uint32_t flag[512];
  uint4 halo[8 * 160];
  uint4 obox[36 * 128];
  uint4 xbox[36 * 128];
  uint4 inbox[2][8 * INBOX];
};
struct Scratch { Group g[32]; uint4 wq[8][36][432]; uint4 woc[8][720]; uint32_t done[64]; };
__device__ __align__(1024) Scratch g_ws;
#define PROF(i)
#define PROFX(i)

#define PROF2(i) PROF(i)

struct Desc { uint32_t lo, hi; };
__device__ __forceinline__ constexpr Desc desc_hi(uint32_t lbo, uint32_t sbo, uint32_t sw) { return Desc{(lbo >> 4) << 16, (sbo >> 4) | sw << 30}; }
__device__ __forceinline__ constexpr Desc operator+(Desc d, uint32_t a) { return Desc{d.lo + a, d.hi}; }

template<int N> __device__ __forceinline__ void wgmma_ss(float (&d)[N / 2], Desc da, Desc db, int sc);
template<> __device__ __forceinline__ void wgmma_ss<192>(float (&d)[96], Desc da, Desc db, int sc) {
  asm volatile("{\n.reg .pred p;\n.reg .b64 a, b;\nsetp.ne.b32 p, %100, 0;\nmov.b64 a, {%96, %97};\nmov.b64 b, {%98, %99};\n"
    "wgmma.mma_async.sync.aligned.m64n192k16.f32.bf16.bf16 {%0,%1,%2,%3,%4,%5,%6,%7,%8,%9,%10,%11,%12,%13,%14,%15,%16,%17,%18,%19,%20,%21,%22,%23,%24,%25,%26,%27,%28,%29,%30,%31,%32,%33,%34,%35,%36,%37,%38,%39,%40,%41,%42,%43,%44,%45,%46,%47,%48,%49,%50,%51,%52,%53,%54,%55,%56,%57,%58,%59,%60,%61,%62,%63,%64,%65,%66,%67,%68,%69,%70,%71,%72,%73,%74,%75,%76,%77,%78,%79,%80,%81,%82,%83,%84,%85,%86,%87,%88,%89,%90,%91,%92,%93,%94,%95}, a, b, p, 1, 1, 0, 1;\n}\n"
    : "+f"(d[0]),"+f"(d[1]),"+f"(d[2]),"+f"(d[3]),"+f"(d[4]),"+f"(d[5]),"+f"(d[6]),"+f"(d[7]),"+f"(d[8]),"+f"(d[9]),"+f"(d[10]),"+f"(d[11]),"+f"(d[12]),"+f"(d[13]),"+f"(d[14]),"+f"(d[15]),"+f"(d[16]),"+f"(d[17]),"+f"(d[18]),"+f"(d[19]),"+f"(d[20]),"+f"(d[21]),"+f"(d[22]),"+f"(d[23]),"+f"(d[24]),"+f"(d[25]),"+f"(d[26]),"+f"(d[27]),"+f"(d[28]),"+f"(d[29]),"+f"(d[30]),"+f"(d[31]),"+f"(d[32]),"+f"(d[33]),"+f"(d[34]),"+f"(d[35]),"+f"(d[36]),"+f"(d[37]),"+f"(d[38]),"+f"(d[39]),"+f"(d[40]),"+f"(d[41]),"+f"(d[42]),"+f"(d[43]),"+f"(d[44]),"+f"(d[45]),"+f"(d[46]),"+f"(d[47]),"+f"(d[48]),"+f"(d[49]),"+f"(d[50]),"+f"(d[51]),"+f"(d[52]),"+f"(d[53]),"+f"(d[54]),"+f"(d[55]),"+f"(d[56]),"+f"(d[57]),"+f"(d[58]),"+f"(d[59]),"+f"(d[60]),"+f"(d[61]),"+f"(d[62]),"+f"(d[63]),"+f"(d[64]),"+f"(d[65]),"+f"(d[66]),"+f"(d[67]),"+f"(d[68]),"+f"(d[69]),"+f"(d[70]),"+f"(d[71]),"+f"(d[72]),"+f"(d[73]),"+f"(d[74]),"+f"(d[75]),"+f"(d[76]),"+f"(d[77]),"+f"(d[78]),"+f"(d[79]),"+f"(d[80]),"+f"(d[81]),"+f"(d[82]),"+f"(d[83]),"+f"(d[84]),"+f"(d[85]),"+f"(d[86]),"+f"(d[87]),"+f"(d[88]),"+f"(d[89]),"+f"(d[90]),"+f"(d[91]),"+f"(d[92]),"+f"(d[93]),"+f"(d[94]),"+f"(d[95]) : "r"(da.lo), "r"(da.hi), "r"(db.lo), "r"(db.hi), "r"(sc));
}
template<> __device__ __forceinline__ void wgmma_ss<256>(float (&d)[128], Desc da, Desc db, int sc) {
  asm volatile("{\n.reg .pred p;\n.reg .b64 a, b;\nsetp.ne.b32 p, %132, 0;\nmov.b64 a, {%128, %129};\nmov.b64 b, {%130, %131};\n"
    "wgmma.mma_async.sync.aligned.m64n256k16.f32.bf16.bf16 {%0,%1,%2,%3,%4,%5,%6,%7,%8,%9,%10,%11,%12,%13,%14,%15,%16,%17,%18,%19,%20,%21,%22,%23,%24,%25,%26,%27,%28,%29,%30,%31,%32,%33,%34,%35,%36,%37,%38,%39,%40,%41,%42,%43,%44,%45,%46,%47,%48,%49,%50,%51,%52,%53,%54,%55,%56,%57,%58,%59,%60,%61,%62,%63,%64,%65,%66,%67,%68,%69,%70,%71,%72,%73,%74,%75,%76,%77,%78,%79,%80,%81,%82,%83,%84,%85,%86,%87,%88,%89,%90,%91,%92,%93,%94,%95,%96,%97,%98,%99,%100,%101,%102,%103,%104,%105,%106,%107,%108,%109,%110,%111,%112,%113,%114,%115,%116,%117,%118,%119,%120,%121,%122,%123,%124,%125,%126,%127}, a, b, p, 1, 1, 0, 1;\n}\n"
    : "+f"(d[0]),"+f"(d[1]),"+f"(d[2]),"+f"(d[3]),"+f"(d[4]),"+f"(d[5]),"+f"(d[6]),"+f"(d[7]),"+f"(d[8]),"+f"(d[9]),"+f"(d[10]),"+f"(d[11]),"+f"(d[12]),"+f"(d[13]),"+f"(d[14]),"+f"(d[15]),"+f"(d[16]),"+f"(d[17]),"+f"(d[18]),"+f"(d[19]),"+f"(d[20]),"+f"(d[21]),"+f"(d[22]),"+f"(d[23]),"+f"(d[24]),"+f"(d[25]),"+f"(d[26]),"+f"(d[27]),"+f"(d[28]),"+f"(d[29]),"+f"(d[30]),"+f"(d[31]),"+f"(d[32]),"+f"(d[33]),"+f"(d[34]),"+f"(d[35]),"+f"(d[36]),"+f"(d[37]),"+f"(d[38]),"+f"(d[39]),"+f"(d[40]),"+f"(d[41]),"+f"(d[42]),"+f"(d[43]),"+f"(d[44]),"+f"(d[45]),"+f"(d[46]),"+f"(d[47]),"+f"(d[48]),"+f"(d[49]),"+f"(d[50]),"+f"(d[51]),"+f"(d[52]),"+f"(d[53]),"+f"(d[54]),"+f"(d[55]),"+f"(d[56]),"+f"(d[57]),"+f"(d[58]),"+f"(d[59]),"+f"(d[60]),"+f"(d[61]),"+f"(d[62]),"+f"(d[63]),"+f"(d[64]),"+f"(d[65]),"+f"(d[66]),"+f"(d[67]),"+f"(d[68]),"+f"(d[69]),"+f"(d[70]),"+f"(d[71]),"+f"(d[72]),"+f"(d[73]),"+f"(d[74]),"+f"(d[75]),"+f"(d[76]),"+f"(d[77]),"+f"(d[78]),"+f"(d[79]),"+f"(d[80]),"+f"(d[81]),"+f"(d[82]),"+f"(d[83]),"+f"(d[84]),"+f"(d[85]),"+f"(d[86]),"+f"(d[87]),"+f"(d[88]),"+f"(d[89]),"+f"(d[90]),"+f"(d[91]),"+f"(d[92]),"+f"(d[93]),"+f"(d[94]),"+f"(d[95]),"+f"(d[96]),"+f"(d[97]),"+f"(d[98]),"+f"(d[99]),"+f"(d[100]),"+f"(d[101]),"+f"(d[102]),"+f"(d[103]),"+f"(d[104]),"+f"(d[105]),"+f"(d[106]),"+f"(d[107]),"+f"(d[108]),"+f"(d[109]),"+f"(d[110]),"+f"(d[111]),"+f"(d[112]),"+f"(d[113]),"+f"(d[114]),"+f"(d[115]),"+f"(d[116]),"+f"(d[117]),"+f"(d[118]),"+f"(d[119]),"+f"(d[120]),"+f"(d[121]),"+f"(d[122]),"+f"(d[123]),"+f"(d[124]),"+f"(d[125]),"+f"(d[126]),"+f"(d[127]) : "r"(da.lo), "r"(da.hi), "r"(db.lo), "r"(db.hi), "r"(sc));
}
template<int N, int ACC> __device__ __forceinline__ void wgmma_rs(float (&d)[N / 2], const uint4& a, Desc db);
template<> __device__ __forceinline__ void wgmma_rs<8, 1>(float (&d)[4], const uint4& a, Desc db) {
  asm volatile("{\n.reg .pred p;\n.reg .b64 b;\nsetp.ne.b32 p, 1, 0;\nmov.b64 b, {%8, %9};\n"
    "wgmma.mma_async.sync.aligned.m64n8k16.f32.bf16.bf16 {%0,%1,%2,%3}, {%4,%5,%6,%7}, b, p, 1, 1, 1;\n}\n"
    : "+f"(d[0]),"+f"(d[1]),"+f"(d[2]),"+f"(d[3]) : "r"(a.x), "r"(a.y), "r"(a.z), "r"(a.w), "r"(db.lo), "r"(db.hi));
}
template<> __device__ __forceinline__ void wgmma_rs<8, 0>(float (&d)[4], const uint4& a, Desc db) {
  asm volatile("{\n.reg .pred p;\n.reg .b64 b;\nsetp.ne.b32 p, 0, 0;\nmov.b64 b, {%8, %9};\n"
    "wgmma.mma_async.sync.aligned.m64n8k16.f32.bf16.bf16 {%0,%1,%2,%3}, {%4,%5,%6,%7}, b, p, 1, 1, 1;\n}\n"
    : "=f"(d[0]),"=f"(d[1]),"=f"(d[2]),"=f"(d[3]) : "r"(a.x), "r"(a.y), "r"(a.z), "r"(a.w), "r"(db.lo), "r"(db.hi));
}
template<> __device__ __forceinline__ void wgmma_rs<24, 1>(float (&d)[12], const uint4& a, Desc db) {
  asm volatile("{\n.reg .pred p;\n.reg .b64 b;\nsetp.ne.b32 p, 1, 0;\nmov.b64 b, {%16, %17};\n"
    "wgmma.mma_async.sync.aligned.m64n24k16.f32.bf16.bf16 {%0,%1,%2,%3,%4,%5,%6,%7,%8,%9,%10,%11}, {%12,%13,%14,%15}, b, p, 1, 1, 1;\n}\n"
    : "+f"(d[0]),"+f"(d[1]),"+f"(d[2]),"+f"(d[3]),"+f"(d[4]),"+f"(d[5]),"+f"(d[6]),"+f"(d[7]),"+f"(d[8]),"+f"(d[9]),"+f"(d[10]),"+f"(d[11]) : "r"(a.x), "r"(a.y), "r"(a.z), "r"(a.w), "r"(db.lo), "r"(db.hi));
}
template<> __device__ __forceinline__ void wgmma_rs<24, 0>(float (&d)[12], const uint4& a, Desc db) {
  asm volatile("{\n.reg .pred p;\n.reg .b64 b;\nsetp.ne.b32 p, 0, 0;\nmov.b64 b, {%16, %17};\n"
    "wgmma.mma_async.sync.aligned.m64n24k16.f32.bf16.bf16 {%0,%1,%2,%3,%4,%5,%6,%7,%8,%9,%10,%11}, {%12,%13,%14,%15}, b, p, 1, 1, 1;\n}\n"
    : "=f"(d[0]),"=f"(d[1]),"=f"(d[2]),"=f"(d[3]),"=f"(d[4]),"=f"(d[5]),"=f"(d[6]),"=f"(d[7]),"=f"(d[8]),"=f"(d[9]),"=f"(d[10]),"=f"(d[11]) : "r"(a.x), "r"(a.y), "r"(a.z), "r"(a.w), "r"(db.lo), "r"(db.hi));
}
template<> __device__ __forceinline__ void wgmma_rs<64, 1>(float (&d)[32], const uint4& a, Desc db) {
  asm volatile("{\n.reg .pred p;\n.reg .b64 b;\nsetp.ne.b32 p, 1, 0;\nmov.b64 b, {%36, %37};\n"
    "wgmma.mma_async.sync.aligned.m64n64k16.f32.bf16.bf16 {%0,%1,%2,%3,%4,%5,%6,%7,%8,%9,%10,%11,%12,%13,%14,%15,%16,%17,%18,%19,%20,%21,%22,%23,%24,%25,%26,%27,%28,%29,%30,%31}, {%32,%33,%34,%35}, b, p, 1, 1, 1;\n}\n"
    : "+f"(d[0]),"+f"(d[1]),"+f"(d[2]),"+f"(d[3]),"+f"(d[4]),"+f"(d[5]),"+f"(d[6]),"+f"(d[7]),"+f"(d[8]),"+f"(d[9]),"+f"(d[10]),"+f"(d[11]),"+f"(d[12]),"+f"(d[13]),"+f"(d[14]),"+f"(d[15]),"+f"(d[16]),"+f"(d[17]),"+f"(d[18]),"+f"(d[19]),"+f"(d[20]),"+f"(d[21]),"+f"(d[22]),"+f"(d[23]),"+f"(d[24]),"+f"(d[25]),"+f"(d[26]),"+f"(d[27]),"+f"(d[28]),"+f"(d[29]),"+f"(d[30]),"+f"(d[31]) : "r"(a.x), "r"(a.y), "r"(a.z), "r"(a.w), "r"(db.lo), "r"(db.hi));
}
template<> __device__ __forceinline__ void wgmma_rs<64, 0>(float (&d)[32], const uint4& a, Desc db) {
  asm volatile("{\n.reg .pred p;\n.reg .b64 b;\nsetp.ne.b32 p, 0, 0;\nmov.b64 b, {%36, %37};\n"
    "wgmma.mma_async.sync.aligned.m64n64k16.f32.bf16.bf16 {%0,%1,%2,%3,%4,%5,%6,%7,%8,%9,%10,%11,%12,%13,%14,%15,%16,%17,%18,%19,%20,%21,%22,%23,%24,%25,%26,%27,%28,%29,%30,%31}, {%32,%33,%34,%35}, b, p, 1, 1, 1;\n}\n"
    : "=f"(d[0]),"=f"(d[1]),"=f"(d[2]),"=f"(d[3]),"=f"(d[4]),"=f"(d[5]),"=f"(d[6]),"=f"(d[7]),"=f"(d[8]),"=f"(d[9]),"=f"(d[10]),"=f"(d[11]),"=f"(d[12]),"=f"(d[13]),"=f"(d[14]),"=f"(d[15]),"=f"(d[16]),"=f"(d[17]),"=f"(d[18]),"=f"(d[19]),"=f"(d[20]),"=f"(d[21]),"=f"(d[22]),"=f"(d[23]),"=f"(d[24]),"=f"(d[25]),"=f"(d[26]),"=f"(d[27]),"=f"(d[28]),"=f"(d[29]),"=f"(d[30]),"=f"(d[31]) : "r"(a.x), "r"(a.y), "r"(a.z), "r"(a.w), "r"(db.lo), "r"(db.hi));
}
template<> __device__ __forceinline__ void wgmma_rs<72, 1>(float (&d)[36], const uint4& a, Desc db) {
  asm volatile("{\n.reg .pred p;\n.reg .b64 b;\nsetp.ne.b32 p, 1, 0;\nmov.b64 b, {%40, %41};\n"
    "wgmma.mma_async.sync.aligned.m64n72k16.f32.bf16.bf16 {%0,%1,%2,%3,%4,%5,%6,%7,%8,%9,%10,%11,%12,%13,%14,%15,%16,%17,%18,%19,%20,%21,%22,%23,%24,%25,%26,%27,%28,%29,%30,%31,%32,%33,%34,%35}, {%36,%37,%38,%39}, b, p, 1, 1, 1;\n}\n"
    : "+f"(d[0]),"+f"(d[1]),"+f"(d[2]),"+f"(d[3]),"+f"(d[4]),"+f"(d[5]),"+f"(d[6]),"+f"(d[7]),"+f"(d[8]),"+f"(d[9]),"+f"(d[10]),"+f"(d[11]),"+f"(d[12]),"+f"(d[13]),"+f"(d[14]),"+f"(d[15]),"+f"(d[16]),"+f"(d[17]),"+f"(d[18]),"+f"(d[19]),"+f"(d[20]),"+f"(d[21]),"+f"(d[22]),"+f"(d[23]),"+f"(d[24]),"+f"(d[25]),"+f"(d[26]),"+f"(d[27]),"+f"(d[28]),"+f"(d[29]),"+f"(d[30]),"+f"(d[31]),"+f"(d[32]),"+f"(d[33]),"+f"(d[34]),"+f"(d[35]) : "r"(a.x), "r"(a.y), "r"(a.z), "r"(a.w), "r"(db.lo), "r"(db.hi));
}
template<> __device__ __forceinline__ void wgmma_rs<72, 0>(float (&d)[36], const uint4& a, Desc db) {
  asm volatile("{\n.reg .pred p;\n.reg .b64 b;\nsetp.ne.b32 p, 0, 0;\nmov.b64 b, {%40, %41};\n"
    "wgmma.mma_async.sync.aligned.m64n72k16.f32.bf16.bf16 {%0,%1,%2,%3,%4,%5,%6,%7,%8,%9,%10,%11,%12,%13,%14,%15,%16,%17,%18,%19,%20,%21,%22,%23,%24,%25,%26,%27,%28,%29,%30,%31,%32,%33,%34,%35}, {%36,%37,%38,%39}, b, p, 1, 1, 1;\n}\n"
    : "=f"(d[0]),"=f"(d[1]),"=f"(d[2]),"=f"(d[3]),"=f"(d[4]),"=f"(d[5]),"=f"(d[6]),"=f"(d[7]),"=f"(d[8]),"=f"(d[9]),"=f"(d[10]),"=f"(d[11]),"=f"(d[12]),"=f"(d[13]),"=f"(d[14]),"=f"(d[15]),"=f"(d[16]),"=f"(d[17]),"=f"(d[18]),"=f"(d[19]),"=f"(d[20]),"=f"(d[21]),"=f"(d[22]),"=f"(d[23]),"=f"(d[24]),"=f"(d[25]),"=f"(d[26]),"=f"(d[27]),"=f"(d[28]),"=f"(d[29]),"=f"(d[30]),"=f"(d[31]),"=f"(d[32]),"=f"(d[33]),"=f"(d[34]),"=f"(d[35]) : "r"(a.x), "r"(a.y), "r"(a.z), "r"(a.w), "r"(db.lo), "r"(db.hi));
}
template<> __device__ __forceinline__ void wgmma_rs<192, 1>(float (&d)[96], const uint4& a, Desc db) {
  asm volatile("{\n.reg .pred p;\n.reg .b64 b;\nsetp.ne.b32 p, 1, 0;\nmov.b64 b, {%100, %101};\n"
    "wgmma.mma_async.sync.aligned.m64n192k16.f32.bf16.bf16 {%0,%1,%2,%3,%4,%5,%6,%7,%8,%9,%10,%11,%12,%13,%14,%15,%16,%17,%18,%19,%20,%21,%22,%23,%24,%25,%26,%27,%28,%29,%30,%31,%32,%33,%34,%35,%36,%37,%38,%39,%40,%41,%42,%43,%44,%45,%46,%47,%48,%49,%50,%51,%52,%53,%54,%55,%56,%57,%58,%59,%60,%61,%62,%63,%64,%65,%66,%67,%68,%69,%70,%71,%72,%73,%74,%75,%76,%77,%78,%79,%80,%81,%82,%83,%84,%85,%86,%87,%88,%89,%90,%91,%92,%93,%94,%95}, {%96,%97,%98,%99}, b, p, 1, 1, 1;\n}\n"
    : "+f"(d[0]),"+f"(d[1]),"+f"(d[2]),"+f"(d[3]),"+f"(d[4]),"+f"(d[5]),"+f"(d[6]),"+f"(d[7]),"+f"(d[8]),"+f"(d[9]),"+f"(d[10]),"+f"(d[11]),"+f"(d[12]),"+f"(d[13]),"+f"(d[14]),"+f"(d[15]),"+f"(d[16]),"+f"(d[17]),"+f"(d[18]),"+f"(d[19]),"+f"(d[20]),"+f"(d[21]),"+f"(d[22]),"+f"(d[23]),"+f"(d[24]),"+f"(d[25]),"+f"(d[26]),"+f"(d[27]),"+f"(d[28]),"+f"(d[29]),"+f"(d[30]),"+f"(d[31]),"+f"(d[32]),"+f"(d[33]),"+f"(d[34]),"+f"(d[35]),"+f"(d[36]),"+f"(d[37]),"+f"(d[38]),"+f"(d[39]),"+f"(d[40]),"+f"(d[41]),"+f"(d[42]),"+f"(d[43]),"+f"(d[44]),"+f"(d[45]),"+f"(d[46]),"+f"(d[47]),"+f"(d[48]),"+f"(d[49]),"+f"(d[50]),"+f"(d[51]),"+f"(d[52]),"+f"(d[53]),"+f"(d[54]),"+f"(d[55]),"+f"(d[56]),"+f"(d[57]),"+f"(d[58]),"+f"(d[59]),"+f"(d[60]),"+f"(d[61]),"+f"(d[62]),"+f"(d[63]),"+f"(d[64]),"+f"(d[65]),"+f"(d[66]),"+f"(d[67]),"+f"(d[68]),"+f"(d[69]),"+f"(d[70]),"+f"(d[71]),"+f"(d[72]),"+f"(d[73]),"+f"(d[74]),"+f"(d[75]),"+f"(d[76]),"+f"(d[77]),"+f"(d[78]),"+f"(d[79]),"+f"(d[80]),"+f"(d[81]),"+f"(d[82]),"+f"(d[83]),"+f"(d[84]),"+f"(d[85]),"+f"(d[86]),"+f"(d[87]),"+f"(d[88]),"+f"(d[89]),"+f"(d[90]),"+f"(d[91]),"+f"(d[92]),"+f"(d[93]),"+f"(d[94]),"+f"(d[95]) : "r"(a.x), "r"(a.y), "r"(a.z), "r"(a.w), "r"(db.lo), "r"(db.hi));
}
template<> __device__ __forceinline__ void wgmma_rs<192, 0>(float (&d)[96], const uint4& a, Desc db) {
  asm volatile("{\n.reg .pred p;\n.reg .b64 b;\nsetp.ne.b32 p, 0, 0;\nmov.b64 b, {%100, %101};\n"
    "wgmma.mma_async.sync.aligned.m64n192k16.f32.bf16.bf16 {%0,%1,%2,%3,%4,%5,%6,%7,%8,%9,%10,%11,%12,%13,%14,%15,%16,%17,%18,%19,%20,%21,%22,%23,%24,%25,%26,%27,%28,%29,%30,%31,%32,%33,%34,%35,%36,%37,%38,%39,%40,%41,%42,%43,%44,%45,%46,%47,%48,%49,%50,%51,%52,%53,%54,%55,%56,%57,%58,%59,%60,%61,%62,%63,%64,%65,%66,%67,%68,%69,%70,%71,%72,%73,%74,%75,%76,%77,%78,%79,%80,%81,%82,%83,%84,%85,%86,%87,%88,%89,%90,%91,%92,%93,%94,%95}, {%96,%97,%98,%99}, b, p, 1, 1, 1;\n}\n"
    : "=f"(d[0]),"=f"(d[1]),"=f"(d[2]),"=f"(d[3]),"=f"(d[4]),"=f"(d[5]),"=f"(d[6]),"=f"(d[7]),"=f"(d[8]),"=f"(d[9]),"=f"(d[10]),"=f"(d[11]),"=f"(d[12]),"=f"(d[13]),"=f"(d[14]),"=f"(d[15]),"=f"(d[16]),"=f"(d[17]),"=f"(d[18]),"=f"(d[19]),"=f"(d[20]),"=f"(d[21]),"=f"(d[22]),"=f"(d[23]),"=f"(d[24]),"=f"(d[25]),"=f"(d[26]),"=f"(d[27]),"=f"(d[28]),"=f"(d[29]),"=f"(d[30]),"=f"(d[31]),"=f"(d[32]),"=f"(d[33]),"=f"(d[34]),"=f"(d[35]),"=f"(d[36]),"=f"(d[37]),"=f"(d[38]),"=f"(d[39]),"=f"(d[40]),"=f"(d[41]),"=f"(d[42]),"=f"(d[43]),"=f"(d[44]),"=f"(d[45]),"=f"(d[46]),"=f"(d[47]),"=f"(d[48]),"=f"(d[49]),"=f"(d[50]),"=f"(d[51]),"=f"(d[52]),"=f"(d[53]),"=f"(d[54]),"=f"(d[55]),"=f"(d[56]),"=f"(d[57]),"=f"(d[58]),"=f"(d[59]),"=f"(d[60]),"=f"(d[61]),"=f"(d[62]),"=f"(d[63]),"=f"(d[64]),"=f"(d[65]),"=f"(d[66]),"=f"(d[67]),"=f"(d[68]),"=f"(d[69]),"=f"(d[70]),"=f"(d[71]),"=f"(d[72]),"=f"(d[73]),"=f"(d[74]),"=f"(d[75]),"=f"(d[76]),"=f"(d[77]),"=f"(d[78]),"=f"(d[79]),"=f"(d[80]),"=f"(d[81]),"=f"(d[82]),"=f"(d[83]),"=f"(d[84]),"=f"(d[85]),"=f"(d[86]),"=f"(d[87]),"=f"(d[88]),"=f"(d[89]),"=f"(d[90]),"=f"(d[91]),"=f"(d[92]),"=f"(d[93]),"=f"(d[94]),"=f"(d[95]) : "r"(a.x), "r"(a.y), "r"(a.z), "r"(a.w), "r"(db.lo), "r"(db.hi));
}
template<> __device__ __forceinline__ void wgmma_rs<256, 1>(float (&d)[128], const uint4& a, Desc db) {
  asm volatile("{\n.reg .pred p;\n.reg .b64 b;\nsetp.ne.b32 p, 1, 0;\nmov.b64 b, {%132, %133};\n"
    "wgmma.mma_async.sync.aligned.m64n256k16.f32.bf16.bf16 {%0,%1,%2,%3,%4,%5,%6,%7,%8,%9,%10,%11,%12,%13,%14,%15,%16,%17,%18,%19,%20,%21,%22,%23,%24,%25,%26,%27,%28,%29,%30,%31,%32,%33,%34,%35,%36,%37,%38,%39,%40,%41,%42,%43,%44,%45,%46,%47,%48,%49,%50,%51,%52,%53,%54,%55,%56,%57,%58,%59,%60,%61,%62,%63,%64,%65,%66,%67,%68,%69,%70,%71,%72,%73,%74,%75,%76,%77,%78,%79,%80,%81,%82,%83,%84,%85,%86,%87,%88,%89,%90,%91,%92,%93,%94,%95,%96,%97,%98,%99,%100,%101,%102,%103,%104,%105,%106,%107,%108,%109,%110,%111,%112,%113,%114,%115,%116,%117,%118,%119,%120,%121,%122,%123,%124,%125,%126,%127}, {%128,%129,%130,%131}, b, p, 1, 1, 1;\n}\n"
    : "+f"(d[0]),"+f"(d[1]),"+f"(d[2]),"+f"(d[3]),"+f"(d[4]),"+f"(d[5]),"+f"(d[6]),"+f"(d[7]),"+f"(d[8]),"+f"(d[9]),"+f"(d[10]),"+f"(d[11]),"+f"(d[12]),"+f"(d[13]),"+f"(d[14]),"+f"(d[15]),"+f"(d[16]),"+f"(d[17]),"+f"(d[18]),"+f"(d[19]),"+f"(d[20]),"+f"(d[21]),"+f"(d[22]),"+f"(d[23]),"+f"(d[24]),"+f"(d[25]),"+f"(d[26]),"+f"(d[27]),"+f"(d[28]),"+f"(d[29]),"+f"(d[30]),"+f"(d[31]),"+f"(d[32]),"+f"(d[33]),"+f"(d[34]),"+f"(d[35]),"+f"(d[36]),"+f"(d[37]),"+f"(d[38]),"+f"(d[39]),"+f"(d[40]),"+f"(d[41]),"+f"(d[42]),"+f"(d[43]),"+f"(d[44]),"+f"(d[45]),"+f"(d[46]),"+f"(d[47]),"+f"(d[48]),"+f"(d[49]),"+f"(d[50]),"+f"(d[51]),"+f"(d[52]),"+f"(d[53]),"+f"(d[54]),"+f"(d[55]),"+f"(d[56]),"+f"(d[57]),"+f"(d[58]),"+f"(d[59]),"+f"(d[60]),"+f"(d[61]),"+f"(d[62]),"+f"(d[63]),"+f"(d[64]),"+f"(d[65]),"+f"(d[66]),"+f"(d[67]),"+f"(d[68]),"+f"(d[69]),"+f"(d[70]),"+f"(d[71]),"+f"(d[72]),"+f"(d[73]),"+f"(d[74]),"+f"(d[75]),"+f"(d[76]),"+f"(d[77]),"+f"(d[78]),"+f"(d[79]),"+f"(d[80]),"+f"(d[81]),"+f"(d[82]),"+f"(d[83]),"+f"(d[84]),"+f"(d[85]),"+f"(d[86]),"+f"(d[87]),"+f"(d[88]),"+f"(d[89]),"+f"(d[90]),"+f"(d[91]),"+f"(d[92]),"+f"(d[93]),"+f"(d[94]),"+f"(d[95]),"+f"(d[96]),"+f"(d[97]),"+f"(d[98]),"+f"(d[99]),"+f"(d[100]),"+f"(d[101]),"+f"(d[102]),"+f"(d[103]),"+f"(d[104]),"+f"(d[105]),"+f"(d[106]),"+f"(d[107]),"+f"(d[108]),"+f"(d[109]),"+f"(d[110]),"+f"(d[111]),"+f"(d[112]),"+f"(d[113]),"+f"(d[114]),"+f"(d[115]),"+f"(d[116]),"+f"(d[117]),"+f"(d[118]),"+f"(d[119]),"+f"(d[120]),"+f"(d[121]),"+f"(d[122]),"+f"(d[123]),"+f"(d[124]),"+f"(d[125]),"+f"(d[126]),"+f"(d[127]) : "r"(a.x), "r"(a.y), "r"(a.z), "r"(a.w), "r"(db.lo), "r"(db.hi));
}
template<> __device__ __forceinline__ void wgmma_rs<256, 0>(float (&d)[128], const uint4& a, Desc db) {
  asm volatile("{\n.reg .pred p;\n.reg .b64 b;\nsetp.ne.b32 p, 0, 0;\nmov.b64 b, {%132, %133};\n"
    "wgmma.mma_async.sync.aligned.m64n256k16.f32.bf16.bf16 {%0,%1,%2,%3,%4,%5,%6,%7,%8,%9,%10,%11,%12,%13,%14,%15,%16,%17,%18,%19,%20,%21,%22,%23,%24,%25,%26,%27,%28,%29,%30,%31,%32,%33,%34,%35,%36,%37,%38,%39,%40,%41,%42,%43,%44,%45,%46,%47,%48,%49,%50,%51,%52,%53,%54,%55,%56,%57,%58,%59,%60,%61,%62,%63,%64,%65,%66,%67,%68,%69,%70,%71,%72,%73,%74,%75,%76,%77,%78,%79,%80,%81,%82,%83,%84,%85,%86,%87,%88,%89,%90,%91,%92,%93,%94,%95,%96,%97,%98,%99,%100,%101,%102,%103,%104,%105,%106,%107,%108,%109,%110,%111,%112,%113,%114,%115,%116,%117,%118,%119,%120,%121,%122,%123,%124,%125,%126,%127}, {%128,%129,%130,%131}, b, p, 1, 1, 1;\n}\n"
    : "=f"(d[0]),"=f"(d[1]),"=f"(d[2]),"=f"(d[3]),"=f"(d[4]),"=f"(d[5]),"=f"(d[6]),"=f"(d[7]),"=f"(d[8]),"=f"(d[9]),"=f"(d[10]),"=f"(d[11]),"=f"(d[12]),"=f"(d[13]),"=f"(d[14]),"=f"(d[15]),"=f"(d[16]),"=f"(d[17]),"=f"(d[18]),"=f"(d[19]),"=f"(d[20]),"=f"(d[21]),"=f"(d[22]),"=f"(d[23]),"=f"(d[24]),"=f"(d[25]),"=f"(d[26]),"=f"(d[27]),"=f"(d[28]),"=f"(d[29]),"=f"(d[30]),"=f"(d[31]),"=f"(d[32]),"=f"(d[33]),"=f"(d[34]),"=f"(d[35]),"=f"(d[36]),"=f"(d[37]),"=f"(d[38]),"=f"(d[39]),"=f"(d[40]),"=f"(d[41]),"=f"(d[42]),"=f"(d[43]),"=f"(d[44]),"=f"(d[45]),"=f"(d[46]),"=f"(d[47]),"=f"(d[48]),"=f"(d[49]),"=f"(d[50]),"=f"(d[51]),"=f"(d[52]),"=f"(d[53]),"=f"(d[54]),"=f"(d[55]),"=f"(d[56]),"=f"(d[57]),"=f"(d[58]),"=f"(d[59]),"=f"(d[60]),"=f"(d[61]),"=f"(d[62]),"=f"(d[63]),"=f"(d[64]),"=f"(d[65]),"=f"(d[66]),"=f"(d[67]),"=f"(d[68]),"=f"(d[69]),"=f"(d[70]),"=f"(d[71]),"=f"(d[72]),"=f"(d[73]),"=f"(d[74]),"=f"(d[75]),"=f"(d[76]),"=f"(d[77]),"=f"(d[78]),"=f"(d[79]),"=f"(d[80]),"=f"(d[81]),"=f"(d[82]),"=f"(d[83]),"=f"(d[84]),"=f"(d[85]),"=f"(d[86]),"=f"(d[87]),"=f"(d[88]),"=f"(d[89]),"=f"(d[90]),"=f"(d[91]),"=f"(d[92]),"=f"(d[93]),"=f"(d[94]),"=f"(d[95]),"=f"(d[96]),"=f"(d[97]),"=f"(d[98]),"=f"(d[99]),"=f"(d[100]),"=f"(d[101]),"=f"(d[102]),"=f"(d[103]),"=f"(d[104]),"=f"(d[105]),"=f"(d[106]),"=f"(d[107]),"=f"(d[108]),"=f"(d[109]),"=f"(d[110]),"=f"(d[111]),"=f"(d[112]),"=f"(d[113]),"=f"(d[114]),"=f"(d[115]),"=f"(d[116]),"=f"(d[117]),"=f"(d[118]),"=f"(d[119]),"=f"(d[120]),"=f"(d[121]),"=f"(d[122]),"=f"(d[123]),"=f"(d[124]),"=f"(d[125]),"=f"(d[126]),"=f"(d[127]) : "r"(a.x), "r"(a.y), "r"(a.z), "r"(a.w), "r"(db.lo), "r"(db.hi));
}
template<int N> __device__ __forceinline__ void wgmma_ra(float (&d)[N / 2], const uint4& a, Desc db, bool acc) {
  if (acc) wgmma_rs<N, 1>(d, a, db); else wgmma_rs<N, 0>(d, a, db);
}

__device__ __forceinline__ uint32_t smem_u32(const void* p) { return (uint32_t)__cvta_generic_to_shared(p); }
__device__ __forceinline__ void mbar_init(uint32_t bar, uint32_t cnt) { asm volatile("mbarrier.init.shared::cta.b64 [%0], %1;" ::"r"(bar), "r"(cnt)); }
__device__ __forceinline__ void mbar_expect_tx(uint32_t bar, uint32_t bytes) { asm volatile("mbarrier.arrive.expect_tx.shared::cta.b64 _, [%0], %1;" ::"r"(bar), "r"(bytes) : "memory"); }
__device__ __forceinline__ void mbar_arrive(uint32_t bar) { asm volatile("mbarrier.arrive.shared::cta.b64 _, [%0];" ::"r"(bar) : "memory"); }
__device__ __forceinline__ void mbar_arrive_remote(uint32_t rbar) { asm volatile("mbarrier.arrive.shared::cluster.b64 _, [%0];" ::"r"(rbar) : "memory"); }
__device__ __forceinline__ void mbar_wait(uint32_t bar, uint32_t parity) {
  asm volatile(
      "{\n.reg .pred p;\n.reg .u32 c;\nmov.u32 c, 0;\nLAB_WAIT:\nmbarrier.try_wait.parity.shared::cta.b64 p, [%0], %1;\n@p bra DONE;\n"
      "add.u32 c, c, 1;\nsetp.lt.u32 p, c, 1000000;\n@p bra LAB_WAIT;\ntrap;\nDONE:\n}\n" ::"r"(bar), "r"(parity) : "memory");
}
__device__ __forceinline__ void mbar_wait_c(uint32_t bar, uint32_t parity) {
  asm volatile("{\n.reg .pred p;\nLAB_WAIT:\nmbarrier.try_wait.parity.shared::cta.b64 p, [%0], %1;\n@!p bra LAB_WAIT;\n}\n" ::"r"(bar), "r"(parity) : "memory");
}
__device__ __forceinline__ uint32_t late(uint32_t bar, uint32_t v) {
  uint32_t r;
  asm volatile("{\n.reg .pred p;\nmbarrier.test_wait.parity.shared::cta.b64 p, [%1], 0;\nselp.b32 %0, %2, %1, p;\n}\n" : "=r"(r) : "r"(bar), "r"(v) : "memory");
  return r;
}
__device__ __forceinline__ void wtma2d(uint32_t dst, const CUtensorMap* m, int c0, int c1, uint32_t bar, uint64_t pol) {
  asm volatile("cp.async.bulk.tensor.2d.shared::cluster.global.mbarrier::complete_tx::bytes.multicast::cluster.L2::cache_hint [%0], [%1, {%3, %4}], [%2], %5, %6;"
               ::"r"(dst), "l"(m), "r"(bar), "r"(c0), "r"(c1), "h"((uint16_t)3), "l"(pol) : "memory");
}
__device__ __forceinline__ void wtma3d(uint32_t dst, const CUtensorMap* m, int c0, int c1, int c2, uint32_t bar, uint64_t pol) {
  asm volatile("cp.async.bulk.tensor.3d.shared::cluster.global.mbarrier::complete_tx::bytes.multicast::cluster.L2::cache_hint [%0], [%1, {%3, %4, %5}], [%2], %6, %7;"
               ::"r"(dst), "l"(m), "r"(bar), "r"(c0), "r"(c1), "r"(c2), "h"((uint16_t)3), "l"(pol) : "memory");
}
__device__ __forceinline__ void wbulk(uint32_t dst, const void* src, uint32_t bytes, uint32_t bar, uint64_t pol) {
  asm volatile("cp.async.bulk.shared::cluster.global.mbarrier::complete_tx::bytes.multicast::cluster.L2::cache_hint [%0], [%1], %2, [%3], %4, %5;"
               ::"r"(dst), "l"(src), "r"(bytes), "r"(bar), "h"((uint16_t)3), "l"(pol) : "memory");
}
__device__ __forceinline__ void tma3d(uint32_t dst, const CUtensorMap* m, int c0, int c1, int c2, uint32_t bar) {
  asm volatile("cp.async.bulk.tensor.3d.shared::cluster.global.mbarrier::complete_tx::bytes [%0], [%1, {%3, %4, %5}], [%2];"
               ::"r"(dst), "l"(m), "r"(bar), "r"(c0), "r"(c1), "r"(c2) : "memory");
}
__device__ __forceinline__ void prefetch_l2(const void* p, uint32_t bytes) { asm volatile("cp.async.bulk.prefetch.L2.global [%0], %1;" ::"l"(p), "r"(bytes) : "memory"); }
__device__ __forceinline__ uint64_t policy_evict_first() { uint64_t p; asm volatile("createpolicy.fractional.L2::evict_first.b64 %0, 1.0;" : "=l"(p)); return p; }
__device__ __forceinline__ uint64_t policy_evict_normal() { uint64_t p; asm volatile("createpolicy.fractional.L2::evict_normal.b64 %0, 1.0;" : "=l"(p)); return p; }
__device__ __forceinline__ void fence_async_smem() { asm volatile("fence.proxy.async.shared::cta;" ::: "memory"); }
__device__ __forceinline__ bool elect_one() {
  uint32_t p;
  asm volatile("{\n.reg .pred P;\nelect.sync _|P, 0xffffffff;\nselp.u32 %0, 1, 0, P;\n}\n" : "=r"(p));
  return p;
}
__device__ __forceinline__ void wg_fence() { asm volatile("wgmma.fence.sync.aligned;" ::: "memory"); }
__device__ __forceinline__ void wg_commit() { asm volatile("wgmma.commit_group.sync.aligned;" ::: "memory"); }
template <int n> __device__ __forceinline__ void wg_wait() { asm volatile("wgmma.wait_group.sync.aligned %0;" ::"n"(n) : "memory"); }
__device__ __forceinline__ void wg_bar(int w) { asm volatile("bar.sync %0, 128;" ::"r"(w + 1) : "memory"); }
__device__ __forceinline__ void fence_gpu() { asm volatile("fence.acq_rel.gpu;" ::: "memory"); }
__device__ __forceinline__ uint32_t ld_relaxed(const uint32_t* p) { uint32_t v; asm volatile("ld.relaxed.gpu.global.u32 %0, [%1];" : "=r"(v) : "l"(p) : "memory"); return v; }
__device__ __forceinline__ uint32_t ld_acquire(const uint32_t* p) { uint32_t v; asm volatile("ld.acquire.gpu.global.u32 %0, [%1];" : "=r"(v) : "l"(p) : "memory"); return v; }
__device__ __forceinline__ uint4 ld_relaxed4(const uint4* p) {
  uint4 v; asm volatile("ld.relaxed.gpu.global.v4.u32 {%0,%1,%2,%3}, [%4];" : "=r"(v.x), "=r"(v.y), "=r"(v.z), "=r"(v.w) : "l"(p) : "memory"); return v;
}
__device__ __forceinline__ uint2 ld_relaxed2(const uint2* p) {
  uint2 v; asm volatile("ld.relaxed.gpu.global.v2.u32 {%0,%1}, [%2];" : "=r"(v.x), "=r"(v.y) : "l"(p) : "memory"); return v;
}
__device__ __forceinline__ void st_relaxed(uint32_t* p, uint32_t a) { asm volatile("st.relaxed.gpu.global.u32 [%0], %1;" ::"l"(p), "r"(a) : "memory"); }
__device__ __forceinline__ void st_relaxed4(uint4* p, uint32_t a, uint32_t b, uint32_t c, uint32_t d) {
  asm volatile("st.relaxed.gpu.global.v4.u32 [%0], {%1,%2,%3,%4};" ::"l"(p), "r"(a), "r"(b), "r"(c), "r"(d) : "memory");
}
__device__ __forceinline__ void st_relaxed2(uint2* p, uint32_t a, uint32_t b) {
  asm volatile("st.relaxed.gpu.global.v2.u32 [%0], {%1,%2};" ::"l"(p), "r"(a), "r"(b) : "memory");
}
__device__ __forceinline__ void red4(uint4* p, uint32_t a, uint32_t b, uint32_t c, uint32_t d) {
  asm volatile("red.relaxed.gpu.global.add.noftz.v4.bf16x2 [%0], {%1,%2,%3,%4};" ::"l"(p), "r"(a), "r"(b), "r"(c), "r"(d) : "memory");
}
__device__ __forceinline__ void red2(uint2* p, uint32_t a, uint32_t b) {
  asm volatile("red.relaxed.gpu.global.add.noftz.v2.bf16x2 [%0], {%1,%2};" ::"l"(p), "r"(a), "r"(b) : "memory");
}
constexpr int SPIN_MAX = 1 << 21;
__device__ __forceinline__ uint32_t pack_bf16(float lo, float hi) { uint32_t r; asm("cvt.rn.bf16x2.f32 %0, %1, %2;" : "=r"(r) : "f"(hi), "f"(lo)); return r; }
__device__ __forceinline__ float bf_lo(uint32_t v) { return __uint_as_float(v << 16); }
__device__ __forceinline__ float bf_hi(uint32_t v) { return __uint_as_float(v & 0xffff0000u); }
__device__ __forceinline__ float2 lds64(uint32_t a) { float2 v; asm volatile("ld.shared.v2.f32 {%0,%1}, [%2];" : "=f"(v.x), "=f"(v.y) : "r"(a)); return v; }
__device__ __forceinline__ uint32_t lds32(uint32_t a) { uint32_t v; asm volatile("ld.shared.b32 %0, [%1];" : "=r"(v) : "r"(a)); return v; }
__device__ __forceinline__ void sts64f(uint32_t a, float x, float y) { asm volatile("st.shared.v2.f32 [%0], {%1,%2};" ::"r"(a), "f"(x), "f"(y) : "memory"); }
__device__ __forceinline__ void sts32(uint32_t a, uint32_t x) { asm volatile("st.volatile.shared.b32 [%0], %1;" ::"r"(a), "r"(x) : "memory"); }
__device__ __forceinline__ void gate(uint32_t a, int need) {
#pragma unroll 1
  for (int it = 0; it < SPIN_MAX; it++) {
    int v; asm volatile("ld.volatile.shared.b32 %0, [%1];" : "=r"(v) : "r"(a) : "memory");
    if (v >= need) break;
    if (GSLEEP) __nanosleep(GSLEEP);
  }
}
__device__ __forceinline__ void sts128(uint32_t a, uint32_t x, uint32_t y, uint32_t z, uint32_t u) { asm volatile("st.shared.v4.b32 [%0], {%1,%2,%3,%4};" ::"r"(a), "r"(x), "r"(y), "r"(z), "r"(u) : "memory"); }
__device__ __forceinline__ uint4 lds128(uint32_t a) { uint4 v; asm volatile("ld.shared.v4.u32 {%0,%1,%2,%3}, [%4];" : "=r"(v.x), "=r"(v.y), "=r"(v.z), "=r"(v.w) : "r"(a) : "memory"); return v; }
__device__ __forceinline__ uint32_t hmul2(uint32_t a, uint32_t b) { uint32_t r; asm("mul.rn.bf16x2 %0, %1, %2;" : "=r"(r) : "r"(a), "r"(b)); return r; }
__device__ __forceinline__ uint32_t hadd2(uint32_t a, uint32_t b) { uint32_t r; asm("add.rn.bf16x2 %0, %1, %2;" : "=r"(r) : "r"(a), "r"(b)); return r; }
__device__ __forceinline__ void stsm4(uint32_t a, uint32_t r0, uint32_t r1, uint32_t r2, uint32_t r3) {
  asm volatile("stmatrix.sync.aligned.m8n8.x4.shared.b16 [%0], {%1,%2,%3,%4};" ::"r"(a), "r"(r0), "r"(r1), "r"(r2), "r"(r3) : "memory");
}
__device__ __forceinline__ void stsm2(uint32_t a, uint32_t r0, uint32_t r1) {
  asm volatile("stmatrix.sync.aligned.m8n8.x2.shared.b16 [%0], {%1,%2};" ::"r"(a), "r"(r0), "r"(r1) : "memory");
}
__device__ __forceinline__ uint4 ldsm4(uint32_t a) {
  uint4 r; asm volatile("ldmatrix.sync.aligned.m8n8.x4.shared.b16 {%0,%1,%2,%3}, [%4];" : "=r"(r.x), "=r"(r.y), "=r"(r.z), "=r"(r.w) : "r"(a) : "memory"); return r;
}
__device__ __forceinline__ uint32_t movm(uint32_t a) { uint32_t r; asm("movmatrix.sync.aligned.m8n8.trans.b16 %0, %1;" : "=r"(r) : "r"(a)); return r; }
__device__ __forceinline__ void mma16816z(float (&d)[4], uint32_t a0, uint32_t a1, uint32_t a2, uint32_t a3, uint32_t b0, uint32_t b1) {
  asm("mma.sync.aligned.m16n8k16.row.col.f32.bf16.bf16.f32 {%0,%1,%2,%3}, {%4,%5,%6,%7}, {%8,%9}, {%10,%10,%10,%10};"
      : "=f"(d[0]), "=f"(d[1]), "=f"(d[2]), "=f"(d[3]) : "r"(a0), "r"(a1), "r"(a2), "r"(a3), "r"(b0), "r"(b1), "f"(0.f));
}
__device__ __forceinline__ void mma16816(float (&d)[4], const uint4& a, uint32_t b0, uint32_t b1) {
  asm("mma.sync.aligned.m16n8k16.row.col.f32.bf16.bf16.f32 {%0,%1,%2,%3}, {%4,%5,%6,%7}, {%8,%9}, {%0,%1,%2,%3};"
      : "+f"(d[0]), "+f"(d[1]), "+f"(d[2]), "+f"(d[3]) : "r"(a.x), "r"(a.y), "r"(a.z), "r"(a.w), "r"(b0), "r"(b1));
}
__device__ __forceinline__ void mma1688(float (&d)[4], uint32_t a0, uint32_t a1, uint32_t b0) {
  asm("mma.sync.aligned.m16n8k8.row.col.f32.bf16.bf16.f32 {%0,%1,%2,%3}, {%4,%5}, {%6}, {%0,%1,%2,%3};"
      : "+f"(d[0]), "+f"(d[1]), "+f"(d[2]), "+f"(d[3]) : "r"(a0), "r"(a1), "r"(b0));
}
__device__ __forceinline__ float quad_sum(float v) { v += __shfl_xor_sync(0xffffffffu, v, 1); v += __shfl_xor_sync(0xffffffffu, v, 2); return v; }
__device__ __forceinline__ float quad_max(float v) { v = fmaxf(v, __shfl_xor_sync(0xffffffffu, v, 1)); v = fmaxf(v, __shfl_xor_sync(0xffffffffu, v, 2)); return v; }
__device__ __forceinline__ float rcp(float x) { float r; asm("rcp.approx.ftz.f32 %0, %1;" : "=f"(r) : "f"(x)); return r; }
__device__ __forceinline__ float rsq(float x) { float r; asm("rsqrt.approx.ftz.f32 %0, %1;" : "=f"(r) : "f"(x)); return r; }
__device__ __forceinline__ float ex2(float x) { float r; asm("ex2.approx.ftz.f32 %0, %1;" : "=f"(r) : "f"(x)); return r; }
__device__ __forceinline__ uint32_t chk(uint32_t acc, uint32_t v, uint32_t tag) { uint32_t r; asm("lop3.b32 %0, %1, %2, %3, 0xF6;" : "=r"(r) : "r"(acc), "r"(v), "r"(tag)); return r; }
__device__ __forceinline__ uint32_t chk2(uint32_t a, uint32_t b, uint32_t tag) { uint32_t r; asm("lop3.b32 %0, %1, %2, %3, 0x7E;" : "=r"(r) : "r"(a), "r"(b), "r"(tag)); return r; }
__device__ __forceinline__ uint32_t tagged(uint32_t v, uint32_t tag) { return (v & ~1u) | tag; }

__device__ __forceinline__ int group_k0(int g, int j) {
  const int h = g >= 9, r = g - 2 - 7 * h;
  return g < 2 ? 64 * j + 32 * g : g < 16 ? 64 * (r + (r >= j)) + 32 * h : 32 * g;
}
__device__ __forceinline__ uint32_t xin_off(int c, int w) { return SM_X + (2 * c + w) * 8192; }
__device__ __forceinline__ uint32_t xin_bar(int c) { return BAR_FULLX + 8 * (c < 8 ? c ^ 4 : c); }
__device__ __forceinline__ constexpr uint32_t qkv_xslot(int g) { return g < 5 || g > 11 ? 2 : (0x5140762u >> (4 * (g - 5))) & 15; }

template <int N> struct IC { static constexpr int v = N; };

struct Cons {
  uint32_t sb;
  uint32_t rem;
  uint32_t sB, mB;
  uint32_t mX;
  bool elect;
  __device__ __forceinline__ void release2(uint32_t bar) const { if (elect) { mbar_arrive(sb + bar); mbar_arrive_remote(rem + bar); } }
  __device__ __forceinline__ uint32_t nextB(uint32_t& prev) {
    mbar_wait_c(sb + BAR_FULLB + sB, mB);
    const uint32_t a = (((sb & 0x3FFFF) + SM_B) >> 4) + sB * (BSLOT / 128);
    prev = sB == 0 ? 32 : sB - 8;
    sB += 8;
    if (sB == 40) { sB = 0; mB ^= 1; }
    return a;
  }
  __device__ __forceinline__ void progress(uint32_t v) const { if (elect) sts32(sb + SM_PROG + (threadIdx.x >> 5), v); }
  __device__ __forceinline__ void releaseLastB() const { release2(BAR_EMPTYB + (sB == 0 ? 32 : sB - 8)); }
};

__device__ __forceinline__ float2 gather_sums(const uint2* a, uint32_t stag) {
  uint2 sa, sc;
  do { sa = ld_relaxed2(a); sc = ld_relaxed2(a + 8); } while (__any_sync(0xffffffffu, chk2(sa.x, sc.x, stag) & 3));
  return make_float2(quad_sum(__uint_as_float(sa.x) + __uint_as_float(sc.x)), quad_sum(__uint_as_float(sa.y) + __uint_as_float(sc.y)));
}

struct Norm {
  float m0, m1;
  uint32_t nm0, nm1;
  float d0, d1;
  uint2 u0, u1;
  __device__ __forceinline__ Norm(float2 sum) : m0(sum.x * (-1.f / 576)), m1(sum.y * (-1.f / 576)), nm0(pack_bf16(m0, m0)), nm1(pack_bf16(m1, m1)), d0(0.f), d1(0.f) {}
  __device__ __forceinline__ uint4 centre(const uint4& a) const { return make_uint4(hadd2(a.x, nm0), hadd2(a.y, nm1), hadd2(a.z, nm0), hadd2(a.w, nm1)); }
  __device__ __forceinline__ void sqr(uint32_t a, uint32_t b) {
    d0 = fmaf(bf_lo(a), bf_lo(a), fmaf(bf_hi(a), bf_hi(a), d0)); d1 = fmaf(bf_lo(b), bf_lo(b), fmaf(bf_hi(b), bf_hi(b), d1));
  }
  __device__ __forceinline__ void send(uint2* a, int t, uint32_t stag) {
    d0 = quad_sum(d0); d1 = quad_sum(d1);
    if ((t & 3) == 0) st_relaxed2(a, (__float_as_uint(d0) & ~3u) | stag, __float_as_uint(d1));
  }
  __device__ __forceinline__ void fetch(const uint2* a) { u0 = ld_relaxed2(a); u1 = ld_relaxed2(a + 8); }
  __device__ __forceinline__ float2 rstd(const uint2* a, uint32_t stag) {
    while (__any_sync(0xffffffffu, chk2(u0.x, u1.x, stag) & 3)) fetch(a);
    const float e0 = bf_lo(nm0) - m0, e1 = bf_lo(nm1) - m1;
    const float v0 = fmaf(quad_sum(__uint_as_float(u0.x) + __uint_as_float(u1.x)), 1.f / 576, -e0 * e0);
    const float v1 = fmaf(quad_sum(__uint_as_float(u0.y) + __uint_as_float(u1.y)), 1.f / 576, -e1 * e1);
    float2 r = make_float2(rsq(fmaxf(v0, 0.f) + 1e-5f), rsq(fmaxf(v1, 0.f) + 1e-5f));
    asm volatile("" : "+f"(r.x), "+f"(r.y));
    return r;
  }
};

template <class Pre, class Mma>
__device__ __forceinline__ float2 ln_gemm_in(Cons& c, Group* G, uint32_t (&p)[18], float2& sum, int w, int st0, int j, int t, Pre&& pre, Mma&& mma) {
  const uint32_t xa = c.sb + (t >> 5) * 2048 + (t & 15) * 128, sw = (((t >> 4) & 1) ^ (t & 7)) * 16;
  float ra[4] = {0.f, 0.f, 0.f, 0.f}, rb[4] = {0.f, 0.f, 0.f, 0.f};
#pragma unroll 1
  for (int cc = 0; cc < 9; cc++) {
    const uint32_t a = xa + xin_off(cc, w);
    mbar_wait_c(c.sb + xin_bar(cc), 0);
    const uint4 u0 = ldsm4(a + sw), u1 = ldsm4(a + (sw ^ 32)), u2 = ldsm4(a + (sw ^ 64)), u3 = ldsm4(a + (sw ^ 96));
    mma16816(ra, u0, 0x3f803f80u, 0x3f803f80u); mma16816(rb, u1, 0x3f803f80u, 0x3f803f80u);
    mma16816(ra, u2, 0x3f803f80u, 0x3f803f80u); mma16816(rb, u3, 0x3f803f80u, 0x3f803f80u);
  }
  sum = make_float2(ra[0] + rb[0], ra[2] + rb[2]);
  pre(0);
  Norm n(sum);
  n.u0 = n.u1 = make_uint2(0, 0);
  auto stats = [&] {
#pragma unroll
    for (int k = 0; k < 5; k++) {
      const uint4 u = ldsm4(xa + (k < 4 ? xin_off(j, w) + (sw ^ (32 * k)) : xin_off(8, w) + ((j ^ (t & 7)) << 4))), e = n.centre(u);
      p[4 * k] = u.x; p[4 * k + 1] = u.y;
      n.sqr(e.x, e.y);
      if (k < 4) { p[4 * k + 2] = u.z; p[4 * k + 3] = u.w; n.sqr(e.z, e.w); }
    }
    n.send(G->sq + st0 + 8 * j, t, 1);
  };
  if (STATP < 0) stats();
  else {
#pragma unroll
    for (int i = 0; i < 18; i++) p[i] = 0;
  }
  pre(1);
  float2 r = make_float2(0.f, 0.f);
  uint4 y0 = ldsm4(xa + xin_off(0, w) + sw), y1 = ldsm4(xa + xin_off(0, w) + (sw ^ 32));
#pragma unroll 1
  for (int cc = 0; cc < 9; cc++) {
#pragma unroll
    for (int i = 0; i < 2; i++) {
      const uint4 f0 = n.centre(y0), f1 = n.centre(y1);
      const uint32_t a = xa + xin_off(min(cc + i, 8), w);
      y0 = ldsm4(a + (sw ^ (64 - 64 * i))); y1 = ldsm4(a + (sw ^ (96 - 64 * i)));
      uint32_t prev;
      const uint32_t bb = c.nextB(prev);
      mma(true, bb, f0, f1);
      if (i == 1) {
        if (STATP >= 0 && cc == STATP * w) stats();
        if (cc == 1) c.progress(3);
        if (cc == 5) n.fetch(G->sq + st0 + 16 * (t & 3));
        if (cc == 7) r = n.rstd(G->sq + st0 + 16 * (t & 3), 1);
        if (cc == 8 && w == 0) asm volatile("bar.arrive 6, 256;" ::: "memory");
      }
      wg_wait<1>();
      if (i + cc > 0) c.release2(BAR_EMPTYB + prev);
      if (2 * cc + i >= WOG && 2 * cc + i < WOG + 4) c.release2(BAR_EMPTYX + 32 + 8 * (2 * cc + i - WOG));
    }
  }
  c.mX = 0xff;
  if (w == 1) asm volatile("bar.sync 6, 256;" ::: "memory");
  wg_wait<0>();
  c.releaseLastB();
  c.release2(BAR_EMPTYX + 24);
  return r;
}

template <bool QKV, class Pre, class Mma>
__device__ __forceinline__ float2 ln_gemm(Cons& c, Group* G, const float (&v)[36], uint32_t (&p)[18], float2& sum, int st0, int j, int t,
                                          int layer, uint32_t tag, Pre&& pre, Mma&& mma) {
  constexpr bool known = !QKV && EARLY;
  const uint32_t stag = (2 * layer + (QKV ? 1 : 2)) & 3;
  uint4 x[6][2];
  uint4* src = G->xbox + t;
  asm volatile("" : "+l"(src));
  auto buf = [&](int g) -> uint4 (&)[2] { return x[g < 16 ? (g - 2) % 6 : g - 13]; };
  auto load = [&](int g0) {
#pragma unroll
    for (int g = g0; g < g0 + (g0 < 14 ? 3 : 2); g++) {
      const uint4* a = g < 16 ? src + ((g - 2) % 7 >= j ? 256 : 0) + (2 * ((g - 2) % 7) + 16 * (g >= 9)) * 128 : src + 2 * g * 128;
      buf(g)[0] = ld_relaxed4(a); buf(g)[1] = ld_relaxed4(a + 128);
    }
  };
  auto invalid = [&](int g, uint32_t tag) {
    uint32_t bad = chk(chk(chk2(buf(g)[0].x, buf(g)[1].x, tag), buf(g + 1)[0].x, tag), buf(g + 1)[1].x, tag);
    if (g < 14) bad = chk(chk(bad, buf(g + 2)[0].x, tag), buf(g + 2)[1].x, tag);
    if (g == 16) bad = chk(chk(chk(chk(bad, buf(g)[0].z, tag), buf(g)[1].z, tag), buf(g + 1)[0].z, tag), buf(g + 1)[1].z, tag);
    return __any_sync(0xffffffffu, bad & 1);
  };
  uint4* const d = src + 2 * j * 128;
  const int sq = st0 + 16 * (t & 3);
  if (!known) {
    float s0 = v[0] + v[1], s1 = v[2] + v[3];
#pragma unroll
    for (int i = 1; i < 9; i++) { s0 += v[4 * i] + v[4 * i + 1]; s1 += v[4 * i + 2] + v[4 * i + 3]; }
    s0 = quad_sum(s0); s1 = quad_sum(s1);
    if ((t & 3) == 0) st_relaxed2(G->sum + st0 + 8 * j, (__float_as_uint(s0) & ~3u) | stag, __float_as_uint(s1));
  }
#pragma unroll
  for (int i = 0; i < 18; i++) p[i] = pack_bf16(v[2 * i], v[2 * i + 1]);
#pragma unroll
  for (int i = 0; i < 2; i++) st_relaxed4(d + i * 128, tagged(p[4 * i], tag), p[4 * i + 1], p[4 * i + 2], p[4 * i + 3]);
  pre(0);
  if (!known) {
    sum = gather_sums(G->sum + sq, stag);
    load(2);
  }
  Norm n(sum);
  pre(1);
  const uint32_t* probe = &(G->xbox + (2 * (t & XPM) + 1) * 128 + (t | 31))->x;
  uint32_t pv;
  float2 r;
  auto inx = [](int g) { return QKV && ((g >= 5 && g < 12) || g == 17); };
  auto use = [](int g) { return QKV ? (g < 5 ? 108 : 101) + g : 18 + g; };
#pragma unroll
  for (int g = 0; g < 18; g++) {
    if (g < 16 ? g % 3 == 2 : g == 16) {
      const uint32_t lt = late(c.sb + BAR_FULLX + 64, tag);
      while (invalid(g, lt)) load(g);
      if (g < 16) load(g < 14 ? g + 3 : 16);
    }
    const uint4 f0 = n.centre(g < 2 ? make_uint4(p[8 * g], p[8 * g + 1], p[8 * g + 2], p[8 * g + 3]) : buf(g)[0]);
    const uint4 f1 = n.centre(g < 2 ? make_uint4(p[8 * g + 4], p[8 * g + 5], p[8 * g + 6], p[8 * g + 7]) : buf(g)[1]);
    if (g == 11) n.fetch(G->sq + sq);
    if (g == 16) r = n.rstd(G->sq + sq, stag);
    if (inx(g)) mbar_wait_c(c.sb + BAR_FULLX + 8 * qkv_xslot(g), ((0x34 >> qkv_xslot(g)) & 1) ^ (g == 17));
    else mbar_wait_c(c.sb + BAR_FULLB + 8 * (use(g) % 5), (use(g) / 5) & 1);
    mma(g, ((c.sb & 0x3FFFF) >> 4) + ((inx(g) ? xslot(qkv_xslot(g)) : SM_B + (use(g) % 5) * BSLOT) >> 4), f0, f1);
    if (g == 1) { wg_wait<1>(); c.release2(BAR_EMPTYB + 8 * (use(0) % 5)); }
    if (g < 2) {
      if (known) {
        if (g == 0) {
          pv = tag;
          if (!ESPEC || layer == 0) pv = ld_relaxed(probe);
        } else {
          const uint32_t lt = late(c.sb + BAR_FULLX + 64, tag);
          while (__any_sync(0xffffffffu, (pv ^ lt) & 1)) pv = ld_relaxed(probe);
          load(2);
        }
      }
      if (g == (known ? 1 : 0)) {
#pragma unroll
        for (int i = 2; i < 4; i++) st_relaxed4(d + (14 + i) * 128, tagged(p[4 * i], tag), p[4 * i + 1], p[4 * i + 2], p[4 * i + 3]);
        st_relaxed2((uint2*)(src + (32 + (j >> 1)) * 128) + (j & 1), tagged(p[16], tag), p[17]);
      }
      n.sqr(f0.x, f0.y); n.sqr(f0.z, f0.w); n.sqr(f1.x, f1.y); n.sqr(f1.z, f1.w);
      if (g == 1) {
        n.sqr(hadd2(p[16], n.nm0), hadd2(p[17], n.nm1));
        n.send(G->sq + st0 + 8 * j, t, stag);
      }
    }
    if (g == 1 && !QKV) { wg_wait<0>(); c.release2(BAR_EMPTYB + 8 * (use(1) % 5)); }
    else wg_wait<1>();
    if (g > (QKV ? 1 : 2) && !inx(g - 1)) c.release2(BAR_EMPTYB + 8 * (use(g - 1) % 5));
    if (QKV && g < 13) c.progress(33 + g);
    if (QKV && g == WOG - 1) c.release2(BAR_EMPTYX + 8 * qkv_xslot(17));
    if (QKV && g >= WOG && g < WOG + 4) c.release2(BAR_EMPTYX + 32 + 8 * (g - WOG));
  }
  if (QKV) c.mX = 0x34 ^ 0xf3;
  else { c.sB = 8 * (36 % 5); c.mB = (36 / 5) & 1; }
  wg_wait<0>();
  if (!QKV) c.release2(BAR_EMPTYB + 8 * (use(17) % 5));
  return r;
}

template <int NB, int OFF>
__device__ __forceinline__ void glu(const float (&a)[128], uint32_t (&h)[144]) {
#pragma unroll
  for (int b = 0; b < 2 * NB; b++) {
    if (HMUL) h[OFF + b] = hmul2(pack_bf16(a[2 * b], a[2 * b + 1]), pack_bf16(a[4 * NB + 2 * b], a[4 * NB + 2 * b + 1]));
    else h[OFF + b] = pack_bf16(a[2 * b] * a[4 * NB + 2 * b], a[2 * b + 1] * a[4 * NB + 2 * b + 1]);
  }
}

__global__ void __cluster_dims__(2, 1, 1) __launch_bounds__(384, 1)
fused_kernel(const __nv_bfloat16* __restrict__ x_in, Group* ws, const char* __restrict__ wqkv,
             const char* __restrict__ wo, char* __restrict__ out, uint32_t first, const __grid_constant__ Maps maps,
             const char* __restrict__ wg, const char* __restrict__ wu, const char* __restrict__ wd) {
  extern __shared__ __align__(1024) uint8_t smem_raw[];
  const uint32_t sb = smem_u32(smem_raw);
  const uint32_t bx = blockIdx.x - first;
  if (bx >= NCTA) {
    const int e = blockIdx.x & 3;
    const uint32_t par = ~ld_relaxed(ws->flag + 32) & 1;
    __nanosleep(RDELAY);
    if (threadIdx.x < 16) prefetch_l2(wo + (144 * e + 9 * threadIdx.x) * 1152, 9 * 1152);
#pragma unroll 1
    for (int r = threadIdx.x >> 3; r < 144; r += 48) {
      const uint4* row = (const uint4*)(wo + (144 * e + r) * 1152) + (threadIdx.x & 7);
      float a = 0.f;
      uint4 u;
#pragma unroll
      for (int i = 0; i < 72; i += 8) {
        u = __ldg(row + i);
        a += ((bf_lo(u.x) + bf_hi(u.x)) + (bf_lo(u.y) + bf_hi(u.y))) + ((bf_lo(u.z) + bf_hi(u.z)) + (bf_lo(u.w) + bf_hi(u.w)));
      }
      const int h = r >= 72, k = r - 72 * h;
      ((Scratch*)ws)->woc[threadIdx.x & 7][k < 64 ? 64 + 8 * k + ((2 * e + h) ^ (k & 7)) : 576 * h + 8 * (k & 7) + (e ^ (k & 7))] = u;
      a = quad_sum(a);
      a += __shfl_xor_sync(0xffffffffu, a, 4);
      if ((threadIdx.x & 7) == 0) ((Scratch*)ws)->woc[2 * e + h][640 + k] = make_uint4(pack_bf16(a, a - bf_lo(pack_bf16(a, 0.f))), 0, 0, 0);
    }
    fence_gpu();
    __syncthreads();
    if (threadIdx.x == 0) st_relaxed(((Scratch*)ws)->done + e, par);
    const int cc = threadIdx.x % 54, r0 = threadIdx.x / 54, part = cc / 18, jj = 2 * e + (cc % 18) / 9, c9 = cc % 9;
    if (r0 < 6) {
#pragma unroll 4
      for (int k = r0; k < 576; k += 6) {
        const uint4 u = __ldg((const uint4*)(wqkv + k * 3456 + part * 1152 + 144 * jj) + c9);
        ((Scratch*)ws)->wq[jj][k >> 4][c9 < 8 ? part * 128 + (k & 15) * 8 + (c9 ^ (k & 7)) : 384 + part * 16 + (k & 15)] = u;
      }
    }
    fence_gpu();
    __syncthreads();
    if (threadIdx.x == 0) st_relaxed(((Scratch*)ws)->done + 32 + e, par);
    return;
  }
  if (threadIdx.x == 0) asm volatile("prefetch.tensormap [%0];" ::"l"(&maps.x) : "memory");
  const int warp = __shfl_sync(0xffffffffu, threadIdx.x >> 5, 0);
  const int lane = threadIdx.x & 31;
  const int rank = blockIdx.x & 1;
  if (elect_one()) {
    if (warp >= 8) {
#pragma unroll
      for (int i = 0; i < 9; i++) mbar_init(sb + SM_BAR + 72 * (warp - 8) + 8 * i, warp < 10 ? 1 : 4);
      sts32(sb + SM_PROG + 4 * (warp - 8), 0);
      asm volatile("fence.mbarrier_init.release.cluster;" ::: "memory");
    } else if (warp == 1 || warp == 2) {
      asm volatile("prefetch.tensormap [%0];" ::"l"(&maps.x + warp) : "memory");
    } else if (warp == 3) {
      if (PFMODE & 1) prefetch_l2((const char*)x_in + bx * 18432, 18432);
    } else if (warp == 4) {
      if (PFMODE & 2) prefetch_l2(wqkv + bx * (15552 / PFQ), 15552 / PFQ);
    }
  }
  __syncwarp();
  asm volatile("barrier.cluster.arrive.relaxed.aligned;" ::: "memory");
  if (warp == 8) PROFX(53);
  int lb = bx;
  if (GPCMAP) {
    const int cl = bx >> 1, u = cl - 36;
    lb = (cl < 4 ? cl : cl < 36 ? 8 * ((cl - 4) & 7) + ((cl - 4) >> 3) + (((cl - 4) & 7) ? 0 : 4) : 8 * (1 + u % 7) + 4 + u / 7) * 2 + rank;
  }
#define CTA_J(b) (((b) >> 1) & 7)
#define CTA_RB(b) ((((b) >> 4) << 1) | ((b) & 1))
  const int j = CTA_J(lb), rb = CTA_RB(lb);

  PROF(23);
  if (warp >= 8) {
    asm volatile("setmaxnreg.dec.sync.aligned.u32 " STR(REGS_P) ";");
    auto x_chunk = [&](int cc) {
      mbar_expect_tx(sb + xin_bar(cc), 16384);
      tma3d(sb + xin_off(cc, 0), &maps.x, 64 * cc, 0, 64 * rb, sb + xin_bar(cc));
      tma3d(sb + xin_off(cc, 1), &maps.x, 64 * cc, 1, 64 * rb, sb + xin_bar(cc));
    };
    if (warp == 9 && elect_one()) {
      fence_async_smem();
#pragma unroll 1
      for (int i = 0; i < 9; i++) x_chunk(i);
    }
    __syncwarp();
    if (warp == 9) PROFX(54);
    asm volatile("barrier.cluster.wait.aligned;" ::: "memory");
    if (warp == 8) PROFX(56);
    const uint64_t pol = W_POLICY(), pola = A_POLICY();
    uint4 (* const wq)[432] = ((Scratch*)ws)->wq[j];
    const uint32_t par = ~ld_relaxed(ws[2 * rb].flag + 32 + 32 * j) & 1;
    auto qkv_group = [&](bool copy, int k, uint32_t dst, uint32_t bar) {
      if (copy) {
        wbulk(dst + rank * 8192, wq[(k >> 4) + rank], 6912, bar, pol);
      } else {
        wtma3d(dst + rank * 8192, &maps.qm, 72 * j, k + 16 * rank, 0, bar, pola);
        wtma3d(dst + rank * 8192 + 6144, &maps.qc, 72 * j + 64, k + 16 * rank, 0, bar, pola);
      }
    };
    auto chore = [&](int i) {
#pragma unroll 1
      for (int it = 0; it < SPIN_MAX; it++)
        if (__all_sync(0xffffffffu, ld_acquire(((Scratch*)ws)->done + i) == par)) break;
      asm volatile("fence.proxy.async.global;" ::: "memory");
    };
    const int ktab = group_k0(lane, j);
    auto qkv_gate = [&](int g) { if (g >= 8) gate(sb + SM_PROG, 33 + ((g - 8) * QPACE >> 4)); };
    if (warp == 8) {
      uint32_t s = 0, ph = 1;
      auto slot = [&](uint32_t bytes, auto&& issue) {
        const uint32_t bar = sb + BAR_FULLB + 8 * s;
        mbar_wait(sb + BAR_EMPTYB + 8 * s, ph);
        if (elect_one()) {
          mbar_expect_tx(bar, bytes);
          issue(sb + SM_B + s * BSLOT, bar);
        }
        if (++s == 5) { s = 0; ph ^= 1; }
      };
#pragma unroll 1
      for (int layer = 0; layer < NLAYERS; layer++) {
        if (layer) chore(32 + (j >> 1));
#pragma unroll 1
        for (int g = 0; g < 18 - layer; g += layer && g == 4 ? 8 : 1) {
          const int k = layer ? __shfl_sync(0xffffffffu, ktab, g) : 32 * g;
          if (layer) qkv_gate(g);
          else if (g == QD) mbar_wait(sb + xin_bar(XH), 0);
          slot(2 * 6912, [&](uint32_t dst, uint32_t bar) { qkv_group(layer, k, dst, bar); });
        }
        if (!FCH) {
          gate(sb + SM_PROG, 32 * layer + 20);
          gate(sb + SM_PROG + 4, 32 * layer + 20);
        }
#pragma unroll 1
        for (int t = 0; t < 5; t++) {
          const CUtensorMap* m = &maps.g + (t < 3 ? rank : 2 + rank);
          asm volatile("" : "+l"(m));
          const int c2 = t < 3 ? 9 * j + 2 * t : 18 * j + 3 + 3 * t;
          const uint32_t half = t < 3 ? 8192 : 6144;
          auto tile = [&](int g) {
            const int k = __shfl_sync(0xffffffffu, ktab, g);
            slot(2 * half, [&](uint32_t dst, uint32_t bar) { wtma3d(dst + rank * half, m, 0, k, c2, bar, pol); });
          };
          int g = 0;
          if (t == 0) {
#pragma unroll 1
            for (; g < 5; g++) {
              mbar_wait(sb + BAR_FULLB + 8 * (s < FCH ? s + 5 - FCH : s - FCH), s < FCH ? ph : ph ^ 1);
              if (FG >= 0 && g == FN) gate(sb + SM_PROG + 4, 32 * layer + 20);
              tile(g);
            }
          }
#pragma unroll 1
          for (; g < 18; g++) tile(g);
        }
      }
    } else if (warp == 9) {
      uint32_t mE = 0;
      auto acquire = [&](uint32_t s) { mbar_wait(sb + BAR_EMPTYX + 8 * s, (mE >> s) & 1); mE ^= 1u << s; };
      auto landed = [&](uint32_t s) { mbar_wait(sb + BAR_FULLX + 8 * s, (mE >> s) & 1); };
      auto slot = [&](uint32_t s, const CUtensorMap* m, int col, int row, uint64_t pol) {
        acquire(s);
        if (elect_one()) {
          mbar_expect_tx(sb + BAR_FULLX + 8 * s, XSLOT);
          wtma2d(sb + xslot(s) + rank * 9216, m, col, row + 72 * rank, sb + BAR_FULLX + 8 * s, pol);
        }
      };
#pragma unroll 1
      for (int layer = 0; layer < NLAYERS; layer++) {
        if (layer) chore(32 + (j >> 1));
#pragma unroll 1
        for (int g = 5; g < 18 * layer; g += g == 11 ? 6 : 1) {
          const uint32_t s = qkv_xslot(g);
          const int k = __shfl_sync(0xffffffffu, ktab, g);
          if (g < 12) qkv_gate(g);
          acquire(s);
          if (elect_one()) {
            mbar_expect_tx(sb + BAR_FULLX + 8 * s, 2 * 6912);
            qkv_group(true, k, sb + xslot(s), sb + BAR_FULLX + 8 * s);
          }
          if (XCH & 1) landed(s);
        }
#pragma unroll 1
        for (int i = 0; i < 4; i++) { slot(4 + i, &maps.o, 64 * j, 144 * i, pola); if (XCH & 2) landed(4 + i); }
        if (layer == 0) { chore(lane & 3); PROFX(57); }
        acquire(3);
        if (elect_one()) {
          mbar_expect_tx(sb + BAR_FULLX + 24, 10240 + 1280);
          wbulk(sb + SM_WOC + rank * 5120, ((Scratch*)ws)->woc[j] + rank * 320, 5120, sb + BAR_FULLX + 24, pola);
          wbulk(sb + SM_WSUM + rank * 640, ((Scratch*)ws)->woc[j] + 640 + rank * 40, 640, sb + BAR_FULLX + 24, pola);
        }
#pragma unroll 1
        for (int u = 0; u < 36; u++) {
          const uint32_t s = 4 * (u & 1) + ((u >> 1) & 3);
          slot(s, &maps.d, u < 4 ? 512 : 64 * ((j + (u >> 2)) & 7), 576 * j + 144 * (u & 3), pol);
          if ((XCH & 4) && u < 3) landed(s);
        }
      }
    } else {
      const int w = warp - 10, grp = 2 * rb + w;
      if (PFMODE & 4) {
        mbar_wait(sb + xin_bar(XP), 0);
        if (lane == 0) prefetch_l2(wqkv + (2 * bx + w) * 7776, 7776);
      }
      gate(sb + SM_PROG, 3);
      if (w == 0) PROFX(58);
      auto prefetch_gu = [&](int l0, int n) {
#pragma unroll 1
        for (int i = lane; i < 36 * n; i += 32) {
          asm volatile("prefetch.global.L2 [%0];" ::"l"((w ? wu : wg) + (size_t)(36 * rb + i / n) * 9216 + 1152 * j + 128 * (l0 + i % n)));
          __nanosleep(PFSLEEP);
        }
      };
      auto clear = [&](uint4* p, int n) {
#pragma unroll 1
        for (int i = lane; i < n; i += 64) { st_relaxed4(p + i, 0, 0, 0, 0); st_relaxed4(p + i + 32, 0, 0, 0, 0); __nanosleep(CLRSLEEP); }
      };
      auto exchange = [&](uint32_t v, uint32_t bar) {
        if (FENCE1) { if (lane == 0) fence_gpu(); } else fence_gpu();
        __syncwarp();
        if (w == 0 && v != 1) PROFX(64 + 58 - 2 * v);
        if (lane == 0) st_relaxed(ws[grp].flag + j, v);
#pragma unroll 1
        for (int it = 0; it < SPIN_MAX; it++) {
          const uint32_t f = ld_relaxed(ws[grp].flag + (lane & 7));
          if (__all_sync(0xffffffffu, v ? f >= v : f == 0)) break;
        }
        if (lane == 0) mbar_arrive(sb + bar + 8 * w);
      };
      if (MAPPF && w == 0 && lane < 6) asm volatile("prefetch.tensormap [%0];" ::"l"(&maps.o + lane) : "memory");
#pragma unroll 1
      for (int layer = 0; layer < NLAYERS; layer++) {
        gate(sb + SM_PROG, 32 * layer + 3);
        if (PFF & 1) prefetch_gu(0, 2);
        gate(sb + SM_PROG, 32 * layer + 22);
        if (PFF & 2) prefetch_gu(2, 2);
        if (layer == 0) {
          clear(ws[grp].inbox[0] + 2 * j * INBOX, 2 * INBOX);
          exchange(1, BAR_CLR);
          if (w == 0) PROFX(59);
        }
        if (PFF & 2) prefetch_gu(4, 2);
        if (PFF & 4) prefetch_gu(6, 3);
#pragma unroll 1
        for (int i = lane; i < ((PFF & 8) ? 162 : 0); i += 32) {
          asm volatile("prefetch.global.L2 [%0];" ::"l"(wd + (size_t)(576 * j + 36 * rb + 18 * w) * 1152 + 128 * i));
          __nanosleep(PFSLEEP);
        }
        if (w == 0 && layer == 0) PROFX(60);
        mbar_wait(sb + BAR_REDDONE + 8 * w, layer);
        if (w == 0) PROFX(64 + 53 + 4 * layer);
        exchange(2 - 2 * layer, BAR_RREADY);
        if (w == 0) PROFX(64 + 56 + 4 * layer);
      }
      mbar_wait(sb + BAR_DONE + 8 * w, 0);
    }
  } else {
    asm volatile("setmaxnreg.inc.sync.aligned.u32 " STR(REGS_C) ";");
#define THREAD_IDS()                                                                   \
    int tid_ = threadIdx.x, bid_ = lb;                                                  \
    asm volatile("" : "+r"(tid_), "+r"(bid_));                                          \
    const int w = warp >> 2, wp = warp & 3;                                             \
    const int lane = tid_ & 31, t = tid_ & 127, g = lane >> 2, q = lane & 3;           \
    const int j = CTA_J(bid_), rb = CTA_RB(bid_), grp = 2 * rb + w;                    \
    const int st0 = wp * 64 + g;                         \
    Group* const G = ws + grp;                                                         \
    const uint32_t dsb = (sb & 0x3FFFF) >> 4;                                          \
    (void)t; (void)g; (void)q; (void)grp; (void)j; (void)st0; (void)dsb; (void)G
    Cons c;
    c.sb = sb; c.sB = 0; c.mB = 0; c.mX = 0; c.elect = (threadIdx.x & 127) == 0;
    asm volatile("mapa.shared::cluster.u32 %0, %1, %2;" : "=r"(c.rem) : "r"(sb), "r"(rank ^ 1));
    float v[36], a1[96], a2[12];
    float2 sum, rs;
    uint32_t res[18], xtag;
    auto qkv_mma = [&](bool acc, uint32_t bb, const uint4& f0, const uint4& f1) {
      wg_fence();
      wgmma_ra<192>(a1, f0, desc_hi(2048, 1024, 1) + bb, acc);
      wgmma_ra<24>(a2, f0, desc_hi(128, 256, 0) + (bb + 384), acc);
      wgmma_ra<192>(a1, f1, desc_hi(2048, 1024, 1) + (bb + 512), true);
      wgmma_ra<24>(a2, f1, desc_hi(128, 256, 0) + (bb + 896), true);
      wg_commit();
    };
    {
      THREAD_IDS();
      if (OPEN) {
        if (q == 0) { st_relaxed2(G->sum + st0 + 8 * j, 0, 0); st_relaxed2(G->sq + st0 + 8 * j, 0, 0); }
        if (wp == 3) {
#pragma unroll
          for (int i = 0; i < 5; i++) st_relaxed4(G->halo + j * 160 + lane + i * 32, 0, 0, 0, 0);
        }
        if (lane >= OPENL) st_relaxed4(G->obox + (8 * WPROBE + j) * 128 + t, 0, 0, 0, 0);
      }
      xtag = __shfl_sync(0xffffffffu, ~ld_relaxed(G->flag + 32 + 32 * j) & 1, 0);
      if (OPEN && EARLY && lane >= OPENL) st_relaxed4(G->xbox + (2 * j + 1) * 128 + t, xtag ^ 1, 0, 0, 0);
      asm volatile("barrier.cluster.wait.aligned;" ::: "memory");
      PROF(0);
#pragma unroll
      for (int i = 0; i < 96; i++) asm volatile("mov.b32 %0, 0;" : "=f"(a1[i]));
#pragma unroll
      for (int i = 0; i < 12; i++) asm volatile("mov.b32 %0, 0;" : "=f"(a2[i]));
      PROF(1);
      rs = ln_gemm_in(c, G, res, sum, w, st0, j, t, [&](int i) { PROF(2 + i); if (i) PROF(4); }, qkv_mma);
    }
#pragma unroll 1
    for (int layer = 0;; layer++) {
      const uint32_t tag = layer ^ 1;
      const int pb = 1 + layer * 30;
      uint4 own[5];
      {
        THREAD_IDS();
        PROF(pb + 4);
        uint32_t kv[3][18];
        auto cvt = [&](int b, float r) {
#pragma unroll
          for (int cc = 0; cc < 18; cc++) {
            const float* a = (cc == 8 ? a2 + 4 : cc == 17 ? a2 + 8 : cc < 8 ? a1 + 32 + 4 * cc : a1 + 28 + 4 * cc) + 2 * (b - 1);
            const uint32_t u = pack_bf16(a[0] * r, a[1] * r);
            kv[b][cc] = cc < 9 ? u : movm(u);
          }
        };
        cvt(2, rs.y);
#pragma unroll
        for (int i = 0; i < 18; i += 4) kv[2][i] = tagged(kv[2][i], tag);
        const uint32_t msg = sb + (w ? xslot(3) : xslot(0) + 24576) + wp * 2304 + lane * 16;
        if (wp == 3) {
          uint4* hp = G->halo + j * 160 + lane;
#pragma unroll
          for (int i = 0; i < 4; i++) st_relaxed4(hp + i * 32, kv[2][4 * i], kv[2][4 * i + 1], kv[2][4 * i + 2], kv[2][4 * i + 3]);
          st_relaxed2((uint2*)(hp + 128), kv[2][16], kv[2][17]);
        } else {
#pragma unroll
          for (int i = 0; i < 4; i++) sts128(msg + i * 512, kv[2][4 * i], kv[2][4 * i + 1], kv[2][4 * i + 2], kv[2][4 * i + 3]);
          sts64f(msg + 2048 - lane * 8, __uint_as_float(kv[2][16]), __uint_as_float(kv[2][17]));
        }
        cvt(1, rs.x);
        uint32_t Q[4][6];
#pragma unroll
        for (int h = 0; h < 4; h++)
#pragma unroll
          for (int i = 0; i < 6; i++) {
            const float* a = 4 * h + i < 16 ? a1 + 8 * h + 2 * i : a2 + 8 * h + 2 * i - 32;
            const uint32_t u = pack_bf16(a[0], a[1]);
            Q[h][i] = i < 2 ? (q >= h ? u : 0) : i < 4 ? u : (q <= h ? u : 0);
          }
        const bool lo0 = 2 * q > g, lo1 = 2 * q + 1 > g;
        const uint32_t M = (lo0 ? 0xffffu : 0u) | (lo1 ? 0xffff0000u : 0u);
        auto scores = [&](int h, int b, float (&s)[4]) {
          mma16816z(s, Q[h][0], Q[h][1], Q[h][2], Q[h][3], kv[b][2 * h], kv[b][2 * h + 1]);
          mma1688(s, Q[h][4], Q[h][5], kv[b][2 * h + 2]);
        };
        auto softmax = [&](float (&l)[4][2], float r, uint32_t (&P)[4]) {
          const float sl = r * (0.23570226039551584f * 1.4426950408889634f);
          float m[4];
#pragma unroll
          for (int h = 0; h < 4; h++) { m[h] = fmaxf(l[h][0], l[h][1]); m[h] = fmaxf(m[h], __shfl_xor_sync(0xffffffffu, m[h], 1)); }
#pragma unroll
          for (int h = 0; h < 4; h++) m[h] = fmaxf(m[h], __shfl_xor_sync(0xffffffffu, m[h], 2)) * sl;
#pragma unroll
          for (int h = 0; h < 4; h++) P[h] = pack_bf16(ex2(fmaf(l[h][0], sl, -m[h])), ex2(fmaf(l[h][1], sl, -m[h])));
        };
        const bool remote = wp == 0 && rb > 0;
        const uint4* hp = (G - 2)->halo + j * 160 + lane;
        auto halo = [&] {
#pragma unroll
          for (int i = 0; i < 4; i++) { const uint4 u = ld_relaxed4(hp + i * 32); kv[0][4 * i] = u.x; kv[0][4 * i + 1] = u.y; kv[0][4 * i + 2] = u.z; kv[0][4 * i + 3] = u.w; }
          const uint2 u = ld_relaxed2((const uint2*)(hp + 128));
          kv[0][16] = u.x; kv[0][17] = u.y;
        };
#pragma unroll
        for (int i = 0; i < 18; i++) kv[0][i] = 0;
        float l0[4][2], l1[4][2];
#pragma unroll
        for (int h = 0; h < 4; h++) {
          float s1[4], s2[4];
          scores(h, 1, s1); scores(h, 2, s2);
          l0[h][0] = s1[0]; l0[h][1] = s1[1];
          l1[h][0] = lo0 ? s1[2] : s2[2]; l1[h][1] = lo1 ? s1[3] : s2[3];
        }
        hp += __float_as_uint(l1[HALOH][0]) & late(sb + BAR_FULLX + 64, 0);
        if (remote) halo();
        uint32_t P0[4], P1[4];
        softmax(l1, rs.y, P1);
        if (remote) {
          while (__any_sync(0xffffffffu, chk(chk2(kv[0][0], kv[0][4], tag) | chk2(kv[0][8], kv[0][12], tag), kv[0][16], tag) & 1)) halo();
        }
        if (FG < 0) c.progress(32 * layer + 20);
        wg_bar(w);
        if (wp > 0) {
          const uint32_t from = msg - 2304;
#pragma unroll
          for (int i = 0; i < 4; i++) { const uint4 u = lds128(from + i * 512); kv[0][4 * i] = u.x; kv[0][4 * i + 1] = u.y; kv[0][4 * i + 2] = u.z; kv[0][4 * i + 3] = u.w; }
          const float2 u = lds64(from + 2048 - lane * 8);
          kv[0][16] = __float_as_uint(u.x); kv[0][17] = __float_as_uint(u.y);
        }
        PROF(pb + 5);
        const bool first = (rb == 0 && wp == 0);
#pragma unroll
        for (int h = 0; h < 4; h++) {
          float s0[4];
          scores(h, 0, s0);
          if (first) s0[0] = s0[1] = -INFINITY;
          l0[h][0] = lo0 ? s0[0] : l0[h][0]; l0[h][1] = lo1 ? s0[1] : l0[h][1];
        }
        softmax(l0, rs.x, P0);
        uint4* ob = G->obox + t;
        uint32_t car0 = 0, car1 = 0;
#pragma unroll
        for (int h = 0; h < 4; h++) {
          float o[3][4], z[4] = {0.f, 0.f, 0.f, 0.f};
          mma1688(z, P0[h], P1[h], 0x3f803f80u);
#pragma unroll
          for (int i = 0; i < 3; i++) {
            mma16816z(o[i], P0[h] & ~M, P1[h] & M, 0u, P1[h] & ~M, kv[1][9 + 2 * h + i], kv[2][9 + 2 * h + i]);
            mma1688(o[i], P0[h] & M, 0u, kv[0][9 + 2 * h + i]);
          }
          const float i0 = rcp(z[0]), i1 = rcp(z[2]);
#pragma unroll
          for (int i = 0; i < 3; i++) { o[i][0] *= i0; o[i][1] *= i0; o[i][2] *= i1; o[i][3] *= i1; }
          const uint32_t o0 = q < h ? car0 : pack_bf16(o[0][0], o[0][1]), o1 = q < h ? car1 : pack_bf16(o[0][2], o[0][3]);
          own[h] = make_uint4(o0 | 1, o1, pack_bf16(o[1][0], o[1][1]), pack_bf16(o[1][2], o[1][3]));
          if (h < OFIRST) st_relaxed4(ob + (8 * h + j) * 128, own[h].x, own[h].y, own[h].z, own[h].w);
          car0 = pack_bf16(o[2][0], o[2][1]); car1 = pack_bf16(o[2][2], o[2][3]);
        }
        car0 = tagged(car0, tag);
        own[4] = make_uint4(car0, car1, 0, 0);
        PROF(pb + 6);
      }
      uint2 sa, sc;
      {
        THREAD_IDS();
        uint4* src = G->obox + t;
        asm volatile("" : "+l"(src));
        uint4 x[32];
        const uint4* from[7];
#pragma unroll
        for (int r = 0; r < 7; r++) { from[r] = src + (r >= j ? 128 : 0); asm volatile("" : "+l"(from[r])); }
        auto load = [&](int i) { x[i] = ld_relaxed4(i < 28 ? from[i % 7] + (8 * (i / 7) + i % 7) * 128 : src + (i + 4) * 128); };
        const uint32_t* probe = &(G->obox + (8 * WPROBE + (lane & 7)) * 128 + (t | 31))->x;
        uint32_t pv = ld_relaxed(probe);
#pragma unroll
        for (int i = 3; i < 8; i++) mbar_wait_c(sb + BAR_FULLX + 8 * i, (c.mX >> i) & 1);
        c.mX ^= 0xf8;
        while (__any_sync(0xffffffffu, ~pv & 1)) pv = ld_relaxed(probe);
        if (layer) PROF(24); else PROF(25);
        if (WOBAR && w == 1) asm volatile("bar.sync 7, 256;" ::: "memory");
#pragma unroll
        for (int i = 0; i < WB1; i++) load(i);
        if (WOBAR && w == 0) asm volatile("bar.arrive 7, 256;" ::: "memory");
#pragma unroll
        for (int h = OFIRST; h < 4; h++) st_relaxed4(src + (8 * h + j) * 128, own[h].x, own[h].y, own[h].z, own[h].w);
        st_relaxed2((uint2*)(src + (32 + (j >> 1)) * 128) + (j & 1), own[4].x, own[4].y);
        if (layer) PROF(26); else PROF(27);
        float a[36];
        auto step = [&](const uint4& f, uint32_t s, int i, bool acc) {
          const uint32_t r = (xslot(4) >> 4) + (i < 4 ? 72 * s + 16 * i : 144 * s + 64) * 8, c = (SM_WOC >> 4) + (i < 4 ? 64 + 128 * i : 0) + s;
          wgmma_ra<72>(a, f, desc_hi(0, i < 4 ? 1024 : 9216, 1) + (dsb + r + ((c - r) << 16)), acc);
        };
        if (OWNBAR) asm volatile("bar.sync 4, 256;" ::: "memory");
        float e[4];
        wg_fence();
        if (EARLY) {
#pragma unroll
          for (int i = 0; i < 5; i++) wgmma_ra<8>(e, own[i], desc_hi(128, 0, 0) + (dsb + (SM_WSUM >> 4) + 16 * i), i > 0);
          wg_commit();
        }
#pragma unroll
        for (int i = 0; i < 4; i++) step(own[i], j, i, i > 0);
        wg_commit();
        if (layer) PROF(28); else PROF(29);
        auto batch = [&](auto e0, auto e1, auto e2, int b) {
          constexpr int E0 = decltype(e0)::v, E1 = decltype(e1)::v, E2 = decltype(e2)::v;
          const uint32_t one = (LATE0 || E0 > 0) && E1 > E0 ? late(sb + BAR_FULLX + 64, 1) : 1;
          while (E1 > E0) {
            uint32_t bad = 0;
#pragma unroll
            for (int i = E0; i < E1; i++) bad = i < 28 ? chk(bad, x[i].x, one) : chk(chk(bad, x[i].x, tag), x[i].z, tag);
            if (!__any_sync(0xffffffffu, bad & 1)) break;
#pragma unroll
            for (int i = E0; i < E1; i++) load(i);
          }
          if (b == 0) PROF(pb + 7);
          if (b == FG) c.progress(32 * layer + 20);
          if (b > 0 && E2 > E1) wg_wait<WOW>();
#pragma unroll
          for (int i = E1; i < E2; i++) load(i);
          if (EARLY && b == 0) {
            wg_wait<1>();
            if (q == 0) st_relaxed2(G->sum + st0 + 8 * j, (__float_as_uint(e[0] + e[1]) & ~3u) | ((2 * layer + 2) & 3), __float_as_uint(e[2] + e[3]));
          }
          if (EARLY && b == SUMB) { sa = ld_relaxed2(G->sum + st0 + 16 * q); sc = ld_relaxed2(G->sum + st0 + 16 * q + 8); }
          if (E1 > E0) {
            wg_fence();
#pragma unroll
            for (int i = E0; i < E1; i++) {
              step(x[i], i % 7 + (i < 28 && i % 7 >= j), i / 7, true);
            }
            wg_commit();
          }
        };
        batch(IC<0>(), IC<WB1>(), IC<WB2>(), 0);
        batch(IC<WB1>(), IC<WB2>(), IC<WB3>(), 1);
        batch(IC<WB2>(), IC<WB3>(), IC<32>(), 2);
        batch(IC<WB3>(), IC<32>(), IC<32>(), 3);
        wg_wait<0>();
        if (w == 0) asm volatile("bar.arrive 3, 256;" ::: "memory");
        PROF(pb + 8);
#pragma unroll
        for (int i = 0; i < 18; i++) {
          v[2 * i] = bf_lo(res[i]) + a[2 * i];
          v[2 * i + 1] = bf_hi(res[i]) + a[2 * i + 1];
        }
      }
      uint32_t lsb;
      uint32_t h[144];
      {
        THREAD_IDS();
        float a[128];
        const uint32_t xd = sb + xslot(4 * w) + (lane >> 4) * 1024 + (16 * wp + (lane & 15)) * 16;
        const float2 rs = ln_gemm<false>(c, G, v, res, sum, st0, j, t, layer, xtag,
          [&](int i) {
            if (i == 0) {
              lsb = ((res[0] & 1) | (res[4] & 1) << 1 | (res[8] & 1) << 2 | (res[12] & 1) << 3 | (res[16] & 1) << 4) ^ (xtag * 31);
              if (EARLY) {
                const uint32_t st = late(sb + BAR_FULLX + 64, (2 * layer + 2) & 3);
                while (__any_sync(0xffffffffu, chk2(sa.x, sc.x, st) & 3)) { sa = ld_relaxed2(G->sum + st0 + 16 * q); sc = ld_relaxed2(G->sum + st0 + 16 * q + 8); }
                sum.x += quad_sum(__uint_as_float(sa.x) + __uint_as_float(sc.x)); sum.y += quad_sum(__uint_as_float(sa.y) + __uint_as_float(sc.y));
              }
              if (w == 1) asm volatile("bar.sync 3, 256;" ::: "memory");
            }
            PROF(pb + 9 + i);
          },
          [&](int gi, uint32_t bb, const uint4& f0, const uint4& f1) {
            if (gi == 0) PROF(pb + 11);
            if (TLEAD0 && gi == 18 - TLEAD0 && w == 1) asm volatile("bar.sync 5, 256;" ::: "memory");
            wg_fence();
            wgmma_ra<256>(a, f0, desc_hi(4096, 1024, 1) + bb, gi > 0);
            wgmma_ra<256>(a, f1, desc_hi(4096, 1024, 1) + (bb + 128), true);
            wg_commit();
            if (TLEAD0 && gi == 17 && w == 0) asm volatile("bar.arrive 5, 256;" ::: "memory");
            stsm4(xd + gi * 4096, f0.x, f0.y, f0.z, f0.w);
            stsm4(xd + gi * 4096 + 2048, f1.x, f1.y, f1.z, f1.w);
            if (gi == 17) { fence_async_smem(); wg_bar(w); }
          });
        sts64f(sb + SM_KEEP + (tid_ >> 2) * 8, rs.x * rs.x, rs.y * rs.y);
        c.progress(32 * layer + 22);
        PROF2(pb + 12);
        glu<16, 0>(a, h);
        const Desc da0 = desc_hi(1024, 128, 0) + (dsb + (xslot(4 * w) >> 4));
        auto tile = [&](auto wide, auto last) {
          const uint32_t xe = BAR_EMPTYX + 32 * (t & 1) + 4 * (t & 6);
          auto group = [&](int gi) {
            uint32_t prev;
            const uint32_t bb = c.nextB(prev);
            const Desc da = da0 + gi * 256;
            wg_fence();
            if (wide()) {
              wgmma_ss<256>(a, da, desc_hi(4096, 1024, 1) + bb, gi);
              wgmma_ss<256>(a, da + 128, desc_hi(4096, 1024, 1) + (bb + 128), 1);
            } else {
              wgmma_ss<192>(*(float(*)[96])a, da, desc_hi(2048, 512, 2) + bb, gi);
              wgmma_ss<192>(*(float(*)[96])a, da + 128, desc_hi(2048, 512, 2) + (bb + 64), 1);
            }
            wg_commit();
            if (gi == 17 && w == 0) asm volatile("bar.arrive 5, 256;" ::: "memory");
            wg_wait<1>();
            if (gi > 0 && !(last() && gi > 13)) c.release2(BAR_EMPTYB + prev);
            if (last() && gi >= XREL && !((gi ^ XREL) & 1)) c.release2(BAR_EMPTYX + 16 * ((gi - XREL) & 2) + 2 * ((gi - XREL) & 12));
          };
          int gi = 0, end = w ? 18 - (wide() ? TLEAD2 : TLEAD) : 18;
#pragma unroll 1
          while (true) {
#pragma unroll 1
            for (; gi < end; gi++) group(gi);
            if (end == 18) break;
            asm volatile("bar.sync 5, 256;" ::: "memory");
            end = 18;
          }
          wg_wait<0>();
          if (!last()) c.releaseLastB();
          if (last() && t >= (19 - XREL) / 2 && t < 8) { mbar_arrive(sb + xe); mbar_arrive_remote(c.rem + xe); }
        };
        auto yes = [] { return true; };
        auto no = [] { return false; };
        tile(yes, no); PROF2(pb + 13); glu<16, 32>(a, h);
        tile(yes, no); PROF2(pb + 14); glu<16, 64>(a, h);
        tile(no, no); PROF2(pb + 15); glu<12, 96>(a, h);
        const uint32_t hole = sb + SM_B + 12288 + tid_ * 16;
#pragma unroll
        for (int i = 0; i < NSPILL; i++) sts128(hole + i * BSLOT, h[96 + 4 * i], h[97 + 4 * i], h[98 + 4 * i], h[99 + 4 * i]);
        if (w == 1) asm volatile("bar.arrive 8, 256;" ::: "memory");
        tile(no, yes); PROF2(pb + 16); glu<12, 120>(a, h);
#pragma unroll
        for (int i = 0; i < NSPILL; i++) { const uint4 u = lds128(hole + i * BSLOT); h[96 + 4 * i] = u.x; h[97 + 4 * i] = u.y; h[98 + 4 * i] = u.z; h[99 + 4 * i] = u.w; }
      }
      {
        THREAD_IDS();
        float d[32];
        uint4* gt = G->obox + t;
        asm volatile("" : "+l"(gt));
        uint4* const ib = gt + 2 * 4608 + layer * 8 * INBOX;
        auto pass = [&](uint32_t s0, bool last, auto&& hook) {
          const Desc db = desc_hi(0, 1024, 1) + (dsb + s0 * (XSLOT >> 4));
          mbar_wait_c(sb + BAR_FULLX + 8 * s0, (c.mX >> s0) & 1);
          if (RHOOK < 0) hook();
          asm volatile("bar.sync %0, 256;" ::"r"(8 + w) : "memory");
#pragma unroll
          for (int i = 0; i < 4; i++) {
            const int si = 4 * (i & 1) + (i >> 1);
            if (i > 0) mbar_wait_c(sb + BAR_FULLX + 8 * (s0 + si), (c.mX >> (s0 + si)) & 1);
            wg_fence();
#pragma unroll
            for (int k = 0; k < 9; k++) {
              const uint32_t* hk = h + 36 * i + 4 * k;
              wgmma_ra<64>(d, make_uint4(hk[0], hk[1], hk[2], hk[3]), db + ((xslot(si) >> 4) + k * 128), last || i + k > 0);
              if (9 * i + k == PPK && !(last && w == 1)) asm volatile("bar.arrive %0, 256;" ::"r"(9 - w) : "memory");
            }
            wg_commit();
            if (i > 0) { wg_wait<1>(); c.release2(BAR_EMPTYX + 8 * (s0 + 4 * ((i - 1) & 1) + ((i - 1) >> 1))); }
            if (i == RHOOK) hook();
          }
          c.mX ^= 0x33u << s0;
        };
        PROF2(pb + 17);
#pragma unroll 1
        for (int p = 0; p < 8; p++) {
          const uint32_t s0 = 2 * (p & 1);
          pass(s0, false, [] {});
          wg_wait<0>();
          c.release2(BAR_EMPTYX + 8 * (s0 + 5));
          if (p == 6 && layer == NLAYERS - 1) c.elect = false;
          uint32_t pk[16];
#pragma unroll
          for (int i = 0; i < 16; i++) pk[i] = pack_bf16(d[2 * i], d[2 * i + 1]);
          if (p >= BREL && p < BREL + 5 && layer < NLAYERS - 1) {
            const uint32_t o = c.sB + 8 * (p - BREL);
            c.release2(BAR_EMPTYB + (o < 40 ? o : o - 40));
          }
          uint4* const dst = ib + ((j + p) & 7) * INBOX;
          if (p == 0) {
            mbar_wait_c(sb + BAR_CLR + 8 * w, 0);
#pragma unroll
            for (int k = 0; k < 8; k++) red2((uint2*)(ib + k * INBOX + 512) - t, pk[2 * k], pk[2 * k + 1]);
          } else if (p < 7) {
#pragma unroll
            for (int k = 0; k < 4; k++) red4(dst + k * 128, pk[4 * k], pk[4 * k + 1], pk[4 * k + 2], pk[4 * k + 3]);
            if (p == 6) { __syncwarp(); if (lane == 0) mbar_arrive(sb + BAR_REDDONE + 8 * w); }
          } else {
#pragma unroll
            for (int k = 0; k < 4; k++) st_relaxed4(gt + ((j + 7) & 7) * 128 + k * 1024, pk[4 * k] & ~1u, pk[4 * k + 1], pk[4 * k + 2], pk[4 * k + 3]);
          }
        }
        PROF2(pb + 18);
        const uint4 *in = ib + j * INBOX, *pin = gt + j * 128;
        const uint2* in9 = (const uint2*)(in + 512) - t;
        asm volatile("" : "+l"(in), "+l"(pin), "+l"(in9));
        const float2 r2 = lds64(sb + SM_KEEP + (tid_ >> 2) * 8);
        uint2 X9;
        {
          uint4 X[4];
          const uint4* box = gt + 4608;
#pragma unroll
          for (int k = 0; k < 4; k++) X[k] = ld_relaxed4(box + 256 * j + ((k & 1) + 8 * (k & 2)) * 128);
          X9 = ld_relaxed2((const uint2*)(box + (32 + (j >> 1)) * 128) + (j & 1));
          const float i0 = rcp(r2.x), i1 = rcp(r2.y);
#pragma unroll
          for (int k = 0; k < 4; k++) {
            float* e = d + 8 * k;
            X[k].x ^= (lsb >> k) & 1;
            e[0] = bf_lo(X[k].x) * i0; e[1] = bf_hi(X[k].x) * i0; e[2] = bf_lo(X[k].y) * i1; e[3] = bf_hi(X[k].y) * i1;
            e[4] = bf_lo(X[k].z) * i0; e[5] = bf_hi(X[k].z) * i0; e[6] = bf_lo(X[k].w) * i1; e[7] = bf_hi(X[k].w) * i1;
          }
        }
        uint4 R[4], P[4];
        uint2 R9;
        PROF2(pb + 19);
        pass(0, true, [&] {
          mbar_wait_c(sb + BAR_RREADY + 8 * w, layer);
#pragma unroll
          for (int k = 0; k < 4; k++) R[k] = ld_relaxed4(in + k * 128);
          R9 = ld_relaxed2(in9);
#pragma unroll
          for (int k = 0; k < 4; k++) P[k] = ld_relaxed4(pin + k * 1024);
        });
        const uint32_t zero = late(sb + BAR_FULLX + 64, 0);
        while (__any_sync(0xffffffffu, (chk2(P[0].x, P[1].x, zero) | chk2(P[2].x, P[3].x, zero)) & 1)) {
#pragma unroll
          for (int k = 0; k < 4; k++) P[k] = ld_relaxed4(pin + k * 1024);
        }
#pragma unroll
        for (int k = 0; k < 4; k++) {
          const uint32_t u[4] = {hadd2(R[k].x, P[k].x), hadd2(R[k].y, P[k].y), hadd2(R[k].z, P[k].z), hadd2(R[k].w, P[k].w)};
#pragma unroll
          for (int i = 0; i < 4; i++) { v[8 * k + 2 * i] = bf_lo(u[i]); v[8 * k + 2 * i + 1] = bf_hi(u[i]); }
        }
        X9.x = chk(zero, X9.x, lsb >> 4);
        v[32] = fmaf(bf_lo(R9.x), r2.x, bf_lo(X9.x)); v[33] = fmaf(bf_hi(R9.x), r2.x, bf_hi(X9.x));
        v[34] = fmaf(bf_lo(R9.y), r2.y, bf_lo(X9.y)); v[35] = fmaf(bf_hi(R9.y), r2.y, bf_hi(X9.y));
        PROF2(pb + 20);
        wg_wait<0>();
        c.release2(BAR_EMPTYX + 40);
        PROF2(pb + 21);
#pragma unroll
        for (int i = 0; i < 32; i++) v[i] = (v[i] + d[i]) * (i & 2 ? r2.y : r2.x);
      }
      if (layer == NLAYERS - 1) break;
      {
        THREAD_IDS();
        PROF(31);
        rs = ln_gemm<true>(c, G, v, res, sum, st0, j, t, 1, xtag ^ 1, [&](int i) { PROF(32 + i); if (i) PROF(34); }, qkv_mma);
      }
    }
    {
      THREAD_IDS();
      const uint32_t stg = sb + SM_B + warp * 4096;
      const uint32_t sd = stg + (lane & 15) * 128;
#pragma unroll
      for (int i = 0; i < 4; i++)
        stsm4(sd + (((2 * i + (lane >> 4)) ^ (lane & 7)) << 4), pack_bf16(v[8 * i], v[8 * i + 1]), pack_bf16(v[8 * i + 2], v[8 * i + 3]),
              pack_bf16(v[8 * i + 4], v[8 * i + 5]), pack_bf16(v[8 * i + 6], v[8 * i + 7]));
      stsm2(stg + 2048 + (lane & 15) * 16, pack_bf16(v[32], v[33]), pack_bf16(v[34], v[35]));
      __syncwarp();
      char* o = out + (128 * rb + 32 * wp + w) * 1152;
#pragma unroll
      for (int i = 0; i < 4; i++) {
        const int r = 4 * i + (lane >> 3);
        *(uint4*)(o + r * 2304 + 128 * j + 16 * (lane & 7)) = lds128(stg + r * 128 + (((lane ^ r) & 7) << 4));
      }
      if (lane < 16) *(uint4*)(o + lane * 2304 + 1024 + 16 * j) = lds128(stg + 2048 + lane * 16);
      if (lane == 0) {
        if (wp == 0) st_relaxed(G->flag + 32 + 32 * j, xtag);
        mbar_arrive(sb + BAR_DONE + 8 * w);
      }
      PROF(61);
    }
  }
}

typedef CUresult (*EncFn)(CUtensorMap*, CUtensorMapDataType, cuuint32_t, void*, const cuuint64_t*, const cuuint64_t*, const cuuint32_t*,
                          const cuuint32_t*, CUtensorMapInterleave, CUtensorMapSwizzle, CUtensorMapL2promotion, CUtensorMapFloatOOBfill);

void make_map(EncFn enc, CUtensorMap* m, const void* p, int rank, uint64_t d0, uint64_t d1, uint64_t d2, uint64_t s1, uint64_t s2, uint32_t b0,
              uint32_t b1, uint32_t b2, CUtensorMapSwizzle sw) {
  cuuint64_t gd[3] = {d0, d1, d2};
  cuuint64_t gs[2] = {s1, s2};
  cuuint32_t bd[3] = {b0, b1, b2};
  cuuint32_t es[3] = {1, 1, 1};
  enc(m, CU_TENSOR_MAP_DATA_TYPE_BFLOAT16, rank, const_cast<void*>(p), gd, gs, bd, es, CU_TENSOR_MAP_INTERLEAVE_NONE, sw,
      CU_TENSOR_MAP_L2_PROMOTION_L2_128B, CU_TENSOR_MAP_FLOAT_OOB_FILL_NONE);
}

}

extern "C" void kernel_launch(void* const* d_in, const int* in_sizes, int n_in, void* d_out, int out_size) {
  const __nv_bfloat16* x = (const __nv_bfloat16*)d_in[0];
  const char *wqkv = (const char*)d_in[1], *wo = (const char*)d_in[2], *wg = (const char*)d_in[4], *wu = (const char*)d_in[5], *wd = (const char*)d_in[6];
  static EncFn enc = nullptr;
  static uint32_t first = 0;
  static Group* ws = nullptr;
  if (!enc) {
    cudaDriverEntryPointQueryResult qr;
    cudaGetDriverEntryPoint("cuTensorMapEncodeTiled", (void**)&enc, cudaEnableDefault, &qr);
    cudaGetSymbolAddress((void**)&ws, g_ws);
    cudaFuncSetAttribute(fused_kernel, cudaFuncAttributeMaxDynamicSharedMemorySize, SMEM_BYTES);
    cudaLaunchConfig_t cfg = {};
    cfg.gridDim = NCTA + 4; cfg.blockDim = 384; cfg.dynamicSmemBytes = SMEM_BYTES;
    int clusters = 0;
    if (XFIRST || cudaOccupancyMaxActiveClusters(&clusters, fused_kernel, &cfg) != cudaSuccess || 2 * clusters < NCTA + 4) first = 4;
    cudaGetLastError();
  }
  const CUtensorMapSwizzle S0 = CU_TENSOR_MAP_SWIZZLE_NONE, S64 = CU_TENSOR_MAP_SWIZZLE_64B, S128 = CU_TENSOR_MAP_SWIZZLE_128B;
  Maps m;
  make_map(enc, &m.x, x, 3, 576, 2, 1024, 1152, 2304, 64, 1, 64, S128);
  make_map(enc, &m.qm, wqkv, 3, 576, 576, 3, 3456, 1152, 64, 16, 3, S128);
  make_map(enc, &m.qc, wqkv, 3, 576, 576, 3, 3456, 1152, 8, 16, 3, S0);
  make_map(enc, &m.o, wo, 2, 576, 576, 1, 1152, 0, 64, 72, 1, S128);
  make_map(enc, &m.g, wg, 3, 64, 576, 72, 9216, 128, 64, 32, 2, S128);
  make_map(enc, &m.u, wu, 3, 64, 576, 72, 9216, 128, 64, 32, 2, S128);
  make_map(enc, &m.g3, wg, 3, 32, 576, 144, 9216, 64, 32, 32, 3, S64);
  make_map(enc, &m.u3, wu, 3, 32, 576, 144, 9216, 64, 32, 32, 3, S64);
  make_map(enc, &m.d, wd, 2, 576, 4608, 1, 1152, 0, 64, 72, 1, S128);
  fused_kernel<<<NCTA + 4, 384, SMEM_BYTES>>>(x, ws, wqkv, wo, (char*)d_out, first, m, wg, wu, wd);
}
```

```cpp
#include <cuda_runtime.h>
#include <cuda_bf16.h>
#include <cuda.h>
#include <stdint.h>
#include <stddef.h>

namespace {

constexpr int D_ = 576;
constexpr int NCTA = 128;
#define NLAYERS 2
#define W_POLICY policy_evict_first
#define A_POLICY policy_evict_normal
#define OPEN 1
#define PFMODE 5
#define WWIN 4
#define WOREL -1
#define WB1 11
#define WB2 21
#define WB3 32
#define WPROBE 1
#define WPROBE2 0
#define SPEC 2
#define POLLFIRST 0
#define SUMFIRST 1
#define EARLYPOLL 1
#define LEAD 0
#define ATTBAR 0
#define GL 18
#define WOBAR 1
#define QD 0
#define QG 4
#define PFQ 1
#define XDELAY 0
#define WOH 1
#define PFSLEEP 700
#define GPCMAP 1
#define PFF 1
#define REDN 1
#define CLRSLEEP 300
#define OPENL 24
#define FG 1
#define NON8 0
#define HMUL 1
#define FCH 1
#define PPK 35
#define RHOOK -1
#define SCHEDBAR 1
#define QH 5
#define XH 3
#define XP 0
#define GSLEEP 32
#define XCH 1
#define MAPPF 1
#define XREL 8
#define WOG 13
#define BREL 1
#define FENCE1 0
#define OWNX 0
#define OWNBAR 0
#define EARLY 1
#define ESPEC 0
#define TESTP 0
#define WOW 1
#define STATP -1
#define WSG 0
#define REPACK 1
#define QPACE 23
#define RDELAY 1000
#define XFIRST 0
#define TLEAD 2
#define TLEAD2 2
#define TLEAD0 2
#define OFIRST 3
#define OSPEC 0
#define FN 3
#define LATE0 0
#define SUMB 2
#define XPM 3
#define HALOH 0
#define NSPILL 4
#define REGS_C 232
#define REGS_P 40
#define STR2(x) #x
#define STR(x) STR2(x)
constexpr uint32_t SM_X = 0;
constexpr uint32_t XSLOT = 18432;
__host__ __device__ constexpr uint32_t xslot(uint32_t s) { return SM_X + (s ^ 4) * XSLOT; }
constexpr uint32_t SM_WOC = xslot(3) + 8192;
constexpr uint32_t SM_B = 147456;
constexpr uint32_t BSLOT = 16384;
constexpr uint32_t SM_KEEP = 229376;
constexpr uint32_t SM_WSUM = SM_KEEP + 512;
constexpr uint32_t SM_BAR = SM_KEEP + 2048;
constexpr uint32_t BAR_FULLB = SM_BAR;
constexpr uint32_t BAR_RREADY = SM_BAR + 40;
constexpr uint32_t BAR_CLR = SM_BAR + 56;
constexpr uint32_t BAR_FULLX = SM_BAR + 72;
constexpr uint32_t BAR_EMPTYB = SM_BAR + 144;
constexpr uint32_t BAR_EMPTYX = SM_BAR + 184;
constexpr uint32_t BAR_REDDONE = SM_BAR + 248;
constexpr uint32_t BAR_DONE = SM_BAR + 264;
constexpr uint32_t SM_PROG = SM_BAR + 288;
constexpr uint32_t SMEM_BYTES = SM_BAR + 1024;

struct Maps { CUtensorMap x, qm, qc, o, g, u, g3, u3, d; };

constexpr int INBOX = 576;
struct Group {
  uint2 sum[4 * 8 * 8];
  uint2 sq[4 * 8 * 8];
  uint32_t pad[512];
  uint32_t flag[512];
  uint4 halo[8 * 160];
  uint4 obox[36 * 128];
  uint4 xbox[36 * 128];
  uint4 inbox[2][8 * INBOX];
};
struct Scratch { Group g[32]; uint4 wq[8][36][432]; uint4 woc[8][720]; uint32_t done[64]; };
__device__ __align__(1024) Scratch g_ws;
#define PROF(i)
#define PROFX(i)

#define PROF2(i) PROF(i)

struct Desc { uint32_t lo, hi; };
__device__ __forceinline__ constexpr Desc desc_hi(uint32_t lbo, uint32_t sbo, uint32_t sw) { return Desc{(lbo >> 4) << 16, (sbo >> 4) | sw << 30}; }
__device__ __forceinline__ constexpr Desc operator+(Desc d, uint32_t a) { return Desc{d.lo + a, d.hi}; }

template<int N> __device__ __forceinline__ void wgmma_ss(float (&d)[N / 2], Desc da, Desc db, int sc);
template<> __device__ __forceinline__ void wgmma_ss<192>(float (&d)[96], Desc da, Desc db, int sc) {
  asm volatile("{\n.reg .pred p;\n.reg .b64 a, b;\nsetp.ne.b32 p, %100, 0;\nmov.b64 a, {%96, %97};\nmov.b64 b, {%98, %99};\n"
    "wgmma.mma_async.sync.aligned.m64n192k16.f32.bf16.bf16 {%0,%1,%2,%3,%4,%5,%6,%7,%8,%9,%10,%11,%12,%13,%14,%15,%16,%17,%18,%19,%20,%21,%22,%23,%24,%25,%26,%27,%28,%29,%30,%31,%32,%33,%34,%35,%36,%37,%38,%39,%40,%41,%42,%43,%44,%45,%46,%47,%48,%49,%50,%51,%52,%53,%54,%55,%56,%57,%58,%59,%60,%61,%62,%63,%64,%65,%66,%67,%68,%69,%70,%71,%72,%73,%74,%75,%76,%77,%78,%79,%80,%81,%82,%83,%84,%85,%86,%87,%88,%89,%90,%91,%92,%93,%94,%95}, a, b, p, 1, 1, 0, 1;\n}\n"
    : "+f"(d[0]),"+f"(d[1]),"+f"(d[2]),"+f"(d[3]),"+f"(d[4]),"+f"(d[5]),"+f"(d[6]),"+f"(d[7]),"+f"(d[8]),"+f"(d[9]),"+f"(d[10]),"+f"(d[11]),"+f"(d[12]),"+f"(d[13]),"+f"(d[14]),"+f"(d[15]),"+f"(d[16]),"+f"(d[17]),"+f"(d[18]),"+f"(d[19]),"+f"(d[20]),"+f"(d[21]),"+f"(d[22]),"+f"(d[23]),"+f"(d[24]),"+f"(d[25]),"+f"(d[26]),"+f"(d[27]),"+f"(d[28]),"+f"(d[29]),"+f"(d[30]),"+f"(d[31]),"+f"(d[32]),"+f"(d[33]),"+f"(d[34]),"+f"(d[35]),"+f"(d[36]),"+f"(d[37]),"+f"(d[38]),"+f"(d[39]),"+f"(d[40]),"+f"(d[41]),"+f"(d[42]),"+f"(d[43]),"+f"(d[44]),"+f"(d[45]),"+f"(d[46]),"+f"(d[47]),"+f"(d[48]),"+f"(d[49]),"+f"(d[50]),"+f"(d[51]),"+f"(d[52]),"+f"(d[53]),"+f"(d[54]),"+f"(d[55]),"+f"(d[56]),"+f"(d[57]),"+f"(d[58]),"+f"(d[59]),"+f"(d[60]),"+f"(d[61]),"+f"(d[62]),"+f"(d[63]),"+f"(d[64]),"+f"(d[65]),"+f"(d[66]),"+f"(d[67]),"+f"(d[68]),"+f"(d[69]),"+f"(d[70]),"+f"(d[71]),"+f"(d[72]),"+f"(d[73]),"+f"(d[74]),"+f"(d[75]),"+f"(d[76]),"+f"(d[77]),"+f"(d[78]),"+f"(d[79]),"+f"(d[80]),"+f"(d[81]),"+f"(d[82]),"+f"(d[83]),"+f"(d[84]),"+f"(d[85]),"+f"(d[86]),"+f"(d[87]),"+f"(d[88]),"+f"(d[89]),"+f"(d[90]),"+f"(d[91]),"+f"(d[92]),"+f"(d[93]),"+f"(d[94]),"+f"(d[95]) : "r"(da.lo), "r"(da.hi), "r"(db.lo), "r"(db.hi), "r"(sc));
}
template<> __device__ __forceinline__ void wgmma_ss<256>(float (&d)[128], Desc da, Desc db, int sc) {
  asm volatile("{\n.reg .pred p;\n.reg .b64 a, b;\nsetp.ne.b32 p, %132, 0;\nmov.b64 a, {%128, %129};\nmov.b64 b, {%130, %131};\n"
    "wgmma.mma_async.sync.aligned.m64n256k16.f32.bf16.bf16 {%0,%1,%2,%3,%4,%5,%6,%7,%8,%9,%10,%11,%12,%13,%14,%15,%16,%17,%18,%19,%20,%21,%22,%23,%24,%25,%26,%27,%28,%29,%30,%31,%32,%33,%34,%35,%36,%37,%38,%39,%40,%41,%42,%43,%44,%45,%46,%47,%48,%49,%50,%51,%52,%53,%54,%55,%56,%57,%58,%59,%60,%61,%62,%63,%64,%65,%66,%67,%68,%69,%70,%71,%72,%73,%74,%75,%76,%77,%78,%79,%80,%81,%82,%83,%84,%85,%86,%87,%88,%89,%90,%91,%92,%93,%94,%95,%96,%97,%98,%99,%100,%101,%102,%103,%104,%105,%106,%107,%108,%109,%110,%111,%112,%113,%114,%115,%116,%117,%118,%119,%120,%121,%122,%123,%124,%125,%126,%127}, a, b, p, 1, 1, 0, 1;\n}\n"
    : "+f"(d[0]),"+f"(d[1]),"+f"(d[2]),"+f"(d[3]),"+f"(d[4]),"+f"(d[5]),"+f"(d[6]),"+f"(d[7]),"+f"(d[8]),"+f"(d[9]),"+f"(d[10]),"+f"(d[11]),"+f"(d[12]),"+f"(d[13]),"+f"(d[14]),"+f"(d[15]),"+f"(d[16]),"+f"(d[17]),"+f"(d[18]),"+f"(d[19]),"+f"(d[20]),"+f"(d[21]),"+f"(d[22]),"+f"(d[23]),"+f"(d[24]),"+f"(d[25]),"+f"(d[26]),"+f"(d[27]),"+f"(d[28]),"+f"(d[29]),"+f"(d[30]),"+f"(d[31]),"+f"(d[32]),"+f"(d[33]),"+f"(d[34]),"+f"(d[35]),"+f"(d[36]),"+f"(d[37]),"+f"(d[38]),"+f"(d[39]),"+f"(d[40]),"+f"(d[41]),"+f"(d[42]),"+f"(d[43]),"+f"(d[44]),"+f"(d[45]),"+f"(d[46]),"+f"(d[47]),"+f"(d[48]),"+f"(d[49]),"+f"(d[50]),"+f"(d[51]),"+f"(d[52]),"+f"(d[53]),"+f"(d[54]),"+f"(d[55]),"+f"(d[56]),"+f"(d[57]),"+f"(d[58]),"+f"(d[59]),"+f"(d[60]),"+f"(d[61]),"+f"(d[62]),"+f"(d[63]),"+f"(d[64]),"+f"(d[65]),"+f"(d[66]),"+f"(d[67]),"+f"(d[68]),"+f"(d[69]),"+f"(d[70]),"+f"(d[71]),"+f"(d[72]),"+f"(d[73]),"+f"(d[74]),"+f"(d[75]),"+f"(d[76]),"+f"(d[77]),"+f"(d[78]),"+f"(d[79]),"+f"(d[80]),"+f"(d[81]),"+f"(d[82]),"+f"(d[83]),"+f"(d[84]),"+f"(d[85]),"+f"(d[86]),"+f"(d[87]),"+f"(d[88]),"+f"(d[89]),"+f"(d[90]),"+f"(d[91]),"+f"(d[92]),"+f"(d[93]),"+f"(d[94]),"+f"(d[95]),"+f"(d[96]),"+f"(d[97]),"+f"(d[98]),"+f"(d[99]),"+f"(d[100]),"+f"(d[101]),"+f"(d[102]),"+f"(d[103]),"+f"(d[104]),"+f"(d[105]),"+f"(d[106]),"+f"(d[107]),"+f"(d[108]),"+f"(d[109]),"+f"(d[110]),"+f"(d[111]),"+f"(d[112]),"+f"(d[113]),"+f"(d[114]),"+f"(d[115]),"+f"(d[116]),"+f"(d[117]),"+f"(d[118]),"+f"(d[119]),"+f"(d[120]),"+f"(d[121]),"+f"(d[122]),"+f"(d[123]),"+f"(d[124]),"+f"(d[125]),"+f"(d[126]),"+f"(d[127]) : "r"(da.lo), "r"(da.hi), "r"(db.lo), "r"(db.hi), "r"(sc));
}
template<int N, int ACC> __device__ __forceinline__ void wgmma_rs(float (&d)[N / 2], const uint4& a, Desc db);
template<> __device__ __forceinline__ void wgmma_rs<8, 1>(float (&d)[4], const uint4& a, Desc db) {
  asm volatile("{\n.reg .pred p;\n.reg .b64 b;\nsetp.ne.b32 p, 1, 0;\nmov.b64 b, {%8, %9};\n"
    "wgmma.mma_async.sync.aligned.m64n8k16.f32.bf16.bf16 {%0,%1,%2,%3}, {%4,%5,%6,%7}, b, p, 1, 1, 1;\n}\n"
    : "+f"(d[0]),"+f"(d[1]),"+f"(d[2]),"+f"(d[3]) : "r"(a.x), "r"(a.y), "r"(a.z), "r"(a.w), "r"(db.lo), "r"(db.hi));
}
template<> __device__ __forceinline__ void wgmma_rs<8, 0>(float (&d)[4], const uint4& a, Desc db) {
  asm volatile("{\n.reg .pred p;\n.reg .b64 b;\nsetp.ne.b32 p, 0, 0;\nmov.b64 b, {%8, %9};\n"
    "wgmma.mma_async.sync.aligned.m64n8k16.f32.bf16.bf16 {%0,%1,%2,%3}, {%4,%5,%6,%7}, b, p, 1, 1, 1;\n}\n"
    : "=f"(d[0]),"=f"(d[1]),"=f"(d[2]),"=f"(d[3]) : "r"(a.x), "r"(a.y), "r"(a.z), "r"(a.w), "r"(db.lo), "r"(db.hi));
}
template<> __device__ __forceinline__ void wgmma_rs<24, 1>(float (&d)[12], const uint4& a, Desc db) {
  asm volatile("{\n.reg .pred p;\n.reg .b64 b;\nsetp.ne.b32 p, 1, 0;\nmov.b64 b, {%16, %17};\n"
    "wgmma.mma_async.sync.aligned.m64n24k16.f32.bf16.bf16 {%0,%1,%2,%3,%4,%5,%6,%7,%8,%9,%10,%11}, {%12,%13,%14,%15}, b, p, 1, 1, 1;\n}\n"
    : "+f"(d[0]),"+f"(d[1]),"+f"(d[2]),"+f"(d[3]),"+f"(d[4]),"+f"(d[5]),"+f"(d[6]),"+f"(d[7]),"+f"(d[8]),"+f"(d[9]),"+f"(d[10]),"+f"(d[11]) : "r"(a.x), "r"(a.y), "r"(a.z), "r"(a.w), "r"(db.lo), "r"(db.hi));
}
template<> __device__ __forceinline__ void wgmma_rs<24, 0>(float (&d)[12], const uint4& a, Desc db) {
  asm volatile("{\n.reg .pred p;\n.reg .b64 b;\nsetp.ne.b32 p, 0, 0;\nmov.b64 b, {%16, %17};\n"
    "wgmma.mma_async.sync.aligned.m64n24k16.f32.bf16.bf16 {%0,%1,%2,%3,%4,%5,%6,%7,%8,%9,%10,%11}, {%12,%13,%14,%15}, b, p, 1, 1, 1;\n}\n"
    : "=f"(d[0]),"=f"(d[1]),"=f"(d[2]),"=f"(d[3]),"=f"(d[4]),"=f"(d[5]),"=f"(d[6]),"=f"(d[7]),"=f"(d[8]),"=f"(d[9]),"=f"(d[10]),"=f"(d[11]) : "r"(a.x), "r"(a.y), "r"(a.z), "r"(a.w), "r"(db.lo), "r"(db.hi));
}
template<> __device__ __forceinline__ void wgmma_rs<64, 1>(float (&d)[32], const uint4& a, Desc db) {
  asm volatile("{\n.reg .pred p;\n.reg .b64 b;\nsetp.ne.b32 p, 1, 0;\nmov.b64 b, {%36, %37};\n"
    "wgmma.mma_async.sync.aligned.m64n64k16.f32.bf16.bf16 {%0,%1,%2,%3,%4,%5,%6,%7,%8,%9,%10,%11,%12,%13,%14,%15,%16,%17,%18,%19,%20,%21,%22,%23,%24,%25,%26,%27,%28,%29,%30,%31}, {%32,%33,%34,%35}, b, p, 1, 1, 1;\n}\n"
    : "+f"(d[0]),"+f"(d[1]),"+f"(d[2]),"+f"(d[3]),"+f"(d[4]),"+f"(d[5]),"+f"(d[6]),"+f"(d[7]),"+f"(d[8]),"+f"(d[9]),"+f"(d[10]),"+f"(d[11]),"+f"(d[12]),"+f"(d[13]),"+f"(d[14]),"+f"(d[15]),"+f"(d[16]),"+f"(d[17]),"+f"(d[18]),"+f"(d[19]),"+f"(d[20]),"+f"(d[21]),"+f"(d[22]),"+f"(d[23]),"+f"(d[24]),"+f"(d[25]),"+f"(d[26]),"+f"(d[27]),"+f"(d[28]),"+f"(d[29]),"+f"(d[30]),"+f"(d[31]) : "r"(a.x), "r"(a.y), "r"(a.z), "r"(a.w), "r"(db.lo), "r"(db.hi));
}
template<> __device__ __forceinline__ void wgmma_rs<64, 0>(float (&d)[32], const uint4& a, Desc db) {
  asm volatile("{\n.reg .pred p;\n.reg .b64 b;\nsetp.ne.b32 p, 0, 0;\nmov.b64 b, {%36, %37};\n"
    "wgmma.mma_async.sync.aligned.m64n64k16.f32.bf16.bf16 {%0,%1,%2,%3,%4,%5,%6,%7,%8,%9,%10,%11,%12,%13,%14,%15,%16,%17,%18,%19,%20,%21,%22,%23,%24,%25,%26,%27,%28,%29,%30,%31}, {%32,%33,%34,%35}, b, p, 1, 1, 1;\n}\n"
    : "=f"(d[0]),"=f"(d[1]),"=f"(d[2]),"=f"(d[3]),"=f"(d[4]),"=f"(d[5]),"=f"(d[6]),"=f"(d[7]),"=f"(d[8]),"=f"(d[9]),"=f"(d[10]),"=f"(d[11]),"=f"(d[12]),"=f"(d[13]),"=f"(d[14]),"=f"(d[15]),"=f"(d[16]),"=f"(d[17]),"=f"(d[18]),"=f"(d[19]),"=f"(d[20]),"=f"(d[21]),"=f"(d[22]),"=f"(d[23]),"=f"(d[24]),"=f"(d[25]),"=f"(d[26]),"=f"(d[27]),"=f"(d[28]),"=f"(d[29]),"=f"(d[30]),"=f"(d[31]) : "r"(a.x), "r"(a.y), "r"(a.z), "r"(a.w), "r"(db.lo), "r"(db.hi));
}
template<> __device__ __forceinline__ void wgmma_rs<72, 1>(float (&d)[36], const uint4& a, Desc db) {
  asm volatile("{\n.reg .pred p;\n.reg .b64 b;\nsetp.ne.b32 p, 1, 0;\nmov.b64 b, {%40, %41};\n"
    "wgmma.mma_async.sync.aligned.m64n72k16.f32.bf16.bf16 {%0,%1,%2,%3,%4,%5,%6,%7,%8,%9,%10,%11,%12,%13,%14,%15,%16,%17,%18,%19,%20,%21,%22,%23,%24,%25,%26,%27,%28,%29,%30,%31,%32,%33,%34,%35}, {%36,%37,%38,%39}, b, p, 1, 1, 1;\n}\n"
    : "+f"(d[0]),"+f"(d[1]),"+f"(d[2]),"+f"(d[3]),"+f"(d[4]),"+f"(d[5]),"+f"(d[6]),"+f"(d[7]),"+f"(d[8]),"+f"(d[9]),"+f"(d[10]),"+f"(d[11]),"+f"(d[12]),"+f"(d[13]),"+f"(d[14]),"+f"(d[15]),"+f"(d[16]),"+f"(d[17]),"+f"(d[18]),"+f"(d[19]),"+f"(d[20]),"+f"(d[21]),"+f"(d[22]),"+f"(d[23]),"+f"(d[24]),"+f"(d[25]),"+f"(d[26]),"+f"(d[27]),"+f"(d[28]),"+f"(d[29]),"+f"(d[30]),"+f"(d[31]),"+f"(d[32]),"+f"(d[33]),"+f"(d[34]),"+f"(d[35]) : "r"(a.x), "r"(a.y), "r"(a.z), "r"(a.w), "r"(db.lo), "r"(db.hi));
}
template<> __device__ __forceinline__ void wgmma_rs<72, 0>(float (&d)[36], const uint4& a, Desc db) {
  asm volatile("{\n.reg .pred p;\n.reg .b64 b;\nsetp.ne.b32 p, 0, 0;\nmov.b64 b, {%40, %41};\n"
    "wgmma.mma_async.sync.aligned.m64n72k16.f32.bf16.bf16 {%0,%1,%2,%3,%4,%5,%6,%7,%8,%9,%10,%11,%12,%13,%14,%15,%16,%17,%18,%19,%20,%21,%22,%23,%24,%25,%26,%27,%28,%29,%30,%31,%32,%33,%34,%35}, {%36,%37,%38,%39}, b, p, 1, 1, 1;\n}\n"
    : "=f"(d[0]),"=f"(d[1]),"=f"(d[2]),"=f"(d[3]),"=f"(d[4]),"=f"(d[5]),"=f"(d[6]),"=f"(d[7]),"=f"(d[8]),"=f"(d[9]),"=f"(d[10]),"=f"(d[11]),"=f"(d[12]),"=f"(d[13]),"=f"(d[14]),"=f"(d[15]),"=f"(d[16]),"=f"(d[17]),"=f"(d[18]),"=f"(d[19]),"=f"(d[20]),"=f"(d[21]),"=f"(d[22]),"=f"(d[23]),"=f"(d[24]),"=f"(d[25]),"=f"(d[26]),"=f"(d[27]),"=f"(d[28]),"=f"(d[29]),"=f"(d[30]),"=f"(d[31]),"=f"(d[32]),"=f"(d[33]),"=f"(d[34]),"=f"(d[35]) : "r"(a.x), "r"(a.y), "r"(a.z), "r"(a.w), "r"(db.lo), "r"(db.hi));
}
template<> __device__ __forceinline__ void wgmma_rs<192, 1>(float (&d)[96], const uint4& a, Desc db) {
  asm volatile("{\n.reg .pred p;\n.reg .b64 b;\nsetp.ne.b32 p, 1, 0;\nmov.b64 b, {%100, %101};\n"
    "wgmma.mma_async.sync.aligned.m64n192k16.f32.bf16.bf16 {%0,%1,%2,%3,%4,%5,%6,%7,%8,%9,%10,%11,%12,%13,%14,%15,%16,%17,%18,%19,%20,%21,%22,%23,%24,%25,%26,%27,%28,%29,%30,%31,%32,%33,%34,%35,%36,%37,%38,%39,%40,%41,%42,%43,%44,%45,%46,%47,%48,%49,%50,%51,%52,%53,%54,%55,%56,%57,%58,%59,%60,%61,%62,%63,%64,%65,%66,%67,%68,%69,%70,%71,%72,%73,%74,%75,%76,%77,%78,%79,%80,%81,%82,%83,%84,%85,%86,%87,%88,%89,%90,%91,%92,%93,%94,%95}, {%96,%97,%98,%99}, b, p, 1, 1, 1;\n}\n"
    : "+f"(d[0]),"+f"(d[1]),"+f"(d[2]),"+f"(d[3]),"+f"(d[4]),"+f"(d[5]),"+f"(d[6]),"+f"(d[7]),"+f"(d[8]),"+f"(d[9]),"+f"(d[10]),"+f"(d[11]),"+f"(d[12]),"+f"(d[13]),"+f"(d[14]),"+f"(d[15]),"+f"(d[16]),"+f"(d[17]),"+f"(d[18]),"+f"(d[19]),"+f"(d[20]),"+f"(d[21]),"+f"(d[22]),"+f"(d[23]),"+f"(d[24]),"+f"(d[25]),"+f"(d[26]),"+f"(d[27]),"+f"(d[28]),"+f"(d[29]),"+f"(d[30]),"+f"(d[31]),"+f"(d[32]),"+f"(d[33]),"+f"(d[34]),"+f"(d[35]),"+f"(d[36]),"+f"(d[37]),"+f"(d[38]),"+f"(d[39]),"+f"(d[40]),"+f"(d[41]),"+f"(d[42]),"+f"(d[43]),"+f"(d[44]),"+f"(d[45]),"+f"(d[46]),"+f"(d[47]),"+f"(d[48]),"+f"(d[49]),"+f"(d[50]),"+f"(d[51]),"+f"(d[52]),"+f"(d[53]),"+f"(d[54]),"+f"(d[55]),"+f"(d[56]),"+f"(d[57]),"+f"(d[58]),"+f"(d[59]),"+f"(d[60]),"+f"(d[61]),"+f"(d[62]),"+f"(d[63]),"+f"(d[64]),"+f"(d[65]),"+f"(d[66]),"+f"(d[67]),"+f"(d[68]),"+f"(d[69]),"+f"(d[70]),"+f"(d[71]),"+f"(d[72]),"+f"(d[73]),"+f"(d[74]),"+f"(d[75]),"+f"(d[76]),"+f"(d[77]),"+f"(d[78]),"+f"(d[79]),"+f"(d[80]),"+f"(d[81]),"+f"(d[82]),"+f"(d[83]),"+f"(d[84]),"+f"(d[85]),"+f"(d[86]),"+f"(d[87]),"+f"(d[88]),"+f"(d[89]),"+f"(d[90]),"+f"(d[91]),"+f"(d[92]),"+f"(d[93]),"+f"(d[94]),"+f"(d[95]) : "r"(a.x), "r"(a.y), "r"(a.z), "r"(a.w), "r"(db.lo), "r"(db.hi));
}
template<> __device__ __forceinline__ void wgmma_rs<192, 0>(float (&d)[96], const uint4& a, Desc db) {
  asm volatile("{\n.reg .pred p;\n.reg .b64 b;\nsetp.ne.b32 p, 0, 0;\nmov.b64 b, {%100, %101};\n"
    "wgmma.mma_async.sync.aligned.m64n192k16.f32.bf16.bf16 {%0,%1,%2,%3,%4,%5,%6,%7,%8,%9,%10,%11,%12,%13,%14,%15,%16,%17,%18,%19,%20,%21,%22,%23,%24,%25,%26,%27,%28,%29,%30,%31,%32,%33,%34,%35,%36,%37,%38,%39,%40,%41,%42,%43,%44,%45,%46,%47,%48,%49,%50,%51,%52,%53,%54,%55,%56,%57,%58,%59,%60,%61,%62,%63,%64,%65,%66,%67,%68,%69,%70,%71,%72,%73,%74,%75,%76,%77,%78,%79,%80,%81,%82,%83,%84,%85,%86,%87,%88,%89,%90,%91,%92,%93,%94,%95}, {%96,%97,%98,%99}, b, p, 1, 1, 1;\n}\n"
    : "=f"(d[0]),"=f"(d[1]),"=f"(d[2]),"=f"(d[3]),"=f"(d[4]),"=f"(d[5]),"=f"(d[6]),"=f"(d[7]),"=f"(d[8]),"=f"(d[9]),"=f"(d[10]),"=f"(d[11]),"=f"(d[12]),"=f"(d[13]),"=f"(d[14]),"=f"(d[15]),"=f"(d[16]),"=f"(d[17]),"=f"(d[18]),"=f"(d[19]),"=f"(d[20]),"=f"(d[21]),"=f"(d[22]),"=f"(d[23]),"=f"(d[24]),"=f"(d[25]),"=f"(d[26]),"=f"(d[27]),"=f"(d[28]),"=f"(d[29]),"=f"(d[30]),"=f"(d[31]),"=f"(d[32]),"=f"(d[33]),"=f"(d[34]),"=f"(d[35]),"=f"(d[36]),"=f"(d[37]),"=f"(d[38]),"=f"(d[39]),"=f"(d[40]),"=f"(d[41]),"=f"(d[42]),"=f"(d[43]),"=f"(d[44]),"=f"(d[45]),"=f"(d[46]),"=f"(d[47]),"=f"(d[48]),"=f"(d[49]),"=f"(d[50]),"=f"(d[51]),"=f"(d[52]),"=f"(d[53]),"=f"(d[54]),"=f"(d[55]),"=f"(d[56]),"=f"(d[57]),"=f"(d[58]),"=f"(d[59]),"=f"(d[60]),"=f"(d[61]),"=f"(d[62]),"=f"(d[63]),"=f"(d[64]),"=f"(d[65]),"=f"(d[66]),"=f"(d[67]),"=f"(d[68]),"=f"(d[69]),"=f"(d[70]),"=f"(d[71]),"=f"(d[72]),"=f"(d[73]),"=f"(d[74]),"=f"(d[75]),"=f"(d[76]),"=f"(d[77]),"=f"(d[78]),"=f"(d[79]),"=f"(d[80]),"=f"(d[81]),"=f"(d[82]),"=f"(d[83]),"=f"(d[84]),"=f"(d[85]),"=f"(d[86]),"=f"(d[87]),"=f"(d[88]),"=f"(d[89]),"=f"(d[90]),"=f"(d[91]),"=f"(d[92]),"=f"(d[93]),"=f"(d[94]),"=f"(d[95]) : "r"(a.x), "r"(a.y), "r"(a.z), "r"(a.w), "r"(db.lo), "r"(db.hi));
}
template<> __device__ __forceinline__ void wgmma_rs<256, 1>(float (&d)[128], const uint4& a, Desc db) {
  asm volatile("{\n.reg .pred p;\n.reg .b64 b;\nsetp.ne.b32 p, 1, 0;\nmov.b64 b, {%132, %133};\n"
    "wgmma.mma_async.sync.aligned.m64n256k16.f32.bf16.bf16 {%0,%1,%2,%3,%4,%5,%6,%7,%8,%9,%10,%11,%12,%13,%14,%15,%16,%17,%18,%19,%20,%21,%22,%23,%24,%25,%26,%27,%28,%29,%30,%31,%32,%33,%34,%35,%36,%37,%38,%39,%40,%41,%42,%43,%44,%45,%46,%47,%48,%49,%50,%51,%52,%53,%54,%55,%56,%57,%58,%59,%60,%61,%62,%63,%64,%65,%66,%67,%68,%69,%70,%71,%72,%73,%74,%75,%76,%77,%78,%79,%80,%81,%82,%83,%84,%85,%86,%87,%88,%89,%90,%91,%92,%93,%94,%95,%96,%97,%98,%99,%100,%101,%102,%103,%104,%105,%106,%107,%108,%109,%110,%111,%112,%113,%114,%115,%116,%117,%118,%119,%120,%121,%122,%123,%124,%125,%126,%127}, {%128,%129,%130,%131}, b, p, 1, 1, 1;\n}\n"
    : "+f"(d[0]),"+f"(d[1]),"+f"(d[2]),"+f"(d[3]),"+f"(d[4]),"+f"(d[5]),"+f"(d[6]),"+f"(d[7]),"+f"(d[8]),"+f"(d[9]),"+f"(d[10]),"+f"(d[11]),"+f"(d[12]),"+f"(d[13]),"+f"(d[14]),"+f"(d[15]),"+f"(d[16]),"+f"(d[17]),"+f"(d[18]),"+f"(d[19]),"+f"(d[20]),"+f"(d[21]),"+f"(d[22]),"+f"(d[23]),"+f"(d[24]),"+f"(d[25]),"+f"(d[26]),"+f"(d[27]),"+f"(d[28]),"+f"(d[29]),"+f"(d[30]),"+f"(d[31]),"+f"(d[32]),"+f"(d[33]),"+f"(d[34]),"+f"(d[35]),"+f"(d[36]),"+f"(d[37]),"+f"(d[38]),"+f"(d[39]),"+f"(d[40]),"+f"(d[41]),"+f"(d[42]),"+f"(d[43]),"+f"(d[44]),"+f"(d[45]),"+f"(d[46]),"+f"(d[47]),"+f"(d[48]),"+f"(d[49]),"+f"(d[50]),"+f"(d[51]),"+f"(d[52]),"+f"(d[53]),"+f"(d[54]),"+f"(d[55]),"+f"(d[56]),"+f"(d[57]),"+f"(d[58]),"+f"(d[59]),"+f"(d[60]),"+f"(d[61]),"+f"(d[62]),"+f"(d[63]),"+f"(d[64]),"+f"(d[65]),"+f"(d[66]),"+f"(d[67]),"+f"(d[68]),"+f"(d[69]),"+f"(d[70]),"+f"(d[71]),"+f"(d[72]),"+f"(d[73]),"+f"(d[74]),"+f"(d[75]),"+f"(d[76]),"+f"(d[77]),"+f"(d[78]),"+f"(d[79]),"+f"(d[80]),"+f"(d[81]),"+f"(d[82]),"+f"(d[83]),"+f"(d[84]),"+f"(d[85]),"+f"(d[86]),"+f"(d[87]),"+f"(d[88]),"+f"(d[89]),"+f"(d[90]),"+f"(d[91]),"+f"(d[92]),"+f"(d[93]),"+f"(d[94]),"+f"(d[95]),"+f"(d[96]),"+f"(d[97]),"+f"(d[98]),"+f"(d[99]),"+f"(d[100]),"+f"(d[101]),"+f"(d[102]),"+f"(d[103]),"+f"(d[104]),"+f"(d[105]),"+f"(d[106]),"+f"(d[107]),"+f"(d[108]),"+f"(d[109]),"+f"(d[110]),"+f"(d[111]),"+f"(d[112]),"+f"(d[113]),"+f"(d[114]),"+f"(d[115]),"+f"(d[116]),"+f"(d[117]),"+f"(d[118]),"+f"(d[119]),"+f"(d[120]),"+f"(d[121]),"+f"(d[122]),"+f"(d[123]),"+f"(d[124]),"+f"(d[125]),"+f"(d[126]),"+f"(d[127]) : "r"(a.x), "r"(a.y), "r"(a.z), "r"(a.w), "r"(db.lo), "r"(db.hi));
}
template<> __device__ __forceinline__ void wgmma_rs<256, 0>(float (&d)[128], const uint4& a, Desc db) {
  asm volatile("{\n.reg .pred p;\n.reg .b64 b;\nsetp.ne.b32 p, 0, 0;\nmov.b64 b, {%132, %133};\n"
    "wgmma.mma_async.sync.aligned.m64n256k16.f32.bf16.bf16 {%0,%1,%2,%3,%4,%5,%6,%7,%8,%9,%10,%11,%12,%13,%14,%15,%16,%17,%18,%19,%20,%21,%22,%23,%24,%25,%26,%27,%28,%29,%30,%31,%32,%33,%34,%35,%36,%37,%38,%39,%40,%41,%42,%43,%44,%45,%46,%47,%48,%49,%50,%51,%52,%53,%54,%55,%56,%57,%58,%59,%60,%61,%62,%63,%64,%65,%66,%67,%68,%69,%70,%71,%72,%73,%74,%75,%76,%77,%78,%79,%80,%81,%82,%83,%84,%85,%86,%87,%88,%89,%90,%91,%92,%93,%94,%95,%96,%97,%98,%99,%100,%101,%102,%103,%104,%105,%106,%107,%108,%109,%110,%111,%112,%113,%114,%115,%116,%117,%118,%119,%120,%121,%122,%123,%124,%125,%126,%127}, {%128,%129,%130,%131}, b, p, 1, 1, 1;\n}\n"
    : "=f"(d[0]),"=f"(d[1]),"=f"(d[2]),"=f"(d[3]),"=f"(d[4]),"=f"(d[5]),"=f"(d[6]),"=f"(d[7]),"=f"(d[8]),"=f"(d[9]),"=f"(d[10]),"=f"(d[11]),"=f"(d[12]),"=f"(d[13]),"=f"(d[14]),"=f"(d[15]),"=f"(d[16]),"=f"(d[17]),"=f"(d[18]),"=f"(d[19]),"=f"(d[20]),"=f"(d[21]),"=f"(d[22]),"=f"(d[23]),"=f"(d[24]),"=f"(d[25]),"=f"(d[26]),"=f"(d[27]),"=f"(d[28]),"=f"(d[29]),"=f"(d[30]),"=f"(d[31]),"=f"(d[32]),"=f"(d[33]),"=f"(d[34]),"=f"(d[35]),"=f"(d[36]),"=f"(d[37]),"=f"(d[38]),"=f"(d[39]),"=f"(d[40]),"=f"(d[41]),"=f"(d[42]),"=f"(d[43]),"=f"(d[44]),"=f"(d[45]),"=f"(d[46]),"=f"(d[47]),"=f"(d[48]),"=f"(d[49]),"=f"(d[50]),"=f"(d[51]),"=f"(d[52]),"=f"(d[53]),"=f"(d[54]),"=f"(d[55]),"=f"(d[56]),"=f"(d[57]),"=f"(d[58]),"=f"(d[59]),"=f"(d[60]),"=f"(d[61]),"=f"(d[62]),"=f"(d[63]),"=f"(d[64]),"=f"(d[65]),"=f"(d[66]),"=f"(d[67]),"=f"(d[68]),"=f"(d[69]),"=f"(d[70]),"=f"(d[71]),"=f"(d[72]),"=f"(d[73]),"=f"(d[74]),"=f"(d[75]),"=f"(d[76]),"=f"(d[77]),"=f"(d[78]),"=f"(d[79]),"=f"(d[80]),"=f"(d[81]),"=f"(d[82]),"=f"(d[83]),"=f"(d[84]),"=f"(d[85]),"=f"(d[86]),"=f"(d[87]),"=f"(d[88]),"=f"(d[89]),"=f"(d[90]),"=f"(d[91]),"=f"(d[92]),"=f"(d[93]),"=f"(d[94]),"=f"(d[95]),"=f"(d[96]),"=f"(d[97]),"=f"(d[98]),"=f"(d[99]),"=f"(d[100]),"=f"(d[101]),"=f"(d[102]),"=f"(d[103]),"=f"(d[104]),"=f"(d[105]),"=f"(d[106]),"=f"(d[107]),"=f"(d[108]),"=f"(d[109]),"=f"(d[110]),"=f"(d[111]),"=f"(d[112]),"=f"(d[113]),"=f"(d[114]),"=f"(d[115]),"=f"(d[116]),"=f"(d[117]),"=f"(d[118]),"=f"(d[119]),"=f"(d[120]),"=f"(d[121]),"=f"(d[122]),"=f"(d[123]),"=f"(d[124]),"=f"(d[125]),"=f"(d[126]),"=f"(d[127]) : "r"(a.x), "r"(a.y), "r"(a.z), "r"(a.w), "r"(db.lo), "r"(db.hi));
}
template<int N> __device__ __forceinline__ void wgmma_ra(float (&d)[N / 2], const uint4& a, Desc db, bool acc) {
  if (acc) wgmma_rs<N, 1>(d, a, db); else wgmma_rs<N, 0>(d, a, db);
}

__device__ __forceinline__ uint32_t smem_u32(const void* p) { return (uint32_t)__cvta_generic_to_shared(p); }
__device__ __forceinline__ void mbar_init(uint32_t bar, uint32_t cnt) { asm volatile("mbarrier.init.shared::cta.b64 [%0], %1;" ::"r"(bar), "r"(cnt)); }
__device__ __forceinline__ void mbar_expect_tx(uint32_t bar, uint32_t bytes) { asm volatile("mbarrier.arrive.expect_tx.shared::cta.b64 _, [%0], %1;" ::"r"(bar), "r"(bytes) : "memory"); }
__device__ __forceinline__ void mbar_arrive(uint32_t bar) { asm volatile("mbarrier.arrive.shared::cta.b64 _, [%0];" ::"r"(bar) : "memory"); }
__device__ __forceinline__ void mbar_arrive_remote(uint32_t rbar) { asm volatile("mbarrier.arrive.shared::cluster.b64 _, [%0];" ::"r"(rbar) : "memory"); }
__device__ __forceinline__ void mbar_wait(uint32_t bar, uint32_t parity) {
  asm volatile(
      "{\n.reg .pred p;\n.reg .u32 c;\nmov.u32 c, 0;\nLAB_WAIT:\nmbarrier.try_wait.parity.shared::cta.b64 p, [%0], %1;\n@p bra DONE;\n"
      "add.u32 c, c, 1;\nsetp.lt.u32 p, c, 1000000;\n@p bra LAB_WAIT;\ntrap;\nDONE:\n}\n" ::"r"(bar), "r"(parity) : "memory");
}
__device__ __forceinline__ void mbar_wait_c(uint32_t bar, uint32_t parity) {
  asm volatile("{\n.reg .pred p;\nLAB_WAIT:\nmbarrier.try_wait.parity.shared::cta.b64 p, [%0], %1;\n@!p bra LAB_WAIT;\n}\n" ::"r"(bar), "r"(parity) : "memory");
}
__device__ __forceinline__ uint32_t late(uint32_t bar, uint32_t v) {
  uint32_t r;
  asm volatile("{\n.reg .pred p;\nmbarrier.test_wait.parity.shared::cta.b64 p, [%1], 0;\nselp.b32 %0, %2, %1, p;\n}\n" : "=r"(r) : "r"(bar), "r"(v) : "memory");
  return r;
}
__device__ __forceinline__ void wtma2d(uint32_t dst, const CUtensorMap* m, int c0, int c1, uint32_t bar, uint64_t pol) {
  asm volatile("cp.async.bulk.tensor.2d.shared::cluster.global.mbarrier::complete_tx::bytes.multicast::cluster.L2::cache_hint [%0], [%1, {%3, %4}], [%2], %5, %6;"
               ::"r"(dst), "l"(m), "r"(bar), "r"(c0), "r"(c1), "h"((uint16_t)3), "l"(pol) : "memory");
}
__device__ __forceinline__ void wtma3d(uint32_t dst, const CUtensorMap* m, int c0, int c1, int c2, uint32_t bar, uint64_t pol) {
  asm volatile("cp.async.bulk.tensor.3d.shared::cluster.global.mbarrier::complete_tx::bytes.multicast::cluster.L2::cache_hint [%0], [%1, {%3, %4, %5}], [%2], %6, %7;"
               ::"r"(dst), "l"(m), "r"(bar), "r"(c0), "r"(c1), "r"(c2), "h"((uint16_t)3), "l"(pol) : "memory");
}
__device__ __forceinline__ void wbulk(uint32_t dst, const void* src, uint32_t bytes, uint32_t bar, uint64_t pol) {
  asm volatile("cp.async.bulk.shared::cluster.global.mbarrier::complete_tx::bytes.multicast::cluster.L2::cache_hint [%0], [%1], %2, [%3], %4, %5;"
               ::"r"(dst), "l"(src), "r"(bytes), "r"(bar), "h"((uint16_t)3), "l"(pol) : "memory");
}
__device__ __forceinline__ void tma3d(uint32_t dst, const CUtensorMap* m, int c0, int c1, int c2, uint32_t bar) {
  asm volatile("cp.async.bulk.tensor.3d.shared::cluster.global.mbarrier::complete_tx::bytes [%0], [%1, {%3, %4, %5}], [%2];"
               ::"r"(dst), "l"(m), "r"(bar), "r"(c0), "r"(c1), "r"(c2) : "memory");
}
__device__ __forceinline__ void prefetch_l2(const void* p, uint32_t bytes) { asm volatile("cp.async.bulk.prefetch.L2.global [%0], %1;" ::"l"(p), "r"(bytes) : "memory"); }
__device__ __forceinline__ uint64_t policy_evict_first() { uint64_t p; asm volatile("createpolicy.fractional.L2::evict_first.b64 %0, 1.0;" : "=l"(p)); return p; }
__device__ __forceinline__ uint64_t policy_evict_normal() { uint64_t p; asm volatile("createpolicy.fractional.L2::evict_normal.b64 %0, 1.0;" : "=l"(p)); return p; }
__device__ __forceinline__ void fence_async_smem() { asm volatile("fence.proxy.async.shared::cta;" ::: "memory"); }
__device__ __forceinline__ bool elect_one() {
  uint32_t p;
  asm volatile("{\n.reg .pred P;\nelect.sync _|P, 0xffffffff;\nselp.u32 %0, 1, 0, P;\n}\n" : "=r"(p));
  return p;
}
__device__ __forceinline__ void wg_fence() { asm volatile("wgmma.fence.sync.aligned;" ::: "memory"); }
__device__ __forceinline__ void wg_commit() { asm volatile("wgmma.commit_group.sync.aligned;" ::: "memory"); }
template <int n> __device__ __forceinline__ void wg_wait() { asm volatile("wgmma.wait_group.sync.aligned %0;" ::"n"(n) : "memory"); }
__device__ __forceinline__ void wg_bar(int w) { asm volatile("bar.sync %0, 128;" ::"r"(w + 1) : "memory"); }
__device__ __forceinline__ void fence_gpu() { asm volatile("fence.acq_rel.gpu;" ::: "memory"); }
__device__ __forceinline__ uint32_t ld_relaxed(const uint32_t* p) { uint32_t v; asm volatile("ld.relaxed.gpu.global.u32 %0, [%1];" : "=r"(v) : "l"(p) : "memory"); return v; }
__device__ __forceinline__ uint32_t ld_acquire(const uint32_t* p) { uint32_t v; asm volatile("ld.acquire.gpu.global.u32 %0, [%1];" : "=r"(v) : "l"(p) : "memory"); return v; }
__device__ __forceinline__ uint4 ld_relaxed4(const uint4* p) {
  uint4 v; asm volatile("ld.relaxed.gpu.global.v4.u32 {%0,%1,%2,%3}, [%4];" : "=r"(v.x), "=r"(v.y), "=r"(v.z), "=r"(v.w) : "l"(p) : "memory"); return v;
}
__device__ __forceinline__ uint2 ld_relaxed2(const uint2* p) {
  uint2 v; asm volatile("ld.relaxed.gpu.global.v2.u32 {%0,%1}, [%2];" : "=r"(v.x), "=r"(v.y) : "l"(p) : "memory"); return v;
}
__device__ __forceinline__ void st_relaxed(uint32_t* p, uint32_t a) { asm volatile("st.relaxed.gpu.global.u32 [%0], %1;" ::"l"(p), "r"(a) : "memory"); }
__device__ __forceinline__ void st_relaxed4(uint4* p, uint32_t a, uint32_t b, uint32_t c, uint32_t d) {
  asm volatile("st.relaxed.gpu.global.v4.u32 [%0], {%1,%2,%3,%4};" ::"l"(p), "r"(a), "r"(b), "r"(c), "r"(d) : "memory");
}
__device__ __forceinline__ void st_relaxed2(uint2* p, uint32_t a, uint32_t b) {
  asm volatile("st.relaxed.gpu.global.v2.u32 [%0], {%1,%2};" ::"l"(p), "r"(a), "r"(b) : "memory");
}
__device__ __forceinline__ void red4(uint4* p, uint32_t a, uint32_t b, uint32_t c, uint32_t d) {
  asm volatile("red.relaxed.gpu.global.add.noftz.v4.bf16x2 [%0], {%1,%2,%3,%4};" ::"l"(p), "r"(a), "r"(b), "r"(c), "r"(d) : "memory");
}
__device__ __forceinline__ void red2(uint2* p, uint32_t a, uint32_t b) {
  asm volatile("red.relaxed.gpu.global.add.noftz.v2.bf16x2 [%0], {%1,%2};" ::"l"(p), "r"(a), "r"(b) : "memory");
}
constexpr int SPIN_MAX = 1 << 21;
__device__ __forceinline__ uint32_t pack_bf16(float lo, float hi) { uint32_t r; asm("cvt.rn.bf16x2.f32 %0, %1, %2;" : "=r"(r) : "f"(hi), "f"(lo)); return r; }
__device__ __forceinline__ float bf_lo(uint32_t v) { return __uint_as_float(v << 16); }
__device__ __forceinline__ float bf_hi(uint32_t v) { return __uint_as_float(v & 0xffff0000u); }
__device__ __forceinline__ float2 lds64(uint32_t a) { float2 v; asm volatile("ld.shared.v2.f32 {%0,%1}, [%2];" : "=f"(v.x), "=f"(v.y) : "r"(a)); return v; }
__device__ __forceinline__ uint32_t lds32(uint32_t a) { uint32_t v; asm volatile("ld.shared.b32 %0, [%1];" : "=r"(v) : "r"(a)); return v; }
__device__ __forceinline__ void sts64f(uint32_t a, float x, float y) { asm volatile("st.shared.v2.f32 [%0], {%1,%2};" ::"r"(a), "f"(x), "f"(y) : "memory"); }
__device__ __forceinline__ void sts32(uint32_t a, uint32_t x) { asm volatile("st.volatile.shared.b32 [%0], %1;" ::"r"(a), "r"(x) : "memory"); }
__device__ __forceinline__ void gate(uint32_t a, int need) {
#pragma unroll 1
  for (int it = 0; it < SPIN_MAX; it++) {
    int v; asm volatile("ld.volatile.shared.b32 %0, [%1];" : "=r"(v) : "r"(a) : "memory");
    if (v >= need) break;
    if (GSLEEP) __nanosleep(GSLEEP);
  }
}
__device__ __forceinline__ void sts128(uint32_t a, uint32_t x, uint32_t y, uint32_t z, uint32_t u) { asm volatile("st.shared.v4.b32 [%0], {%1,%2,%3,%4};" ::"r"(a), "r"(x), "r"(y), "r"(z), "r"(u) : "memory"); }
__device__ __forceinline__ uint4 lds128(uint32_t a) { uint4 v; asm volatile("ld.shared.v4.u32 {%0,%1,%2,%3}, [%4];" : "=r"(v.x), "=r"(v.y), "=r"(v.z), "=r"(v.w) : "r"(a) : "memory"); return v; }
__device__ __forceinline__ uint32_t hmul2(uint32_t a, uint32_t b) { uint32_t r; asm("mul.rn.bf16x2 %0, %1, %2;" : "=r"(r) : "r"(a), "r"(b)); return r; }
__device__ __forceinline__ uint32_t hadd2(uint32_t a, uint32_t b) { uint32_t r; asm("add.rn.bf16x2 %0, %1, %2;" : "=r"(r) : "r"(a), "r"(b)); return r; }
__device__ __forceinline__ void stsm4(uint32_t a, uint32_t r0, uint32_t r1, uint32_t r2, uint32_t r3) {
  asm volatile("stmatrix.sync.aligned.m8n8.x4.shared.b16 [%0], {%1,%2,%3,%4};" ::"r"(a), "r"(r0), "r"(r1), "r"(r2), "r"(r3) : "memory");
}
__device__ __forceinline__ void stsm2(uint32_t a, uint32_t r0, uint32_t r1) {
  asm volatile("stmatrix.sync.aligned.m8n8.x2.shared.b16 [%0], {%1,%2};" ::"r"(a), "r"(r0), "r"(r1) : "memory");
}
__device__ __forceinline__ uint4 ldsm4(uint32_t a) {
  uint4 r; asm volatile("ldmatrix.sync.aligned.m8n8.x4.shared.b16 {%0,%1,%2,%3}, [%4];" : "=r"(r.x), "=r"(r.y), "=r"(r.z), "=r"(r.w) : "r"(a) : "memory"); return r;
}
__device__ __forceinline__ uint32_t movm(uint32_t a) { uint32_t r; asm("movmatrix.sync.aligned.m8n8.trans.b16 %0, %1;" : "=r"(r) : "r"(a)); return r; }
__device__ __forceinline__ void mma16816z(float (&d)[4], uint32_t a0, uint32_t a1, uint32_t a2, uint32_t a3, uint32_t b0, uint32_t b1) {
  asm("mma.sync.aligned.m16n8k16.row.col.f32.bf16.bf16.f32 {%0,%1,%2,%3}, {%4,%5,%6,%7}, {%8,%9}, {%10,%10,%10,%10};"
      : "=f"(d[0]), "=f"(d[1]), "=f"(d[2]), "=f"(d[3]) : "r"(a0), "r"(a1), "r"(a2), "r"(a3), "r"(b0), "r"(b1), "f"(0.f));
}
__device__ __forceinline__ void mma16816(float (&d)[4], const uint4& a, uint32_t b0, uint32_t b1) {
  asm("mma.sync.aligned.m16n8k16.row.col.f32.bf16.bf16.f32 {%0,%1,%2,%3}, {%4,%5,%6,%7}, {%8,%9}, {%0,%1,%2,%3};"
      : "+f"(d[0]), "+f"(d[1]), "+f"(d[2]), "+f"(d[3]) : "r"(a.x), "r"(a.y), "r"(a.z), "r"(a.w), "r"(b0), "r"(b1));
}
__device__ __forceinline__ void mma1688(float (&d)[4], uint32_t a0, uint32_t a1, uint32_t b0) {
  asm("mma.sync.aligned.m16n8k8.row.col.f32.bf16.bf16.f32 {%0,%1,%2,%3}, {%4,%5}, {%6}, {%0,%1,%2,%3};"
      : "+f"(d[0]), "+f"(d[1]), "+f"(d[2]), "+f"(d[3]) : "r"(a0), "r"(a1), "r"(b0));
}
__device__ __forceinline__ float quad_sum(float v) { v += __shfl_xor_sync(0xffffffffu, v, 1); v += __shfl_xor_sync(0xffffffffu, v, 2); return v; }
__device__ __forceinline__ float quad_max(float v) { v = fmaxf(v, __shfl_xor_sync(0xffffffffu, v, 1)); v = fmaxf(v, __shfl_xor_sync(0xffffffffu, v, 2)); return v; }
__device__ __forceinline__ float rcp(float x) { float r; asm("rcp.approx.ftz.f32 %0, %1;" : "=f"(r) : "f"(x)); return r; }
__device__ __forceinline__ float rsq(float x) { float r; asm("rsqrt.approx.ftz.f32 %0, %1;" : "=f"(r) : "f"(x)); return r; }
__device__ __forceinline__ float ex2(float x) { float r; asm("ex2.approx.ftz.f32 %0, %1;" : "=f"(r) : "f"(x)); return r; }
__device__ __forceinline__ uint32_t chk(uint32_t acc, uint32_t v, uint32_t tag) { uint32_t r; asm("lop3.b32 %0, %1, %2, %3, 0xF6;" : "=r"(r) : "r"(acc), "r"(v), "r"(tag)); return r; }
__device__ __forceinline__ uint32_t chk2(uint32_t a, uint32_t b, uint32_t tag) { uint32_t r; asm("lop3.b32 %0, %1, %2, %3, 0x7E;" : "=r"(r) : "r"(a), "r"(b), "r"(tag)); return r; }
__device__ __forceinline__ uint32_t tagged(uint32_t v, uint32_t tag) { return (v & ~1u) | tag; }

__device__ __forceinline__ int group_k0(int g, int j) {
  const int h = g >= 9, r = g - 2 - 7 * h;
  return g < 2 ? 64 * j + 32 * g : g < 16 ? 64 * (r + (r >= j)) + 32 * h : 32 * g;
}
__device__ __forceinline__ uint32_t xin_off(int c, int w) { return SM_X + (2 * c + w) * 8192; }
__device__ __forceinline__ uint32_t xin_bar(int c) { return BAR_FULLX + 8 * (c < 8 ? c ^ 4 : c); }
__device__ __forceinline__ constexpr uint32_t qkv_xslot(int g) { return g < 5 || g > 11 ? 2 : (0x5140762u >> (4 * (g - 5))) & 15; }

template <int N> struct IC { static constexpr int v = N; };

struct Cons {
  uint32_t sb;
  uint32_t rem;
  uint32_t sB, mB;
  uint32_t mX;
  bool elect;
  __device__ __forceinline__ void release2(uint32_t bar) const { if (elect) { mbar_arrive(sb + bar); mbar_arrive_remote(rem + bar); } }
  __device__ __forceinline__ uint32_t nextB(uint32_t& prev) {
    mbar_wait_c(sb + BAR_FULLB + sB, mB);
    const uint32_t a = (((sb & 0x3FFFF) + SM_B) >> 4) + sB * (BSLOT / 128);
    prev = sB == 0 ? 32 : sB - 8;
    sB += 8;
    if (sB == 40) { sB = 0; mB ^= 1; }
    return a;
  }
  __device__ __forceinline__ void progress(uint32_t v) const { if (elect) sts32(sb + SM_PROG + (threadIdx.x >> 5), v); }
  __device__ __forceinline__ void releaseLastB() const { release2(BAR_EMPTYB + (sB == 0 ? 32 : sB - 8)); }
};

__device__ __forceinline__ float2 gather_sums(const uint2* a, uint32_t stag) {
  uint2 sa, sc;
  do { sa = ld_relaxed2(a); sc = ld_relaxed2(a + 8); } while (__any_sync(0xffffffffu, chk2(sa.x, sc.x, stag) & 3));
  return make_float2(quad_sum(__uint_as_float(sa.x) + __uint_as_float(sc.x)), quad_sum(__uint_as_float(sa.y) + __uint_as_float(sc.y)));
}

struct Norm {
  float m0, m1;
  uint32_t nm0, nm1;
  float d0, d1;
  uint2 u0, u1;
  __device__ __forceinline__ Norm(float2 sum) : m0(sum.x * (-1.f / 576)), m1(sum.y * (-1.f / 576)), nm0(pack_bf16(m0, m0)), nm1(pack_bf16(m1, m1)), d0(0.f), d1(0.f) {}
  __device__ __forceinline__ uint4 centre(const uint4& a) const { return make_uint4(hadd2(a.x, nm0), hadd2(a.y, nm1), hadd2(a.z, nm0), hadd2(a.w, nm1)); }
  __device__ __forceinline__ void sqr(uint32_t a, uint32_t b) {
    d0 = fmaf(bf_lo(a), bf_lo(a), fmaf(bf_hi(a), bf_hi(a), d0)); d1 = fmaf(bf_lo(b), bf_lo(b), fmaf(bf_hi(b), bf_hi(b), d1));
  }
  __device__ __forceinline__ void send(uint2* a, int t, uint32_t stag) {
    d0 = quad_sum(d0); d1 = quad_sum(d1);
    if ((t & 3) == 0) st_relaxed2(a, (__float_as_uint(d0) & ~3u) | stag, __float_as_uint(d1));
  }
  __device__ __forceinline__ void fetch(const uint2* a) { u0 = ld_relaxed2(a); u1 = ld_relaxed2(a + 8); }
  __device__ __forceinline__ float2 rstd(const uint2* a, uint32_t stag) {
    while (__any_sync(0xffffffffu, chk2(u0.x, u1.x, stag) & 3)) fetch(a);
    const float e0 = bf_lo(nm0) - m0, e1 = bf_lo(nm1) - m1;
    const float v0 = fmaf(quad_sum(__uint_as_float(u0.x) + __uint_as_float(u1.x)), 1.f / 576, -e0 * e0);
    const float v1 = fmaf(quad_sum(__uint_as_float(u0.y) + __uint_as_float(u1.y)), 1.f / 576, -e1 * e1);
    float2 r = make_float2(rsq(fmaxf(v0, 0.f) + 1e-5f), rsq(fmaxf(v1, 0.f) + 1e-5f));
    asm volatile("" : "+f"(r.x), "+f"(r.y));
    return r;
  }
};

template <class Pre, class Mma>
__device__ __forceinline__ float2 ln_gemm_in(Cons& c, Group* G, uint32_t (&p)[18], float2& sum, int w, int st0, int j, int t, Pre&& pre, Mma&& mma) {
  const uint32_t xa = c.sb + (t >> 5) * 2048 + (t & 15) * 128, sw = (((t >> 4) & 1) ^ (t & 7)) * 16;
  float ra[4] = {0.f, 0.f, 0.f, 0.f}, rb[4] = {0.f, 0.f, 0.f, 0.f};
#pragma unroll 1
  for (int cc = 0; cc < 9; cc++) {
    const uint32_t a = xa + xin_off(cc, w);
    mbar_wait_c(c.sb + xin_bar(cc), 0);
    const uint4 u0 = ldsm4(a + sw), u1 = ldsm4(a + (sw ^ 32)), u2 = ldsm4(a + (sw ^ 64)), u3 = ldsm4(a + (sw ^ 96));
    mma16816(ra, u0, 0x3f803f80u, 0x3f803f80u); mma16816(rb, u1, 0x3f803f80u, 0x3f803f80u);
    mma16816(ra, u2, 0x3f803f80u, 0x3f803f80u); mma16816(rb, u3, 0x3f803f80u, 0x3f803f80u);
  }
  sum = make_float2(ra[0] + rb[0], ra[2] + rb[2]);
  pre(0);
  Norm n(sum);
  n.u0 = n.u1 = make_uint2(0, 0);
  auto stats = [&] {
#pragma unroll
    for (int k = 0; k < 5; k++) {
      const uint4 u = ldsm4(xa + (k < 4 ? xin_off(j, w) + (sw ^ (32 * k)) : xin_off(8, w) + ((j ^ (t & 7)) << 4))), e = n.centre(u);
      p[4 * k] = u.x; p[4 * k + 1] = u.y;
      n.sqr(e.x, e.y);
      if (k < 4) { p[4 * k + 2] = u.z; p[4 * k + 3] = u.w; n.sqr(e.z, e.w); }
    }
    n.send(G->sq + st0 + 8 * j, t, 1);
  };
  if (STATP < 0) stats();
  else {
#pragma unroll
    for (int i = 0; i < 18; i++) p[i] = 0;
  }
  pre(1);
  float2 r = make_float2(0.f, 0.f);
  uint4 y0 = ldsm4(xa + xin_off(0, w) + sw), y1 = ldsm4(xa + xin_off(0, w) + (sw ^ 32));
#pragma unroll 1
  for (int cc = 0; cc < 9; cc++) {
#pragma unroll
    for (int i = 0; i < 2; i++) {
      const uint4 f0 = n.centre(y0), f1 = n.centre(y1);
      const uint32_t a = xa + xin_off(min(cc + i, 8), w);
      y0 = ldsm4(a + (sw ^ (64 - 64 * i))); y1 = ldsm4(a + (sw ^ (96 - 64 * i)));
      uint32_t prev;
      const uint32_t bb = c.nextB(prev);
      mma(true, bb, f0, f1);
      if (i == 1) {
        if (STATP >= 0 && cc == STATP * w) stats();
        if (cc == 1) c.progress(3);
        if (cc == 5) n.fetch(G->sq + st0 + 16 * (t & 3));
        if (cc == 7) r = n.rstd(G->sq + st0 + 16 * (t & 3), 1);
        if (cc == 8 && w == 0) asm volatile("bar.arrive 6, 256;" ::: "memory");
      }
      wg_wait<1>();
      if (i + cc > 0) c.release2(BAR_EMPTYB + prev);
      if (2 * cc + i >= WOG && 2 * cc + i < WOG + 4) c.release2(BAR_EMPTYX + 32 + 8 * (2 * cc + i - WOG));
    }
  }
  c.mX = 0xff;
  if (w == 1) asm volatile("bar.sync 6, 256;" ::: "memory");
  wg_wait<0>();
  c.releaseLastB();
  c.release2(BAR_EMPTYX + 24);
  return r;
}

template <bool QKV, class Pre, class Mma>
__device__ __forceinline__ float2 ln_gemm(Cons& c, Group* G, const float (&v)[36], uint32_t (&p)[18], float2& sum, int st0, int j, int t,
                                          int layer, uint32_t tag, Pre&& pre, Mma&& mma) {
  constexpr bool known = !QKV && EARLY;
  const uint32_t stag = (2 * layer + (QKV ? 1 : 2)) & 3;
  uint4 x[6][2];
  uint4* src = G->xbox + t;
  asm volatile("" : "+l"(src));
  auto buf = [&](int g) -> uint4 (&)[2] { return x[g < 16 ? (g - 2) % 6 : g - 13]; };
  auto load = [&](int g0) {
#pragma unroll
    for (int g = g0; g < g0 + (g0 < 14 ? 3 : 2); g++) {
      const uint4* a = g < 16 ? src + ((g - 2) % 7 >= j ? 256 : 0) + (2 * ((g - 2) % 7) + 16 * (g >= 9)) * 128 : src + 2 * g * 128;
      buf(g)[0] = ld_relaxed4(a); buf(g)[1] = ld_relaxed4(a + 128);
    }
  };
  auto invalid = [&](int g, uint32_t tag) {
    uint32_t bad = chk(chk(chk2(buf(g)[0].x, buf(g)[1].x, tag), buf(g + 1)[0].x, tag), buf(g + 1)[1].x, tag);
    if (g < 14) bad = chk(chk(bad, buf(g + 2)[0].x, tag), buf(g + 2)[1].x, tag);
    if (g == 16) bad = chk(chk(chk(chk(bad, buf(g)[0].z, tag), buf(g)[1].z, tag), buf(g + 1)[0].z, tag), buf(g + 1)[1].z, tag);
    return __any_sync(0xffffffffu, bad & 1);
  };
  uint4* const d = src + 2 * j * 128;
  const int sq = st0 + 16 * (t & 3);
  if (!known) {
    float s0 = v[0] + v[1], s1 = v[2] + v[3];
#pragma unroll
    for (int i = 1; i < 9; i++) { s0 += v[4 * i] + v[4 * i + 1]; s1 += v[4 * i + 2] + v[4 * i + 3]; }
    s0 = quad_sum(s0); s1 = quad_sum(s1);
    if ((t & 3) == 0) st_relaxed2(G->sum + st0 + 8 * j, (__float_as_uint(s0) & ~3u) | stag, __float_as_uint(s1));
  }
#pragma unroll
  for (int i = 0; i < 18; i++) p[i] = pack_bf16(v[2 * i], v[2 * i + 1]);
#pragma unroll
  for (int i = 0; i < 2; i++) st_relaxed4(d + i * 128, tagged(p[4 * i], tag), p[4 * i + 1], p[4 * i + 2], p[4 * i + 3]);
  pre(0);
  if (!known) {
    sum = gather_sums(G->sum + sq, stag);
    load(2);
  }
  Norm n(sum);
  pre(1);
  const uint32_t* probe = &(G->xbox + (2 * (t & XPM) + 1) * 128 + (t | 31))->x;
  uint32_t pv;
  float2 r;
  auto inx = [](int g) { return QKV && ((g >= 5 && g < 12) || g == 17); };
  auto use = [](int g) { return QKV ? (g < 5 ? 108 : 101) + g : 18 + g; };
#pragma unroll
  for (int g = 0; g < 18; g++) {
    if (g < 16 ? g % 3 == 2 : g == 16) {
      const uint32_t lt = late(c.sb + BAR_FULLX + 64, tag);
      while (invalid(g, lt)) load(g);
      if (g < 16) load(g < 14 ? g + 3 : 16);
    }
    const uint4 f0 = n.centre(g < 2 ? make_uint4(p[8 * g], p[8 * g + 1], p[8 * g + 2], p[8 * g + 3]) : buf(g)[0]);
    const uint4 f1 = n.centre(g < 2 ? make_uint4(p[8 * g + 4], p[8 * g + 5], p[8 * g + 6], p[8 * g + 7]) : buf(g)[1]);
    if (g == 11) n.fetch(G->sq + sq);
    if (g == 16) r = n.rstd(G->sq + sq, stag);
    if (inx(g)) mbar_wait_c(c.sb + BAR_FULLX + 8 * qkv_xslot(g), ((0x34 >> qkv_xslot(g)) & 1) ^ (g == 17));
    else mbar_wait_c(c.sb + BAR_FULLB + 8 * (use(g) % 5), (use(g) / 5) & 1);
    mma(g, ((c.sb & 0x3FFFF) >> 4) + ((inx(g) ? xslot(qkv_xslot(g)) : SM_B + (use(g) % 5) * BSLOT) >> 4), f0, f1);
    if (g == 1) { wg_wait<1>(); c.release2(BAR_EMPTYB + 8 * (use(0) % 5)); }
    if (g < 2) {
      if (known) {
        if (g == 0) {
          pv = tag;
          if (!ESPEC || layer == 0) pv = ld_relaxed(probe);
        } else {
          const uint32_t lt = late(c.sb + BAR_FULLX + 64, tag);
          while (__any_sync(0xffffffffu, (pv ^ lt) & 1)) pv = ld_relaxed(probe);
          load(2);
        }
      }
      if (g == (known ? 1 : 0)) {
#pragma unroll
        for (int i = 2; i < 4; i++) st_relaxed4(d + (14 + i) * 128, tagged(p[4 * i], tag), p[4 * i + 1], p[4 * i + 2], p[4 * i + 3]);
        st_relaxed2((uint2*)(src + (32 + (j >> 1)) * 128) + (j & 1), tagged(p[16], tag), p[17]);
      }
      n.sqr(f0.x, f0.y); n.sqr(f0.z, f0.w); n.sqr(f1.x, f1.y); n.sqr(f1.z, f1.w);
      if (g == 1) {
        n.sqr(hadd2(p[16], n.nm0), hadd2(p[17], n.nm1));
        n.send(G->sq + st0 + 8 * j, t, stag);
      }
    }
    if (g == 1 && !QKV) { wg_wait<0>(); c.release2(BAR_EMPTYB + 8 * (use(1) % 5)); }
    else wg_wait<1>();
    if (g > (QKV ? 1 : 2) && !inx(g - 1)) c.release2(BAR_EMPTYB + 8 * (use(g - 1) % 5));
    if (QKV && g < 13) c.progress(33 + g);
    if (QKV && g == WOG - 1) c.release2(BAR_EMPTYX + 8 * qkv_xslot(17));
    if (QKV && g >= WOG && g < WOG + 4) c.release2(BAR_EMPTYX + 32 + 8 * (g - WOG));
  }
  if (QKV) c.mX = 0x34 ^ 0xf3;
  else { c.sB = 8 * (36 % 5); c.mB = (36 / 5) & 1; }
  wg_wait<0>();
  if (!QKV) c.release2(BAR_EMPTYB + 8 * (use(17) % 5));
  return r;
}

template <int NB, int OFF>
__device__ __forceinline__ void glu(const float (&a)[128], uint32_t (&h)[144]) {
#pragma unroll
  for (int b = 0; b < 2 * NB; b++) {
    if (HMUL) h[OFF + b] = hmul2(pack_bf16(a[2 * b], a[2 * b + 1]), pack_bf16(a[4 * NB + 2 * b], a[4 * NB + 2 * b + 1]));
    else h[OFF + b] = pack_bf16(a[2 * b] * a[4 * NB + 2 * b], a[2 * b + 1] * a[4 * NB + 2 * b + 1]);
  }
}

__global__ void __cluster_dims__(2, 1, 1) __launch_bounds__(384, 1)
fused_kernel(const __nv_bfloat16* __restrict__ x_in, Group* ws, const char* __restrict__ wqkv,
             const char* __restrict__ wo, char* __restrict__ out, uint32_t first, const __grid_constant__ Maps maps,
             const char* __restrict__ wg, const char* __restrict__ wu, const char* __restrict__ wd) {
  extern __shared__ __align__(1024) uint8_t smem_raw[];
  const uint32_t sb = smem_u32(smem_raw);
  const uint32_t bx = blockIdx.x - first;
  if (bx >= NCTA) {
    const int e = blockIdx.x & 3;
    const uint32_t par = ~ld_relaxed(ws->flag + 32) & 1;
    __nanosleep(RDELAY);
    if (threadIdx.x < 16) prefetch_l2(wo + (144 * e + 9 * threadIdx.x) * 1152, 9 * 1152);
#pragma unroll 1
    for (int r = threadIdx.x >> 3; r < 144; r += 48) {
      const uint4* row = (const uint4*)(wo + (144 * e + r) * 1152) + (threadIdx.x & 7);
      float a = 0.f;
      uint4 u;
#pragma unroll
      for (int i = 0; i < 72; i += 8) {
        u = __ldg(row + i);
        a += ((bf_lo(u.x) + bf_hi(u.x)) + (bf_lo(u.y) + bf_hi(u.y))) + ((bf_lo(u.z) + bf_hi(u.z)) + (bf_lo(u.w) + bf_hi(u.w)));
      }
      const int h = r >= 72, k = r - 72 * h;
      ((Scratch*)ws)->woc[threadIdx.x & 7][k < 64 ? 64 + 8 * k + ((2 * e + h) ^ (k & 7)) : 576 * h + 8 * (k & 7) + (e ^ (k & 7))] = u;
      a = quad_sum(a);
      a += __shfl_xor_sync(0xffffffffu, a, 4);
      if ((threadIdx.x & 7) == 0) ((Scratch*)ws)->woc[2 * e + h][640 + k] = make_uint4(pack_bf16(a, a - bf_lo(pack_bf16(a, 0.f))), 0, 0, 0);
    }
    fence_gpu();
    __syncthreads();
    if (threadIdx.x == 0) st_relaxed(((Scratch*)ws)->done + e, par);
    const int cc = threadIdx.x % 54, r0 = threadIdx.x / 54, part = cc / 18, jj = 2 * e + (cc % 18) / 9, c9 = cc % 9;
    if (r0 < 6) {
#pragma unroll 4
      for (int k = r0; k < 576; k += 6) {
        const uint4 u = __ldg((const uint4*)(wqkv + k * 3456 + part * 1152 + 144 * jj) + c9);
        ((Scratch*)ws)->wq[jj][k >> 4][c9 < 8 ? part * 128 + (k & 15) * 8 + (c9 ^ (k & 7)) : 384 + part * 16 + (k & 15)] = u;
      }
    }
    fence_gpu();
    __syncthreads();
    if (threadIdx.x == 0) st_relaxed(((Scratch*)ws)->done + 32 + e, par);
    return;
  }
  if (threadIdx.x == 0) asm volatile("prefetch.tensormap [%0];" ::"l"(&maps.x) : "memory");
  const int warp = __shfl_sync(0xffffffffu, threadIdx.x >> 5, 0);
  const int lane = threadIdx.x & 31;
  const int rank = blockIdx.x & 1;
  if (elect_one()) {
    if (warp >= 8) {
#pragma unroll
      for (int i = 0; i < 9; i++) mbar_init(sb + SM_BAR + 72 * (warp - 8) + 8 * i, warp < 10 ? 1 : 4);
      sts32(sb + SM_PROG + 4 * (warp - 8), 0);
      asm volatile("fence.mbarrier_init.release.cluster;" ::: "memory");
    } else if (warp == 1 || warp == 2) {
      asm volatile("prefetch.tensormap [%0];" ::"l"(&maps.x + warp) : "memory");
    } else if (warp == 3) {
      if (PFMODE & 1) prefetch_l2((const char*)x_in + bx * 18432, 18432);
    } else if (warp == 4) {
      if (PFMODE & 2) prefetch_l2(wqkv + bx * (15552 / PFQ), 15552 / PFQ);
    }
  }
  __syncwarp();
  asm volatile("barrier.cluster.arrive.relaxed.aligned;" ::: "memory");
  if (warp == 8) PROFX(53);
  int lb = bx;
  if (GPCMAP) {
    const int cl = bx >> 1, u = cl - 36;
    lb = (cl < 4 ? cl : cl < 36 ? 8 * ((cl - 4) & 7) + ((cl - 4) >> 3) + (((cl - 4) & 7) ? 0 : 4) : 8 * (1 + u % 7) + 4 + u / 7) * 2 + rank;
  }
#define CTA_J(b) (((b) >> 1) & 7)
#define CTA_RB(b) ((((b) >> 4) << 1) | ((b) & 1))
  const int j = CTA_J(lb), rb = CTA_RB(lb);

  PROF(23);
  if (warp >= 8) {
    asm volatile("setmaxnreg.dec.sync.aligned.u32 " STR(REGS_P) ";");
    auto x_chunk = [&](int cc) {
      mbar_expect_tx(sb + xin_bar(cc), 16384);
      tma3d(sb + xin_off(cc, 0), &maps.x, 64 * cc, 0, 64 * rb, sb + xin_bar(cc));
      tma3d(sb + xin_off(cc, 1), &maps.x, 64 * cc, 1, 64 * rb, sb + xin_bar(cc));
    };
    if (warp == 9 && elect_one()) {
      fence_async_smem();
#pragma unroll 1
      for (int i = 0; i < 9; i++) x_chunk(i);
    }
    __syncwarp();
    if (warp == 9) PROFX(54);
    asm volatile("barrier.cluster.wait.aligned;" ::: "memory");
    if (warp == 8) PROFX(56);
    const uint64_t pol = W_POLICY(), pola = A_POLICY();
    uint4 (* const wq)[432] = ((Scratch*)ws)->wq[j];
    const uint32_t par = ~ld_relaxed(ws[2 * rb].flag + 32 + 32 * j) & 1;
    auto qkv_group = [&](bool copy, int k, uint32_t dst, uint32_t bar) {
      if (copy) {
        wbulk(dst + rank * 8192, wq[(k >> 4) + rank], 6912, bar, pol);
      } else {
        wtma3d(dst + rank * 8192, &maps.qm, 72 * j, k + 16 * rank, 0, bar, pola);
        wtma3d(dst + rank * 8192 + 6144, &maps.qc, 72 * j + 64, k + 16 * rank, 0, bar, pola);
      }
    };
    auto chore = [&](int i) {
#pragma unroll 1
      for (int it = 0; it < SPIN_MAX; it++)
        if (__all_sync(0xffffffffu, ld_acquire(((Scratch*)ws)->done + i) == par)) break;
      asm volatile("fence.proxy.async.global;" ::: "memory");
    };
    const int ktab = group_k0(lane, j);
    auto qkv_gate = [&](int g) { if (g >= 8) gate(sb + SM_PROG, 33 + ((g - 8) * QPACE >> 4)); };
    if (warp == 8) {
      uint32_t s = 0, ph = 1;
      auto slot = [&](uint32_t bytes, auto&& issue) {
        const uint32_t bar = sb + BAR_FULLB + 8 * s;
        mbar_wait(sb + BAR_EMPTYB + 8 * s, ph);
        if (elect_one()) {
          mbar_expect_tx(bar, bytes);
          issue(sb + SM_B + s * BSLOT, bar);
        }
        if (++s == 5) { s = 0; ph ^= 1; }
      };
#pragma unroll 1
      for (int layer = 0; layer < NLAYERS; layer++) {
        if (layer) chore(32 + (j >> 1));
#pragma unroll 1
        for (int g = 0; g < 18 - layer; g += layer && g == 4 ? 8 : 1) {
          const int k = layer ? __shfl_sync(0xffffffffu, ktab, g) : 32 * g;
          if (layer) qkv_gate(g);
          else if (g == QD) mbar_wait(sb + xin_bar(XH), 0);
          slot(2 * 6912, [&](uint32_t dst, uint32_t bar) { qkv_group(layer, k, dst, bar); });
        }
        if (!FCH) {
          gate(sb + SM_PROG, 32 * layer + 20);
          gate(sb + SM_PROG + 4, 32 * layer + 20);
        }
#pragma unroll 1
        for (int t = 0; t < 5; t++) {
          const CUtensorMap* m = &maps.g + (t < 3 ? rank : 2 + rank);
          asm volatile("" : "+l"(m));
          const int c2 = t < 3 ? 9 * j + 2 * t : 18 * j + 3 + 3 * t;
          const uint32_t half = t < 3 ? 8192 : 6144;
          auto tile = [&](int g) {
            const int k = __shfl_sync(0xffffffffu, ktab, g);
            slot(2 * half, [&](uint32_t dst, uint32_t bar) { wtma3d(dst + rank * half, m, 0, k, c2, bar, pol); });
          };
          int g = 0;
          if (t == 0) {
#pragma unroll 1
            for (; g < 5; g++) {
              mbar_wait(sb + BAR_FULLB + 8 * (s < FCH ? s + 5 - FCH : s - FCH), s < FCH ? ph : ph ^ 1);
              if (FG >= 0 && g == FN) gate(sb + SM_PROG + 4, 32 * layer + 20);
              tile(g);
            }
          }
#pragma unroll 1
          for (; g < 18; g++) tile(g);
        }
      }
    } else if (warp == 9) {
      uint32_t mE = 0;
      auto acquire = [&](uint32_t s) { mbar_wait(sb + BAR_EMPTYX + 8 * s, (mE >> s) & 1); mE ^= 1u << s; };
      auto landed = [&](uint32_t s) { mbar_wait(sb + BAR_FULLX + 8 * s, (mE >> s) & 1); };
      auto slot = [&](uint32_t s, const CUtensorMap* m, int col, int row, uint64_t pol) {
        acquire(s);
        if (elect_one()) {
          mbar_expect_tx(sb + BAR_FULLX + 8 * s, XSLOT);
          wtma2d(sb + xslot(s) + rank * 9216, m, col, row + 72 * rank, sb + BAR_FULLX + 8 * s, pol);
        }
      };
#pragma unroll 1
      for (int layer = 0; layer < NLAYERS; layer++) {
        if (layer) chore(32 + (j >> 1));
#pragma unroll 1
        for (int g = 5; g < 18 * layer; g += g == 11 ? 6 : 1) {
          const uint32_t s = qkv_xslot(g);
          const int k = __shfl_sync(0xffffffffu, ktab, g);
          if (g < 12) qkv_gate(g);
          acquire(s);
          if (elect_one()) {
            mbar_expect_tx(sb + BAR_FULLX + 8 * s, 2 * 6912);
            qkv_group(true, k, sb + xslot(s), sb + BAR_FULLX + 8 * s);
          }
          if (XCH & 1) landed(s);
        }
#pragma unroll 1
        for (int i = 0; i < 4; i++) { slot(4 + i, &maps.o, 64 * j, 144 * i, pola); if (XCH & 2) landed(4 + i); }
        if (layer == 0) { chore(lane & 3); PROFX(57); }
        acquire(3);
        if (elect_one()) {
          mbar_expect_tx(sb + BAR_FULLX + 24, 10240 + 1280);
          wbulk(sb + SM_WOC + rank * 5120, ((Scratch*)ws)->woc[j] + rank * 320, 5120, sb + BAR_FULLX + 24, pola);
          wbulk(sb + SM_WSUM + rank * 640, ((Scratch*)ws)->woc[j] + 640 + rank * 40, 640, sb + BAR_FULLX + 24, pola);
        }
#pragma unroll 1
        for (int u = 0; u < 36; u++) {
          const uint32_t s = 4 * (u & 1) + ((u >> 1) & 3);
          slot(s, &maps.d, u < 4 ? 512 : 64 * ((j + (u >> 2)) & 7), 576 * j + 144 * (u & 3), pol);
          if ((XCH & 4) && u < 3) landed(s);
        }
      }
    } else {
      const int w = warp - 10, grp = 2 * rb + w;
      if (PFMODE & 4) {
        mbar_wait(sb + xin_bar(XP), 0);
        if (lane == 0) prefetch_l2(wqkv + (2 * bx + w) * 7776, 7776);
      }
      gate(sb + SM_PROG, 3);
      if (w == 0) PROFX(58);
      auto prefetch_gu = [&](int l0, int n) {
#pragma unroll 1
        for (int i = lane; i < 36 * n; i += 32) {
          asm volatile("prefetch.global.L2 [%0];" ::"l"((w ? wu : wg) + (size_t)(36 * rb + i / n) * 9216 + 1152 * j + 128 * (l0 + i % n)));
          __nanosleep(PFSLEEP);
        }
      };
      auto clear = [&](uint4* p, int n) {
#pragma unroll 1
        for (int i = lane; i < n; i += 64) { st_relaxed4(p + i, 0, 0, 0, 0); st_relaxed4(p + i + 32, 0, 0, 0, 0); __nanosleep(CLRSLEEP); }
      };
      auto exchange = [&](uint32_t v, uint32_t bar) {
        if (FENCE1) { if (lane == 0) fence_gpu(); } else fence_gpu();
        __syncwarp();
        if (w == 0 && v != 1) PROFX(64 + 58 - 2 * v);
        if (lane == 0) st_relaxed(ws[grp].flag + j, v);
#pragma unroll 1
        for (int it = 0; it < SPIN_MAX; it++) {
          const uint32_t f = ld_relaxed(ws[grp].flag + (lane & 7));
          if (__all_sync(0xffffffffu, v ? f >= v : f == 0)) break;
        }
        if (lane == 0) mbar_arrive(sb + bar + 8 * w);
      };
      if (MAPPF && w == 0 && lane < 6) asm volatile("prefetch.tensormap [%0];" ::"l"(&maps.o + lane) : "memory");
#pragma unroll 1
      for (int layer = 0; layer < NLAYERS; layer++) {
        gate(sb + SM_PROG, 32 * layer + 3);
        if (PFF & 1) prefetch_gu(0, 2);
        gate(sb + SM_PROG, 32 * layer + 22);
        if (PFF & 2) prefetch_gu(2, 2);
        if (layer == 0) {
          clear(ws[grp].inbox[0] + 2 * j * INBOX, 2 * INBOX);
          exchange(1, BAR_CLR);
          if (w == 0) PROFX(59);
        }
        if (PFF & 2) prefetch_gu(4, 2);
        if (PFF & 4) prefetch_gu(6, 3);
#pragma unroll 1
        for (int i = lane; i < ((PFF & 8) ? 162 : 0); i += 32) {
          asm volatile("prefetch.global.L2 [%0];" ::"l"(wd + (size_t)(576 * j + 36 * rb + 18 * w) * 1152 + 128 * i));
          __nanosleep(PFSLEEP);
        }
        if (w == 0 && layer == 0) PROFX(60);
        mbar_wait(sb + BAR_REDDONE + 8 * w, layer);
        if (w == 0) PROFX(64 + 53 + 4 * layer);
        exchange(2 - 2 * layer, BAR_RREADY);
        if (w == 0) PROFX(64 + 56 + 4 * layer);
      }
      mbar_wait(sb + BAR_DONE + 8 * w, 0);
    }
  } else {
    asm volatile("setmaxnreg.inc.sync.aligned.u32 " STR(REGS_C) ";");
#define THREAD_IDS()                                                                   \
    int tid_ = threadIdx.x, bid_ = lb;                                                  \
    asm volatile("" : "+r"(tid_), "+r"(bid_));                                          \
    const int w = warp >> 2, wp = warp & 3;                                             \
    const int lane = tid_ & 31, t = tid_ & 127, g = lane >> 2, q = lane & 3;           \
    const int j = CTA_J(bid_), rb = CTA_RB(bid_), grp = 2 * rb + w;                    \
    const int st0 = wp * 64 + g;                         \
    Group* const G = ws + grp;                                                         \
    const uint32_t dsb = (sb & 0x3FFFF) >> 4;                                          \
    (void)t; (void)g; (void)q; (void)grp; (void)j; (void)st0; (void)dsb; (void)G
    Cons c;
    c.sb = sb; c.sB = 0; c.mB = 0; c.mX = 0; c.elect = (threadIdx.x & 127) == 0;
    asm volatile("mapa.shared::cluster.u32 %0, %1, %2;" : "=r"(c.rem) : "r"(sb), "r"(rank ^ 1));
    float v[36], a1[96], a2[12];
    float2 sum, rs;
    uint32_t res[18], xtag;
    auto qkv_mma = [&](bool acc, uint32_t bb, const uint4& f0, const uint4& f1) {
      wg_fence();
      wgmma_ra<192>(a1, f0, desc_hi(2048, 1024, 1) + bb, acc);
      wgmma_ra<24>(a2, f0, desc_hi(128, 256, 0) + (bb + 384), acc);
      wgmma_ra<192>(a1, f1, desc_hi(2048, 1024, 1) + (bb + 512), true);
      wgmma_ra<24>(a2, f1, desc_hi(128, 256, 0) + (bb + 896), true);
      wg_commit();
    };
    {
      THREAD_IDS();
      if (OPEN) {
        if (q == 0) { st_relaxed2(G->sum + st0 + 8 * j, 0, 0); st_relaxed2(G->sq + st0 + 8 * j, 0, 0); }
        if (wp == 3) {
#pragma unroll
          for (int i = 0; i < 5; i++) st_relaxed4(G->halo + j * 160 + lane + i * 32, 0, 0, 0, 0);
        }
        if (lane >= OPENL) st_relaxed4(G->obox + (8 * WPROBE + j) * 128 + t, 0, 0, 0, 0);
      }
      xtag = __shfl_sync(0xffffffffu, ~ld_relaxed(G->flag + 32 + 32 * j) & 1, 0);
      if (OPEN && EARLY && lane >= OPENL) st_relaxed4(G->xbox + (2 * j + 1) * 128 + t, xtag ^ 1, 0, 0, 0);
      asm volatile("barrier.cluster.wait.aligned;" ::: "memory");
      PROF(0);
#pragma unroll
      for (int i = 0; i < 96; i++) asm volatile("mov.b32 %0, 0;" : "=f"(a1[i]));
#pragma unroll
      for (int i = 0; i < 12; i++) asm volatile("mov.b32 %0, 0;" : "=f"(a2[i]));
      PROF(1);
      rs = ln_gemm_in(c, G, res, sum, w, st0, j, t, [&](int i) { PROF(2 + i); if (i) PROF(4); }, qkv_mma);
    }
#pragma unroll 1
    for (int layer = 0;; layer++) {
      const uint32_t tag = layer ^ 1;
      const int pb = 1 + layer * 30;
      uint4 own[5];
      {
        THREAD_IDS();
        PROF(pb + 4);
        uint32_t kv[3][18];
        auto cvt = [&](int b, float r) {
#pragma unroll
          for (int cc = 0; cc < 18; cc++) {
            const float* a = (cc == 8 ? a2 + 4 : cc == 17 ? a2 + 8 : cc < 8 ? a1 + 32 + 4 * cc : a1 + 28 + 4 * cc) + 2 * (b - 1);
            const uint32_t u = pack_bf16(a[0] * r, a[1] * r);
            kv[b][cc] = cc < 9 ? u : movm(u);
          }
        };
        cvt(2, rs.y);
#pragma unroll
        for (int i = 0; i < 18; i += 4) kv[2][i] = tagged(kv[2][i], tag);
        const uint32_t msg = sb + (w ? xslot(3) : xslot(0) + 24576) + wp * 2304 + lane * 16;
        if (wp == 3) {
          uint4* hp = G->halo + j * 160 + lane;
#pragma unroll
          for (int i = 0; i < 4; i++) st_relaxed4(hp + i * 32, kv[2][4 * i], kv[2][4 * i + 1], kv[2][4 * i + 2], kv[2][4 * i + 3]);
          st_relaxed2((uint2*)(hp + 128), kv[2][16], kv[2][17]);
        } else {
#pragma unroll
          for (int i = 0; i < 4; i++) sts128(msg + i * 512, kv[2][4 * i], kv[2][4 * i + 1], kv[2][4 * i + 2], kv[2][4 * i + 3]);
          sts64f(msg + 2048 - lane * 8, __uint_as_float(kv[2][16]), __uint_as_float(kv[2][17]));
        }
        cvt(1, rs.x);
        uint32_t Q[4][6];
#pragma unroll
        for (int h = 0; h < 4; h++)
#pragma unroll
          for (int i = 0; i < 6; i++) {
            const float* a = 4 * h + i < 16 ? a1 + 8 * h + 2 * i : a2 + 8 * h + 2 * i - 32;
            const uint32_t u = pack_bf16(a[0], a[1]);
            Q[h][i] = i < 2 ? (q >= h ? u : 0) : i < 4 ? u : (q <= h ? u : 0);
          }
        const bool lo0 = 2 * q > g, lo1 = 2 * q + 1 > g;
        const uint32_t M = (lo0 ? 0xffffu : 0u) | (lo1 ? 0xffff0000u : 0u);
        auto scores = [&](int h, int b, float (&s)[4]) {
          mma16816z(s, Q[h][0], Q[h][1], Q[h][2], Q[h][3], kv[b][2 * h], kv[b][2 * h + 1]);
          mma1688(s, Q[h][4], Q[h][5], kv[b][2 * h + 2]);
        };
        auto softmax = [&](float (&l)[4][2], float r, uint32_t (&P)[4]) {
          const float sl = r * (0.23570226039551584f * 1.4426950408889634f);
          float m[4];
#pragma unroll
          for (int h = 0; h < 4; h++) { m[h] = fmaxf(l[h][0], l[h][1]); m[h] = fmaxf(m[h], __shfl_xor_sync(0xffffffffu, m[h], 1)); }
#pragma unroll
          for (int h = 0; h < 4; h++) m[h] = fmaxf(m[h], __shfl_xor_sync(0xffffffffu, m[h], 2)) * sl;
#pragma unroll
          for (int h = 0; h < 4; h++) P[h] = pack_bf16(ex2(fmaf(l[h][0], sl, -m[h])), ex2(fmaf(l[h][1], sl, -m[h])));
        };
        const bool remote = wp == 0 && rb > 0;
        const uint4* hp = (G - 2)->halo + j * 160 + lane;
        auto halo = [&] {
#pragma unroll
          for (int i = 0; i < 4; i++) { const uint4 u = ld_relaxed4(hp + i * 32); kv[0][4 * i] = u.x; kv[0][4 * i + 1] = u.y; kv[0][4 * i + 2] = u.z; kv[0][4 * i + 3] = u.w; }
          const uint2 u = ld_relaxed2((const uint2*)(hp + 128));
          kv[0][16] = u.x; kv[0][17] = u.y;
        };
#pragma unroll
        for (int i = 0; i < 18; i++) kv[0][i] = 0;
        float l0[4][2], l1[4][2];
#pragma unroll
        for (int h = 0; h < 4; h++) {
          float s1[4], s2[4];
          scores(h, 1, s1); scores(h, 2, s2);
          l0[h][0] = s1[0]; l0[h][1] = s1[1];
          l1[h][0] = lo0 ? s1[2] : s2[2]; l1[h][1] = lo1 ? s1[3] : s2[3];
        }
        hp += __float_as_uint(l1[HALOH][0]) & late(sb + BAR_FULLX + 64, 0);
        if (remote) halo();
        uint32_t P0[4], P1[4];
        softmax(l1, rs.y, P1);
        if (remote) {
          while (__any_sync(0xffffffffu, chk(chk2(kv[0][0], kv[0][4], tag) | chk2(kv[0][8], kv[0][12], tag), kv[0][16], tag) & 1)) halo();
        }
        if (FG < 0) c.progress(32 * layer + 20);
        wg_bar(w);
        if (wp > 0) {
          const uint32_t from = msg - 2304;
#pragma unroll
          for (int i = 0; i < 4; i++) { const uint4 u = lds128(from + i * 512); kv[0][4 * i] = u.x; kv[0][4 * i + 1] = u.y; kv[0][4 * i + 2] = u.z; kv[0][4 * i + 3] = u.w; }
          const float2 u = lds64(from + 2048 - lane * 8);
          kv[0][16] = __float_as_uint(u.x); kv[0][17] = __float_as_uint(u.y);
        }
        PROF(pb + 5);
        const bool first = (rb == 0 && wp == 0);
#pragma unroll
        for (int h = 0; h < 4; h++) {
          float s0[4];
          scores(h, 0, s0);
          if (first) s0[0] = s0[1] = -INFINITY;
          l0[h][0] = lo0 ? s0[0] : l0[h][0]; l0[h][1] = lo1 ? s0[1] : l0[h][1];
        }
        softmax(l0, rs.x, P0);
        uint4* ob = G->obox + t;
        uint32_t car0 = 0, car1 = 0;
#pragma unroll
        for (int h = 0; h < 4; h++) {
          float o[3][4], z[4] = {0.f, 0.f, 0.f, 0.f};
          mma1688(z, P0[h], P1[h], 0x3f803f80u);
#pragma unroll
          for (int i = 0; i < 3; i++) {
            mma16816z(o[i], P0[h] & ~M, P1[h] & M, 0u, P1[h] & ~M, kv[1][9 + 2 * h + i], kv[2][9 + 2 * h + i]);
            mma1688(o[i], P0[h] & M, 0u, kv[0][9 + 2 * h + i]);
          }
          const float i0 = rcp(z[0]), i1 = rcp(z[2]);
#pragma unroll
          for (int i = 0; i < 3; i++) { o[i][0] *= i0; o[i][1] *= i0; o[i][2] *= i1; o[i][3] *= i1; }
          const uint32_t o0 = q < h ? car0 : pack_bf16(o[0][0], o[0][1]), o1 = q < h ? car1 : pack_bf16(o[0][2], o[0][3]);
          own[h] = make_uint4(o0 | 1, o1, pack_bf16(o[1][0], o[1][1]), pack_bf16(o[1][2], o[1][3]));
          if (h < OFIRST) st_relaxed4(ob + (8 * h + j) * 128, own[h].x, own[h].y, own[h].z, own[h].w);
          car0 = pack_bf16(o[2][0], o[2][1]); car1 = pack_bf16(o[2][2], o[2][3]);
        }
        car0 = tagged(car0, tag);
        own[4] = make_uint4(car0, car1, 0, 0);
        PROF(pb + 6);
      }
      uint2 sa, sc;
      {
        THREAD_IDS();
        uint4* src = G->obox + t;
        asm volatile("" : "+l"(src));
        uint4 x[32];
        const uint4* from[7];
#pragma unroll
        for (int r = 0; r < 7; r++) { from[r] = src + (r >= j ? 128 : 0); asm volatile("" : "+l"(from[r])); }
        auto at = [&](int i) { return i < 28 ? from[i % 7] + (8 * (i / 7) + i % 7) * 128 : src + (i + 4) * 128; };
        auto load = [&](int i) { x[i] = ld_relaxed4(at(i)); };
        const uint32_t* probe = &(G->obox + (8 * WPROBE + (lane & 7)) * 128 + (t | 31))->x;
        uint32_t pv = ld_relaxed(probe);
#pragma unroll
        for (int i = 3; i < 8; i++) mbar_wait_c(sb + BAR_FULLX + 8 * i, (c.mX >> i) & 1);
        c.mX ^= 0xf8;
        while (__any_sync(0xffffffffu, ~pv & 1)) pv = ld_relaxed(probe);
        if (layer) PROF(24); else PROF(25);
        if (WOBAR && w == 1) asm volatile("bar.sync 7, 256;" ::: "memory");
#pragma unroll
        for (int i = 0; i < WB1; i++) load(i);
        if (WOBAR && w == 0) asm volatile("bar.arrive 7, 256;" ::: "memory");
#pragma unroll
        for (int h = OFIRST; h < 4; h++) st_relaxed4(src + (8 * h + j) * 128, own[h].x, own[h].y, own[h].z, own[h].w);
        st_relaxed2((uint2*)(src + (32 + (j >> 1)) * 128) + (j & 1), own[4].x, own[4].y);
        if (layer) PROF(26); else PROF(27);
        float a[36];
        constexpr uint32_t NEXT = 576 - (575u << 16);
        auto step = [&](const uint4& f, uint32_t s, int i, uint32_t more, bool acc) {
          const uint32_t r = (xslot(4) >> 4) + (i < 4 ? 72 * s + 16 * i : 144 * s + 64) * 8, c = (SM_WOC >> 4) + (i < 4 ? 64 + 128 * i : 0) + s;
          wgmma_ra<72>(a, f, desc_hi(0, i < 4 ? 1024 : 9216, 1) + (dsb + more + (r + ((c - r) << 16))), acc);
        };
        if (OWNBAR) asm volatile("bar.sync 4, 256;" ::: "memory");
        float e[4];
        wg_fence();
        if (EARLY) {
#pragma unroll
          for (int i = 0; i < 5; i++) wgmma_ra<8>(e, own[i], desc_hi(128, 0, 0) + (dsb + (SM_WSUM >> 4) + 16 * i), i > 0);
          wg_commit();
        }
#pragma unroll
        for (int i = 0; i < 4; i++) step(own[i], 0, i, j * NEXT, i > 0);
        wg_commit();
        if (layer) PROF(28); else PROF(29);
        auto batch = [&](auto e0, auto e1, auto e2, int b) {
          constexpr int E0 = decltype(e0)::v, E1 = decltype(e1)::v, E2 = decltype(e2)::v;
          const uint32_t one = (LATE0 || E0 > 0) && E1 > E0 ? late(sb + BAR_FULLX + 64, 1) : 1;
          while (E1 > E0) {
            uint32_t bad = 0;
#pragma unroll
            for (int i = E0; i < E1; i++) bad = i < 28 ? chk(bad, x[i].x, one) : chk(chk(bad, x[i].x, tag), x[i].z, tag);
            if (!__any_sync(0xffffffffu, bad & 1)) break;
#pragma unroll
            for (int i = E0; i < E1; i++) load(i);
          }
          if (b == 0) PROF(pb + 7);
          if (b == FG) c.progress(32 * layer + 20);
          if (b > 0 && E2 > E1) wg_wait<WOW>();
#pragma unroll
          for (int i = E1; i < E2; i++) load(i);
          if (EARLY && b == 0) {
            wg_wait<1>();
            if (q == 0) st_relaxed2(G->sum + st0 + 8 * j, (__float_as_uint(e[0] + e[1]) & ~3u) | ((2 * layer + 2) & 3), __float_as_uint(e[2] + e[3]));
          }
          if (EARLY && b == SUMB) { sa = ld_relaxed2(G->sum + st0 + 16 * q); sc = ld_relaxed2(G->sum + st0 + 16 * q + 8); }
          if (E1 > E0) {
            wg_fence();
#pragma unroll
            for (int i = E0; i < E1; i++) {
              step(x[i], i % 7, i / 7, i < 28 && i % 7 >= j ? NEXT : 0, true);
            }
            wg_commit();
          }
        };
        batch(IC<0>(), IC<WB1>(), IC<WB2>(), 0);
        batch(IC<WB1>(), IC<WB2>(), IC<WB3>(), 1);
        batch(IC<WB2>(), IC<WB3>(), IC<32>(), 2);
        batch(IC<WB3>(), IC<32>(), IC<32>(), 3);
        wg_wait<0>();
        if (w == 0) asm volatile("bar.arrive 3, 256;" ::: "memory");
        PROF(pb + 8);
#pragma unroll
        for (int i = 0; i < 18; i++) {
          v[2 * i] = bf_lo(res[i]) + a[2 * i];
          v[2 * i + 1] = bf_hi(res[i]) + a[2 * i + 1];
        }
      }
      uint32_t lsb;
      uint32_t h[144];
      {
        THREAD_IDS();
        float a[128];
        const uint32_t xd = sb + xslot(4 * w) + (lane >> 4) * 1024 + (16 * wp + (lane & 15)) * 16;
        const float2 rs = ln_gemm<false>(c, G, v, res, sum, st0, j, t, layer, xtag,
          [&](int i) {
            if (i == 0) {
              lsb = ((res[0] & 1) | (res[4] & 1) << 1 | (res[8] & 1) << 2 | (res[12] & 1) << 3 | (res[16] & 1) << 4) ^ (xtag * 31);
              if (EARLY) {
                const uint32_t st = late(sb + BAR_FULLX + 64, (2 * layer + 2) & 3);
                while (__any_sync(0xffffffffu, chk2(sa.x, sc.x, st) & 3)) { sa = ld_relaxed2(G->sum + st0 + 16 * q); sc = ld_relaxed2(G->sum + st0 + 16 * q + 8); }
                sum.x += quad_sum(__uint_as_float(sa.x) + __uint_as_float(sc.x)); sum.y += quad_sum(__uint_as_float(sa.y) + __uint_as_float(sc.y));
              }
              if (w == 1) asm volatile("bar.sync 3, 256;" ::: "memory");
            }
            PROF(pb + 9 + i);
          },
          [&](int gi, uint32_t bb, const uint4& f0, const uint4& f1) {
            if (gi == 0) PROF(pb + 11);
            if (TLEAD0 && gi == 18 - TLEAD0 && w == 1) asm volatile("bar.sync 5, 256;" ::: "memory");
            wg_fence();
            wgmma_ra<256>(a, f0, desc_hi(4096, 1024, 1) + bb, gi > 0);
            wgmma_ra<256>(a, f1, desc_hi(4096, 1024, 1) + (bb + 128), true);
            wg_commit();
            if (TLEAD0 && gi == 17 && w == 0) asm volatile("bar.arrive 5, 256;" ::: "memory");
            stsm4(xd + gi * 4096, f0.x, f0.y, f0.z, f0.w);
            stsm4(xd + gi * 4096 + 2048, f1.x, f1.y, f1.z, f1.w);
            if (gi == 17) { fence_async_smem(); wg_bar(w); }
          });
        sts64f(sb + SM_KEEP + (tid_ >> 2) * 8, rs.x * rs.x, rs.y * rs.y);
        c.progress(32 * layer + 22);
        PROF2(pb + 12);
        glu<16, 0>(a, h);
        const Desc da0 = desc_hi(1024, 128, 0) + (dsb + (xslot(4 * w) >> 4));
        auto tile = [&](auto wide, auto last) {
          const uint32_t xe = BAR_EMPTYX + 32 * (t & 1) + 4 * (t & 6);
          auto group = [&](int gi) {
            uint32_t prev;
            const uint32_t bb = c.nextB(prev);
            const Desc da = da0 + gi * 256;
            wg_fence();
            if (wide()) {
              wgmma_ss<256>(a, da, desc_hi(4096, 1024, 1) + bb, gi);
              wgmma_ss<256>(a, da + 128, desc_hi(4096, 1024, 1) + (bb + 128), 1);
            } else {
              wgmma_ss<192>(*(float(*)[96])a, da, desc_hi(2048, 512, 2) + bb, gi);
              wgmma_ss<192>(*(float(*)[96])a, da + 128, desc_hi(2048, 512, 2) + (bb + 64), 1);
            }
            wg_commit();
            if (gi == 17 && w == 0) asm volatile("bar.arrive 5, 256;" ::: "memory");
            wg_wait<1>();
            if (gi > 0 && !(last() && gi > 13)) c.release2(BAR_EMPTYB + prev);
            if (last() && gi >= XREL && !((gi ^ XREL) & 1)) c.release2(BAR_EMPTYX + 16 * ((gi - XREL) & 2) + 2 * ((gi - XREL) & 12));
          };
          int gi = 0, end = w ? 18 - (wide() ? TLEAD2 : TLEAD) : 18;
#pragma unroll 1
          while (true) {
#pragma unroll 1
            for (; gi < end; gi++) group(gi);
            if (end == 18) break;
            asm volatile("bar.sync 5, 256;" ::: "memory");
            end = 18;
          }
          wg_wait<0>();
          if (!last()) c.releaseLastB();
          if (last() && t >= (19 - XREL) / 2 && t < 8) { mbar_arrive(sb + xe); mbar_arrive_remote(c.rem + xe); }
        };
        auto yes = [] { return true; };
        auto no = [] { return false; };
        tile(yes, no); PROF2(pb + 13); glu<16, 32>(a, h);
        tile(yes, no); PROF2(pb + 14); glu<16, 64>(a, h);
        tile(no, no); PROF2(pb + 15); glu<12, 96>(a, h);
        const uint32_t hole = sb + SM_B + 12288 + tid_ * 16;
#pragma unroll
        for (int i = 0; i < NSPILL; i++) sts128(hole + i * BSLOT, h[96 + 4 * i], h[97 + 4 * i], h[98 + 4 * i], h[99 + 4 * i]);
        if (w == 1) asm volatile("bar.arrive 8, 256;" ::: "memory");
        tile(no, yes); PROF2(pb + 16); glu<12, 120>(a, h);
#pragma unroll
        for (int i = 0; i < NSPILL; i++) { const uint4 u = lds128(hole + i * BSLOT); h[96 + 4 * i] = u.x; h[97 + 4 * i] = u.y; h[98 + 4 * i] = u.z; h[99 + 4 * i] = u.w; }
      }
      {
        THREAD_IDS();
        float d[32];
        uint4* gt = G->obox + t;
        asm volatile("" : "+l"(gt));
        uint4* const ib = gt + 2 * 4608 + layer * 8 * INBOX;
        auto pass = [&](uint32_t s0, bool last, auto&& hook) {
          const Desc db = desc_hi(0, 1024, 1) + (dsb + s0 * (XSLOT >> 4));
          mbar_wait_c(sb + BAR_FULLX + 8 * s0, (c.mX >> s0) & 1);
          if (RHOOK < 0) hook();
          asm volatile("bar.sync %0, 256;" ::"r"(8 + w) : "memory");
#pragma unroll
          for (int i = 0; i < 4; i++) {
            const int si = 4 * (i & 1) + (i >> 1);
            if (i > 0) mbar_wait_c(sb + BAR_FULLX + 8 * (s0 + si), (c.mX >> (s0 + si)) & 1);
            wg_fence();
#pragma unroll
            for (int k = 0; k < 9; k++) {
              const uint32_t* hk = h + 36 * i + 4 * k;
              wgmma_ra<64>(d, make_uint4(hk[0], hk[1], hk[2], hk[3]), db + ((xslot(si) >> 4) + k * 128), last || i + k > 0);
              if (9 * i + k == PPK && !(last && w == 1)) asm volatile("bar.arrive %0, 256;" ::"r"(9 - w) : "memory");
            }
            wg_commit();
            if (i > 0) { wg_wait<1>(); c.release2(BAR_EMPTYX + 8 * (s0 + 4 * ((i - 1) & 1) + ((i - 1) >> 1))); }
            if (i == RHOOK) hook();
          }
          c.mX ^= 0x33u << s0;
        };
        PROF2(pb + 17);
#pragma unroll 1
        for (int p = 0; p < 8; p++) {
          const uint32_t s0 = 2 * (p & 1);
          pass(s0, false, [] {});
          wg_wait<0>();
          c.release2(BAR_EMPTYX + 8 * (s0 + 5));
          if (p == 6 && layer == NLAYERS - 1) c.elect = false;
          uint32_t pk[16];
#pragma unroll
          for (int i = 0; i < 16; i++) pk[i] = pack_bf16(d[2 * i], d[2 * i + 1]);
          if (p >= BREL && p < BREL + 5 && layer < NLAYERS - 1) {
            const uint32_t o = c.sB + 8 * (p - BREL);
            c.release2(BAR_EMPTYB + (o < 40 ? o : o - 40));
          }
          uint4* const dst = ib + ((j + p) & 7) * INBOX;
          if (p == 0) {
            mbar_wait_c(sb + BAR_CLR + 8 * w, 0);
#pragma unroll
            for (int k = 0; k < 8; k++) red2((uint2*)(ib + k * INBOX + 512) - t, pk[2 * k], pk[2 * k + 1]);
          } else if (p < 7) {
#pragma unroll
            for (int k = 0; k < 4; k++) red4(dst + k * 128, pk[4 * k], pk[4 * k + 1], pk[4 * k + 2], pk[4 * k + 3]);
            if (p == 6) { __syncwarp(); if (lane == 0) mbar_arrive(sb + BAR_REDDONE + 8 * w); }
          } else {
#pragma unroll
            for (int k = 0; k < 4; k++) st_relaxed4(gt + ((j + 7) & 7) * 128 + k * 1024, pk[4 * k] & ~1u, pk[4 * k + 1], pk[4 * k + 2], pk[4 * k + 3]);
          }
        }
        PROF2(pb + 18);
        const uint4 *in = ib + j * INBOX, *pin = gt + j * 128;
        const uint2* in9 = (const uint2*)(in + 512) - t;
        asm volatile("" : "+l"(in), "+l"(pin), "+l"(in9));
        const float2 r2 = lds64(sb + SM_KEEP + (tid_ >> 2) * 8);
        uint2 X9;
        {
          uint4 X[4];
          const uint4* box = gt + 4608;
#pragma unroll
          for (int k = 0; k < 4; k++) X[k] = ld_relaxed4(box + 256 * j + ((k & 1) + 8 * (k & 2)) * 128);
          X9 = ld_relaxed2((const uint2*)(box + (32 + (j >> 1)) * 128) + (j & 1));
          const float i0 = rcp(r2.x), i1 = rcp(r2.y);
#pragma unroll
          for (int k = 0; k < 4; k++) {
            float* e = d + 8 * k;
            X[k].x ^= (lsb >> k) & 1;
            e[0] = bf_lo(X[k].x) * i0; e[1] = bf_hi(X[k].x) * i0; e[2] = bf_lo(X[k].y) * i1; e[3] = bf_hi(X[k].y) * i1;
            e[4] = bf_lo(X[k].z) * i0; e[5] = bf_hi(X[k].z) * i0; e[6] = bf_lo(X[k].w) * i1; e[7] = bf_hi(X[k].w) * i1;
          }
        }
        uint4 R[4], P[4];
        uint2 R9;
        PROF2(pb + 19);
        pass(0, true, [&] {
          mbar_wait_c(sb + BAR_RREADY + 8 * w, layer);
#pragma unroll
          for (int k = 0; k < 4; k++) R[k] = ld_relaxed4(in + k * 128);
          R9 = ld_relaxed2(in9);
#pragma unroll
          for (int k = 0; k < 4; k++) P[k] = ld_relaxed4(pin + k * 1024);
        });
        const uint32_t zero = late(sb + BAR_FULLX + 64, 0);
        while (__any_sync(0xffffffffu, (chk2(P[0].x, P[1].x, zero) | chk2(P[2].x, P[3].x, zero)) & 1)) {
#pragma unroll
          for (int k = 0; k < 4; k++) P[k] = ld_relaxed4(pin + k * 1024);
        }
#pragma unroll
        for (int k = 0; k < 4; k++) {
          const uint32_t u[4] = {hadd2(R[k].x, P[k].x), hadd2(R[k].y, P[k].y), hadd2(R[k].z, P[k].z), hadd2(R[k].w, P[k].w)};
#pragma unroll
          for (int i = 0; i < 4; i++) { v[8 * k + 2 * i] = bf_lo(u[i]); v[8 * k + 2 * i + 1] = bf_hi(u[i]); }
        }
        X9.x = chk(zero, X9.x, lsb >> 4);
        v[32] = fmaf(bf_lo(R9.x), r2.x, bf_lo(X9.x)); v[33] = fmaf(bf_hi(R9.x), r2.x, bf_hi(X9.x));
        v[34] = fmaf(bf_lo(R9.y), r2.y, bf_lo(X9.y)); v[35] = fmaf(bf_hi(R9.y), r2.y, bf_hi(X9.y));
        PROF2(pb + 20);
        wg_wait<0>();
        c.release2(BAR_EMPTYX + 40);
        PROF2(pb + 21);
#pragma unroll
        for (int i = 0; i < 32; i++) v[i] = (v[i] + d[i]) * (i & 2 ? r2.y : r2.x);
      }
      if (layer == NLAYERS - 1) break;
      {
        THREAD_IDS();
        PROF(31);
        rs = ln_gemm<true>(c, G, v, res, sum, st0, j, t, 1, xtag ^ 1, [&](int i) { PROF(32 + i); if (i) PROF(34); }, qkv_mma);
      }
    }
    {
      THREAD_IDS();
      const uint32_t stg = sb + SM_B + warp * 4096;
      const uint32_t sd = stg + (lane & 15) * 128;
#pragma unroll
      for (int i = 0; i < 4; i++)
        stsm4(sd + (((2 * i + (lane >> 4)) ^ (lane & 7)) << 4), pack_bf16(v[8 * i], v[8 * i + 1]), pack_bf16(v[8 * i + 2], v[8 * i + 3]),
              pack_bf16(v[8 * i + 4], v[8 * i + 5]), pack_bf16(v[8 * i + 6], v[8 * i + 7]));
      stsm2(stg + 2048 + (lane & 15) * 16, pack_bf16(v[32], v[33]), pack_bf16(v[34], v[35]));
      __syncwarp();
      char* o = out + (128 * rb + 32 * wp + w) * 1152;
#pragma unroll
      for (int i = 0; i < 4; i++) {
        const int r = 4 * i + (lane >> 3);
        *(uint4*)(o + r * 2304 + 128 * j + 16 * (lane & 7)) = lds128(stg + r * 128 + (((lane ^ r) & 7) << 4));
      }
      if (lane < 16) *(uint4*)(o + lane * 2304 + 1024 + 16 * j) = lds128(stg + 2048 + lane * 16);
      if (lane == 0) {
        if (wp == 0) st_relaxed(G->flag + 32 + 32 * j, xtag);
        mbar_arrive(sb + BAR_DONE + 8 * w);
      }
      PROF(61);
    }
  }
}

typedef CUresult (*EncFn)(CUtensorMap*, CUtensorMapDataType, cuuint32_t, void*, const cuuint64_t*, const cuuint64_t*, const cuuint32_t*,
                          const cuuint32_t*, CUtensorMapInterleave, CUtensorMapSwizzle, CUtensorMapL2promotion, CUtensorMapFloatOOBfill);

void make_map(EncFn enc, CUtensorMap* m, const void* p, int rank, uint64_t d0, uint64_t d1, uint64_t d2, uint64_t s1, uint64_t s2, uint32_t b0,
              uint32_t b1, uint32_t b2, CUtensorMapSwizzle sw) {
  cuuint64_t gd[3] = {d0, d1, d2};
  cuuint64_t gs[2] = {s1, s2};
  cuuint32_t bd[3] = {b0, b1, b2};
  cuuint32_t es[3] = {1, 1, 1};
  enc(m, CU_TENSOR_MAP_DATA_TYPE_BFLOAT16, rank, const_cast<void*>(p), gd, gs, bd, es, CU_TENSOR_MAP_INTERLEAVE_NONE, sw,
      CU_TENSOR_MAP_L2_PROMOTION_L2_128B, CU_TENSOR_MAP_FLOAT_OOB_FILL_NONE);
}

}

extern "C" void kernel_launch(void* const* d_in, const int* in_sizes, int n_in, void* d_out, int out_size) {
  const __nv_bfloat16* x = (const __nv_bfloat16*)d_in[0];
  const char *wqkv = (const char*)d_in[1], *wo = (const char*)d_in[2], *wg = (const char*)d_in[4], *wu = (const char*)d_in[5], *wd = (const char*)d_in[6];
  static EncFn enc = nullptr;
  static uint32_t first = 0;
  static Group* ws = nullptr;
  if (!enc) {
    cudaDriverEntryPointQueryResult qr;
    cudaGetDriverEntryPoint("cuTensorMapEncodeTiled", (void**)&enc, cudaEnableDefault, &qr);
    cudaGetSymbolAddress((void**)&ws, g_ws);
    cudaFuncSetAttribute(fused_kernel, cudaFuncAttributeMaxDynamicSharedMemorySize, SMEM_BYTES);
    cudaLaunchConfig_t cfg = {};
    cfg.gridDim = NCTA + 4; cfg.blockDim = 384; cfg.dynamicSmemBytes = SMEM_BYTES;
    int clusters = 0;
    if (XFIRST || cudaOccupancyMaxActiveClusters(&clusters, fused_kernel, &cfg) != cudaSuccess || 2 * clusters < NCTA + 4) first = 4;
    cudaGetLastError();
  }
  const CUtensorMapSwizzle S0 = CU_TENSOR_MAP_SWIZZLE_NONE, S64 = CU_TENSOR_MAP_SWIZZLE_64B, S128 = CU_TENSOR_MAP_SWIZZLE_128B;
  Maps m;
  make_map(enc, &m.x, x, 3, 576, 2, 1024, 1152, 2304, 64, 1, 64, S128);
  make_map(enc, &m.qm, wqkv, 3, 576, 576, 3, 3456, 1152, 64, 16, 3, S128);
  make_map(enc, &m.qc, wqkv, 3, 576, 576, 3, 3456, 1152, 8, 16, 3, S0);
  make_map(enc, &m.o, wo, 2, 576, 576, 1, 1152, 0, 64, 72, 1, S128);
  make_map(enc, &m.g, wg, 3, 64, 576, 72, 9216, 128, 64, 32, 2, S128);
  make_map(enc, &m.u, wu, 3, 64, 576, 72, 9216, 128, 64, 32, 2, S128);
  make_map(enc, &m.g3, wg, 3, 32, 576, 144, 9216, 64, 32, 32, 3, S64);
  make_map(enc, &m.u3, wu, 3, 32, 576, 144, 9216, 64, 32, 32, 3, S64);
  make_map(enc, &m.d, wd, 2, 576, 4608, 1, 1152, 0, 64, 72, 1, S128);
  fused_kernel<<<NCTA + 4, 384, SMEM_BYTES>>>(x, ws, wqkv, wo, (char*)d_out, first, m, wg, wu, wd);
}
```

```cpp
#include <cuda_runtime.h>
#include <cuda_bf16.h>
#include <cuda.h>
#include <stdint.h>
#include <stddef.h>

namespace {

constexpr int D_ = 576;
constexpr int NCTA = 128;
#define NLAYERS 2
#define W_POLICY policy_evict_first
#define A_POLICY policy_evict_normal
#define OPEN 1
#define PFMODE 5
#define WB1 11
#define WB2 21
#define WB3 32
#define WPROBE 1
#define WOBAR 1
#define QD 0
#define PFQ 1
#define PFSLEEP 700
#define GPCMAP 1
#define PFF 1
#define CLRSLEEP 300
#define OPENL 24
#define FG 1
#define HMUL 1
#define FCH 1
#define PPK 35
#define RHOOK -1
#define XH 3
#define XP 0
#define GSLEEP 32
#define XCH 1
#define MAPPF 1
#define XREL 8
#define WOG 13
#define BREL 1
#define FENCE1 0
#define OWNBAR 0
#define EARLY 1
#define ESPEC 0
#define WOW 1
#define STATP -1
#define QPACE 23
#define RDELAY 1000
#define XFIRST 0
#define TLEAD 2
#define TLEAD2 2
#define TLEAD0 2
#define OFIRST 3
#define FN 3
#define LATE0 0
#define SUMB 2
#define XPM 3
#define HALOH 0
#define KEEPW 25
#define NSPILL 4
#define REGS_C 232
#define REGS_P 40
#define STR2(x) #x
#define STR(x) STR2(x)
constexpr uint32_t SM_X = 0;
constexpr uint32_t XSLOT = 18432;
__host__ __device__ constexpr uint32_t xslot(uint32_t s) { return SM_X + (s ^ 4) * XSLOT; }
constexpr uint32_t SM_WOC = xslot(3) + 8192;
constexpr uint32_t SM_B = 147456;
constexpr uint32_t BSLOT = 16384;
constexpr uint32_t SM_KEEP = 229376;
constexpr uint32_t SM_WSUM = SM_KEEP + 512;
constexpr uint32_t SM_BAR = SM_KEEP + 2048;
constexpr uint32_t BAR_FULLB = SM_BAR;
constexpr uint32_t BAR_RREADY = SM_BAR + 40;
constexpr uint32_t BAR_CLR = SM_BAR + 56;
constexpr uint32_t BAR_FULLX = SM_BAR + 72;
constexpr uint32_t BAR_EMPTYB = SM_BAR + 144;
constexpr uint32_t BAR_EMPTYX = SM_BAR + 184;
constexpr uint32_t BAR_REDDONE = SM_BAR + 248;
constexpr uint32_t BAR_DONE = SM_BAR + 264;
constexpr uint32_t SM_PROG = SM_BAR + 288;
constexpr uint32_t SMEM_BYTES = SM_BAR + 1024;

struct Maps { CUtensorMap x, qm, qc, o, g, u, g3, u3, d; };

constexpr int INBOX = 576;
struct Group {
  uint2 sum[4 * 8 * 8];
  uint2 sq[4 * 8 * 8];
  uint32_t pad[512];
  uint32_t flag[512];
  uint4 halo[8 * 160];
  uint4 obox[36 * 128];
  uint4 xbox[36 * 128];
  uint4 inbox[2][8 * INBOX];
};
struct Scratch { Group g[32]; uint4 wq[8][36][432]; uint4 woc[8][720]; uint32_t done[64]; };
__device__ __align__(1024) Scratch g_ws;
#define PROF(i)
#define PROFX(i)

#define PROF2(i) PROF(i)

struct Desc { uint32_t lo, hi; };
__device__ __forceinline__ constexpr Desc desc_hi(uint32_t lbo, uint32_t sbo, uint32_t sw) { return Desc{(lbo >> 4) << 16, (sbo >> 4) | sw << 30}; }
__device__ __forceinline__ constexpr Desc operator+(Desc d, uint32_t a) { return Desc{d.lo + a, d.hi}; }

template<int N> __device__ __forceinline__ void wgmma_ss(float (&d)[N / 2], Desc da, Desc db, int sc);
template<> __device__ __forceinline__ void wgmma_ss<192>(float (&d)[96], Desc da, Desc db, int sc) {
  asm volatile("{\n.reg .pred p;\n.reg .b64 a, b;\nsetp.ne.b32 p, %100, 0;\nmov.b64 a, {%96, %97};\nmov.b64 b, {%98, %99};\n"
    "wgmma.mma_async.sync.aligned.m64n192k16.f32.bf16.bf16 {%0,%1,%2,%3,%4,%5,%6,%7,%8,%9,%10,%11,%12,%13,%14,%15,%16,%17,%18,%19,%20,%21,%22,%23,%24,%25,%26,%27,%28,%29,%30,%31,%32,%33,%34,%35,%36,%37,%38,%39,%40,%41,%42,%43,%44,%45,%46,%47,%48,%49,%50,%51,%52,%53,%54,%55,%56,%57,%58,%59,%60,%61,%62,%63,%64,%65,%66,%67,%68,%69,%70,%71,%72,%73,%74,%75,%76,%77,%78,%79,%80,%81,%82,%83,%84,%85,%86,%87,%88,%89,%90,%91,%92,%93,%94,%95}, a, b, p, 1, 1, 0, 1;\n}\n"
    : "+f"(d[0]),"+f"(d[1]),"+f"(d[2]),"+f"(d[3]),"+f"(d[4]),"+f"(d[5]),"+f"(d[6]),"+f"(d[7]),"+f"(d[8]),"+f"(d[9]),"+f"(d[10]),"+f"(d[11]),"+f"(d[12]),"+f"(d[13]),"+f"(d[14]),"+f"(d[15]),"+f"(d[16]),"+f"(d[17]),"+f"(d[18]),"+f"(d[19]),"+f"(d[20]),"+f"(d[21]),"+f"(d[22]),"+f"(d[23]),"+f"(d[24]),"+f"(d[25]),"+f"(d[26]),"+f"(d[27]),"+f"(d[28]),"+f"(d[29]),"+f"(d[30]),"+f"(d[31]),"+f"(d[32]),"+f"(d[33]),"+f"(d[34]),"+f"(d[35]),"+f"(d[36]),"+f"(d[37]),"+f"(d[38]),"+f"(d[39]),"+f"(d[40]),"+f"(d[41]),"+f"(d[42]),"+f"(d[43]),"+f"(d[44]),"+f"(d[45]),"+f"(d[46]),"+f"(d[47]),"+f"(d[48]),"+f"(d[49]),"+f"(d[50]),"+f"(d[51]),"+f"(d[52]),"+f"(d[53]),"+f"(d[54]),"+f"(d[55]),"+f"(d[56]),"+f"(d[57]),"+f"(d[58]),"+f"(d[59]),"+f"(d[60]),"+f"(d[61]),"+f"(d[62]),"+f"(d[63]),"+f"(d[64]),"+f"(d[65]),"+f"(d[66]),"+f"(d[67]),"+f"(d[68]),"+f"(d[69]),"+f"(d[70]),"+f"(d[71]),"+f"(d[72]),"+f"(d[73]),"+f"(d[74]),"+f"(d[75]),"+f"(d[76]),"+f"(d[77]),"+f"(d[78]),"+f"(d[79]),"+f"(d[80]),"+f"(d[81]),"+f"(d[82]),"+f"(d[83]),"+f"(d[84]),"+f"(d[85]),"+f"(d[86]),"+f"(d[87]),"+f"(d[88]),"+f"(d[89]),"+f"(d[90]),"+f"(d[91]),"+f"(d[92]),"+f"(d[93]),"+f"(d[94]),"+f"(d[95]) : "r"(da.lo), "r"(da.hi), "r"(db.lo), "r"(db.hi), "r"(sc));
}
template<> __device__ __forceinline__ void wgmma_ss<256>(float (&d)[128], Desc da, Desc db, int sc) {
  asm volatile("{\n.reg .pred p;\n.reg .b64 a, b;\nsetp.ne.b32 p, %132, 0;\nmov.b64 a, {%128, %129};\nmov.b64 b, {%130, %131};\n"
    "wgmma.mma_async.sync.aligned.m64n256k16.f32.bf16.bf16 {%0,%1,%2,%3,%4,%5,%6,%7,%8,%9,%10,%11,%12,%13,%14,%15,%16,%17,%18,%19,%20,%21,%22,%23,%24,%25,%26,%27,%28,%29,%30,%31,%32,%33,%34,%35,%36,%37,%38,%39,%40,%41,%42,%43,%44,%45,%46,%47,%48,%49,%50,%51,%52,%53,%54,%55,%56,%57,%58,%59,%60,%61,%62,%63,%64,%65,%66,%67,%68,%69,%70,%71,%72,%73,%74,%75,%76,%77,%78,%79,%80,%81,%82,%83,%84,%85,%86,%87,%88,%89,%90,%91,%92,%93,%94,%95,%96,%97,%98,%99,%100,%101,%102,%103,%104,%105,%106,%107,%108,%109,%110,%111,%112,%113,%114,%115,%116,%117,%118,%119,%120,%121,%122,%123,%124,%125,%126,%127}, a, b, p, 1, 1, 0, 1;\n}\n"
    : "+f"(d[0]),"+f"(d[1]),"+f"(d[2]),"+f"(d[3]),"+f"(d[4]),"+f"(d[5]),"+f"(d[6]),"+f"(d[7]),"+f"(d[8]),"+f"(d[9]),"+f"(d[10]),"+f"(d[11]),"+f"(d[12]),"+f"(d[13]),"+f"(d[14]),"+f"(d[15]),"+f"(d[16]),"+f"(d[17]),"+f"(d[18]),"+f"(d[19]),"+f"(d[20]),"+f"(d[21]),"+f"(d[22]),"+f"(d[23]),"+f"(d[24]),"+f"(d[25]),"+f"(d[26]),"+f"(d[27]),"+f"(d[28]),"+f"(d[29]),"+f"(d[30]),"+f"(d[31]),"+f"(d[32]),"+f"(d[33]),"+f"(d[34]),"+f"(d[35]),"+f"(d[36]),"+f"(d[37]),"+f"(d[38]),"+f"(d[39]),"+f"(d[40]),"+f"(d[41]),"+f"(d[42]),"+f"(d[43]),"+f"(d[44]),"+f"(d[45]),"+f"(d[46]),"+f"(d[47]),"+f"(d[48]),"+f"(d[49]),"+f"(d[50]),"+f"(d[51]),"+f"(d[52]),"+f"(d[53]),"+f"(d[54]),"+f"(d[55]),"+f"(d[56]),"+f"(d[57]),"+f"(d[58]),"+f"(d[59]),"+f"(d[60]),"+f"(d[61]),"+f"(d[62]),"+f"(d[63]),"+f"(d[64]),"+f"(d[65]),"+f"(d[66]),"+f"(d[67]),"+f"(d[68]),"+f"(d[69]),"+f"(d[70]),"+f"(d[71]),"+f"(d[72]),"+f"(d[73]),"+f"(d[74]),"+f"(d[75]),"+f"(d[76]),"+f"(d[77]),"+f"(d[78]),"+f"(d[79]),"+f"(d[80]),"+f"(d[81]),"+f"(d[82]),"+f"(d[83]),"+f"(d[84]),"+f"(d[85]),"+f"(d[86]),"+f"(d[87]),"+f"(d[88]),"+f"(d[89]),"+f"(d[90]),"+f"(d[91]),"+f"(d[92]),"+f"(d[93]),"+f"(d[94]),"+f"(d[95]),"+f"(d[96]),"+f"(d[97]),"+f"(d[98]),"+f"(d[99]),"+f"(d[100]),"+f"(d[101]),"+f"(d[102]),"+f"(d[103]),"+f"(d[104]),"+f"(d[105]),"+f"(d[106]),"+f"(d[107]),"+f"(d[108]),"+f"(d[109]),"+f"(d[110]),"+f"(d[111]),"+f"(d[112]),"+f"(d[113]),"+f"(d[114]),"+f"(d[115]),"+f"(d[116]),"+f"(d[117]),"+f"(d[118]),"+f"(d[119]),"+f"(d[120]),"+f"(d[121]),"+f"(d[122]),"+f"(d[123]),"+f"(d[124]),"+f"(d[125]),"+f"(d[126]),"+f"(d[127]) : "r"(da.lo), "r"(da.hi), "r"(db.lo), "r"(db.hi), "r"(sc));
}
template<int N, int ACC> __device__ __forceinline__ void wgmma_rs(float (&d)[N / 2], const uint4& a, Desc db);
template<> __device__ __forceinline__ void wgmma_rs<8, 1>(float (&d)[4], const uint4& a, Desc db) {
  asm volatile("{\n.reg .pred p;\n.reg .b64 b;\nsetp.ne.b32 p, 1, 0;\nmov.b64 b, {%8, %9};\n"
    "wgmma.mma_async.sync.aligned.m64n8k16.f32.bf16.bf16 {%0,%1,%2,%3}, {%4,%5,%6,%7}, b, p, 1, 1, 1;\n}\n"
    : "+f"(d[0]),"+f"(d[1]),"+f"(d[2]),"+f"(d[3]) : "r"(a.x), "r"(a.y), "r"(a.z), "r"(a.w), "r"(db.lo), "r"(db.hi));
}
template<> __device__ __forceinline__ void wgmma_rs<8, 0>(float (&d)[4], const uint4& a, Desc db) {
  asm volatile("{\n.reg .pred p;\n.reg .b64 b;\nsetp.ne.b32 p, 0, 0;\nmov.b64 b, {%8, %9};\n"
    "wgmma.mma_async.sync.aligned.m64n8k16.f32.bf16.bf16 {%0,%1,%2,%3}, {%4,%5,%6,%7}, b, p, 1, 1, 1;\n}\n"
    : "=f"(d[0]),"=f"(d[1]),"=f"(d[2]),"=f"(d[3]) : "r"(a.x), "r"(a.y), "r"(a.z), "r"(a.w), "r"(db.lo), "r"(db.hi));
}
template<> __device__ __forceinline__ void wgmma_rs<24, 1>(float (&d)[12], const uint4& a, Desc db) {
  asm volatile("{\n.reg .pred p;\n.reg .b64 b;\nsetp.ne.b32 p, 1, 0;\nmov.b64 b, {%16, %17};\n"
    "wgmma.mma_async.sync.aligned.m64n24k16.f32.bf16.bf16 {%0,%1,%2,%3,%4,%5,%6,%7,%8,%9,%10,%11}, {%12,%13,%14,%15}, b, p, 1, 1, 1;\n}\n"
    : "+f"(d[0]),"+f"(d[1]),"+f"(d[2]),"+f"(d[3]),"+f"(d[4]),"+f"(d[5]),"+f"(d[6]),"+f"(d[7]),"+f"(d[8]),"+f"(d[9]),"+f"(d[10]),"+f"(d[11]) : "r"(a.x), "r"(a.y), "r"(a.z), "r"(a.w), "r"(db.lo), "r"(db.hi));
}
template<> __device__ __forceinline__ void wgmma_rs<24, 0>(float (&d)[12], const uint4& a, Desc db) {
  asm volatile("{\n.reg .pred p;\n.reg .b64 b;\nsetp.ne.b32 p, 0, 0;\nmov.b64 b, {%16, %17};\n"
    "wgmma.mma_async.sync.aligned.m64n24k16.f32.bf16.bf16 {%0,%1,%2,%3,%4,%5,%6,%7,%8,%9,%10,%11}, {%12,%13,%14,%15}, b, p, 1, 1, 1;\n}\n"
    : "=f"(d[0]),"=f"(d[1]),"=f"(d[2]),"=f"(d[3]),"=f"(d[4]),"=f"(d[5]),"=f"(d[6]),"=f"(d[7]),"=f"(d[8]),"=f"(d[9]),"=f"(d[10]),"=f"(d[11]) : "r"(a.x), "r"(a.y), "r"(a.z), "r"(a.w), "r"(db.lo), "r"(db.hi));
}
template<> __device__ __forceinline__ void wgmma_rs<64, 1>(float (&d)[32], const uint4& a, Desc db) {
  asm volatile("{\n.reg .pred p;\n.reg .b64 b;\nsetp.ne.b32 p, 1, 0;\nmov.b64 b, {%36, %37};\n"
    "wgmma.mma_async.sync.aligned.m64n64k16.f32.bf16.bf16 {%0,%1,%2,%3,%4,%5,%6,%7,%8,%9,%10,%11,%12,%13,%14,%15,%16,%17,%18,%19,%20,%21,%22,%23,%24,%25,%26,%27,%28,%29,%30,%31}, {%32,%33,%34,%35}, b, p, 1, 1, 1;\n}\n"
    : "+f"(d[0]),"+f"(d[1]),"+f"(d[2]),"+f"(d[3]),"+f"(d[4]),"+f"(d[5]),"+f"(d[6]),"+f"(d[7]),"+f"(d[8]),"+f"(d[9]),"+f"(d[10]),"+f"(d[11]),"+f"(d[12]),"+f"(d[13]),"+f"(d[14]),"+f"(d[15]),"+f"(d[16]),"+f"(d[17]),"+f"(d[18]),"+f"(d[19]),"+f"(d[20]),"+f"(d[21]),"+f"(d[22]),"+f"(d[23]),"+f"(d[24]),"+f"(d[25]),"+f"(d[26]),"+f"(d[27]),"+f"(d[28]),"+f"(d[29]),"+f"(d[30]),"+f"(d[31]) : "r"(a.x), "r"(a.y), "r"(a.z), "r"(a.w), "r"(db.lo), "r"(db.hi));
}
template<> __device__ __forceinline__ void wgmma_rs<64, 0>(float (&d)[32], const uint4& a, Desc db) {
  asm volatile("{\n.reg .pred p;\n.reg .b64 b;\nsetp.ne.b32 p, 0, 0;\nmov.b64 b, {%36, %37};\n"
    "wgmma.mma_async.sync.aligned.m64n64k16.f32.bf16.bf16 {%0,%1,%2,%3,%4,%5,%6,%7,%8,%9,%10,%11,%12,%13,%14,%15,%16,%17,%18,%19,%20,%21,%22,%23,%24,%25,%26,%27,%28,%29,%30,%31}, {%32,%33,%34,%35}, b, p, 1, 1, 1;\n}\n"
    : "=f"(d[0]),"=f"(d[1]),"=f"(d[2]),"=f"(d[3]),"=f"(d[4]),"=f"(d[5]),"=f"(d[6]),"=f"(d[7]),"=f"(d[8]),"=f"(d[9]),"=f"(d[10]),"=f"(d[11]),"=f"(d[12]),"=f"(d[13]),"=f"(d[14]),"=f"(d[15]),"=f"(d[16]),"=f"(d[17]),"=f"(d[18]),"=f"(d[19]),"=f"(d[20]),"=f"(d[21]),"=f"(d[22]),"=f"(d[23]),"=f"(d[24]),"=f"(d[25]),"=f"(d[26]),"=f"(d[27]),"=f"(d[28]),"=f"(d[29]),"=f"(d[30]),"=f"(d[31]) : "r"(a.x), "r"(a.y), "r"(a.z), "r"(a.w), "r"(db.lo), "r"(db.hi));
}
template<> __device__ __forceinline__ void wgmma_rs<72, 1>(float (&d)[36], const uint4& a, Desc db) {
  asm volatile("{\n.reg .pred p;\n.reg .b64 b;\nsetp.ne.b32 p, 1, 0;\nmov.b64 b, {%40, %41};\n"
    "wgmma.mma_async.sync.aligned.m64n72k16.f32.bf16.bf16 {%0,%1,%2,%3,%4,%5,%6,%7,%8,%9,%10,%11,%12,%13,%14,%15,%16,%17,%18,%19,%20,%21,%22,%23,%24,%25,%26,%27,%28,%29,%30,%31,%32,%33,%34,%35}, {%36,%37,%38,%39}, b, p, 1, 1, 1;\n}\n"
    : "+f"(d[0]),"+f"(d[1]),"+f"(d[2]),"+f"(d[3]),"+f"(d[4]),"+f"(d[5]),"+f"(d[6]),"+f"(d[7]),"+f"(d[8]),"+f"(d[9]),"+f"(d[10]),"+f"(d[11]),"+f"(d[12]),"+f"(d[13]),"+f"(d[14]),"+f"(d[15]),"+f"(d[16]),"+f"(d[17]),"+f"(d[18]),"+f"(d[19]),"+f"(d[20]),"+f"(d[21]),"+f"(d[22]),"+f"(d[23]),"+f"(d[24]),"+f"(d[25]),"+f"(d[26]),"+f"(d[27]),"+f"(d[28]),"+f"(d[29]),"+f"(d[30]),"+f"(d[31]),"+f"(d[32]),"+f"(d[33]),"+f"(d[34]),"+f"(d[35]) : "r"(a.x), "r"(a.y), "r"(a.z), "r"(a.w), "r"(db.lo), "r"(db.hi));
}
template<> __device__ __forceinline__ void wgmma_rs<72, 0>(float (&d)[36], const uint4& a, Desc db) {
  asm volatile("{\n.reg .pred p;\n.reg .b64 b;\nsetp.ne.b32 p, 0, 0;\nmov.b64 b, {%40, %41};\n"
    "wgmma.mma_async.sync.aligned.m64n72k16.f32.bf16.bf16 {%0,%1,%2,%3,%4,%5,%6,%7,%8,%9,%10,%11,%12,%13,%14,%15,%16,%17,%18,%19,%20,%21,%22,%23,%24,%25,%26,%27,%28,%29,%30,%31,%32,%33,%34,%35}, {%36,%37,%38,%39}, b, p, 1, 1, 1;\n}\n"
    : "=f"(d[0]),"=f"(d[1]),"=f"(d[2]),"=f"(d[3]),"=f"(d[4]),"=f"(d[5]),"=f"(d[6]),"=f"(d[7]),"=f"(d[8]),"=f"(d[9]),"=f"(d[10]),"=f"(d[11]),"=f"(d[12]),"=f"(d[13]),"=f"(d[14]),"=f"(d[15]),"=f"(d[16]),"=f"(d[17]),"=f"(d[18]),"=f"(d[19]),"=f"(d[20]),"=f"(d[21]),"=f"(d[22]),"=f"(d[23]),"=f"(d[24]),"=f"(d[25]),"=f"(d[26]),"=f"(d[27]),"=f"(d[28]),"=f"(d[29]),"=f"(d[30]),"=f"(d[31]),"=f"(d[32]),"=f"(d[33]),"=f"(d[34]),"=f"(d[35]) : "r"(a.x), "r"(a.y), "r"(a.z), "r"(a.w), "r"(db.lo), "r"(db.hi));
}
template<> __device__ __forceinline__ void wgmma_rs<192, 1>(float (&d)[96], const uint4& a, Desc db) {
  asm volatile("{\n.reg .pred p;\n.reg .b64 b;\nsetp.ne.b32 p, 1, 0;\nmov.b64 b, {%100, %101};\n"
    "wgmma.mma_async.sync.aligned.m64n192k16.f32.bf16.bf16 {%0,%1,%2,%3,%4,%5,%6,%7,%8,%9,%10,%11,%12,%13,%14,%15,%16,%17,%18,%19,%20,%21,%22,%23,%24,%25,%26,%27,%28,%29,%30,%31,%32,%33,%34,%35,%36,%37,%38,%39,%40,%41,%42,%43,%44,%45,%46,%47,%48,%49,%50,%51,%52,%53,%54,%55,%56,%57,%58,%59,%60,%61,%62,%63,%64,%65,%66,%67,%68,%69,%70,%71,%72,%73,%74,%75,%76,%77,%78,%79,%80,%81,%82,%83,%84,%85,%86,%87,%88,%89,%90,%91,%92,%93,%94,%95}, {%96,%97,%98,%99}, b, p, 1, 1, 1;\n}\n"
    : "+f"(d[0]),"+f"(d[1]),"+f"(d[2]),"+f"(d[3]),"+f"(d[4]),"+f"(d[5]),"+f"(d[6]),"+f"(d[7]),"+f"(d[8]),"+f"(d[9]),"+f"(d[10]),"+f"(d[11]),"+f"(d[12]),"+f"(d[13]),"+f"(d[14]),"+f"(d[15]),"+f"(d[16]),"+f"(d[17]),"+f"(d[18]),"+f"(d[19]),"+f"(d[20]),"+f"(d[21]),"+f"(d[22]),"+f"(d[23]),"+f"(d[24]),"+f"(d[25]),"+f"(d[26]),"+f"(d[27]),"+f"(d[28]),"+f"(d[29]),"+f"(d[30]),"+f"(d[31]),"+f"(d[32]),"+f"(d[33]),"+f"(d[34]),"+f"(d[35]),"+f"(d[36]),"+f"(d[37]),"+f"(d[38]),"+f"(d[39]),"+f"(d[40]),"+f"(d[41]),"+f"(d[42]),"+f"(d[43]),"+f"(d[44]),"+f"(d[45]),"+f"(d[46]),"+f"(d[47]),"+f"(d[48]),"+f"(d[49]),"+f"(d[50]),"+f"(d[51]),"+f"(d[52]),"+f"(d[53]),"+f"(d[54]),"+f"(d[55]),"+f"(d[56]),"+f"(d[57]),"+f"(d[58]),"+f"(d[59]),"+f"(d[60]),"+f"(d[61]),"+f"(d[62]),"+f"(d[63]),"+f"(d[64]),"+f"(d[65]),"+f"(d[66]),"+f"(d[67]),"+f"(d[68]),"+f"(d[69]),"+f"(d[70]),"+f"(d[71]),"+f"(d[72]),"+f"(d[73]),"+f"(d[74]),"+f"(d[75]),"+f"(d[76]),"+f"(d[77]),"+f"(d[78]),"+f"(d[79]),"+f"(d[80]),"+f"(d[81]),"+f"(d[82]),"+f"(d[83]),"+f"(d[84]),"+f"(d[85]),"+f"(d[86]),"+f"(d[87]),"+f"(d[88]),"+f"(d[89]),"+f"(d[90]),"+f"(d[91]),"+f"(d[92]),"+f"(d[93]),"+f"(d[94]),"+f"(d[95]) : "r"(a.x), "r"(a.y), "r"(a.z), "r"(a.w), "r"(db.lo), "r"(db.hi));
}
template<> __device__ __forceinline__ void wgmma_rs<192, 0>(float (&d)[96], const uint4& a, Desc db) {
  asm volatile("{\n.reg .pred p;\n.reg .b64 b;\nsetp.ne.b32 p, 0, 0;\nmov.b64 b, {%100, %101};\n"
    "wgmma.mma_async.sync.aligned.m64n192k16.f32.bf16.bf16 {%0,%1,%2,%3,%4,%5,%6,%7,%8,%9,%10,%11,%12,%13,%14,%15,%16,%17,%18,%19,%20,%21,%22,%23,%24,%25,%26,%27,%28,%29,%30,%31,%32,%33,%34,%35,%36,%37,%38,%39,%40,%41,%42,%43,%44,%45,%46,%47,%48,%49,%50,%51,%52,%53,%54,%55,%56,%57,%58,%59,%60,%61,%62,%63,%64,%65,%66,%67,%68,%69,%70,%71,%72,%73,%74,%75,%76,%77,%78,%79,%80,%81,%82,%83,%84,%85,%86,%87,%88,%89,%90,%91,%92,%93,%94,%95}, {%96,%97,%98,%99}, b, p, 1, 1, 1;\n}\n"
    : "=f"(d[0]),"=f"(d[1]),"=f"(d[2]),"=f"(d[3]),"=f"(d[4]),"=f"(d[5]),"=f"(d[6]),"=f"(d[7]),"=f"(d[8]),"=f"(d[9]),"=f"(d[10]),"=f"(d[11]),"=f"(d[12]),"=f"(d[13]),"=f"(d[14]),"=f"(d[15]),"=f"(d[16]),"=f"(d[17]),"=f"(d[18]),"=f"(d[19]),"=f"(d[20]),"=f"(d[21]),"=f"(d[22]),"=f"(d[23]),"=f"(d[24]),"=f"(d[25]),"=f"(d[26]),"=f"(d[27]),"=f"(d[28]),"=f"(d[29]),"=f"(d[30]),"=f"(d[31]),"=f"(d[32]),"=f"(d[33]),"=f"(d[34]),"=f"(d[35]),"=f"(d[36]),"=f"(d[37]),"=f"(d[38]),"=f"(d[39]),"=f"(d[40]),"=f"(d[41]),"=f"(d[42]),"=f"(d[43]),"=f"(d[44]),"=f"(d[45]),"=f"(d[46]),"=f"(d[47]),"=f"(d[48]),"=f"(d[49]),"=f"(d[50]),"=f"(d[51]),"=f"(d[52]),"=f"(d[53]),"=f"(d[54]),"=f"(d[55]),"=f"(d[56]),"=f"(d[57]),"=f"(d[58]),"=f"(d[59]),"=f"(d[60]),"=f"(d[61]),"=f"(d[62]),"=f"(d[63]),"=f"(d[64]),"=f"(d[65]),"=f"(d[66]),"=f"(d[67]),"=f"(d[68]),"=f"(d[69]),"=f"(d[70]),"=f"(d[71]),"=f"(d[72]),"=f"(d[73]),"=f"(d[74]),"=f"(d[75]),"=f"(d[76]),"=f"(d[77]),"=f"(d[78]),"=f"(d[79]),"=f"(d[80]),"=f"(d[81]),"=f"(d[82]),"=f"(d[83]),"=f"(d[84]),"=f"(d[85]),"=f"(d[86]),"=f"(d[87]),"=f"(d[88]),"=f"(d[89]),"=f"(d[90]),"=f"(d[91]),"=f"(d[92]),"=f"(d[93]),"=f"(d[94]),"=f"(d[95]) : "r"(a.x), "r"(a.y), "r"(a.z), "r"(a.w), "r"(db.lo), "r"(db.hi));
}
template<> __device__ __forceinline__ void wgmma_rs<256, 1>(float (&d)[128], const uint4& a, Desc db) {
  asm volatile("{\n.reg .pred p;\n.reg .b64 b;\nsetp.ne.b32 p, 1, 0;\nmov.b64 b, {%132, %133};\n"
    "wgmma.mma_async.sync.aligned.m64n256k16.f32.bf16.bf16 {%0,%1,%2,%3,%4,%5,%6,%7,%8,%9,%10,%11,%12,%13,%14,%15,%16,%17,%18,%19,%20,%21,%22,%23,%24,%25,%26,%27,%28,%29,%30,%31,%32,%33,%34,%35,%36,%37,%38,%39,%40,%41,%42,%43,%44,%45,%46,%47,%48,%49,%50,%51,%52,%53,%54,%55,%56,%57,%58,%59,%60,%61,%62,%63,%64,%65,%66,%67,%68,%69,%70,%71,%72,%73,%74,%75,%76,%77,%78,%79,%80,%81,%82,%83,%84,%85,%86,%87,%88,%89,%90,%91,%92,%93,%94,%95,%96,%97,%98,%99,%100,%101,%102,%103,%104,%105,%106,%107,%108,%109,%110,%111,%112,%113,%114,%115,%116,%117,%118,%119,%120,%121,%122,%123,%124,%125,%126,%127}, {%128,%129,%130,%131}, b, p, 1, 1, 1;\n}\n"
    : "+f"(d[0]),"+f"(d[1]),"+f"(d[2]),"+f"(d[3]),"+f"(d[4]),"+f"(d[5]),"+f"(d[6]),"+f"(d[7]),"+f"(d[8]),"+f"(d[9]),"+f"(d[10]),"+f"(d[11]),"+f"(d[12]),"+f"(d[13]),"+f"(d[14]),"+f"(d[15]),"+f"(d[16]),"+f"(d[17]),"+f"(d[18]),"+f"(d[19]),"+f"(d[20]),"+f"(d[21]),"+f"(d[22]),"+f"(d[23]),"+f"(d[24]),"+f"(d[25]),"+f"(d[26]),"+f"(d[27]),"+f"(d[28]),"+f"(d[29]),"+f"(d[30]),"+f"(d[31]),"+f"(d[32]),"+f"(d[33]),"+f"(d[34]),"+f"(d[35]),"+f"(d[36]),"+f"(d[37]),"+f"(d[38]),"+f"(d[39]),"+f"(d[40]),"+f"(d[41]),"+f"(d[42]),"+f"(d[43]),"+f"(d[44]),"+f"(d[45]),"+f"(d[46]),"+f"(d[47]),"+f"(d[48]),"+f"(d[49]),"+f"(d[50]),"+f"(d[51]),"+f"(d[52]),"+f"(d[53]),"+f"(d[54]),"+f"(d[55]),"+f"(d[56]),"+f"(d[57]),"+f"(d[58]),"+f"(d[59]),"+f"(d[60]),"+f"(d[61]),"+f"(d[62]),"+f"(d[63]),"+f"(d[64]),"+f"(d[65]),"+f"(d[66]),"+f"(d[67]),"+f"(d[68]),"+f"(d[69]),"+f"(d[70]),"+f"(d[71]),"+f"(d[72]),"+f"(d[73]),"+f"(d[74]),"+f"(d[75]),"+f"(d[76]),"+f"(d[77]),"+f"(d[78]),"+f"(d[79]),"+f"(d[80]),"+f"(d[81]),"+f"(d[82]),"+f"(d[83]),"+f"(d[84]),"+f"(d[85]),"+f"(d[86]),"+f"(d[87]),"+f"(d[88]),"+f"(d[89]),"+f"(d[90]),"+f"(d[91]),"+f"(d[92]),"+f"(d[93]),"+f"(d[94]),"+f"(d[95]),"+f"(d[96]),"+f"(d[97]),"+f"(d[98]),"+f"(d[99]),"+f"(d[100]),"+f"(d[101]),"+f"(d[102]),"+f"(d[103]),"+f"(d[104]),"+f"(d[105]),"+f"(d[106]),"+f"(d[107]),"+f"(d[108]),"+f"(d[109]),"+f"(d[110]),"+f"(d[111]),"+f"(d[112]),"+f"(d[113]),"+f"(d[114]),"+f"(d[115]),"+f"(d[116]),"+f"(d[117]),"+f"(d[118]),"+f"(d[119]),"+f"(d[120]),"+f"(d[121]),"+f"(d[122]),"+f"(d[123]),"+f"(d[124]),"+f"(d[125]),"+f"(d[126]),"+f"(d[127]) : "r"(a.x), "r"(a.y), "r"(a.z), "r"(a.w), "r"(db.lo), "r"(db.hi));
}
template<> __device__ __forceinline__ void wgmma_rs<256, 0>(float (&d)[128], const uint4& a, Desc db) {
  asm volatile("{\n.reg .pred p;\n.reg .b64 b;\nsetp.ne.b32 p, 0, 0;\nmov.b64 b, {%132, %133};\n"
    "wgmma.mma_async.sync.aligned.m64n256k16.f32.bf16.bf16 {%0,%1,%2,%3,%4,%5,%6,%7,%8,%9,%10,%11,%12,%13,%14,%15,%16,%17,%18,%19,%20,%21,%22,%23,%24,%25,%26,%27,%28,%29,%30,%31,%32,%33,%34,%35,%36,%37,%38,%39,%40,%41,%42,%43,%44,%45,%46,%47,%48,%49,%50,%51,%52,%53,%54,%55,%56,%57,%58,%59,%60,%61,%62,%63,%64,%65,%66,%67,%68,%69,%70,%71,%72,%73,%74,%75,%76,%77,%78,%79,%80,%81,%82,%83,%84,%85,%86,%87,%88,%89,%90,%91,%92,%93,%94,%95,%96,%97,%98,%99,%100,%101,%102,%103,%104,%105,%106,%107,%108,%109,%110,%111,%112,%113,%114,%115,%116,%117,%118,%119,%120,%121,%122,%123,%124,%125,%126,%127}, {%128,%129,%130,%131}, b, p, 1, 1, 1;\n}\n"
    : "=f"(d[0]),"=f"(d[1]),"=f"(d[2]),"=f"(d[3]),"=f"(d[4]),"=f"(d[5]),"=f"(d[6]),"=f"(d[7]),"=f"(d[8]),"=f"(d[9]),"=f"(d[10]),"=f"(d[11]),"=f"(d[12]),"=f"(d[13]),"=f"(d[14]),"=f"(d[15]),"=f"(d[16]),"=f"(d[17]),"=f"(d[18]),"=f"(d[19]),"=f"(d[20]),"=f"(d[21]),"=f"(d[22]),"=f"(d[23]),"=f"(d[24]),"=f"(d[25]),"=f"(d[26]),"=f"(d[27]),"=f"(d[28]),"=f"(d[29]),"=f"(d[30]),"=f"(d[31]),"=f"(d[32]),"=f"(d[33]),"=f"(d[34]),"=f"(d[35]),"=f"(d[36]),"=f"(d[37]),"=f"(d[38]),"=f"(d[39]),"=f"(d[40]),"=f"(d[41]),"=f"(d[42]),"=f"(d[43]),"=f"(d[44]),"=f"(d[45]),"=f"(d[46]),"=f"(d[47]),"=f"(d[48]),"=f"(d[49]),"=f"(d[50]),"=f"(d[51]),"=f"(d[52]),"=f"(d[53]),"=f"(d[54]),"=f"(d[55]),"=f"(d[56]),"=f"(d[57]),"=f"(d[58]),"=f"(d[59]),"=f"(d[60]),"=f"(d[61]),"=f"(d[62]),"=f"(d[63]),"=f"(d[64]),"=f"(d[65]),"=f"(d[66]),"=f"(d[67]),"=f"(d[68]),"=f"(d[69]),"=f"(d[70]),"=f"(d[71]),"=f"(d[72]),"=f"(d[73]),"=f"(d[74]),"=f"(d[75]),"=f"(d[76]),"=f"(d[77]),"=f"(d[78]),"=f"(d[79]),"=f"(d[80]),"=f"(d[81]),"=f"(d[82]),"=f"(d[83]),"=f"(d[84]),"=f"(d[85]),"=f"(d[86]),"=f"(d[87]),"=f"(d[88]),"=f"(d[89]),"=f"(d[90]),"=f"(d[91]),"=f"(d[92]),"=f"(d[93]),"=f"(d[94]),"=f"(d[95]),"=f"(d[96]),"=f"(d[97]),"=f"(d[98]),"=f"(d[99]),"=f"(d[100]),"=f"(d[101]),"=f"(d[102]),"=f"(d[103]),"=f"(d[104]),"=f"(d[105]),"=f"(d[106]),"=f"(d[107]),"=f"(d[108]),"=f"(d[109]),"=f"(d[110]),"=f"(d[111]),"=f"(d[112]),"=f"(d[113]),"=f"(d[114]),"=f"(d[115]),"=f"(d[116]),"=f"(d[117]),"=f"(d[118]),"=f"(d[119]),"=f"(d[120]),"=f"(d[121]),"=f"(d[122]),"=f"(d[123]),"=f"(d[124]),"=f"(d[125]),"=f"(d[126]),"=f"(d[127]) : "r"(a.x), "r"(a.y), "r"(a.z), "r"(a.w), "r"(db.lo), "r"(db.hi));
}
template<int N> __device__ __forceinline__ void wgmma_ra(float (&d)[N / 2], const uint4& a, Desc db, bool acc) {
  if (acc) wgmma_rs<N, 1>(d, a, db); else wgmma_rs<N, 0>(d, a, db);
}

__device__ __forceinline__ uint32_t smem_u32(const void* p) { return (uint32_t)__cvta_generic_to_shared(p); }
__device__ __forceinline__ void mbar_init(uint32_t bar, uint32_t cnt) { asm volatile("mbarrier.init.shared::cta.b64 [%0], %1;" ::"r"(bar), "r"(cnt)); }
__device__ __forceinline__ void mbar_expect_tx(uint32_t bar, uint32_t bytes) { asm volatile("mbarrier.arrive.expect_tx.shared::cta.b64 _, [%0], %1;" ::"r"(bar), "r"(bytes) : "memory"); }
__device__ __forceinline__ void mbar_arrive(uint32_t bar) { asm volatile("mbarrier.arrive.shared::cta.b64 _, [%0];" ::"r"(bar) : "memory"); }
__device__ __forceinline__ void mbar_arrive_remote(uint32_t rbar) { asm volatile("mbarrier.arrive.shared::cluster.b64 _, [%0];" ::"r"(rbar) : "memory"); }
__device__ __forceinline__ void mbar_wait(uint32_t bar, uint32_t parity) {
  asm volatile(
      "{\n.reg .pred p;\n.reg .u32 c;\nmov.u32 c, 0;\nLAB_WAIT:\nmbarrier.try_wait.parity.shared::cta.b64 p, [%0], %1;\n@p bra DONE;\n"
      "add.u32 c, c, 1;\nsetp.lt.u32 p, c, 1000000;\n@p bra LAB_WAIT;\ntrap;\nDONE:\n}\n" ::"r"(bar), "r"(parity) : "memory");
}
__device__ __forceinline__ void mbar_wait_c(uint32_t bar, uint32_t parity) {
  asm volatile("{\n.reg .pred p;\nLAB_WAIT:\nmbarrier.try_wait.parity.shared::cta.b64 p, [%0], %1;\n@!p bra LAB_WAIT;\n}\n" ::"r"(bar), "r"(parity) : "memory");
}
__device__ __forceinline__ uint32_t late(uint32_t bar, uint32_t v) {
  uint32_t r;
  asm volatile("{\n.reg .pred p;\nmbarrier.test_wait.parity.shared::cta.b64 p, [%1], 0;\nselp.b32 %0, %2, %1, p;\n}\n" : "=r"(r) : "r"(bar), "r"(v) : "memory");
  return r;
}
__device__ __forceinline__ void wtma2d(uint32_t dst, const CUtensorMap* m, int c0, int c1, uint32_t bar, uint64_t pol) {
  asm volatile("cp.async.bulk.tensor.2d.shared::cluster.global.mbarrier::complete_tx::bytes.multicast::cluster.L2::cache_hint [%0], [%1, {%3, %4}], [%2], %5, %6;"
               ::"r"(dst), "l"(m), "r"(bar), "r"(c0), "r"(c1), "h"((uint16_t)3), "l"(pol) : "memory");
}
__device__ __forceinline__ void wtma3d(uint32_t dst, const CUtensorMap* m, int c0, int c1, int c2, uint32_t bar, uint64_t pol) {
  asm volatile("cp.async.bulk.tensor.3d.shared::cluster.global.mbarrier::complete_tx::bytes.multicast::cluster.L2::cache_hint [%0], [%1, {%3, %4, %5}], [%2], %6, %7;"
               ::"r"(dst), "l"(m), "r"(bar), "r"(c0), "r"(c1), "r"(c2), "h"((uint16_t)3), "l"(pol) : "memory");
}
__device__ __forceinline__ void wbulk(uint32_t dst, const void* src, uint32_t bytes, uint32_t bar, uint64_t pol) {
  asm volatile("cp.async.bulk.shared::cluster.global.mbarrier::complete_tx::bytes.multicast::cluster.L2::cache_hint [%0], [%1], %2, [%3], %4, %5;"
               ::"r"(dst), "l"(src), "r"(bytes), "r"(bar), "h"((uint16_t)3), "l"(pol) : "memory");
}
__device__ __forceinline__ void tma3d(uint32_t dst, const CUtensorMap* m, int c0, int c1, int c2, uint32_t bar) {
  asm volatile("cp.async.bulk.tensor.3d.shared::cluster.global.mbarrier::complete_tx::bytes [%0], [%1, {%3, %4, %5}], [%2];"
               ::"r"(dst), "l"(m), "r"(bar), "r"(c0), "r"(c1), "r"(c2) : "memory");
}
__device__ __forceinline__ void prefetch_l2(const void* p, uint32_t bytes) { asm volatile("cp.async.bulk.prefetch.L2.global [%0], %1;" ::"l"(p), "r"(bytes) : "memory"); }
__device__ __forceinline__ uint64_t policy_evict_first() { uint64_t p; asm volatile("createpolicy.fractional.L2::evict_first.b64 %0, 1.0;" : "=l"(p)); return p; }
__device__ __forceinline__ uint64_t policy_evict_normal() { uint64_t p; asm volatile("createpolicy.fractional.L2::evict_normal.b64 %0, 1.0;" : "=l"(p)); return p; }
__device__ __forceinline__ void fence_async_smem() { asm volatile("fence.proxy.async.shared::cta;" ::: "memory"); }
__device__ __forceinline__ bool elect_one() {
  uint32_t p;
  asm volatile("{\n.reg .pred P;\nelect.sync _|P, 0xffffffff;\nselp.u32 %0, 1, 0, P;\n}\n" : "=r"(p));
  return p;
}
__device__ __forceinline__ void wg_fence() { asm volatile("wgmma.fence.sync.aligned;" ::: "memory"); }
__device__ __forceinline__ void wg_commit() { asm volatile("wgmma.commit_group.sync.aligned;" ::: "memory"); }
template <int n> __device__ __forceinline__ void wg_wait() { asm volatile("wgmma.wait_group.sync.aligned %0;" ::"n"(n) : "memory"); }
__device__ __forceinline__ void wg_bar(int w) { asm volatile("bar.sync %0, 128;" ::"r"(w + 1) : "memory"); }
__device__ __forceinline__ void fence_gpu() { asm volatile("fence.acq_rel.gpu;" ::: "memory"); }
__device__ __forceinline__ uint32_t ld_relaxed(const uint32_t* p) { uint32_t v; asm volatile("ld.relaxed.gpu.global.u32 %0, [%1];" : "=r"(v) : "l"(p) : "memory"); return v; }
__device__ __forceinline__ uint32_t ld_acquire(const uint32_t* p) { uint32_t v; asm volatile("ld.acquire.gpu.global.u32 %0, [%1];" : "=r"(v) : "l"(p) : "memory"); return v; }
__device__ __forceinline__ uint4 ld_relaxed4(const uint4* p) {
  uint4 v; asm volatile("ld.relaxed.gpu.global.v4.u32 {%0,%1,%2,%3}, [%4];" : "=r"(v.x), "=r"(v.y), "=r"(v.z), "=r"(v.w) : "l"(p) : "memory"); return v;
}
__device__ __forceinline__ uint2 ld_relaxed2(const uint2* p) {
  uint2 v; asm volatile("ld.relaxed.gpu.global.v2.u32 {%0,%1}, [%2];" : "=r"(v.x), "=r"(v.y) : "l"(p) : "memory"); return v;
}
__device__ __forceinline__ void st_relaxed(uint32_t* p, uint32_t a) { asm volatile("st.relaxed.gpu.global.u32 [%0], %1;" ::"l"(p), "r"(a) : "memory"); }
__device__ __forceinline__ void st_relaxed4(uint4* p, uint32_t a, uint32_t b, uint32_t c, uint32_t d) {
  asm volatile("st.relaxed.gpu.global.v4.u32 [%0], {%1,%2,%3,%4};" ::"l"(p), "r"(a), "r"(b), "r"(c), "r"(d) : "memory");
}
__device__ __forceinline__ void st_relaxed2(uint2* p, uint32_t a, uint32_t b) {
  asm volatile("st.relaxed.gpu.global.v2.u32 [%0], {%1,%2};" ::"l"(p), "r"(a), "r"(b) : "memory");
}
__device__ __forceinline__ void red4(uint4* p, uint32_t a, uint32_t b, uint32_t c, uint32_t d) {
  asm volatile("red.relaxed.gpu.global.add.noftz.v4.bf16x2 [%0], {%1,%2,%3,%4};" ::"l"(p), "r"(a), "r"(b), "r"(c), "r"(d) : "memory");
}
__device__ __forceinline__ void red2(uint2* p, uint32_t a, uint32_t b) {
  asm volatile("red.relaxed.gpu.global.add.noftz.v2.bf16x2 [%0], {%1,%2};" ::"l"(p), "r"(a), "r"(b) : "memory");
}
constexpr int SPIN_MAX = 1 << 21;
__device__ __forceinline__ uint32_t pack_bf16(float lo, float hi) { uint32_t r; asm("cvt.rn.bf16x2.f32 %0, %1, %2;" : "=r"(r) : "f"(hi), "f"(lo)); return r; }
__device__ __forceinline__ float bf_lo(uint32_t v) { return __uint_as_float(v << 16); }
__device__ __forceinline__ float bf_hi(uint32_t v) { return __uint_as_float(v & 0xffff0000u); }
__device__ __forceinline__ float2 lds64(uint32_t a) { float2 v; asm volatile("ld.shared.v2.f32 {%0,%1}, [%2];" : "=f"(v.x), "=f"(v.y) : "r"(a)); return v; }
__device__ __forceinline__ uint32_t lds32(uint32_t a) { uint32_t v; asm volatile("ld.shared.b32 %0, [%1];" : "=r"(v) : "r"(a)); return v; }
__device__ __forceinline__ void sts64f(uint32_t a, float x, float y) { asm volatile("st.shared.v2.f32 [%0], {%1,%2};" ::"r"(a), "f"(x), "f"(y) : "memory"); }
__device__ __forceinline__ void sts32(uint32_t a, uint32_t x) { asm volatile("st.volatile.shared.b32 [%0], %1;" ::"r"(a), "r"(x) : "memory"); }
__device__ __forceinline__ void gate(uint32_t a, int need) {
#pragma unroll 1
  for (int it = 0; it < SPIN_MAX; it++) {
    int v; asm volatile("ld.volatile.shared.b32 %0, [%1];" : "=r"(v) : "r"(a) : "memory");
    if (v >= need) break;
    if (GSLEEP) __nanosleep(GSLEEP);
  }
}
__device__ __forceinline__ void sts128(uint32_t a, uint32_t x, uint32_t y, uint32_t z, uint32_t u) { asm volatile("st.shared.v4.b32 [%0], {%1,%2,%3,%4};" ::"r"(a), "r"(x), "r"(y), "r"(z), "r"(u) : "memory"); }
__device__ __forceinline__ uint4 lds128(uint32_t a) { uint4 v; asm volatile("ld.shared.v4.u32 {%0,%1,%2,%3}, [%4];" : "=r"(v.x), "=r"(v.y), "=r"(v.z), "=r"(v.w) : "r"(a) : "memory"); return v; }
__device__ __forceinline__ uint32_t hmul2(uint32_t a, uint32_t b) { uint32_t r; asm("mul.rn.bf16x2 %0, %1, %2;" : "=r"(r) : "r"(a), "r"(b)); return r; }
__device__ __forceinline__ uint32_t hadd2(uint32_t a, uint32_t b) { uint32_t r; asm("add.rn.bf16x2 %0, %1, %2;" : "=r"(r) : "r"(a), "r"(b)); return r; }
__device__ __forceinline__ void stsm4(uint32_t a, uint32_t r0, uint32_t r1, uint32_t r2, uint32_t r3) {
  asm volatile("stmatrix.sync.aligned.m8n8.x4.shared.b16 [%0], {%1,%2,%3,%4};" ::"r"(a), "r"(r0), "r"(r1), "r"(r2), "r"(r3) : "memory");
}
__device__ __forceinline__ void stsm2(uint32_t a, uint32_t r0, uint32_t r1) {
  asm volatile("stmatrix.sync.aligned.m8n8.x2.shared.b16 [%0], {%1,%2};" ::"r"(a), "r"(r0), "r"(r1) : "memory");
}
__device__ __forceinline__ uint4 ldsm4(uint32_t a) {
  uint4 r; asm volatile("ldmatrix.sync.aligned.m8n8.x4.shared.b16 {%0,%1,%2,%3}, [%4];" : "=r"(r.x), "=r"(r.y), "=r"(r.z), "=r"(r.w) : "r"(a) : "memory"); return r;
}
__device__ __forceinline__ uint32_t movm(uint32_t a) { uint32_t r; asm("movmatrix.sync.aligned.m8n8.trans.b16 %0, %1;" : "=r"(r) : "r"(a)); return r; }
__device__ __forceinline__ void mma16816z(float (&d)[4], uint32_t a0, uint32_t a1, uint32_t a2, uint32_t a3, uint32_t b0, uint32_t b1) {
  asm("mma.sync.aligned.m16n8k16.row.col.f32.bf16.bf16.f32 {%0,%1,%2,%3}, {%4,%5,%6,%7}, {%8,%9}, {%10,%10,%10,%10};"
      : "=f"(d[0]), "=f"(d[1]), "=f"(d[2]), "=f"(d[3]) : "r"(a0), "r"(a1), "r"(a2), "r"(a3), "r"(b0), "r"(b1), "f"(0.f));
}
__device__ __forceinline__ void mma16816(float (&d)[4], const uint4& a, uint32_t b0, uint32_t b1) {
  asm("mma.sync.aligned.m16n8k16.row.col.f32.bf16.bf16.f32 {%0,%1,%2,%3}, {%4,%5,%6,%7}, {%8,%9}, {%0,%1,%2,%3};"
      : "+f"(d[0]), "+f"(d[1]), "+f"(d[2]), "+f"(d[3]) : "r"(a.x), "r"(a.y), "r"(a.z), "r"(a.w), "r"(b0), "r"(b1));
}
__device__ __forceinline__ void mma1688(float (&d)[4], uint32_t a0, uint32_t a1, uint32_t b0) {
  asm("mma.sync.aligned.m16n8k8.row.col.f32.bf16.bf16.f32 {%0,%1,%2,%3}, {%4,%5}, {%6}, {%0,%1,%2,%3};"
      : "+f"(d[0]), "+f"(d[1]), "+f"(d[2]), "+f"(d[3]) : "r"(a0), "r"(a1), "r"(b0));
}
__device__ __forceinline__ float quad_sum(float v) { v += __shfl_xor_sync(0xffffffffu, v, 1); v += __shfl_xor_sync(0xffffffffu, v, 2); return v; }
__device__ __forceinline__ float quad_max(float v) { v = fmaxf(v, __shfl_xor_sync(0xffffffffu, v, 1)); v = fmaxf(v, __shfl_xor_sync(0xffffffffu, v, 2)); return v; }
__device__ __forceinline__ float rcp(float x) { float r; asm("rcp.approx.ftz.f32 %0, %1;" : "=f"(r) : "f"(x)); return r; }
__device__ __forceinline__ float rsq(float x) { float r; asm("rsqrt.approx.ftz.f32 %0, %1;" : "=f"(r) : "f"(x)); return r; }
__device__ __forceinline__ float ex2(float x) { float r; asm("ex2.approx.ftz.f32 %0, %1;" : "=f"(r) : "f"(x)); return r; }
__device__ __forceinline__ uint32_t chk(uint32_t acc, uint32_t v, uint32_t tag) { uint32_t r; asm("lop3.b32 %0, %1, %2, %3, 0xF6;" : "=r"(r) : "r"(acc), "r"(v), "r"(tag)); return r; }
__device__ __forceinline__ uint32_t chk2(uint32_t a, uint32_t b, uint32_t tag) { uint32_t r; asm("lop3.b32 %0, %1, %2, %3, 0x7E;" : "=r"(r) : "r"(a), "r"(b), "r"(tag)); return r; }
__device__ __forceinline__ uint32_t tagged(uint32_t v, uint32_t tag) { return (v & ~1u) | tag; }

__device__ __forceinline__ int group_k0(int g, int j) {
  const int h = g >= 9, r = g - 2 - 7 * h;
  return g < 2 ? 64 * j + 32 * g : g < 16 ? 64 * (r + (r >= j)) + 32 * h : 32 * g;
}
__device__ __forceinline__ uint32_t xin_off(int c, int w) { return SM_X + (2 * c + w) * 8192; }
__device__ __forceinline__ uint32_t xin_bar(int c) { return BAR_FULLX + 8 * (c < 8 ? c ^ 4 : c); }
__device__ __forceinline__ constexpr uint32_t qkv_xslot(int g) { return g < 5 || g > 11 ? 2 : (0x5140762u >> (4 * (g - 5))) & 15; }

template <int N> struct IC { static constexpr int v = N; };

struct Cons {
  uint32_t sb;
  uint32_t rem;
  uint32_t sB, mB;
  uint32_t mX;
  bool elect;
  __device__ __forceinline__ void release2(uint32_t bar) const { if (elect) { mbar_arrive(sb + bar); mbar_arrive_remote(rem + bar); } }
  __device__ __forceinline__ uint32_t nextB(uint32_t& prev) {
    mbar_wait_c(sb + BAR_FULLB + sB, mB);
    const uint32_t a = (((sb & 0x3FFFF) + SM_B) >> 4) + sB * (BSLOT / 128);
    prev = sB == 0 ? 32 : sB - 8;
    sB += 8;
    if (sB == 40) { sB = 0; mB ^= 1; }
    return a;
  }
  __device__ __forceinline__ void progress(uint32_t v) const { if (elect) sts32(sb + SM_PROG + (threadIdx.x >> 5), v); }
  __device__ __forceinline__ void releaseLastB() const { release2(BAR_EMPTYB + (sB == 0 ? 32 : sB - 8)); }
};

__device__ __forceinline__ float2 gather_sums(const uint2* a, uint32_t stag) {
  uint2 sa, sc;
  do { sa = ld_relaxed2(a); sc = ld_relaxed2(a + 8); } while (__any_sync(0xffffffffu, chk2(sa.x, sc.x, stag) & 3));
  return make_float2(quad_sum(__uint_as_float(sa.x) + __uint_as_float(sc.x)), quad_sum(__uint_as_float(sa.y) + __uint_as_float(sc.y)));
}

struct Norm {
  float m0, m1;
  uint32_t nm0, nm1;
  float d0, d1;
  uint2 u0, u1;
  __device__ __forceinline__ Norm(float2 sum) : m0(sum.x * (-1.f / 576)), m1(sum.y * (-1.f / 576)), nm0(pack_bf16(m0, m0)), nm1(pack_bf16(m1, m1)), d0(0.f), d1(0.f) {}
  __device__ __forceinline__ uint4 centre(const uint4& a) const { return make_uint4(hadd2(a.x, nm0), hadd2(a.y, nm1), hadd2(a.z, nm0), hadd2(a.w, nm1)); }
  __device__ __forceinline__ void sqr(uint32_t a, uint32_t b) {
    d0 = fmaf(bf_lo(a), bf_lo(a), fmaf(bf_hi(a), bf_hi(a), d0)); d1 = fmaf(bf_lo(b), bf_lo(b), fmaf(bf_hi(b), bf_hi(b), d1));
  }
  __device__ __forceinline__ void send(uint2* a, int t, uint32_t stag) {
    d0 = quad_sum(d0); d1 = quad_sum(d1);
    if ((t & 3) == 0) st_relaxed2(a, (__float_as_uint(d0) & ~3u) | stag, __float_as_uint(d1));
  }
  __device__ __forceinline__ void fetch(const uint2* a) { u0 = ld_relaxed2(a); u1 = ld_relaxed2(a + 8); }
  __device__ __forceinline__ float2 rstd(const uint2* a, uint32_t stag) {
    while (__any_sync(0xffffffffu, chk2(u0.x, u1.x, stag) & 3)) fetch(a);
    const float e0 = bf_lo(nm0) - m0, e1 = bf_lo(nm1) - m1;
    const float v0 = fmaf(quad_sum(__uint_as_float(u0.x) + __uint_as_float(u1.x)), 1.f / 576, -e0 * e0);
    const float v1 = fmaf(quad_sum(__uint_as_float(u0.y) + __uint_as_float(u1.y)), 1.f / 576, -e1 * e1);
    float2 r = make_float2(rsq(fmaxf(v0, 0.f) + 1e-5f), rsq(fmaxf(v1, 0.f) + 1e-5f));
    asm volatile("" : "+f"(r.x), "+f"(r.y));
    return r;
  }
};

template <class Pre, class Mma>
__device__ __forceinline__ float2 ln_gemm_in(Cons& c, Group* G, uint32_t (&p)[18], float2& sum, int w, int st0, int j, int t, Pre&& pre, Mma&& mma) {
  const uint32_t xa = c.sb + (t >> 5) * 2048 + (t & 15) * 128, sw = (((t >> 4) & 1) ^ (t & 7)) * 16;
  float ra[4] = {0.f, 0.f, 0.f, 0.f}, rb[4] = {0.f, 0.f, 0.f, 0.f};
#pragma unroll 1
  for (int cc = 0; cc < 9; cc++) {
    const uint32_t a = xa + xin_off(cc, w);
    mbar_wait_c(c.sb + xin_bar(cc), 0);
    const uint4 u0 = ldsm4(a + sw), u1 = ldsm4(a + (sw ^ 32)), u2 = ldsm4(a + (sw ^ 64)), u3 = ldsm4(a + (sw ^ 96));
    mma16816(ra, u0, 0x3f803f80u, 0x3f803f80u); mma16816(rb, u1, 0x3f803f80u, 0x3f803f80u);
    mma16816(ra, u2, 0x3f803f80u, 0x3f803f80u); mma16816(rb, u3, 0x3f803f80u, 0x3f803f80u);
  }
  sum = make_float2(ra[0] + rb[0], ra[2] + rb[2]);
  pre(0);
  Norm n(sum);
  n.u0 = n.u1 = make_uint2(0, 0);
  auto stats = [&] {
#pragma unroll
    for (int k = 0; k < 5; k++) {
      const uint4 u = ldsm4(xa + (k < 4 ? xin_off(j, w) + (sw ^ (32 * k)) : xin_off(8, w) + ((j ^ (t & 7)) << 4))), e = n.centre(u);
      p[4 * k] = u.x; p[4 * k + 1] = u.y;
      n.sqr(e.x, e.y);
      if (k < 4) { p[4 * k + 2] = u.z; p[4 * k + 3] = u.w; n.sqr(e.z, e.w); }
    }
    n.send(G->sq + st0 + 8 * j, t, 1);
  };
  if (STATP < 0) stats();
  else {
#pragma unroll
    for (int i = 0; i < 18; i++) p[i] = 0;
  }
  pre(1);
  float2 r = make_float2(0.f, 0.f);
  uint4 y0 = ldsm4(xa + xin_off(0, w) + sw), y1 = ldsm4(xa + xin_off(0, w) + (sw ^ 32));
#pragma unroll 1
  for (int cc = 0; cc < 9; cc++) {
#pragma unroll
    for (int i = 0; i < 2; i++) {
      const uint4 f0 = n.centre(y0), f1 = n.centre(y1);
      const uint32_t a = xa + xin_off(min(cc + i, 8), w);
      y0 = ldsm4(a + (sw ^ (64 - 64 * i))); y1 = ldsm4(a + (sw ^ (96 - 64 * i)));
      uint32_t prev;
      const uint32_t bb = c.nextB(prev);
      mma(true, bb, f0, f1);
      if (i == 1) {
        if (STATP >= 0 && cc == STATP * w) stats();
        if (cc == 1) c.progress(3);
        if (cc == 5) n.fetch(G->sq + st0 + 16 * (t & 3));
        if (cc == 7) r = n.rstd(G->sq + st0 + 16 * (t & 3), 1);
        if (cc == 8 && w == 0) asm volatile("bar.arrive 6, 256;" ::: "memory");
      }
      wg_wait<1>();
      if (i + cc > 0) c.release2(BAR_EMPTYB + prev);
      if (2 * cc + i >= WOG && 2 * cc + i < WOG + 4) c.release2(BAR_EMPTYX + 32 + 8 * (2 * cc + i - WOG));
    }
  }
  c.mX = 0xff;
  if (w == 1) asm volatile("bar.sync 6, 256;" ::: "memory");
  wg_wait<0>();
  c.releaseLastB();
  c.release2(BAR_EMPTYX + 24);
  return r;
}

template <bool QKV, class Pre, class Mma>
__device__ __forceinline__ float2 ln_gemm(Cons& c, Group* G, const float (&v)[36], uint32_t (&p)[18], float2& sum, int st0, int j, int t,
                                          int layer, uint32_t tag, Pre&& pre, Mma&& mma) {
  constexpr bool known = !QKV && EARLY;
  const uint32_t stag = (2 * layer + (QKV ? 1 : 2)) & 3;
  uint4 x[6][2];
  uint4* src = G->xbox + t;
  asm volatile("" : "+l"(src));
  auto buf = [&](int g) -> uint4 (&)[2] { return x[g < 16 ? (g - 2) % 6 : g - 13]; };
  auto load = [&](int g0) {
#pragma unroll
    for (int g = g0; g < g0 + (g0 < 14 ? 3 : 2); g++) {
      const uint4* a = g < 16 ? src + ((g - 2) % 7 >= j ? 256 : 0) + (2 * ((g - 2) % 7) + 16 * (g >= 9)) * 128 : src + 2 * g * 128;
      buf(g)[0] = ld_relaxed4(a); buf(g)[1] = ld_relaxed4(a + 128);
    }
  };
  auto invalid = [&](int g, uint32_t tag) {
    uint32_t bad = chk(chk(chk2(buf(g)[0].x, buf(g)[1].x, tag), buf(g + 1)[0].x, tag), buf(g + 1)[1].x, tag);
    if (g < 14) bad = chk(chk(bad, buf(g + 2)[0].x, tag), buf(g + 2)[1].x, tag);
    if (g == 16) bad = chk(chk(chk(chk(bad, buf(g)[0].z, tag), buf(g)[1].z, tag), buf(g + 1)[0].z, tag), buf(g + 1)[1].z, tag);
    return __any_sync(0xffffffffu, bad & 1);
  };
  uint4* const d = src + 2 * j * 128;
  const int sq = st0 + 16 * (t & 3);
  if (!known) {
    float s0 = v[0] + v[1], s1 = v[2] + v[3];
#pragma unroll
    for (int i = 1; i < 9; i++) { s0 += v[4 * i] + v[4 * i + 1]; s1 += v[4 * i + 2] + v[4 * i + 3]; }
    s0 = quad_sum(s0); s1 = quad_sum(s1);
    if ((t & 3) == 0) st_relaxed2(G->sum + st0 + 8 * j, (__float_as_uint(s0) & ~3u) | stag, __float_as_uint(s1));
  }
#pragma unroll
  for (int i = 0; i < 18; i++) p[i] = pack_bf16(v[2 * i], v[2 * i + 1]);
#pragma unroll
  for (int i = 0; i < 2; i++) st_relaxed4(d + i * 128, tagged(p[4 * i], tag), p[4 * i + 1], p[4 * i + 2], p[4 * i + 3]);
  pre(0);
  if (!known) {
    sum = gather_sums(G->sum + sq, stag);
    load(2);
  }
  Norm n(sum);
  pre(1);
  const uint32_t* probe = &(G->xbox + (2 * (t & XPM) + 1) * 128 + (t | 31))->x;
  uint32_t pv;
  float2 r;
  auto inx = [](int g) { return QKV && ((g >= 5 && g < 12) || g == 17); };
  auto use = [](int g) { return QKV ? (g < 5 ? 108 : 101) + g : 18 + g; };
#pragma unroll
  for (int g = 0; g < 18; g++) {
    if (g < 16 ? g % 3 == 2 : g == 16) {
      const uint32_t lt = late(c.sb + BAR_FULLX + 64, tag);
      while (invalid(g, lt)) load(g);
      if (g < 16) load(g < 14 ? g + 3 : 16);
    }
    const uint4 f0 = n.centre(g < 2 ? make_uint4(p[8 * g], p[8 * g + 1], p[8 * g + 2], p[8 * g + 3]) : buf(g)[0]);
    const uint4 f1 = n.centre(g < 2 ? make_uint4(p[8 * g + 4], p[8 * g + 5], p[8 * g + 6], p[8 * g + 7]) : buf(g)[1]);
    if (g == 11) n.fetch(G->sq + sq);
    if (g == 16) r = n.rstd(G->sq + sq, stag);
    if (inx(g)) mbar_wait_c(c.sb + BAR_FULLX + 8 * qkv_xslot(g), ((0x34 >> qkv_xslot(g)) & 1) ^ (g == 17));
    else mbar_wait_c(c.sb + BAR_FULLB + 8 * (use(g) % 5), (use(g) / 5) & 1);
    mma(g, ((c.sb & 0x3FFFF) >> 4) + ((inx(g) ? xslot(qkv_xslot(g)) : SM_B + (use(g) % 5) * BSLOT) >> 4), f0, f1);
    if (g == 1) { wg_wait<1>(); c.release2(BAR_EMPTYB + 8 * (use(0) % 5)); }
    if (g < 2) {
      if (known) {
        if (g == 0) {
          pv = tag;
          if (!ESPEC || layer == 0) pv = ld_relaxed(probe);
        } else {
          const uint32_t lt = late(c.sb + BAR_FULLX + 64, tag);
          while (__any_sync(0xffffffffu, (pv ^ lt) & 1)) pv = ld_relaxed(probe);
          load(2);
        }
      }
      if (g == (known ? 1 : 0)) {
#pragma unroll
        for (int i = 2; i < 4; i++) st_relaxed4(d + (14 + i) * 128, tagged(p[4 * i], tag), p[4 * i + 1], p[4 * i + 2], p[4 * i + 3]);
        st_relaxed2((uint2*)(src + (32 + (j >> 1)) * 128) + (j & 1), tagged(p[16], tag), p[17]);
      }
      n.sqr(f0.x, f0.y); n.sqr(f0.z, f0.w); n.sqr(f1.x, f1.y); n.sqr(f1.z, f1.w);
      if (g == 1) {
        n.sqr(hadd2(p[16], n.nm0), hadd2(p[17], n.nm1));
        n.send(G->sq + st0 + 8 * j, t, stag);
      }
    }
    if (g == 1 && !QKV) { wg_wait<0>(); c.release2(BAR_EMPTYB + 8 * (use(1) % 5)); }
    else wg_wait<1>();
    if (g > (QKV ? 1 : 2) && !inx(g - 1)) c.release2(BAR_EMPTYB + 8 * (use(g - 1) % 5));
    if (QKV && g < 13) c.progress(33 + g);
    if (QKV && g == WOG - 1) c.release2(BAR_EMPTYX + 8 * qkv_xslot(17));
    if (QKV && g >= WOG && g < WOG + 4) c.release2(BAR_EMPTYX + 32 + 8 * (g - WOG));
  }
  if (QKV) c.mX = 0x34 ^ 0xf3;
  else { c.sB = 8 * (36 % 5); c.mB = (36 / 5) & 1; }
  wg_wait<0>();
  if (!QKV) c.release2(BAR_EMPTYB + 8 * (use(17) % 5));
  return r;
}

template <int NB, int OFF>
__device__ __forceinline__ void glu(const float (&a)[128], uint32_t (&h)[144]) {
#pragma unroll
  for (int b = 0; b < 2 * NB; b++) {
    if (HMUL) h[OFF + b] = hmul2(pack_bf16(a[2 * b], a[2 * b + 1]), pack_bf16(a[4 * NB + 2 * b], a[4 * NB + 2 * b + 1]));
    else h[OFF + b] = pack_bf16(a[2 * b] * a[4 * NB + 2 * b], a[2 * b + 1] * a[4 * NB + 2 * b + 1]);
  }
}

__global__ void __cluster_dims__(2, 1, 1) __launch_bounds__(384, 1)
fused_kernel(const __nv_bfloat16* __restrict__ x_in, Group* ws, const char* __restrict__ wqkv,
             const char* __restrict__ wo, char* __restrict__ out, uint32_t first, const __grid_constant__ Maps maps,
             const char* __restrict__ wg, const char* __restrict__ wu, const char* __restrict__ wd) {
  extern __shared__ __align__(1024) uint8_t smem_raw[];
  const uint32_t sb = smem_u32(smem_raw);
  const uint32_t bx = blockIdx.x - first;
  if (bx >= NCTA) {
    const int e = blockIdx.x & 3;
    const uint32_t par = ~ld_relaxed(ws->flag + 32) & 1;
    __nanosleep(RDELAY);
    if (threadIdx.x < 16) prefetch_l2(wo + (144 * e + 9 * threadIdx.x) * 1152, 9 * 1152);
#pragma unroll 1
    for (int r = threadIdx.x >> 3; r < 144; r += 48) {
      const uint4* row = (const uint4*)(wo + (144 * e + r) * 1152) + (threadIdx.x & 7);
      float a = 0.f;
      uint4 u;
#pragma unroll
      for (int i = 0; i < 72; i += 8) {
        u = __ldg(row + i);
        a += ((bf_lo(u.x) + bf_hi(u.x)) + (bf_lo(u.y) + bf_hi(u.y))) + ((bf_lo(u.z) + bf_hi(u.z)) + (bf_lo(u.w) + bf_hi(u.w)));
      }
      const int h = r >= 72, k = r - 72 * h;
      ((Scratch*)ws)->woc[threadIdx.x & 7][k < 64 ? 64 + 8 * k + ((2 * e + h) ^ (k & 7)) : 576 * h + 8 * (k & 7) + (e ^ (k & 7))] = u;
      a = quad_sum(a);
      a += __shfl_xor_sync(0xffffffffu, a, 4);
      if ((threadIdx.x & 7) == 0) ((Scratch*)ws)->woc[2 * e + h][640 + k] = make_uint4(pack_bf16(a, a - bf_lo(pack_bf16(a, 0.f))), 0, 0, 0);
    }
    fence_gpu();
    __syncthreads();
    if (threadIdx.x == 0) st_relaxed(((Scratch*)ws)->done + e, par);
    const int cc = threadIdx.x % 54, r0 = threadIdx.x / 54, part = cc / 18, jj = 2 * e + (cc % 18) / 9, c9 = cc % 9;
    if (r0 < 6) {
#pragma unroll 4
      for (int k = r0; k < 576; k += 6) {
        const uint4 u = __ldg((const uint4*)(wqkv + k * 3456 + part * 1152 + 144 * jj) + c9);
        ((Scratch*)ws)->wq[jj][k >> 4][c9 < 8 ? part * 128 + (k & 15) * 8 + (c9 ^ (k & 7)) : 384 + part * 16 + (k & 15)] = u;
      }
    }
    fence_gpu();
    __syncthreads();
    if (threadIdx.x == 0) st_relaxed(((Scratch*)ws)->done + 32 + e, par);
    return;
  }
  if (threadIdx.x == 0) asm volatile("prefetch.tensormap [%0];" ::"l"(&maps.x) : "memory");
  const int warp = __shfl_sync(0xffffffffu, threadIdx.x >> 5, 0);
  const int lane = threadIdx.x & 31;
  const int rank = blockIdx.x & 1;
  if (elect_one()) {
    if (warp >= 8) {
#pragma unroll
      for (int i = 0; i < 9; i++) mbar_init(sb + SM_BAR + 72 * (warp - 8) + 8 * i, warp < 10 ? 1 : 4);
      sts32(sb + SM_PROG + 4 * (warp - 8), 0);
      asm volatile("fence.mbarrier_init.release.cluster;" ::: "memory");
    } else if (warp == 1 || warp == 2) {
      asm volatile("prefetch.tensormap [%0];" ::"l"(&maps.x + warp) : "memory");
    } else if (warp == 3) {
      if (PFMODE & 1) prefetch_l2((const char*)x_in + bx * 18432, 18432);
    } else if (warp == 4) {
      if (PFMODE & 2) prefetch_l2(wqkv + bx * (15552 / PFQ), 15552 / PFQ);
    }
  }
  __syncwarp();
  asm volatile("barrier.cluster.arrive.relaxed.aligned;" ::: "memory");
  if (warp == 8) PROFX(53);
  int lb = bx;
  if (GPCMAP) {
    const int cl = bx >> 1, u = cl - 36;
    lb = (cl < 4 ? cl : cl < 36 ? 8 * ((cl - 4) & 7) + ((cl - 4) >> 3) + (((cl - 4) & 7) ? 0 : 4) : 8 * (1 + u % 7) + 4 + u / 7) * 2 + rank;
  }
#define CTA_J(b) (((b) >> 1) & 7)
#define CTA_RB(b) ((((b) >> 4) << 1) | ((b) & 1))
  const int j = CTA_J(lb), rb = CTA_RB(lb);

  PROF(23);
  if (warp >= 8) {
    asm volatile("setmaxnreg.dec.sync.aligned.u32 " STR(REGS_P) ";");
    auto x_chunk = [&](int cc) {
      mbar_expect_tx(sb + xin_bar(cc), 16384);
      tma3d(sb + xin_off(cc, 0), &maps.x, 64 * cc, 0, 64 * rb, sb + xin_bar(cc));
      tma3d(sb + xin_off(cc, 1), &maps.x, 64 * cc, 1, 64 * rb, sb + xin_bar(cc));
    };
    if (warp == 9 && elect_one()) {
      fence_async_smem();
#pragma unroll 1
      for (int i = 0; i < 9; i++) x_chunk(i);
    }
    __syncwarp();
    if (warp == 9) PROFX(54);
    asm volatile("barrier.cluster.wait.aligned;" ::: "memory");
    if (warp == 8) PROFX(56);
    const uint64_t pol = W_POLICY(), pola = A_POLICY();
    uint4 (* const wq)[432] = ((Scratch*)ws)->wq[j];
    const uint32_t par = ~ld_relaxed(ws[2 * rb].flag + 32 + 32 * j) & 1;
    auto qkv_group = [&](bool copy, int k, uint32_t dst, uint32_t bar) {
      if (copy) {
        wbulk(dst + rank * 8192, wq[(k >> 4) + rank], 6912, bar, pol);
      } else {
        wtma3d(dst + rank * 8192, &maps.qm, 72 * j, k + 16 * rank, 0, bar, pola);
        wtma3d(dst + rank * 8192 + 6144, &maps.qc, 72 * j + 64, k + 16 * rank, 0, bar, pola);
      }
    };
    auto chore = [&](int i) {
#pragma unroll 1
      for (int it = 0; it < SPIN_MAX; it++)
        if (__all_sync(0xffffffffu, ld_acquire(((Scratch*)ws)->done + i) == par)) break;
      asm volatile("fence.proxy.async.global;" ::: "memory");
    };
    const int ktab = group_k0(lane, j);
    auto qkv_gate = [&](int g) { if (g >= 8) gate(sb + SM_PROG, 33 + ((g - 8) * QPACE >> 4)); };
    if (warp == 8) {
      uint32_t s = 0, ph = 1;
      auto slot = [&](uint32_t bytes, auto&& issue) {
        const uint32_t bar = sb + BAR_FULLB + 8 * s;
        mbar_wait(sb + BAR_EMPTYB + 8 * s, ph);
        if (elect_one()) {
          mbar_expect_tx(bar, bytes);
          issue(sb + SM_B + s * BSLOT, bar);
        }
        if (++s == 5) { s = 0; ph ^= 1; }
      };
#pragma unroll 1
      for (int layer = 0; layer < NLAYERS; layer++) {
        if (layer) chore(32 + (j >> 1));
#pragma unroll 1
        for (int g = 0; g < 18 - layer; g += layer && g == 4 ? 8 : 1) {
          const int k = layer ? __shfl_sync(0xffffffffu, ktab, g) : 32 * g;
          if (layer) qkv_gate(g);
          else if (g == QD) mbar_wait(sb + xin_bar(XH), 0);
          slot(2 * 6912, [&](uint32_t dst, uint32_t bar) { qkv_group(layer, k, dst, bar); });
        }
        if (!FCH) {
          gate(sb + SM_PROG, 32 * layer + 20);
          gate(sb + SM_PROG + 4, 32 * layer + 20);
        }
#pragma unroll 1
        for (int t = 0; t < 5; t++) {
          const CUtensorMap* m = &maps.g + (t < 3 ? rank : 2 + rank);
          asm volatile("" : "+l"(m));
          const int c2 = t < 3 ? 9 * j + 2 * t : 18 * j + 3 + 3 * t;
          const uint32_t half = t < 3 ? 8192 : 6144;
          const uint64_t pt = layer == 0 && ((KEEPW >> t) & 1) ? pola : pol;
          auto tile = [&](int g) {
            const int k = __shfl_sync(0xffffffffu, ktab, g);
            slot(2 * half, [&](uint32_t dst, uint32_t bar) { wtma3d(dst + rank * half, m, 0, k, c2, bar, pt); });
          };
          int g = 0;
          if (t == 0) {
#pragma unroll 1
            for (; g < 5; g++) {
              mbar_wait(sb + BAR_FULLB + 8 * (s < FCH ? s + 5 - FCH : s - FCH), s < FCH ? ph : ph ^ 1);
              if (FG >= 0 && g == FN) gate(sb + SM_PROG + 4, 32 * layer + 20);
              tile(g);
            }
          }
#pragma unroll 1
          for (; g < 18; g++) tile(g);
        }
      }
    } else if (warp == 9) {
      uint32_t mE = 0;
      auto acquire = [&](uint32_t s) { mbar_wait(sb + BAR_EMPTYX + 8 * s, (mE >> s) & 1); mE ^= 1u << s; };
      auto landed = [&](uint32_t s) { mbar_wait(sb + BAR_FULLX + 8 * s, (mE >> s) & 1); };
      auto slot = [&](uint32_t s, const CUtensorMap* m, int col, int row, uint64_t pol) {
        acquire(s);
        if (elect_one()) {
          mbar_expect_tx(sb + BAR_FULLX + 8 * s, XSLOT);
          wtma2d(sb + xslot(s) + rank * 9216, m, col, row + 72 * rank, sb + BAR_FULLX + 8 * s, pol);
        }
      };
#pragma unroll 1
      for (int layer = 0; layer < NLAYERS; layer++) {
        if (layer) chore(32 + (j >> 1));
#pragma unroll 1
        for (int g = 5; g < 18 * layer; g += g == 11 ? 6 : 1) {
          const uint32_t s = qkv_xslot(g);
          const int k = __shfl_sync(0xffffffffu, ktab, g);
          if (g < 12) qkv_gate(g);
          acquire(s);
          if (elect_one()) {
            mbar_expect_tx(sb + BAR_FULLX + 8 * s, 2 * 6912);
            qkv_group(true, k, sb + xslot(s), sb + BAR_FULLX + 8 * s);
          }
          if (XCH & 1) landed(s);
        }
#pragma unroll 1
        for (int i = 0; i < 4; i++) { slot(4 + i, &maps.o, 64 * j, 144 * i, pola); if (XCH & 2) landed(4 + i); }
        if (layer == 0) { chore(lane & 3); PROFX(57); }
        acquire(3);
        if (elect_one()) {
          mbar_expect_tx(sb + BAR_FULLX + 24, 10240 + 1280);
          wbulk(sb + SM_WOC + rank * 5120, ((Scratch*)ws)->woc[j] + rank * 320, 5120, sb + BAR_FULLX + 24, pola);
          wbulk(sb + SM_WSUM + rank * 640, ((Scratch*)ws)->woc[j] + 640 + rank * 40, 640, sb + BAR_FULLX + 24, pola);
        }
#pragma unroll 1
        for (int u = 0; u < 36; u++) {
          const uint32_t s = 4 * (u & 1) + ((u >> 1) & 3);
          slot(s, &maps.d, u < 4 ? 512 : 64 * ((j + (u >> 2)) & 7), 576 * j + 144 * (u & 3), pol);
          if ((XCH & 4) && u < 3) landed(s);
        }
      }
    } else {
      const int w = warp - 10, grp = 2 * rb + w;
      if (PFMODE & 4) {
        mbar_wait(sb + xin_bar(XP), 0);
        if (lane == 0) prefetch_l2(wqkv + (2 * bx + w) * 7776, 7776);
      }
      gate(sb + SM_PROG, 3);
      if (w == 0) PROFX(58);
      auto prefetch_gu = [&](int l0, int n) {
#pragma unroll 1
        for (int i = lane; i < 36 * n; i += 32) {
          asm volatile("prefetch.global.L2 [%0];" ::"l"((w ? wu : wg) + (size_t)(36 * rb + i / n) * 9216 + 1152 * j + 128 * (l0 + i % n)));
          __nanosleep(PFSLEEP);
        }
      };
      auto clear = [&](uint4* p, int n) {
#pragma unroll 1
        for (int i = lane; i < n; i += 64) { st_relaxed4(p + i, 0, 0, 0, 0); st_relaxed4(p + i + 32, 0, 0, 0, 0); __nanosleep(CLRSLEEP); }
      };
      auto exchange = [&](uint32_t v, uint32_t bar) {
        if (FENCE1) { if (lane == 0) fence_gpu(); } else fence_gpu();
        __syncwarp();
        if (w == 0 && v != 1) PROFX(64 + 58 - 2 * v);
        if (lane == 0) st_relaxed(ws[grp].flag + j, v);
#pragma unroll 1
        for (int it = 0; it < SPIN_MAX; it++) {
          const uint32_t f = ld_relaxed(ws[grp].flag + (lane & 7));
          if (__all_sync(0xffffffffu, v ? f >= v : f == 0)) break;
        }
        if (lane == 0) mbar_arrive(sb + bar + 8 * w);
      };
      if (MAPPF && w == 0 && lane < 6) asm volatile("prefetch.tensormap [%0];" ::"l"(&maps.o + lane) : "memory");
#pragma unroll 1
      for (int layer = 0; layer < NLAYERS; layer++) {
        gate(sb + SM_PROG, 32 * layer + 3);
        if ((PFF & 1) && (layer == 0 || !(KEEPW & 1))) prefetch_gu(0, 2);
        gate(sb + SM_PROG, 32 * layer + 22);
        if (PFF & 2) prefetch_gu(2, 2);
        if (layer == 0) {
          clear(ws[grp].inbox[0] + 2 * j * INBOX, 2 * INBOX);
          exchange(1, BAR_CLR);
          if (w == 0) PROFX(59);
        }
        if (PFF & 2) prefetch_gu(4, 2);
        if (PFF & 4) prefetch_gu(6, 3);
#pragma unroll 1
        for (int i = lane; i < ((PFF & 8) ? 162 : 0); i += 32) {
          asm volatile("prefetch.global.L2 [%0];" ::"l"(wd + (size_t)(576 * j + 36 * rb + 18 * w) * 1152 + 128 * i));
          __nanosleep(PFSLEEP);
        }
        if (w == 0 && layer == 0) PROFX(60);
        mbar_wait(sb + BAR_REDDONE + 8 * w, layer);
        if (w == 0) PROFX(64 + 53 + 4 * layer);
        exchange(2 - 2 * layer, BAR_RREADY);
        if (w == 0) PROFX(64 + 56 + 4 * layer);
      }
      mbar_wait(sb + BAR_DONE + 8 * w, 0);
    }
  } else {
    asm volatile("setmaxnreg.inc.sync.aligned.u32 " STR(REGS_C) ";");
#define THREAD_IDS()                                                                   \
    int tid_ = threadIdx.x, bid_ = lb;                                                  \
    asm volatile("" : "+r"(tid_), "+r"(bid_));                                          \
    const int w = warp >> 2, wp = warp & 3;                                             \
    const int lane = tid_ & 31, t = tid_ & 127, g = lane >> 2, q = lane & 3;           \
    const int j = CTA_J(bid_), rb = CTA_RB(bid_), grp = 2 * rb + w;                    \
    const int st0 = wp * 64 + g;                         \
    Group* const G = ws + grp;                                                         \
    const uint32_t dsb = (sb & 0x3FFFF) >> 4;                                          \
    (void)t; (void)g; (void)q; (void)grp; (void)j; (void)st0; (void)dsb; (void)G
    Cons c;
    c.sb = sb; c.sB = 0; c.mB = 0; c.mX = 0; c.elect = (threadIdx.x & 127) == 0;
    asm volatile("mapa.shared::cluster.u32 %0, %1, %2;" : "=r"(c.rem) : "r"(sb), "r"(rank ^ 1));
    float v[36], a1[96], a2[12];
    float2 sum, rs;
    uint32_t res[18], xtag;
    auto qkv_mma = [&](bool acc, uint32_t bb, const uint4& f0, const uint4& f1) {
      wg_fence();
      wgmma_ra<192>(a1, f0, desc_hi(2048, 1024, 1) + bb, acc);
      wgmma_ra<24>(a2, f0, desc_hi(128, 256, 0) + (bb + 384), acc);
      wgmma_ra<192>(a1, f1, desc_hi(2048, 1024, 1) + (bb + 512), true);
      wgmma_ra<24>(a2, f1, desc_hi(128, 256, 0) + (bb + 896), true);
      wg_commit();
    };
    {
      THREAD_IDS();
      if (OPEN) {
        if (q == 0) { st_relaxed2(G->sum + st0 + 8 * j, 0, 0); st_relaxed2(G->sq + st0 + 8 * j, 0, 0); }
        if (wp == 3) {
#pragma unroll
          for (int i = 0; i < 5; i++) st_relaxed4(G->halo + j * 160 + lane + i * 32, 0, 0, 0, 0);
        }
        if (lane >= OPENL) st_relaxed4(G->obox + (8 * WPROBE + j) * 128 + t, 0, 0, 0, 0);
      }
      xtag = __shfl_sync(0xffffffffu, ~ld_relaxed(G->flag + 32 + 32 * j) & 1, 0);
      if (OPEN && EARLY && lane >= OPENL) st_relaxed4(G->xbox + (2 * j + 1) * 128 + t, xtag ^ 1, 0, 0, 0);
      asm volatile("barrier.cluster.wait.aligned;" ::: "memory");
      PROF(0);
#pragma unroll
      for (int i = 0; i < 96; i++) asm volatile("mov.b32 %0, 0;" : "=f"(a1[i]));
#pragma unroll
      for (int i = 0; i < 12; i++) asm volatile("mov.b32 %0, 0;" : "=f"(a2[i]));
      PROF(1);
      rs = ln_gemm_in(c, G, res, sum, w, st0, j, t, [&](int i) { PROF(2 + i); if (i) PROF(4); }, qkv_mma);
    }
#pragma unroll 1
    for (int layer = 0;; layer++) {
      const uint32_t tag = layer ^ 1;
      const int pb = 1 + layer * 30;
      uint4 own[5];
      {
        THREAD_IDS();
        PROF(pb + 4);
        uint32_t kv[3][18];
        auto cvt = [&](int b, float r) {
#pragma unroll
          for (int cc = 0; cc < 18; cc++) {
            const float* a = (cc == 8 ? a2 + 4 : cc == 17 ? a2 + 8 : cc < 8 ? a1 + 32 + 4 * cc : a1 + 28 + 4 * cc) + 2 * (b - 1);
            const uint32_t u = pack_bf16(a[0] * r, a[1] * r);
            kv[b][cc] = cc < 9 ? u : movm(u);
          }
        };
        cvt(2, rs.y);
#pragma unroll
        for (int i = 0; i < 18; i += 4) kv[2][i] = tagged(kv[2][i], tag);
        const uint32_t msg = sb + (w ? xslot(3) : xslot(0) + 24576) + wp * 2304 + lane * 16;
        if (wp == 3) {
          uint4* hp = G->halo + j * 160 + lane;
#pragma unroll
          for (int i = 0; i < 4; i++) st_relaxed4(hp + i * 32, kv[2][4 * i], kv[2][4 * i + 1], kv[2][4 * i + 2], kv[2][4 * i + 3]);
          st_relaxed2((uint2*)(hp + 128), kv[2][16], kv[2][17]);
        } else {
#pragma unroll
          for (int i = 0; i < 4; i++) sts128(msg + i * 512, kv[2][4 * i], kv[2][4 * i + 1], kv[2][4 * i + 2], kv[2][4 * i + 3]);
          sts64f(msg + 2048 - lane * 8, __uint_as_float(kv[2][16]), __uint_as_float(kv[2][17]));
        }
        cvt(1, rs.x);
        uint32_t Q[4][6];
#pragma unroll
        for (int h = 0; h < 4; h++)
#pragma unroll
          for (int i = 0; i < 6; i++) {
            const float* a = 4 * h + i < 16 ? a1 + 8 * h + 2 * i : a2 + 8 * h + 2 * i - 32;
            const uint32_t u = pack_bf16(a[0], a[1]);
            Q[h][i] = i < 2 ? (q >= h ? u : 0) : i < 4 ? u : (q <= h ? u : 0);
          }
        const bool lo0 = 2 * q > g, lo1 = 2 * q + 1 > g;
        const uint32_t M = (lo0 ? 0xffffu : 0u) | (lo1 ? 0xffff0000u : 0u);
        auto scores = [&](int h, int b, float (&s)[4]) {
          mma16816z(s, Q[h][0], Q[h][1], Q[h][2], Q[h][3], kv[b][2 * h], kv[b][2 * h + 1]);
          mma1688(s, Q[h][4], Q[h][5], kv[b][2 * h + 2]);
        };
        auto softmax = [&](float (&l)[4][2], float r, uint32_t (&P)[4]) {
          const float sl = r * (0.23570226039551584f * 1.4426950408889634f);
          float m[4];
#pragma unroll
          for (int h = 0; h < 4; h++) { m[h] = fmaxf(l[h][0], l[h][1]); m[h] = fmaxf(m[h], __shfl_xor_sync(0xffffffffu, m[h], 1)); }
#pragma unroll
          for (int h = 0; h < 4; h++) m[h] = fmaxf(m[h], __shfl_xor_sync(0xffffffffu, m[h], 2)) * sl;
#pragma unroll
          for (int h = 0; h < 4; h++) P[h] = pack_bf16(ex2(fmaf(l[h][0], sl, -m[h])), ex2(fmaf(l[h][1], sl, -m[h])));
        };
        const bool remote = wp == 0 && rb > 0;
        const uint4* hp = (G - 2)->halo + j * 160 + lane;
        auto halo = [&] {
#pragma unroll
          for (int i = 0; i < 4; i++) { const uint4 u = ld_relaxed4(hp + i * 32); kv[0][4 * i] = u.x; kv[0][4 * i + 1] = u.y; kv[0][4 * i + 2] = u.z; kv[0][4 * i + 3] = u.w; }
          const uint2 u = ld_relaxed2((const uint2*)(hp + 128));
          kv[0][16] = u.x; kv[0][17] = u.y;
        };
#pragma unroll
        for (int i = 0; i < 18; i++) kv[0][i] = 0;
        float l0[4][2], l1[4][2];
#pragma unroll
        for (int h = 0; h < 4; h++) {
          float s1[4], s2[4];
          scores(h, 1, s1); scores(h, 2, s2);
          l0[h][0] = s1[0]; l0[h][1] = s1[1];
          l1[h][0] = lo0 ? s1[2] : s2[2]; l1[h][1] = lo1 ? s1[3] : s2[3];
        }
        hp += __float_as_uint(l1[HALOH][0]) & late(sb + BAR_FULLX + 64, 0);
        if (remote) halo();
        uint32_t P0[4], P1[4];
        softmax(l1, rs.y, P1);
        if (remote) {
          while (__any_sync(0xffffffffu, chk(chk2(kv[0][0], kv[0][4], tag) | chk2(kv[0][8], kv[0][12], tag), kv[0][16], tag) & 1)) halo();
        }
        if (FG < 0) c.progress(32 * layer + 20);
        wg_bar(w);
        if (wp > 0) {
          const uint32_t from = msg - 2304;
#pragma unroll
          for (int i = 0; i < 4; i++) { const uint4 u = lds128(from + i * 512); kv[0][4 * i] = u.x; kv[0][4 * i + 1] = u.y; kv[0][4 * i + 2] = u.z; kv[0][4 * i + 3] = u.w; }
          const float2 u = lds64(from + 2048 - lane * 8);
          kv[0][16] = __float_as_uint(u.x); kv[0][17] = __float_as_uint(u.y);
        }
        PROF(pb + 5);
        const bool first = (rb == 0 && wp == 0);
#pragma unroll
        for (int h = 0; h < 4; h++) {
          float s0[4];
          scores(h, 0, s0);
          if (first) s0[0] = s0[1] = -INFINITY;
          l0[h][0] = lo0 ? s0[0] : l0[h][0]; l0[h][1] = lo1 ? s0[1] : l0[h][1];
        }
        softmax(l0, rs.x, P0);
        uint4* ob = G->obox + t;
        uint32_t car0 = 0, car1 = 0;
#pragma unroll
        for (int h = 0; h < 4; h++) {
          float o[3][4], z[4] = {0.f, 0.f, 0.f, 0.f};
          mma1688(z, P0[h], P1[h], 0x3f803f80u);
#pragma unroll
          for (int i = 0; i < 3; i++) {
            mma16816z(o[i], P0[h] & ~M, P1[h] & M, 0u, P1[h] & ~M, kv[1][9 + 2 * h + i], kv[2][9 + 2 * h + i]);
            mma1688(o[i], P0[h] & M, 0u, kv[0][9 + 2 * h + i]);
          }
          const float i0 = rcp(z[0]), i1 = rcp(z[2]);
#pragma unroll
          for (int i = 0; i < 3; i++) { o[i][0] *= i0; o[i][1] *= i0; o[i][2] *= i1; o[i][3] *= i1; }
          const uint32_t o0 = q < h ? car0 : pack_bf16(o[0][0], o[0][1]), o1 = q < h ? car1 : pack_bf16(o[0][2], o[0][3]);
          own[h] = make_uint4(o0 | 1, o1, pack_bf16(o[1][0], o[1][1]), pack_bf16(o[1][2], o[1][3]));
          if (h < OFIRST) st_relaxed4(ob + (8 * h + j) * 128, own[h].x, own[h].y, own[h].z, own[h].w);
          car0 = pack_bf16(o[2][0], o[2][1]); car1 = pack_bf16(o[2][2], o[2][3]);
        }
        car0 = tagged(car0, tag);
        own[4] = make_uint4(car0, car1, 0, 0);
        PROF(pb + 6);
      }
      uint2 sa, sc;
      {
        THREAD_IDS();
        uint4* src = G->obox + t;
        asm volatile("" : "+l"(src));
        uint4 x[32];
        const uint4* from[7];
#pragma unroll
        for (int r = 0; r < 7; r++) { from[r] = src + (r >= j ? 128 : 0); asm volatile("" : "+l"(from[r])); }
        auto at = [&](int i) { return i < 28 ? from[i % 7] + (8 * (i / 7) + i % 7) * 128 : src + (i + 4) * 128; };
        auto load = [&](int i) { x[i] = ld_relaxed4(at(i)); };
        const uint32_t* probe = &(G->obox + (8 * WPROBE + (lane & 7)) * 128 + (t | 31))->x;
        uint32_t pv = ld_relaxed(probe);
#pragma unroll
        for (int i = 3; i < 8; i++) mbar_wait_c(sb + BAR_FULLX + 8 * i, (c.mX >> i) & 1);
        c.mX ^= 0xf8;
        while (__any_sync(0xffffffffu, ~pv & 1)) pv = ld_relaxed(probe);
        if (layer) PROF(24); else PROF(25);
        if (WOBAR && w == 1) asm volatile("bar.sync 7, 256;" ::: "memory");
#pragma unroll
        for (int i = 0; i < WB1; i++) load(i);
        if (WOBAR && w == 0) asm volatile("bar.arrive 7, 256;" ::: "memory");
#pragma unroll
        for (int h = OFIRST; h < 4; h++) st_relaxed4(src + (8 * h + j) * 128, own[h].x, own[h].y, own[h].z, own[h].w);
        st_relaxed2((uint2*)(src + (32 + (j >> 1)) * 128) + (j & 1), own[4].x, own[4].y);
        if (layer) PROF(26); else PROF(27);
        float a[36];
        constexpr uint32_t NEXT = 576 - (575u << 16);
        auto step = [&](const uint4& f, uint32_t s, int i, uint32_t more, bool acc) {
          const uint32_t r = (xslot(4) >> 4) + (i < 4 ? 72 * s + 16 * i : 144 * s + 64) * 8, c = (SM_WOC >> 4) + (i < 4 ? 64 + 128 * i : 0) + s;
          wgmma_ra<72>(a, f, desc_hi(0, i < 4 ? 1024 : 9216, 1) + (dsb + more + (r + ((c - r) << 16))), acc);
        };
        if (OWNBAR) asm volatile("bar.sync 4, 256;" ::: "memory");
        float e[4];
        wg_fence();
        if (EARLY) {
#pragma unroll
          for (int i = 0; i < 5; i++) wgmma_ra<8>(e, own[i], desc_hi(128, 0, 0) + (dsb + (SM_WSUM >> 4) + 16 * i), i > 0);
          wg_commit();
        }
#pragma unroll
        for (int i = 0; i < 4; i++) step(own[i], 0, i, j * NEXT, i > 0);
        wg_commit();
        if (layer) PROF(28); else PROF(29);
        auto batch = [&](auto e0, auto e1, auto e2, int b) {
          constexpr int E0 = decltype(e0)::v, E1 = decltype(e1)::v, E2 = decltype(e2)::v;
          const uint32_t one = (LATE0 || E0 > 0) && E1 > E0 ? late(sb + BAR_FULLX + 64, 1) : 1;
          while (E1 > E0) {
            uint32_t bad = 0;
#pragma unroll
            for (int i = E0; i < E1; i++) bad = i < 28 ? chk(bad, x[i].x, one) : chk(chk(bad, x[i].x, tag), x[i].z, tag);
            if (!__any_sync(0xffffffffu, bad & 1)) break;
#pragma unroll
            for (int i = E0; i < E1; i++) load(i);
          }
          if (b == 0) PROF(pb + 7);
          if (b == FG) c.progress(32 * layer + 20);
          if (b > 0 && E2 > E1) wg_wait<WOW>();
#pragma unroll
          for (int i = E1; i < E2; i++) load(i);
          if (EARLY && b == 0) {
            wg_wait<1>();
            if (q == 0) st_relaxed2(G->sum + st0 + 8 * j, (__float_as_uint(e[0] + e[1]) & ~3u) | ((2 * layer + 2) & 3), __float_as_uint(e[2] + e[3]));
          }
          if (EARLY && b == SUMB) { sa = ld_relaxed2(G->sum + st0 + 16 * q); sc = ld_relaxed2(G->sum + st0 + 16 * q + 8); }
          if (E1 > E0) {
            wg_fence();
#pragma unroll
            for (int i = E0; i < E1; i++) {
              step(x[i], i % 7, i / 7, i < 28 && i % 7 >= j ? NEXT : 0, true);
            }
            wg_commit();
          }
        };
        batch(IC<0>(), IC<WB1>(), IC<WB2>(), 0);
        batch(IC<WB1>(), IC<WB2>(), IC<WB3>(), 1);
        batch(IC<WB2>(), IC<WB3>(), IC<32>(), 2);
        batch(IC<WB3>(), IC<32>(), IC<32>(), 3);
        wg_wait<0>();
        if (w == 0) asm volatile("bar.arrive 3, 256;" ::: "memory");
        PROF(pb + 8);
#pragma unroll
        for (int i = 0; i < 18; i++) {
          v[2 * i] = bf_lo(res[i]) + a[2 * i];
          v[2 * i + 1] = bf_hi(res[i]) + a[2 * i + 1];
        }
      }
      uint32_t lsb;
      uint32_t h[144];
      {
        THREAD_IDS();
        float a[128];
        const uint32_t xd = sb + xslot(4 * w) + (lane >> 4) * 1024 + (16 * wp + (lane & 15)) * 16;
        const float2 rs = ln_gemm<false>(c, G, v, res, sum, st0, j, t, layer, xtag,
          [&](int i) {
            if (i == 0) {
              lsb = ((res[0] & 1) | (res[4] & 1) << 1 | (res[8] & 1) << 2 | (res[12] & 1) << 3 | (res[16] & 1) << 4) ^ (xtag * 31);
              if (EARLY) {
                const uint32_t st = late(sb + BAR_FULLX + 64, (2 * layer + 2) & 3);
                while (__any_sync(0xffffffffu, chk2(sa.x, sc.x, st) & 3)) { sa = ld_relaxed2(G->sum + st0 + 16 * q); sc = ld_relaxed2(G->sum + st0 + 16 * q + 8); }
                sum.x += quad_sum(__uint_as_float(sa.x) + __uint_as_float(sc.x)); sum.y += quad_sum(__uint_as_float(sa.y) + __uint_as_float(sc.y));
              }
              if (w == 1) asm volatile("bar.sync 3, 256;" ::: "memory");
            }
            PROF(pb + 9 + i);
          },
          [&](int gi, uint32_t bb, const uint4& f0, const uint4& f1) {
            if (gi == 0) PROF(pb + 11);
            if (TLEAD0 && gi == 18 - TLEAD0 && w == 1) asm volatile("bar.sync 5, 256;" ::: "memory");
            wg_fence();
            wgmma_ra<256>(a, f0, desc_hi(4096, 1024, 1) + bb, gi > 0);
            wgmma_ra<256>(a, f1, desc_hi(4096, 1024, 1) + (bb + 128), true);
            wg_commit();
            if (TLEAD0 && gi == 17 && w == 0) asm volatile("bar.arrive 5, 256;" ::: "memory");
            stsm4(xd + gi * 4096, f0.x, f0.y, f0.z, f0.w);
            stsm4(xd + gi * 4096 + 2048, f1.x, f1.y, f1.z, f1.w);
            if (gi == 17) { fence_async_smem(); wg_bar(w); }
          });
        sts64f(sb + SM_KEEP + (tid_ >> 2) * 8, rs.x * rs.x, rs.y * rs.y);
        c.progress(32 * layer + 22);
        PROF2(pb + 12);
        glu<16, 0>(a, h);
        const Desc da0 = desc_hi(1024, 128, 0) + (dsb + (xslot(4 * w) >> 4));
        auto tile = [&](auto wide, auto last) {
          const uint32_t xe = BAR_EMPTYX + 32 * (t & 1) + 4 * (t & 6);
          auto group = [&](int gi) {
            uint32_t prev;
            const uint32_t bb = c.nextB(prev);
            const Desc da = da0 + gi * 256;
            wg_fence();
            if (wide()) {
              wgmma_ss<256>(a, da, desc_hi(4096, 1024, 1) + bb, gi);
              wgmma_ss<256>(a, da + 128, desc_hi(4096, 1024, 1) + (bb + 128), 1);
            } else {
              wgmma_ss<192>(*(float(*)[96])a, da, desc_hi(2048, 512, 2) + bb, gi);
              wgmma_ss<192>(*(float(*)[96])a, da + 128, desc_hi(2048, 512, 2) + (bb + 64), 1);
            }
            wg_commit();
            if (gi == 17 && w == 0) asm volatile("bar.arrive 5, 256;" ::: "memory");
            wg_wait<1>();
            if (gi > 0 && !(last() && gi > 13)) c.release2(BAR_EMPTYB + prev);
            if (last() && gi >= XREL && !((gi ^ XREL) & 1)) c.release2(BAR_EMPTYX + 16 * ((gi - XREL) & 2) + 2 * ((gi - XREL) & 12));
          };
          int gi = 0, end = w ? 18 - (wide() ? TLEAD2 : TLEAD) : 18;
#pragma unroll 1
          while (true) {
#pragma unroll 1
            for (; gi < end; gi++) group(gi);
            if (end == 18) break;
            asm volatile("bar.sync 5, 256;" ::: "memory");
            end = 18;
          }
          wg_wait<0>();
          if (!last()) c.releaseLastB();
          if (last() && t >= (19 - XREL) / 2 && t < 8) { mbar_arrive(sb + xe); mbar_arrive_remote(c.rem + xe); }
        };
        auto yes = [] { return true; };
        auto no = [] { return false; };
        tile(yes, no); PROF2(pb + 13); glu<16, 32>(a, h);
        tile(yes, no); PROF2(pb + 14); glu<16, 64>(a, h);
        tile(no, no); PROF2(pb + 15); glu<12, 96>(a, h);
        const uint32_t hole = sb + SM_B + 12288 + tid_ * 16;
#pragma unroll
        for (int i = 0; i < NSPILL; i++) sts128(hole + i * BSLOT, h[96 + 4 * i], h[97 + 4 * i], h[98 + 4 * i], h[99 + 4 * i]);
        if (w == 1) asm volatile("bar.arrive 8, 256;" ::: "memory");
        tile(no, yes); PROF2(pb + 16); glu<12, 120>(a, h);
#pragma unroll
        for (int i = 0; i < NSPILL; i++) { const uint4 u = lds128(hole + i * BSLOT); h[96 + 4 * i] = u.x; h[97 + 4 * i] = u.y; h[98 + 4 * i] = u.z; h[99 + 4 * i] = u.w; }
      }
      {
        THREAD_IDS();
        float d[32];
        uint4* gt = G->obox + t;
        asm volatile("" : "+l"(gt));
        uint4* const ib = gt + 2 * 4608 + layer * 8 * INBOX;
        auto pass = [&](uint32_t s0, bool last, auto&& hook) {
          const Desc db = desc_hi(0, 1024, 1) + (dsb + s0 * (XSLOT >> 4));
          mbar_wait_c(sb + BAR_FULLX + 8 * s0, (c.mX >> s0) & 1);
          if (RHOOK < 0) hook();
          asm volatile("bar.sync %0, 256;" ::"r"(8 + w) : "memory");
#pragma unroll
          for (int i = 0; i < 4; i++) {
            const int si = 4 * (i & 1) + (i >> 1);
            if (i > 0) mbar_wait_c(sb + BAR_FULLX + 8 * (s0 + si), (c.mX >> (s0 + si)) & 1);
            wg_fence();
#pragma unroll
            for (int k = 0; k < 9; k++) {
              const uint32_t* hk = h + 36 * i + 4 * k;
              wgmma_ra<64>(d, make_uint4(hk[0], hk[1], hk[2], hk[3]), db + ((xslot(si) >> 4) + k * 128), last || i + k > 0);
              if (9 * i + k == PPK && !(last && w == 1)) asm volatile("bar.arrive %0, 256;" ::"r"(9 - w) : "memory");
            }
            wg_commit();
            if (i > 0) { wg_wait<1>(); c.release2(BAR_EMPTYX + 8 * (s0 + 4 * ((i - 1) & 1) + ((i - 1) >> 1))); }
            if (i == RHOOK) hook();
          }
          c.mX ^= 0x33u << s0;
        };
        PROF2(pb + 17);
#pragma unroll 1
        for (int p = 0; p < 8; p++) {
          const uint32_t s0 = 2 * (p & 1);
          pass(s0, false, [] {});
          wg_wait<0>();
          c.release2(BAR_EMPTYX + 8 * (s0 + 5));
          if (p == 6 && layer == NLAYERS - 1) c.elect = false;
          uint32_t pk[16];
#pragma unroll
          for (int i = 0; i < 16; i++) pk[i] = pack_bf16(d[2 * i], d[2 * i + 1]);
          if (p >= BREL && p < BREL + 5 && layer < NLAYERS - 1) {
            const uint32_t o = c.sB + 8 * (p - BREL);
            c.release2(BAR_EMPTYB + (o < 40 ? o : o - 40));
          }
          uint4* const dst = ib + ((j + p) & 7) * INBOX;
          if (p == 0) {
            mbar_wait_c(sb + BAR_CLR + 8 * w, 0);
#pragma unroll
            for (int k = 0; k < 8; k++) red2((uint2*)(ib + k * INBOX + 512) - t, pk[2 * k], pk[2 * k + 1]);
          } else if (p < 7) {
#pragma unroll
            for (int k = 0; k < 4; k++) red4(dst + k * 128, pk[4 * k], pk[4 * k + 1], pk[4 * k + 2], pk[4 * k + 3]);
            if (p == 6) { __syncwarp(); if (lane == 0) mbar_arrive(sb + BAR_REDDONE + 8 * w); }
          } else {
#pragma unroll
            for (int k = 0; k < 4; k++) st_relaxed4(gt + ((j + 7) & 7) * 128 + k * 1024, pk[4 * k] & ~1u, pk[4 * k + 1], pk[4 * k + 2], pk[4 * k + 3]);
          }
        }
        PROF2(pb + 18);
        const uint4 *in = ib + j * INBOX, *pin = gt + j * 128;
        const uint2* in9 = (const uint2*)(in + 512) - t;
        asm volatile("" : "+l"(in), "+l"(pin), "+l"(in9));
        const float2 r2 = lds64(sb + SM_KEEP + (tid_ >> 2) * 8);
        uint2 X9;
        {
          uint4 X[4];
          const uint4* box = gt + 4608;
#pragma unroll
          for (int k = 0; k < 4; k++) X[k] = ld_relaxed4(box + 256 * j + ((k & 1) + 8 * (k & 2)) * 128);
          X9 = ld_relaxed2((const uint2*)(box + (32 + (j >> 1)) * 128) + (j & 1));
          const float i0 = rcp(r2.x), i1 = rcp(r2.y);
#pragma unroll
          for (int k = 0; k < 4; k++) {
            float* e = d + 8 * k;
            X[k].x ^= (lsb >> k) & 1;
            e[0] = bf_lo(X[k].x) * i0; e[1] = bf_hi(X[k].x) * i0; e[2] = bf_lo(X[k].y) * i1; e[3] = bf_hi(X[k].y) * i1;
            e[4] = bf_lo(X[k].z) * i0; e[5] = bf_hi(X[k].z) * i0; e[6] = bf_lo(X[k].w) * i1; e[7] = bf_hi(X[k].w) * i1;
          }
        }
        uint4 R[4], P[4];
        uint2 R9;
        PROF2(pb + 19);
        pass(0, true, [&] {
          mbar_wait_c(sb + BAR_RREADY + 8 * w, layer);
#pragma unroll
          for (int k = 0; k < 4; k++) R[k] = ld_relaxed4(in + k * 128);
          R9 = ld_relaxed2(in9);
#pragma unroll
          for (int k = 0; k < 4; k++) P[k] = ld_relaxed4(pin + k * 1024);
        });
        const uint32_t zero = late(sb + BAR_FULLX + 64, 0);
        while (__any_sync(0xffffffffu, (chk2(P[0].x, P[1].x, zero) | chk2(P[2].x, P[3].x, zero)) & 1)) {
#pragma unroll
          for (int k = 0; k < 4; k++) P[k] = ld_relaxed4(pin + k * 1024);
        }
#pragma unroll
        for (int k = 0; k < 4; k++) {
          const uint32_t u[4] = {hadd2(R[k].x, P[k].x), hadd2(R[k].y, P[k].y), hadd2(R[k].z, P[k].z), hadd2(R[k].w, P[k].w)};
#pragma unroll
          for (int i = 0; i < 4; i++) { v[8 * k + 2 * i] = bf_lo(u[i]); v[8 * k + 2 * i + 1] = bf_hi(u[i]); }
        }
        X9.x = chk(zero, X9.x, lsb >> 4);
        v[32] = fmaf(bf_lo(R9.x), r2.x, bf_lo(X9.x)); v[33] = fmaf(bf_hi(R9.x), r2.x, bf_hi(X9.x));
        v[34] = fmaf(bf_lo(R9.y), r2.y, bf_lo(X9.y)); v[35] = fmaf(bf_hi(R9.y), r2.y, bf_hi(X9.y));
        PROF2(pb + 20);
        wg_wait<0>();
        c.release2(BAR_EMPTYX + 40);
        PROF2(pb + 21);
#pragma unroll
        for (int i = 0; i < 32; i++) v[i] = (v[i] + d[i]) * (i & 2 ? r2.y : r2.x);
      }
      if (layer == NLAYERS - 1) break;
      {
        THREAD_IDS();
        PROF(31);
        rs = ln_gemm<true>(c, G, v, res, sum, st0, j, t, 1, xtag ^ 1, [&](int i) { PROF(32 + i); if (i) PROF(34); }, qkv_mma);
      }
    }
    {
      THREAD_IDS();
      const uint32_t stg = sb + SM_B + warp * 4096;
      const uint32_t sd = stg + (lane & 15) * 128;
#pragma unroll
      for (int i = 0; i < 4; i++)
        stsm4(sd + (((2 * i + (lane >> 4)) ^ (lane & 7)) << 4), pack_bf16(v[8 * i], v[8 * i + 1]), pack_bf16(v[8 * i + 2], v[8 * i + 3]),
              pack_bf16(v[8 * i + 4], v[8 * i + 5]), pack_bf16(v[8 * i + 6], v[8 * i + 7]));
      stsm2(stg + 2048 + (lane & 15) * 16, pack_bf16(v[32], v[33]), pack_bf16(v[34], v[35]));
      __syncwarp();
      char* o = out + (128 * rb + 32 * wp + w) * 1152;
#pragma unroll
      for (int i = 0; i < 4; i++) {
        const int r = 4 * i + (lane >> 3);
        *(uint4*)(o + r * 2304 + 128 * j + 16 * (lane & 7)) = lds128(stg + r * 128 + (((lane ^ r) & 7) << 4));
      }
      if (lane < 16) *(uint4*)(o + lane * 2304 + 1024 + 16 * j) = lds128(stg + 2048 + lane * 16);
      if (lane == 0) {
        if (wp == 0) st_relaxed(G->flag + 32 + 32 * j, xtag);
        mbar_arrive(sb + BAR_DONE + 8 * w);
      }
      PROF(61);
    }
  }
}

typedef CUresult (*EncFn)(CUtensorMap*, CUtensorMapDataType, cuuint32_t, void*, const cuuint64_t*, const cuuint64_t*, const cuuint32_t*,
                          const cuuint32_t*, CUtensorMapInterleave, CUtensorMapSwizzle, CUtensorMapL2promotion, CUtensorMapFloatOOBfill);

void make_map(EncFn enc, CUtensorMap* m, const void* p, int rank, uint64_t d0, uint64_t d1, uint64_t d2, uint64_t s1, uint64_t s2, uint32_t b0,
              uint32_t b1, uint32_t b2, CUtensorMapSwizzle sw) {
  cuuint64_t gd[3] = {d0, d1, d2};
  cuuint64_t gs[2] = {s1, s2};
  cuuint32_t bd[3] = {b0, b1, b2};
  cuuint32_t es[3] = {1, 1, 1};
  enc(m, CU_TENSOR_MAP_DATA_TYPE_BFLOAT16, rank, const_cast<void*>(p), gd, gs, bd, es, CU_TENSOR_MAP_INTERLEAVE_NONE, sw,
      CU_TENSOR_MAP_L2_PROMOTION_L2_128B, CU_TENSOR_MAP_FLOAT_OOB_FILL_NONE);
}

}

extern "C" void kernel_launch(void* const* d_in, const int* in_sizes, int n_in, void* d_out, int out_size) {
  const __nv_bfloat16* x = (const __nv_bfloat16*)d_in[0];
  const char *wqkv = (const char*)d_in[1], *wo = (const char*)d_in[2], *wg = (const char*)d_in[4], *wu = (const char*)d_in[5], *wd = (const char*)d_in[6];
  static EncFn enc = nullptr;
  static uint32_t first = 0;
  static Group* ws = nullptr;
  if (!enc) {
    cudaDriverEntryPointQueryResult qr;
    cudaGetDriverEntryPoint("cuTensorMapEncodeTiled", (void**)&enc, cudaEnableDefault, &qr);
    cudaGetSymbolAddress((void**)&ws, g_ws);
    cudaFuncSetAttribute(fused_kernel, cudaFuncAttributeMaxDynamicSharedMemorySize, SMEM_BYTES);
    cudaLaunchConfig_t cfg = {};
    cfg.gridDim = NCTA + 4; cfg.blockDim = 384; cfg.dynamicSmemBytes = SMEM_BYTES;
    int clusters = 0;
    if (XFIRST || cudaOccupancyMaxActiveClusters(&clusters, fused_kernel, &cfg) != cudaSuccess || 2 * clusters < NCTA + 4) first = 4;
    cudaGetLastError();
  }
  const CUtensorMapSwizzle S0 = CU_TENSOR_MAP_SWIZZLE_NONE, S64 = CU_TENSOR_MAP_SWIZZLE_64B, S128 = CU_TENSOR_MAP_SWIZZLE_128B;
  Maps m;
  make_map(enc, &m.x, x, 3, 576, 2, 1024, 1152, 2304, 64, 1, 64, S128);
  make_map(enc, &m.qm, wqkv, 3, 576, 576, 3, 3456, 1152, 64, 16, 3, S128);
  make_map(enc, &m.qc, wqkv, 3, 576, 576, 3, 3456, 1152, 8, 16, 3, S0);
  make_map(enc, &m.o, wo, 2, 576, 576, 1, 1152, 0, 64, 72, 1, S128);
  make_map(enc, &m.g, wg, 3, 64, 576, 72, 9216, 128, 64, 32, 2, S128);
  make_map(enc, &m.u, wu, 3, 64, 576, 72, 9216, 128, 64, 32, 2, S128);
  make_map(enc, &m.g3, wg, 3, 32, 576, 144, 9216, 64, 32, 32, 3, S64);
  make_map(enc, &m.u3, wu, 3, 32, 576, 144, 9216, 64, 32, 32, 3, S64);
  make_map(enc, &m.d, wd, 2, 576, 4608, 1, 1152, 0, 64, 72, 1, S128);
  fused_kernel<<<NCTA + 4, 384, SMEM_BYTES>>>(x, ws, wqkv, wo, (char*)d_out, first, m, wg, wu, wd);
}
```

```cpp
#include <cuda_runtime.h>
#include <cuda_bf16.h>
#include <cuda.h>
#include <stdint.h>
#include <stddef.h>

namespace {

constexpr int D_ = 576;
constexpr int NCTA = 128;
#define NLAYERS 2
#define W_POLICY policy_evict_first
#define A_POLICY policy_evict_normal
#define OPEN 1
#define PFMODE 5
#define WB1 11
#define WB2 21
#define WB3 32
#define WPROBE 1
#define WOBAR 1
#define QD 0
#define PFQ 1
#define PFSLEEP 700
#define GPCMAP 1
#define PFF 1
#define CLRSLEEP 300
#define OPENL 24
#define FG 1
#define HMUL 1
#define FCH 1
#define PPK 35
#define RHOOK -1
#define XH 3
#define XP 0
#define GSLEEP 32
#define XCH 1
#define MAPPF 1
#define XREL 8
#define WOG 13
#define BREL 1
#define FENCE1 0
#define OWNBAR 0
#define EARLY 1
#define ESPEC 0
#define WOW 1
#define STATP -1
#define QPACE 23
#define RDELAY 1000
#define XFIRST 0
#define TLEAD 2
#define TLEAD2 2
#define TLEAD0 2
#define OFIRST 3
#define FN 3
#define LATE0 1
#define SUMB 2
#define XPM 3
#define HALOH 0
#define KEEPW 25
#define NSPILL 4
#define REGS_C 232
#define REGS_P 40
#define STR2(x) #x
#define STR(x) STR2(x)
constexpr uint32_t SM_X = 0;
constexpr uint32_t XSLOT = 18432;
__host__ __device__ constexpr uint32_t xslot(uint32_t s) { return SM_X + (s ^ 4) * XSLOT; }
constexpr uint32_t SM_WOC = xslot(3) + 8192;
constexpr uint32_t SM_B = 147456;
constexpr uint32_t BSLOT = 16384;
constexpr uint32_t SM_KEEP = 229376;
constexpr uint32_t SM_WSUM = SM_KEEP + 512;
constexpr uint32_t SM_BAR = SM_KEEP + 2048;
constexpr uint32_t BAR_FULLB = SM_BAR;
constexpr uint32_t BAR_RREADY = SM_BAR + 40;
constexpr uint32_t BAR_CLR = SM_BAR + 56;
constexpr uint32_t BAR_FULLX = SM_BAR + 72;
constexpr uint32_t BAR_EMPTYB = SM_BAR + 144;
constexpr uint32_t BAR_EMPTYX = SM_BAR + 184;
constexpr uint32_t BAR_REDDONE = SM_BAR + 248;
constexpr uint32_t BAR_DONE = SM_BAR + 264;
constexpr uint32_t SM_PROG = SM_BAR + 288;
constexpr uint32_t SMEM_BYTES = SM_BAR + 1024;

struct Maps { CUtensorMap x, qm, qc, o, g, u, g3, u3, d; };

constexpr int INBOX = 576;
struct Group {
  uint2 sum[4 * 8 * 8];
  uint2 sq[4 * 8 * 8];
  uint32_t pad[512];
  uint32_t flag[512];
  uint4 halo[8 * 160];
  uint4 obox[36 * 128];
  uint4 xbox[36 * 128];
  uint4 inbox[2][8 * INBOX];
};
struct Scratch { Group g[32]; uint4 wq[8][36][432]; uint4 woc[8][720]; uint32_t done[64]; };
__device__ __align__(1024) Scratch g_ws;
#define PROF(i)
#define PROFX(i)

#define PROF2(i) PROF(i)

struct Desc { uint32_t lo, hi; };
__device__ __forceinline__ constexpr Desc desc_hi(uint32_t lbo, uint32_t sbo, uint32_t sw) { return Desc{(lbo >> 4) << 16, (sbo >> 4) | sw << 30}; }
__device__ __forceinline__ constexpr Desc operator+(Desc d, uint32_t a) { return Desc{d.lo + a, d.hi}; }

template<int N> __device__ __forceinline__ void wgmma_ss(float (&d)[N / 2], Desc da, Desc db, int sc);
template<> __device__ __forceinline__ void wgmma_ss<192>(float (&d)[96], Desc da, Desc db, int sc) {
  asm volatile("{\n.reg .pred p;\n.reg .b64 a, b;\nsetp.ne.b32 p, %100, 0;\nmov.b64 a, {%96, %97};\nmov.b64 b, {%98, %99};\n"
    "wgmma.mma_async.sync.aligned.m64n192k16.f32.bf16.bf16 {%0,%1,%2,%3,%4,%5,%6,%7,%8,%9,%10,%11,%12,%13,%14,%15,%16,%17,%18,%19,%20,%21,%22,%23,%24,%25,%26,%27,%28,%29,%30,%31,%32,%33,%34,%35,%36,%37,%38,%39,%40,%41,%42,%43,%44,%45,%46,%47,%48,%49,%50,%51,%52,%53,%54,%55,%56,%57,%58,%59,%60,%61,%62,%63,%64,%65,%66,%67,%68,%69,%70,%71,%72,%73,%74,%75,%76,%77,%78,%79,%80,%81,%82,%83,%84,%85,%86,%87,%88,%89,%90,%91,%92,%93,%94,%95}, a, b, p, 1, 1, 0, 1;\n}\n"
    : "+f"(d[0]),"+f"(d[1]),"+f"(d[2]),"+f"(d[3]),"+f"(d[4]),"+f"(d[5]),"+f"(d[6]),"+f"(d[7]),"+f"(d[8]),"+f"(d[9]),"+f"(d[10]),"+f"(d[11]),"+f"(d[12]),"+f"(d[13]),"+f"(d[14]),"+f"(d[15]),"+f"(d[16]),"+f"(d[17]),"+f"(d[18]),"+f"(d[19]),"+f"(d[20]),"+f"(d[21]),"+f"(d[22]),"+f"(d[23]),"+f"(d[24]),"+f"(d[25]),"+f"(d[26]),"+f"(d[27]),"+f"(d[28]),"+f"(d[29]),"+f"(d[30]),"+f"(d[31]),"+f"(d[32]),"+f"(d[33]),"+f"(d[34]),"+f"(d[35]),"+f"(d[36]),"+f"(d[37]),"+f"(d[38]),"+f"(d[39]),"+f"(d[40]),"+f"(d[41]),"+f"(d[42]),"+f"(d[43]),"+f"(d[44]),"+f"(d[45]),"+f"(d[46]),"+f"(d[47]),"+f"(d[48]),"+f"(d[49]),"+f"(d[50]),"+f"(d[51]),"+f"(d[52]),"+f"(d[53]),"+f"(d[54]),"+f"(d[55]),"+f"(d[56]),"+f"(d[57]),"+f"(d[58]),"+f"(d[59]),"+f"(d[60]),"+f"(d[61]),"+f"(d[62]),"+f"(d[63]),"+f"(d[64]),"+f"(d[65]),"+f"(d[66]),"+f"(d[67]),"+f"(d[68]),"+f"(d[69]),"+f"(d[70]),"+f"(d[71]),"+f"(d[72]),"+f"(d[73]),"+f"(d[74]),"+f"(d[75]),"+f"(d[76]),"+f"(d[77]),"+f"(d[78]),"+f"(d[79]),"+f"(d[80]),"+f"(d[81]),"+f"(d[82]),"+f"(d[83]),"+f"(d[84]),"+f"(d[85]),"+f"(d[86]),"+f"(d[87]),"+f"(d[88]),"+f"(d[89]),"+f"(d[90]),"+f"(d[91]),"+f"(d[92]),"+f"(d[93]),"+f"(d[94]),"+f"(d[95]) : "r"(da.lo), "r"(da.hi), "r"(db.lo), "r"(db.hi), "r"(sc));
}
template<> __device__ __forceinline__ void wgmma_ss<256>(float (&d)[128], Desc da, Desc db, int sc) {
  asm volatile("{\n.reg .pred p;\n.reg .b64 a, b;\nsetp.ne.b32 p, %132, 0;\nmov.b64 a, {%128, %129};\nmov.b64 b, {%130, %131};\n"
    "wgmma.mma_async.sync.aligned.m64n256k16.f32.bf16.bf16 {%0,%1,%2,%3,%4,%5,%6,%7,%8,%9,%10,%11,%12,%13,%14,%15,%16,%17,%18,%19,%20,%21,%22,%23,%24,%25,%26,%27,%28,%29,%30,%31,%32,%33,%34,%35,%36,%37,%38,%39,%40,%41,%42,%43,%44,%45,%46,%47,%48,%49,%50,%51,%52,%53,%54,%55,%56,%57,%58,%59,%60,%61,%62,%63,%64,%65,%66,%67,%68,%69,%70,%71,%72,%73,%74,%75,%76,%77,%78,%79,%80,%81,%82,%83,%84,%85,%86,%87,%88,%89,%90,%91,%92,%93,%94,%95,%96,%97,%98,%99,%100,%101,%102,%103,%104,%105,%106,%107,%108,%109,%110,%111,%112,%113,%114,%115,%116,%117,%118,%119,%120,%121,%122,%123,%124,%125,%126,%127}, a, b, p, 1, 1, 0, 1;\n}\n"
    : "+f"(d[0]),"+f"(d[1]),"+f"(d[2]),"+f"(d[3]),"+f"(d[4]),"+f"(d[5]),"+f"(d[6]),"+f"(d[7]),"+f"(d[8]),"+f"(d[9]),"+f"(d[10]),"+f"(d[11]),"+f"(d[12]),"+f"(d[13]),"+f"(d[14]),"+f"(d[15]),"+f"(d[16]),"+f"(d[17]),"+f"(d[18]),"+f"(d[19]),"+f"(d[20]),"+f"(d[21]),"+f"(d[22]),"+f"(d[23]),"+f"(d[24]),"+f"(d[25]),"+f"(d[26]),"+f"(d[27]),"+f"(d[28]),"+f"(d[29]),"+f"(d[30]),"+f"(d[31]),"+f"(d[32]),"+f"(d[33]),"+f"(d[34]),"+f"(d[35]),"+f"(d[36]),"+f"(d[37]),"+f"(d[38]),"+f"(d[39]),"+f"(d[40]),"+f"(d[41]),"+f"(d[42]),"+f"(d[43]),"+f"(d[44]),"+f"(d[45]),"+f"(d[46]),"+f"(d[47]),"+f"(d[48]),"+f"(d[49]),"+f"(d[50]),"+f"(d[51]),"+f"(d[52]),"+f"(d[53]),"+f"(d[54]),"+f"(d[55]),"+f"(d[56]),"+f"(d[57]),"+f"(d[58]),"+f"(d[59]),"+f"(d[60]),"+f"(d[61]),"+f"(d[62]),"+f"(d[63]),"+f"(d[64]),"+f"(d[65]),"+f"(d[66]),"+f"(d[67]),"+f"(d[68]),"+f"(d[69]),"+f"(d[70]),"+f"(d[71]),"+f"(d[72]),"+f"(d[73]),"+f"(d[74]),"+f"(d[75]),"+f"(d[76]),"+f"(d[77]),"+f"(d[78]),"+f"(d[79]),"+f"(d[80]),"+f"(d[81]),"+f"(d[82]),"+f"(d[83]),"+f"(d[84]),"+f"(d[85]),"+f"(d[86]),"+f"(d[87]),"+f"(d[88]),"+f"(d[89]),"+f"(d[90]),"+f"(d[91]),"+f"(d[92]),"+f"(d[93]),"+f"(d[94]),"+f"(d[95]),"+f"(d[96]),"+f"(d[97]),"+f"(d[98]),"+f"(d[99]),"+f"(d[100]),"+f"(d[101]),"+f"(d[102]),"+f"(d[103]),"+f"(d[104]),"+f"(d[105]),"+f"(d[106]),"+f"(d[107]),"+f"(d[108]),"+f"(d[109]),"+f"(d[110]),"+f"(d[111]),"+f"(d[112]),"+f"(d[113]),"+f"(d[114]),"+f"(d[115]),"+f"(d[116]),"+f"(d[117]),"+f"(d[118]),"+f"(d[119]),"+f"(d[120]),"+f"(d[121]),"+f"(d[122]),"+f"(d[123]),"+f"(d[124]),"+f"(d[125]),"+f"(d[126]),"+f"(d[127]) : "r"(da.lo), "r"(da.hi), "r"(db.lo), "r"(db.hi), "r"(sc));
}
template<int N, int ACC> __device__ __forceinline__ void wgmma_rs(float (&d)[N / 2], const uint4& a, Desc db);
template<> __device__ __forceinline__ void wgmma_rs<8, 1>(float (&d)[4], const uint4& a, Desc db) {
  asm volatile("{\n.reg .pred p;\n.reg .b64 b;\nsetp.ne.b32 p, 1, 0;\nmov.b64 b, {%8, %9};\n"
    "wgmma.mma_async.sync.aligned.m64n8k16.f32.bf16.bf16 {%0,%1,%2,%3}, {%4,%5,%6,%7}, b, p, 1, 1, 1;\n}\n"
    : "+f"(d[0]),"+f"(d[1]),"+f"(d[2]),"+f"(d[3]) : "r"(a.x), "r"(a.y), "r"(a.z), "r"(a.w), "r"(db.lo), "r"(db.hi));
}
template<> __device__ __forceinline__ void wgmma_rs<8, 0>(float (&d)[4], const uint4& a, Desc db) {
  asm volatile("{\n.reg .pred p;\n.reg .b64 b;\nsetp.ne.b32 p, 0, 0;\nmov.b64 b, {%8, %9};\n"
    "wgmma.mma_async.sync.aligned.m64n8k16.f32.bf16.bf16 {%0,%1,%2,%3}, {%4,%5,%6,%7}, b, p, 1, 1, 1;\n}\n"
    : "=f"(d[0]),"=f"(d[1]),"=f"(d[2]),"=f"(d[3]) : "r"(a.x), "r"(a.y), "r"(a.z), "r"(a.w), "r"(db.lo), "r"(db.hi));
}
template<> __device__ __forceinline__ void wgmma_rs<24, 1>(float (&d)[12], const uint4& a, Desc db) {
  asm volatile("{\n.reg .pred p;\n.reg .b64 b;\nsetp.ne.b32 p, 1, 0;\nmov.b64 b, {%16, %17};\n"
    "wgmma.mma_async.sync.aligned.m64n24k16.f32.bf16.bf16 {%0,%1,%2,%3,%4,%5,%6,%7,%8,%9,%10,%11}, {%12,%13,%14,%15}, b, p, 1, 1, 1;\n}\n"
    : "+f"(d[0]),"+f"(d[1]),"+f"(d[2]),"+f"(d[3]),"+f"(d[4]),"+f"(d[5]),"+f"(d[6]),"+f"(d[7]),"+f"(d[8]),"+f"(d[9]),"+f"(d[10]),"+f"(d[11]) : "r"(a.x), "r"(a.y), "r"(a.z), "r"(a.w), "r"(db.lo), "r"(db.hi));
}
template<> __device__ __forceinline__ void wgmma_rs<24, 0>(float (&d)[12], const uint4& a, Desc db) {
  asm volatile("{\n.reg .pred p;\n.reg .b64 b;\nsetp.ne.b32 p, 0, 0;\nmov.b64 b, {%16, %17};\n"
    "wgmma.mma_async.sync.aligned.m64n24k16.f32.bf16.bf16 {%0,%1,%2,%3,%4,%5,%6,%7,%8,%9,%10,%11}, {%12,%13,%14,%15}, b, p, 1, 1, 1;\n}\n"
    : "=f"(d[0]),"=f"(d[1]),"=f"(d[2]),"=f"(d[3]),"=f"(d[4]),"=f"(d[5]),"=f"(d[6]),"=f"(d[7]),"=f"(d[8]),"=f"(d[9]),"=f"(d[10]),"=f"(d[11]) : "r"(a.x), "r"(a.y), "r"(a.z), "r"(a.w), "r"(db.lo), "r"(db.hi));
}
template<> __device__ __forceinline__ void wgmma_rs<64, 1>(float (&d)[32], const uint4& a, Desc db) {
  asm volatile("{\n.reg .pred p;\n.reg .b64 b;\nsetp.ne.b32 p, 1, 0;\nmov.b64 b, {%36, %37};\n"
    "wgmma.mma_async.sync.aligned.m64n64k16.f32.bf16.bf16 {%0,%1,%2,%3,%4,%5,%6,%7,%8,%9,%10,%11,%12,%13,%14,%15,%16,%17,%18,%19,%20,%21,%22,%23,%24,%25,%26,%27,%28,%29,%30,%31}, {%32,%33,%34,%35}, b, p, 1, 1, 1;\n}\n"
    : "+f"(d[0]),"+f"(d[1]),"+f"(d[2]),"+f"(d[3]),"+f"(d[4]),"+f"(d[5]),"+f"(d[6]),"+f"(d[7]),"+f"(d[8]),"+f"(d[9]),"+f"(d[10]),"+f"(d[11]),"+f"(d[12]),"+f"(d[13]),"+f"(d[14]),"+f"(d[15]),"+f"(d[16]),"+f"(d[17]),"+f"(d[18]),"+f"(d[19]),"+f"(d[20]),"+f"(d[21]),"+f"(d[22]),"+f"(d[23]),"+f"(d[24]),"+f"(d[25]),"+f"(d[26]),"+f"(d[27]),"+f"(d[28]),"+f"(d[29]),"+f"(d[30]),"+f"(d[31]) : "r"(a.x), "r"(a.y), "r"(a.z), "r"(a.w), "r"(db.lo), "r"(db.hi));
}
template<> __device__ __forceinline__ void wgmma_rs<64, 0>(float (&d)[32], const uint4& a, Desc db) {
  asm volatile("{\n.reg .pred p;\n.reg .b64 b;\nsetp.ne.b32 p, 0, 0;\nmov.b64 b, {%36, %37};\n"
    "wgmma.mma_async.sync.aligned.m64n64k16.f32.bf16.bf16 {%0,%1,%2,%3,%4,%5,%6,%7,%8,%9,%10,%11,%12,%13,%14,%15,%16,%17,%18,%19,%20,%21,%22,%23,%24,%25,%26,%27,%28,%29,%30,%31}, {%32,%33,%34,%35}, b, p, 1, 1, 1;\n}\n"
    : "=f"(d[0]),"=f"(d[1]),"=f"(d[2]),"=f"(d[3]),"=f"(d[4]),"=f"(d[5]),"=f"(d[6]),"=f"(d[7]),"=f"(d[8]),"=f"(d[9]),"=f"(d[10]),"=f"(d[11]),"=f"(d[12]),"=f"(d[13]),"=f"(d[14]),"=f"(d[15]),"=f"(d[16]),"=f"(d[17]),"=f"(d[18]),"=f"(d[19]),"=f"(d[20]),"=f"(d[21]),"=f"(d[22]),"=f"(d[23]),"=f"(d[24]),"=f"(d[25]),"=f"(d[26]),"=f"(d[27]),"=f"(d[28]),"=f"(d[29]),"=f"(d[30]),"=f"(d[31]) : "r"(a.x), "r"(a.y), "r"(a.z), "r"(a.w), "r"(db.lo), "r"(db.hi));
}
template<> __device__ __forceinline__ void wgmma_rs<72, 1>(float (&d)[36], const uint4& a, Desc db) {
  asm volatile("{\n.reg .pred p;\n.reg .b64 b;\nsetp.ne.b32 p, 1, 0;\nmov.b64 b, {%40, %41};\n"
    "wgmma.mma_async.sync.aligned.m64n72k16.f32.bf16.bf16 {%0,%1,%2,%3,%4,%5,%6,%7,%8,%9,%10,%11,%12,%13,%14,%15,%16,%17,%18,%19,%20,%21,%22,%23,%24,%25,%26,%27,%28,%29,%30,%31,%32,%33,%34,%35}, {%36,%37,%38,%39}, b, p, 1, 1, 1;\n}\n"
    : "+f"(d[0]),"+f"(d[1]),"+f"(d[2]),"+f"(d[3]),"+f"(d[4]),"+f"(d[5]),"+f"(d[6]),"+f"(d[7]),"+f"(d[8]),"+f"(d[9]),"+f"(d[10]),"+f"(d[11]),"+f"(d[12]),"+f"(d[13]),"+f"(d[14]),"+f"(d[15]),"+f"(d[16]),"+f"(d[17]),"+f"(d[18]),"+f"(d[19]),"+f"(d[20]),"+f"(d[21]),"+f"(d[22]),"+f"(d[23]),"+f"(d[24]),"+f"(d[25]),"+f"(d[26]),"+f"(d[27]),"+f"(d[28]),"+f"(d[29]),"+f"(d[30]),"+f"(d[31]),"+f"(d[32]),"+f"(d[33]),"+f"(d[34]),"+f"(d[35]) : "r"(a.x), "r"(a.y), "r"(a.z), "r"(a.w), "r"(db.lo), "r"(db.hi));
}
template<> __device__ __forceinline__ void wgmma_rs<72, 0>(float (&d)[36], const uint4& a, Desc db) {
  asm volatile("{\n.reg .pred p;\n.reg .b64 b;\nsetp.ne.b32 p, 0, 0;\nmov.b64 b, {%40, %41};\n"
    "wgmma.mma_async.sync.aligned.m64n72k16.f32.bf16.bf16 {%0,%1,%2,%3,%4,%5,%6,%7,%8,%9,%10,%11,%12,%13,%14,%15,%16,%17,%18,%19,%20,%21,%22,%23,%24,%25,%26,%27,%28,%29,%30,%31,%32,%33,%34,%35}, {%36,%37,%38,%39}, b, p, 1, 1, 1;\n}\n"
    : "=f"(d[0]),"=f"(d[1]),"=f"(d[2]),"=f"(d[3]),"=f"(d[4]),"=f"(d[5]),"=f"(d[6]),"=f"(d[7]),"=f"(d[8]),"=f"(d[9]),"=f"(d[10]),"=f"(d[11]),"=f"(d[12]),"=f"(d[13]),"=f"(d[14]),"=f"(d[15]),"=f"(d[16]),"=f"(d[17]),"=f"(d[18]),"=f"(d[19]),"=f"(d[20]),"=f"(d[21]),"=f"(d[22]),"=f"(d[23]),"=f"(d[24]),"=f"(d[25]),"=f"(d[26]),"=f"(d[27]),"=f"(d[28]),"=f"(d[29]),"=f"(d[30]),"=f"(d[31]),"=f"(d[32]),"=f"(d[33]),"=f"(d[34]),"=f"(d[35]) : "r"(a.x), "r"(a.y), "r"(a.z), "r"(a.w), "r"(db.lo), "r"(db.hi));
}
template<> __device__ __forceinline__ void wgmma_rs<192, 1>(float (&d)[96], const uint4& a, Desc db) {
  asm volatile("{\n.reg .pred p;\n.reg .b64 b;\nsetp.ne.b32 p, 1, 0;\nmov.b64 b, {%100, %101};\n"
    "wgmma.mma_async.sync.aligned.m64n192k16.f32.bf16.bf16 {%0,%1,%2,%3,%4,%5,%6,%7,%8,%9,%10,%11,%12,%13,%14,%15,%16,%17,%18,%19,%20,%21,%22,%23,%24,%25,%26,%27,%28,%29,%30,%31,%32,%33,%34,%35,%36,%37,%38,%39,%40,%41,%42,%43,%44,%45,%46,%47,%48,%49,%50,%51,%52,%53,%54,%55,%56,%57,%58,%59,%60,%61,%62,%63,%64,%65,%66,%67,%68,%69,%70,%71,%72,%73,%74,%75,%76,%77,%78,%79,%80,%81,%82,%83,%84,%85,%86,%87,%88,%89,%90,%91,%92,%93,%94,%95}, {%96,%97,%98,%99}, b, p, 1, 1, 1;\n}\n"
    : "+f"(d[0]),"+f"(d[1]),"+f"(d[2]),"+f"(d[3]),"+f"(d[4]),"+f"(d[5]),"+f"(d[6]),"+f"(d[7]),"+f"(d[8]),"+f"(d[9]),"+f"(d[10]),"+f"(d[11]),"+f"(d[12]),"+f"(d[13]),"+f"(d[14]),"+f"(d[15]),"+f"(d[16]),"+f"(d[17]),"+f"(d[18]),"+f"(d[19]),"+f"(d[20]),"+f"(d[21]),"+f"(d[22]),"+f"(d[23]),"+f"(d[24]),"+f"(d[25]),"+f"(d[26]),"+f"(d[27]),"+f"(d[28]),"+f"(d[29]),"+f"(d[30]),"+f"(d[31]),"+f"(d[32]),"+f"(d[33]),"+f"(d[34]),"+f"(d[35]),"+f"(d[36]),"+f"(d[37]),"+f"(d[38]),"+f"(d[39]),"+f"(d[40]),"+f"(d[41]),"+f"(d[42]),"+f"(d[43]),"+f"(d[44]),"+f"(d[45]),"+f"(d[46]),"+f"(d[47]),"+f"(d[48]),"+f"(d[49]),"+f"(d[50]),"+f"(d[51]),"+f"(d[52]),"+f"(d[53]),"+f"(d[54]),"+f"(d[55]),"+f"(d[56]),"+f"(d[57]),"+f"(d[58]),"+f"(d[59]),"+f"(d[60]),"+f"(d[61]),"+f"(d[62]),"+f"(d[63]),"+f"(d[64]),"+f"(d[65]),"+f"(d[66]),"+f"(d[67]),"+f"(d[68]),"+f"(d[69]),"+f"(d[70]),"+f"(d[71]),"+f"(d[72]),"+f"(d[73]),"+f"(d[74]),"+f"(d[75]),"+f"(d[76]),"+f"(d[77]),"+f"(d[78]),"+f"(d[79]),"+f"(d[80]),"+f"(d[81]),"+f"(d[82]),"+f"(d[83]),"+f"(d[84]),"+f"(d[85]),"+f"(d[86]),"+f"(d[87]),"+f"(d[88]),"+f"(d[89]),"+f"(d[90]),"+f"(d[91]),"+f"(d[92]),"+f"(d[93]),"+f"(d[94]),"+f"(d[95]) : "r"(a.x), "r"(a.y), "r"(a.z), "r"(a.w), "r"(db.lo), "r"(db.hi));
}
template<> __device__ __forceinline__ void wgmma_rs<192, 0>(float (&d)[96], const uint4& a, Desc db) {
  asm volatile("{\n.reg .pred p;\n.reg .b64 b;\nsetp.ne.b32 p, 0, 0;\nmov.b64 b, {%100, %101};\n"
    "wgmma.mma_async.sync.aligned.m64n192k16.f32.bf16.bf16 {%0,%1,%2,%3,%4,%5,%6,%7,%8,%9,%10,%11,%12,%13,%14,%15,%16,%17,%18,%19,%20,%21,%22,%23,%24,%25,%26,%27,%28,%29,%30,%31,%32,%33,%34,%35,%36,%37,%38,%39,%40,%41,%42,%43,%44,%45,%46,%47,%48,%49,%50,%51,%52,%53,%54,%55,%56,%57,%58,%59,%60,%61,%62,%63,%64,%65,%66,%67,%68,%69,%70,%71,%72,%73,%74,%75,%76,%77,%78,%79,%80,%81,%82,%83,%84,%85,%86,%87,%88,%89,%90,%91,%92,%93,%94,%95}, {%96,%97,%98,%99}, b, p, 1, 1, 1;\n}\n"
    : "=f"(d[0]),"=f"(d[1]),"=f"(d[2]),"=f"(d[3]),"=f"(d[4]),"=f"(d[5]),"=f"(d[6]),"=f"(d[7]),"=f"(d[8]),"=f"(d[9]),"=f"(d[10]),"=f"(d[11]),"=f"(d[12]),"=f"(d[13]),"=f"(d[14]),"=f"(d[15]),"=f"(d[16]),"=f"(d[17]),"=f"(d[18]),"=f"(d[19]),"=f"(d[20]),"=f"(d[21]),"=f"(d[22]),"=f"(d[23]),"=f"(d[24]),"=f"(d[25]),"=f"(d[26]),"=f"(d[27]),"=f"(d[28]),"=f"(d[29]),"=f"(d[30]),"=f"(d[31]),"=f"(d[32]),"=f"(d[33]),"=f"(d[34]),"=f"(d[35]),"=f"(d[36]),"=f"(d[37]),"=f"(d[38]),"=f"(d[39]),"=f"(d[40]),"=f"(d[41]),"=f"(d[42]),"=f"(d[43]),"=f"(d[44]),"=f"(d[45]),"=f"(d[46]),"=f"(d[47]),"=f"(d[48]),"=f"(d[49]),"=f"(d[50]),"=f"(d[51]),"=f"(d[52]),"=f"(d[53]),"=f"(d[54]),"=f"(d[55]),"=f"(d[56]),"=f"(d[57]),"=f"(d[58]),"=f"(d[59]),"=f"(d[60]),"=f"(d[61]),"=f"(d[62]),"=f"(d[63]),"=f"(d[64]),"=f"(d[65]),"=f"(d[66]),"=f"(d[67]),"=f"(d[68]),"=f"(d[69]),"=f"(d[70]),"=f"(d[71]),"=f"(d[72]),"=f"(d[73]),"=f"(d[74]),"=f"(d[75]),"=f"(d[76]),"=f"(d[77]),"=f"(d[78]),"=f"(d[79]),"=f"(d[80]),"=f"(d[81]),"=f"(d[82]),"=f"(d[83]),"=f"(d[84]),"=f"(d[85]),"=f"(d[86]),"=f"(d[87]),"=f"(d[88]),"=f"(d[89]),"=f"(d[90]),"=f"(d[91]),"=f"(d[92]),"=f"(d[93]),"=f"(d[94]),"=f"(d[95]) : "r"(a.x), "r"(a.y), "r"(a.z), "r"(a.w), "r"(db.lo), "r"(db.hi));
}
template<> __device__ __forceinline__ void wgmma_rs<256, 1>(float (&d)[128], const uint4& a, Desc db) {
  asm volatile("{\n.reg .pred p;\n.reg .b64 b;\nsetp.ne.b32 p, 1, 0;\nmov.b64 b, {%132, %133};\n"
    "wgmma.mma_async.sync.aligned.m64n256k16.f32.bf16.bf16 {%0,%1,%2,%3,%4,%5,%6,%7,%8,%9,%10,%11,%12,%13,%14,%15,%16,%17,%18,%19,%20,%21,%22,%23,%24,%25,%26,%27,%28,%29,%30,%31,%32,%33,%34,%35,%36,%37,%38,%39,%40,%41,%42,%43,%44,%45,%46,%47,%48,%49,%50,%51,%52,%53,%54,%55,%56,%57,%58,%59,%60,%61,%62,%63,%64,%65,%66,%67,%68,%69,%70,%71,%72,%73,%74,%75,%76,%77,%78,%79,%80,%81,%82,%83,%84,%85,%86,%87,%88,%89,%90,%91,%92,%93,%94,%95,%96,%97,%98,%99,%100,%101,%102,%103,%104,%105,%106,%107,%108,%109,%110,%111,%112,%113,%114,%115,%116,%117,%118,%119,%120,%121,%122,%123,%124,%125,%126,%127}, {%128,%129,%130,%131}, b, p, 1, 1, 1;\n}\n"
    : "+f"(d[0]),"+f"(d[1]),"+f"(d[2]),"+f"(d[3]),"+f"(d[4]),"+f"(d[5]),"+f"(d[6]),"+f"(d[7]),"+f"(d[8]),"+f"(d[9]),"+f"(d[10]),"+f"(d[11]),"+f"(d[12]),"+f"(d[13]),"+f"(d[14]),"+f"(d[15]),"+f"(d[16]),"+f"(d[17]),"+f"(d[18]),"+f"(d[19]),"+f"(d[20]),"+f"(d[21]),"+f"(d[22]),"+f"(d[23]),"+f"(d[24]),"+f"(d[25]),"+f"(d[26]),"+f"(d[27]),"+f"(d[28]),"+f"(d[29]),"+f"(d[30]),"+f"(d[31]),"+f"(d[32]),"+f"(d[33]),"+f"(d[34]),"+f"(d[35]),"+f"(d[36]),"+f"(d[37]),"+f"(d[38]),"+f"(d[39]),"+f"(d[40]),"+f"(d[41]),"+f"(d[42]),"+f"(d[43]),"+f"(d[44]),"+f"(d[45]),"+f"(d[46]),"+f"(d[47]),"+f"(d[48]),"+f"(d[49]),"+f"(d[50]),"+f"(d[51]),"+f"(d[52]),"+f"(d[53]),"+f"(d[54]),"+f"(d[55]),"+f"(d[56]),"+f"(d[57]),"+f"(d[58]),"+f"(d[59]),"+f"(d[60]),"+f"(d[61]),"+f"(d[62]),"+f"(d[63]),"+f"(d[64]),"+f"(d[65]),"+f"(d[66]),"+f"(d[67]),"+f"(d[68]),"+f"(d[69]),"+f"(d[70]),"+f"(d[71]),"+f"(d[72]),"+f"(d[73]),"+f"(d[74]),"+f"(d[75]),"+f"(d[76]),"+f"(d[77]),"+f"(d[78]),"+f"(d[79]),"+f"(d[80]),"+f"(d[81]),"+f"(d[82]),"+f"(d[83]),"+f"(d[84]),"+f"(d[85]),"+f"(d[86]),"+f"(d[87]),"+f"(d[88]),"+f"(d[89]),"+f"(d[90]),"+f"(d[91]),"+f"(d[92]),"+f"(d[93]),"+f"(d[94]),"+f"(d[95]),"+f"(d[96]),"+f"(d[97]),"+f"(d[98]),"+f"(d[99]),"+f"(d[100]),"+f"(d[101]),"+f"(d[102]),"+f"(d[103]),"+f"(d[104]),"+f"(d[105]),"+f"(d[106]),"+f"(d[107]),"+f"(d[108]),"+f"(d[109]),"+f"(d[110]),"+f"(d[111]),"+f"(d[112]),"+f"(d[113]),"+f"(d[114]),"+f"(d[115]),"+f"(d[116]),"+f"(d[117]),"+f"(d[118]),"+f"(d[119]),"+f"(d[120]),"+f"(d[121]),"+f"(d[122]),"+f"(d[123]),"+f"(d[124]),"+f"(d[125]),"+f"(d[126]),"+f"(d[127]) : "r"(a.x), "r"(a.y), "r"(a.z), "r"(a.w), "r"(db.lo), "r"(db.hi));
}
template<> __device__ __forceinline__ void wgmma_rs<256, 0>(float (&d)[128], const uint4& a, Desc db) {
  asm volatile("{\n.reg .pred p;\n.reg .b64 b;\nsetp.ne.b32 p, 0, 0;\nmov.b64 b, {%132, %133};\n"
    "wgmma.mma_async.sync.aligned.m64n256k16.f32.bf16.bf16 {%0,%1,%2,%3,%4,%5,%6,%7,%8,%9,%10,%11,%12,%13,%14,%15,%16,%17,%18,%19,%20,%21,%22,%23,%24,%25,%26,%27,%28,%29,%30,%31,%32,%33,%34,%35,%36,%37,%38,%39,%40,%41,%42,%43,%44,%45,%46,%47,%48,%49,%50,%51,%52,%53,%54,%55,%56,%57,%58,%59,%60,%61,%62,%63,%64,%65,%66,%67,%68,%69,%70,%71,%72,%73,%74,%75,%76,%77,%78,%79,%80,%81,%82,%83,%84,%85,%86,%87,%88,%89,%90,%91,%92,%93,%94,%95,%96,%97,%98,%99,%100,%101,%102,%103,%104,%105,%106,%107,%108,%109,%110,%111,%112,%113,%114,%115,%116,%117,%118,%119,%120,%121,%122,%123,%124,%125,%126,%127}, {%128,%129,%130,%131}, b, p, 1, 1, 1;\n}\n"
    : "=f"(d[0]),"=f"(d[1]),"=f"(d[2]),"=f"(d[3]),"=f"(d[4]),"=f"(d[5]),"=f"(d[6]),"=f"(d[7]),"=f"(d[8]),"=f"(d[9]),"=f"(d[10]),"=f"(d[11]),"=f"(d[12]),"=f"(d[13]),"=f"(d[14]),"=f"(d[15]),"=f"(d[16]),"=f"(d[17]),"=f"(d[18]),"=f"(d[19]),"=f"(d[20]),"=f"(d[21]),"=f"(d[22]),"=f"(d[23]),"=f"(d[24]),"=f"(d[25]),"=f"(d[26]),"=f"(d[27]),"=f"(d[28]),"=f"(d[29]),"=f"(d[30]),"=f"(d[31]),"=f"(d[32]),"=f"(d[33]),"=f"(d[34]),"=f"(d[35]),"=f"(d[36]),"=f"(d[37]),"=f"(d[38]),"=f"(d[39]),"=f"(d[40]),"=f"(d[41]),"=f"(d[42]),"=f"(d[43]),"=f"(d[44]),"=f"(d[45]),"=f"(d[46]),"=f"(d[47]),"=f"(d[48]),"=f"(d[49]),"=f"(d[50]),"=f"(d[51]),"=f"(d[52]),"=f"(d[53]),"=f"(d[54]),"=f"(d[55]),"=f"(d[56]),"=f"(d[57]),"=f"(d[58]),"=f"(d[59]),"=f"(d[60]),"=f"(d[61]),"=f"(d[62]),"=f"(d[63]),"=f"(d[64]),"=f"(d[65]),"=f"(d[66]),"=f"(d[67]),"=f"(d[68]),"=f"(d[69]),"=f"(d[70]),"=f"(d[71]),"=f"(d[72]),"=f"(d[73]),"=f"(d[74]),"=f"(d[75]),"=f"(d[76]),"=f"(d[77]),"=f"(d[78]),"=f"(d[79]),"=f"(d[80]),"=f"(d[81]),"=f"(d[82]),"=f"(d[83]),"=f"(d[84]),"=f"(d[85]),"=f"(d[86]),"=f"(d[87]),"=f"(d[88]),"=f"(d[89]),"=f"(d[90]),"=f"(d[91]),"=f"(d[92]),"=f"(d[93]),"=f"(d[94]),"=f"(d[95]),"=f"(d[96]),"=f"(d[97]),"=f"(d[98]),"=f"(d[99]),"=f"(d[100]),"=f"(d[101]),"=f"(d[102]),"=f"(d[103]),"=f"(d[104]),"=f"(d[105]),"=f"(d[106]),"=f"(d[107]),"=f"(d[108]),"=f"(d[109]),"=f"(d[110]),"=f"(d[111]),"=f"(d[112]),"=f"(d[113]),"=f"(d[114]),"=f"(d[115]),"=f"(d[116]),"=f"(d[117]),"=f"(d[118]),"=f"(d[119]),"=f"(d[120]),"=f"(d[121]),"=f"(d[122]),"=f"(d[123]),"=f"(d[124]),"=f"(d[125]),"=f"(d[126]),"=f"(d[127]) : "r"(a.x), "r"(a.y), "r"(a.z), "r"(a.w), "r"(db.lo), "r"(db.hi));
}
template<int N> __device__ __forceinline__ void wgmma_ra(float (&d)[N / 2], const uint4& a, Desc db, bool acc) {
  if (acc) wgmma_rs<N, 1>(d, a, db); else wgmma_rs<N, 0>(d, a, db);
}

__device__ __forceinline__ uint32_t smem_u32(const void* p) { return (uint32_t)__cvta_generic_to_shared(p); }
__device__ __forceinline__ void mbar_init(uint32_t bar, uint32_t cnt) { asm volatile("mbarrier.init.shared::cta.b64 [%0], %1;" ::"r"(bar), "r"(cnt)); }
__device__ __forceinline__ void mbar_expect_tx(uint32_t bar, uint32_t bytes) { asm volatile("mbarrier.arrive.expect_tx.shared::cta.b64 _, [%0], %1;" ::"r"(bar), "r"(bytes) : "memory"); }
__device__ __forceinline__ void mbar_arrive(uint32_t bar) { asm volatile("mbarrier.arrive.shared::cta.b64 _, [%0];" ::"r"(bar) : "memory"); }
__device__ __forceinline__ void mbar_arrive_remote(uint32_t rbar) { asm volatile("mbarrier.arrive.shared::cluster.b64 _, [%0];" ::"r"(rbar) : "memory"); }
__device__ __forceinline__ void mbar_wait(uint32_t bar, uint32_t parity) {
  asm volatile(
      "{\n.reg .pred p;\n.reg .u32 c;\nmov.u32 c, 0;\nLAB_WAIT:\nmbarrier.try_wait.parity.shared::cta.b64 p, [%0], %1;\n@p bra DONE;\n"
      "add.u32 c, c, 1;\nsetp.lt.u32 p, c, 1000000;\n@p bra LAB_WAIT;\ntrap;\nDONE:\n}\n" ::"r"(bar), "r"(parity) : "memory");
}
__device__ __forceinline__ void mbar_wait_c(uint32_t bar, uint32_t parity) {
  asm volatile("{\n.reg .pred p;\nLAB_WAIT:\nmbarrier.try_wait.parity.shared::cta.b64 p, [%0], %1;\n@!p bra LAB_WAIT;\n}\n" ::"r"(bar), "r"(parity) : "memory");
}
__device__ __forceinline__ uint32_t late(uint32_t bar, uint32_t v) {
  uint32_t r;
  asm volatile("{\n.reg .pred p;\nmbarrier.test_wait.parity.shared::cta.b64 p, [%1], 0;\nselp.b32 %0, %2, %1, p;\n}\n" : "=r"(r) : "r"(bar), "r"(v) : "memory");
  return r;
}
__device__ __forceinline__ void wtma2d(uint32_t dst, const CUtensorMap* m, int c0, int c1, uint32_t bar, uint64_t pol) {
  asm volatile("cp.async.bulk.tensor.2d.shared::cluster.global.mbarrier::complete_tx::bytes.multicast::cluster.L2::cache_hint [%0], [%1, {%3, %4}], [%2], %5, %6;"
               ::"r"(dst), "l"(m), "r"(bar), "r"(c0), "r"(c1), "h"((uint16_t)3), "l"(pol) : "memory");
}
__device__ __forceinline__ void wtma3d(uint32_t dst, const CUtensorMap* m, int c0, int c1, int c2, uint32_t bar, uint64_t pol) {
  asm volatile("cp.async.bulk.tensor.3d.shared::cluster.global.mbarrier::complete_tx::bytes.multicast::cluster.L2::cache_hint [%0], [%1, {%3, %4, %5}], [%2], %6, %7;"
               ::"r"(dst), "l"(m), "r"(bar), "r"(c0), "r"(c1), "r"(c2), "h"((uint16_t)3), "l"(pol) : "memory");
}
__device__ __forceinline__ void wbulk(uint32_t dst, const void* src, uint32_t bytes, uint32_t bar, uint64_t pol) {
  asm volatile("cp.async.bulk.shared::cluster.global.mbarrier::complete_tx::bytes.multicast::cluster.L2::cache_hint [%0], [%1], %2, [%3], %4, %5;"
               ::"r"(dst), "l"(src), "r"(bytes), "r"(bar), "h"((uint16_t)3), "l"(pol) : "memory");
}
__device__ __forceinline__ void tma3d(uint32_t dst, const CUtensorMap* m, int c0, int c1, int c2, uint32_t bar) {
  asm volatile("cp.async.bulk.tensor.3d.shared::cluster.global.mbarrier::complete_tx::bytes [%0], [%1, {%3, %4, %5}], [%2];"
               ::"r"(dst), "l"(m), "r"(bar), "r"(c0), "r"(c1), "r"(c2) : "memory");
}
__device__ __forceinline__ void prefetch_l2(const void* p, uint32_t bytes) { asm volatile("cp.async.bulk.prefetch.L2.global [%0], %1;" ::"l"(p), "r"(bytes) : "memory"); }
__device__ __forceinline__ uint64_t policy_evict_first() { uint64_t p; asm volatile("createpolicy.fractional.L2::evict_first.b64 %0, 1.0;" : "=l"(p)); return p; }
__device__ __forceinline__ uint64_t policy_evict_normal() { uint64_t p; asm volatile("createpolicy.fractional.L2::evict_normal.b64 %0, 1.0;" : "=l"(p)); return p; }
__device__ __forceinline__ void fence_async_smem() { asm volatile("fence.proxy.async.shared::cta;" ::: "memory"); }
__device__ __forceinline__ bool elect_one() {
  uint32_t p;
  asm volatile("{\n.reg .pred P;\nelect.sync _|P, 0xffffffff;\nselp.u32 %0, 1, 0, P;\n}\n" : "=r"(p));
  return p;
}
__device__ __forceinline__ void wg_fence() { asm volatile("wgmma.fence.sync.aligned;" ::: "memory"); }
__device__ __forceinline__ void wg_commit() { asm volatile("wgmma.commit_group.sync.aligned;" ::: "memory"); }
template <int n> __device__ __forceinline__ void wg_wait() { asm volatile("wgmma.wait_group.sync.aligned %0;" ::"n"(n) : "memory"); }
__device__ __forceinline__ void wg_bar(int w) { asm volatile("bar.sync %0, 128;" ::"r"(w + 1) : "memory"); }
__device__ __forceinline__ void fence_gpu() { asm volatile("fence.acq_rel.gpu;" ::: "memory"); }
__device__ __forceinline__ uint32_t ld_relaxed(const uint32_t* p) { uint32_t v; asm volatile("ld.relaxed.gpu.global.u32 %0, [%1];" : "=r"(v) : "l"(p) : "memory"); return v; }
__device__ __forceinline__ uint32_t ld_acquire(const uint32_t* p) { uint32_t v; asm volatile("ld.acquire.gpu.global.u32 %0, [%1];" : "=r"(v) : "l"(p) : "memory"); return v; }
__device__ __forceinline__ uint4 ld_relaxed4(const uint4* p) {
  uint4 v; asm volatile("ld.relaxed.gpu.global.v4.u32 {%0,%1,%2,%3}, [%4];" : "=r"(v.x), "=r"(v.y), "=r"(v.z), "=r"(v.w) : "l"(p) : "memory"); return v;
}
__device__ __forceinline__ uint2 ld_relaxed2(const uint2* p) {
  uint2 v; asm volatile("ld.relaxed.gpu.global.v2.u32 {%0,%1}, [%2];" : "=r"(v.x), "=r"(v.y) : "l"(p) : "memory"); return v;
}
__device__ __forceinline__ void st_relaxed(uint32_t* p, uint32_t a) { asm volatile("st.relaxed.gpu.global.u32 [%0], %1;" ::"l"(p), "r"(a) : "memory"); }
__device__ __forceinline__ void st_relaxed4(uint4* p, uint32_t a, uint32_t b, uint32_t c, uint32_t d) {
  asm volatile("st.relaxed.gpu.global.v4.u32 [%0], {%1,%2,%3,%4};" ::"l"(p), "r"(a), "r"(b), "r"(c), "r"(d) : "memory");
}
__device__ __forceinline__ void st_relaxed2(uint2* p, uint32_t a, uint32_t b) {
  asm volatile("st.relaxed.gpu.global.v2.u32 [%0], {%1,%2};" ::"l"(p), "r"(a), "r"(b) : "memory");
}
__device__ __forceinline__ void red4(uint4* p, uint32_t a, uint32_t b, uint32_t c, uint32_t d) {
  asm volatile("red.relaxed.gpu.global.add.noftz.v4.bf16x2 [%0], {%1,%2,%3,%4};" ::"l"(p), "r"(a), "r"(b), "r"(c), "r"(d) : "memory");
}
__device__ __forceinline__ void red2(uint2* p, uint32_t a, uint32_t b) {
  asm volatile("red.relaxed.gpu.global.add.noftz.v2.bf16x2 [%0], {%1,%2};" ::"l"(p), "r"(a), "r"(b) : "memory");
}
constexpr int SPIN_MAX = 1 << 21;
__device__ __forceinline__ uint32_t pack_bf16(float lo, float hi) { uint32_t r; asm("cvt.rn.bf16x2.f32 %0, %1, %2;" : "=r"(r) : "f"(hi), "f"(lo)); return r; }
__device__ __forceinline__ float bf_lo(uint32_t v) { return __uint_as_float(v << 16); }
__device__ __forceinline__ float bf_hi(uint32_t v) { return __uint_as_float(v & 0xffff0000u); }
__device__ __forceinline__ float2 lds64(uint32_t a) { float2 v; asm volatile("ld.shared.v2.f32 {%0,%1}, [%2];" : "=f"(v.x), "=f"(v.y) : "r"(a)); return v; }
__device__ __forceinline__ uint32_t lds32(uint32_t a) { uint32_t v; asm volatile("ld.shared.b32 %0, [%1];" : "=r"(v) : "r"(a)); return v; }
__device__ __forceinline__ void sts64f(uint32_t a, float x, float y) { asm volatile("st.shared.v2.f32 [%0], {%1,%2};" ::"r"(a), "f"(x), "f"(y) : "memory"); }
__device__ __forceinline__ void sts32(uint32_t a, uint32_t x) { asm volatile("st.volatile.shared.b32 [%0], %1;" ::"r"(a), "r"(x) : "memory"); }
__device__ __forceinline__ void gate(uint32_t a, int need) {
#pragma unroll 1
  for (int it = 0; it < SPIN_MAX; it++) {
    int v; asm volatile("ld.volatile.shared.b32 %0, [%1];" : "=r"(v) : "r"(a) : "memory");
    if (v >= need) break;
    if (GSLEEP) __nanosleep(GSLEEP);
  }
}
__device__ __forceinline__ void sts128(uint32_t a, uint32_t x, uint32_t y, uint32_t z, uint32_t u) { asm volatile("st.shared.v4.b32 [%0], {%1,%2,%3,%4};" ::"r"(a), "r"(x), "r"(y), "r"(z), "r"(u) : "memory"); }
__device__ __forceinline__ uint4 lds128(uint32_t a) { uint4 v; asm volatile("ld.shared.v4.u32 {%0,%1,%2,%3}, [%4];" : "=r"(v.x), "=r"(v.y), "=r"(v.z), "=r"(v.w) : "r"(a) : "memory"); return v; }
__device__ __forceinline__ uint32_t hmul2(uint32_t a, uint32_t b) { uint32_t r; asm("mul.rn.bf16x2 %0, %1, %2;" : "=r"(r) : "r"(a), "r"(b)); return r; }
__device__ __forceinline__ uint32_t hadd2(uint32_t a, uint32_t b) { uint32_t r; asm("add.rn.bf16x2 %0, %1, %2;" : "=r"(r) : "r"(a), "r"(b)); return r; }
__device__ __forceinline__ void stsm4(uint32_t a, uint32_t r0, uint32_t r1, uint32_t r2, uint32_t r3) {
  asm volatile("stmatrix.sync.aligned.m8n8.x4.shared.b16 [%0], {%1,%2,%3,%4};" ::"r"(a), "r"(r0), "r"(r1), "r"(r2), "r"(r3) : "memory");
}
__device__ __forceinline__ void stsm2(uint32_t a, uint32_t r0, uint32_t r1) {
  asm volatile("stmatrix.sync.aligned.m8n8.x2.shared.b16 [%0], {%1,%2};" ::"r"(a), "r"(r0), "r"(r1) : "memory");
}
__device__ __forceinline__ uint4 ldsm4(uint32_t a) {
  uint4 r; asm volatile("ldmatrix.sync.aligned.m8n8.x4.shared.b16 {%0,%1,%2,%3}, [%4];" : "=r"(r.x), "=r"(r.y), "=r"(r.z), "=r"(r.w) : "r"(a) : "memory"); return r;
}
__device__ __forceinline__ uint32_t movm(uint32_t a) { uint32_t r; asm("movmatrix.sync.aligned.m8n8.trans.b16 %0, %1;" : "=r"(r) : "r"(a)); return r; }
__device__ __forceinline__ void mma16816z(float (&d)[4], uint32_t a0, uint32_t a1, uint32_t a2, uint32_t a3, uint32_t b0, uint32_t b1) {
  asm("mma.sync.aligned.m16n8k16.row.col.f32.bf16.bf16.f32 {%0,%1,%2,%3}, {%4,%5,%6,%7}, {%8,%9}, {%10,%10,%10,%10};"
      : "=f"(d[0]), "=f"(d[1]), "=f"(d[2]), "=f"(d[3]) : "r"(a0), "r"(a1), "r"(a2), "r"(a3), "r"(b0), "r"(b1), "f"(0.f));
}
__device__ __forceinline__ void mma16816(float (&d)[4], const uint4& a, uint32_t b0, uint32_t b1) {
  asm("mma.sync.aligned.m16n8k16.row.col.f32.bf16.bf16.f32 {%0,%1,%2,%3}, {%4,%5,%6,%7}, {%8,%9}, {%0,%1,%2,%3};"
      : "+f"(d[0]), "+f"(d[1]), "+f"(d[2]), "+f"(d[3]) : "r"(a.x), "r"(a.y), "r"(a.z), "r"(a.w), "r"(b0), "r"(b1));
}
__device__ __forceinline__ void mma1688(float (&d)[4], uint32_t a0, uint32_t a1, uint32_t b0) {
  asm("mma.sync.aligned.m16n8k8.row.col.f32.bf16.bf16.f32 {%0,%1,%2,%3}, {%4,%5}, {%6}, {%0,%1,%2,%3};"
      : "+f"(d[0]), "+f"(d[1]), "+f"(d[2]), "+f"(d[3]) : "r"(a0), "r"(a1), "r"(b0));
}
__device__ __forceinline__ float quad_sum(float v) { v += __shfl_xor_sync(0xffffffffu, v, 1); v += __shfl_xor_sync(0xffffffffu, v, 2); return v; }
__device__ __forceinline__ float quad_max(float v) { v = fmaxf(v, __shfl_xor_sync(0xffffffffu, v, 1)); v = fmaxf(v, __shfl_xor_sync(0xffffffffu, v, 2)); return v; }
__device__ __forceinline__ float rcp(float x) { float r; asm("rcp.approx.ftz.f32 %0, %1;" : "=f"(r) : "f"(x)); return r; }
__device__ __forceinline__ float rsq(float x) { float r; asm("rsqrt.approx.ftz.f32 %0, %1;" : "=f"(r) : "f"(x)); return r; }
__device__ __forceinline__ float ex2(float x) { float r; asm("ex2.approx.ftz.f32 %0, %1;" : "=f"(r) : "f"(x)); return r; }
__device__ __forceinline__ uint32_t chk(uint32_t acc, uint32_t v, uint32_t tag) { uint32_t r; asm("lop3.b32 %0, %1, %2, %3, 0xF6;" : "=r"(r) : "r"(acc), "r"(v), "r"(tag)); return r; }
__device__ __forceinline__ uint32_t chk2(uint32_t a, uint32_t b, uint32_t tag) { uint32_t r; asm("lop3.b32 %0, %1, %2, %3, 0x7E;" : "=r"(r) : "r"(a), "r"(b), "r"(tag)); return r; }
__device__ __forceinline__ uint32_t tagged(uint32_t v, uint32_t tag) { return (v & ~1u) | tag; }

__device__ __forceinline__ int group_k0(int g, int j) {
  const int h = g >= 9, r = g - 2 - 7 * h;
  return g < 2 ? 64 * j + 32 * g : g < 16 ? 64 * (r + (r >= j)) + 32 * h : 32 * g;
}
__device__ __forceinline__ uint32_t xin_off(int c, int w) { return SM_X + (2 * c + w) * 8192; }
__device__ __forceinline__ uint32_t xin_bar(int c) { return BAR_FULLX + 8 * (c < 8 ? c ^ 4 : c); }
__device__ __forceinline__ constexpr uint32_t qkv_xslot(int g) { return g < 5 || g > 11 ? 2 : (0x5140762u >> (4 * (g - 5))) & 15; }

template <int N> struct IC { static constexpr int v = N; };

struct Cons {
  uint32_t sb;
  uint32_t rem;
  uint32_t sB, mB;
  uint32_t mX;
  bool elect;
  __device__ __forceinline__ void release2(uint32_t bar) const { if (elect) { mbar_arrive(sb + bar); mbar_arrive_remote(rem + bar); } }
  __device__ __forceinline__ uint32_t nextB(uint32_t& prev) {
    mbar_wait_c(sb + BAR_FULLB + sB, mB);
    const uint32_t a = (((sb & 0x3FFFF) + SM_B) >> 4) + sB * (BSLOT / 128);
    prev = sB == 0 ? 32 : sB - 8;
    sB += 8;
    if (sB == 40) { sB = 0; mB ^= 1; }
    return a;
  }
  __device__ __forceinline__ void progress(uint32_t v) const { if (elect) sts32(sb + SM_PROG + (threadIdx.x >> 5), v); }
  __device__ __forceinline__ void releaseLastB() const { release2(BAR_EMPTYB + (sB == 0 ? 32 : sB - 8)); }
};

__device__ __forceinline__ float2 gather_sums(const uint2* a, uint32_t stag) {
  uint2 sa, sc;
  do { sa = ld_relaxed2(a); sc = ld_relaxed2(a + 8); } while (__any_sync(0xffffffffu, chk2(sa.x, sc.x, stag) & 3));
  return make_float2(quad_sum(__uint_as_float(sa.x) + __uint_as_float(sc.x)), quad_sum(__uint_as_float(sa.y) + __uint_as_float(sc.y)));
}

struct Norm {
  float m0, m1;
  uint32_t nm0, nm1;
  float d0, d1;
  uint2 u0, u1;
  __device__ __forceinline__ Norm(float2 sum) : m0(sum.x * (-1.f / 576)), m1(sum.y * (-1.f / 576)), nm0(pack_bf16(m0, m0)), nm1(pack_bf16(m1, m1)), d0(0.f), d1(0.f) {}
  __device__ __forceinline__ uint4 centre(const uint4& a) const { return make_uint4(hadd2(a.x, nm0), hadd2(a.y, nm1), hadd2(a.z, nm0), hadd2(a.w, nm1)); }
  __device__ __forceinline__ void sqr(uint32_t a, uint32_t b) {
    d0 = fmaf(bf_lo(a), bf_lo(a), fmaf(bf_hi(a), bf_hi(a), d0)); d1 = fmaf(bf_lo(b), bf_lo(b), fmaf(bf_hi(b), bf_hi(b), d1));
  }
  __device__ __forceinline__ void send(uint2* a, int t, uint32_t stag) {
    d0 = quad_sum(d0); d1 = quad_sum(d1);
    if ((t & 3) == 0) st_relaxed2(a, (__float_as_uint(d0) & ~3u) | stag, __float_as_uint(d1));
  }
  __device__ __forceinline__ void fetch(const uint2* a) { u0 = ld_relaxed2(a); u1 = ld_relaxed2(a + 8); }
  __device__ __forceinline__ float2 rstd(const uint2* a, uint32_t stag) {
    while (__any_sync(0xffffffffu, chk2(u0.x, u1.x, stag) & 3)) fetch(a);
    const float e0 = bf_lo(nm0) - m0, e1 = bf_lo(nm1) - m1;
    const float v0 = fmaf(quad_sum(__uint_as_float(u0.x) + __uint_as_float(u1.x)), 1.f / 576, -e0 * e0);
    const float v1 = fmaf(quad_sum(__uint_as_float(u0.y) + __uint_as_float(u1.y)), 1.f / 576, -e1 * e1);
    uint32_t u = pack_bf16(fmaxf(v0, 0.f), fmaxf(v1, 0.f));
    u = pack_bf16(bf_lo(u) + 1e-5f, bf_hi(u) + 1e-5f);
    u = pack_bf16(bf_lo(u) * rsq(bf_lo(u)), bf_hi(u) * rsq(bf_hi(u)));
    float2 r = make_float2(rcp(bf_lo(u)), rcp(bf_hi(u)));
    asm volatile("" : "+f"(r.x), "+f"(r.y));
    return r;
  }
};

template <class Pre, class Mma>
__device__ __forceinline__ float2 ln_gemm_in(Cons& c, Group* G, uint32_t (&p)[18], float2& sum, int w, int st0, int j, int t, Pre&& pre, Mma&& mma) {
  const uint32_t xa = c.sb + (t >> 5) * 2048 + (t & 15) * 128, sw = (((t >> 4) & 1) ^ (t & 7)) * 16;
  float ra[4] = {0.f, 0.f, 0.f, 0.f}, rb[4] = {0.f, 0.f, 0.f, 0.f};
#pragma unroll 1
  for (int cc = 0; cc < 9; cc++) {
    const uint32_t a = xa + xin_off(cc, w);
    mbar_wait_c(c.sb + xin_bar(cc), 0);
    const uint4 u0 = ldsm4(a + sw), u1 = ldsm4(a + (sw ^ 32)), u2 = ldsm4(a + (sw ^ 64)), u3 = ldsm4(a + (sw ^ 96));
    mma16816(ra, u0, 0x3f803f80u, 0x3f803f80u); mma16816(rb, u1, 0x3f803f80u, 0x3f803f80u);
    mma16816(ra, u2, 0x3f803f80u, 0x3f803f80u); mma16816(rb, u3, 0x3f803f80u, 0x3f803f80u);
  }
  sum = make_float2(ra[0] + rb[0], ra[2] + rb[2]);
  pre(0);
  Norm n(sum);
  n.u0 = n.u1 = make_uint2(0, 0);
  auto stats = [&] {
#pragma unroll
    for (int k = 0; k < 5; k++) {
      const uint4 u = ldsm4(xa + (k < 4 ? xin_off(j, w) + (sw ^ (32 * k)) : xin_off(8, w) + ((j ^ (t & 7)) << 4))), e = n.centre(u);
      p[4 * k] = u.x; p[4 * k + 1] = u.y;
      n.sqr(e.x, e.y);
      if (k < 4) { p[4 * k + 2] = u.z; p[4 * k + 3] = u.w; n.sqr(e.z, e.w); }
    }
    n.send(G->sq + st0 + 8 * j, t, 1);
  };
  if (STATP < 0) stats();
  else {
#pragma unroll
    for (int i = 0; i < 18; i++) p[i] = 0;
  }
  pre(1);
  float2 r = make_float2(0.f, 0.f);
  uint4 y0 = ldsm4(xa + xin_off(0, w) + sw), y1 = ldsm4(xa + xin_off(0, w) + (sw ^ 32));
#pragma unroll 1
  for (int cc = 0; cc < 9; cc++) {
#pragma unroll
    for (int i = 0; i < 2; i++) {
      const uint4 f0 = n.centre(y0), f1 = n.centre(y1);
      const uint32_t a = xa + xin_off(min(cc + i, 8), w);
      y0 = ldsm4(a + (sw ^ (64 - 64 * i))); y1 = ldsm4(a + (sw ^ (96 - 64 * i)));
      uint32_t prev;
      const uint32_t bb = c.nextB(prev);
      mma(true, bb, f0, f1);
      if (i == 1) {
        if (STATP >= 0 && cc == STATP * w) stats();
        if (cc == 1) c.progress(3);
        if (cc == 5) n.fetch(G->sq + st0 + 16 * (t & 3));
        if (cc == 7) r = n.rstd(G->sq + st0 + 16 * (t & 3), 1);
        if (cc == 8 && w == 0) asm volatile("bar.arrive 6, 256;" ::: "memory");
      }
      wg_wait<1>();
      if (i + cc > 0) c.release2(BAR_EMPTYB + prev);
      if (2 * cc + i >= WOG && 2 * cc + i < WOG + 4) c.release2(BAR_EMPTYX + 32 + 8 * (2 * cc + i - WOG));
    }
  }
  c.mX = 0xff;
  if (w == 1) asm volatile("bar.sync 6, 256;" ::: "memory");
  wg_wait<0>();
  c.releaseLastB();
  c.release2(BAR_EMPTYX + 24);
  return r;
}

template <bool QKV, class Pre, class Mma>
__device__ __forceinline__ float2 ln_gemm(Cons& c, Group* G, const float (&v)[36], uint32_t (&p)[18], float2& sum, int st0, int j, int t,
                                          int layer, uint32_t tag, Pre&& pre, Mma&& mma) {
  constexpr bool known = !QKV && EARLY;
  const uint32_t stag = (2 * layer + (QKV ? 1 : 2)) & 3;
  uint4 x[6][2];
  uint4* src = G->xbox + t;
  asm volatile("" : "+l"(src));
  auto buf = [&](int g) -> uint4 (&)[2] { return x[g < 16 ? (g - 2) % 6 : g - 13]; };
  auto load = [&](int g0) {
#pragma unroll
    for (int g = g0; g < g0 + (g0 < 14 ? 3 : 2); g++) {
      const uint4* a = g < 16 ? src + ((g - 2) % 7 >= j ? 256 : 0) + (2 * ((g - 2) % 7) + 16 * (g >= 9)) * 128 : src + 2 * g * 128;
      buf(g)[0] = ld_relaxed4(a); buf(g)[1] = ld_relaxed4(a + 128);
    }
  };
  auto invalid = [&](int g, uint32_t tag) {
    uint32_t bad = chk(chk(chk2(buf(g)[0].x, buf(g)[1].x, tag), buf(g + 1)[0].x, tag), buf(g + 1)[1].x, tag);
    if (g < 14) bad = chk(chk(bad, buf(g + 2)[0].x, tag), buf(g + 2)[1].x, tag);
    if (g == 16) bad = chk(chk(chk(chk(bad, buf(g)[0].z, tag), buf(g)[1].z, tag), buf(g + 1)[0].z, tag), buf(g + 1)[1].z, tag);
    return __any_sync(0xffffffffu, bad & 1);
  };
  uint4* const d = src + 2 * j * 128;
  const int sq = st0 + 16 * (t & 3);
  if (!known) {
    float s0 = v[0] + v[1], s1 = v[2] + v[3];
#pragma unroll
    for (int i = 1; i < 9; i++) { s0 += v[4 * i] + v[4 * i + 1]; s1 += v[4 * i + 2] + v[4 * i + 3]; }
    s0 = quad_sum(s0); s1 = quad_sum(s1);
    if ((t & 3) == 0) st_relaxed2(G->sum + st0 + 8 * j, (__float_as_uint(s0) & ~3u) | stag, __float_as_uint(s1));
  }
#pragma unroll
  for (int i = 0; i < 18; i++) p[i] = pack_bf16(v[2 * i], v[2 * i + 1]);
#pragma unroll
  for (int i = 0; i < 2; i++) st_relaxed4(d + i * 128, tagged(p[4 * i], tag), p[4 * i + 1], p[4 * i + 2], p[4 * i + 3]);
  pre(0);
  if (!known) {
    sum = gather_sums(G->sum + sq, stag);
    load(2);
  }
  Norm n(sum);
  pre(1);
  const uint32_t* probe = &(G->xbox + (2 * (t & XPM) + 1) * 128 + (t | 31))->x;
  uint32_t pv;
  float2 r;
  auto inx = [](int g) { return QKV && ((g >= 5 && g < 12) || g == 17); };
  auto use = [](int g) { return QKV ? (g < 5 ? 108 : 101) + g : 18 + g; };
#pragma unroll
  for (int g = 0; g < 18; g++) {
    if (g < 16 ? g % 3 == 2 : g == 16) {
      const uint32_t lt = late(c.sb + BAR_FULLX + 64, tag);
      while (invalid(g, lt)) load(g);
      if (g < 16) load(g < 14 ? g + 3 : 16);
    }
    const uint4 f0 = n.centre(g < 2 ? make_uint4(p[8 * g], p[8 * g + 1], p[8 * g + 2], p[8 * g + 3]) : buf(g)[0]);
    const uint4 f1 = n.centre(g < 2 ? make_uint4(p[8 * g + 4], p[8 * g + 5], p[8 * g + 6], p[8 * g + 7]) : buf(g)[1]);
    if (g == 11) n.fetch(G->sq + sq);
    if (g == 16) r = n.rstd(G->sq + sq, stag);
    if (inx(g)) mbar_wait_c(c.sb + BAR_FULLX + 8 * qkv_xslot(g), ((0x34 >> qkv_xslot(g)) & 1) ^ (g == 17));
    else mbar_wait_c(c.sb + BAR_FULLB + 8 * (use(g) % 5), (use(g) / 5) & 1);
    mma(g, ((c.sb & 0x3FFFF) >> 4) + ((inx(g) ? xslot(qkv_xslot(g)) : SM_B + (use(g) % 5) * BSLOT) >> 4), f0, f1);
    if (g == 1) { wg_wait<1>(); c.release2(BAR_EMPTYB + 8 * (use(0) % 5)); }
    if (g < 2) {
      if (known) {
        if (g == 0) {
          pv = tag;
          if (!ESPEC || layer == 0) pv = ld_relaxed(probe);
        } else {
          const uint32_t lt = late(c.sb + BAR_FULLX + 64, tag);
          while (__any_sync(0xffffffffu, (pv ^ lt) & 1)) pv = ld_relaxed(probe);
          load(2);
        }
      }
      if (g == (known ? 1 : 0)) {
#pragma unroll
        for (int i = 2; i < 4; i++) st_relaxed4(d + (14 + i) * 128, tagged(p[4 * i], tag), p[4 * i + 1], p[4 * i + 2], p[4 * i + 3]);
        st_relaxed2((uint2*)(src + (32 + (j >> 1)) * 128) + (j & 1), tagged(p[16], tag), p[17]);
      }
      n.sqr(f0.x, f0.y); n.sqr(f0.z, f0.w); n.sqr(f1.x, f1.y); n.sqr(f1.z, f1.w);
      if (g == 1) {
        n.sqr(hadd2(p[16], n.nm0), hadd2(p[17], n.nm1));
        n.send(G->sq + st0 + 8 * j, t, stag);
      }
    }
    if (g == 1 && !QKV) { wg_wait<0>(); c.release2(BAR_EMPTYB + 8 * (use(1) % 5)); }
    else wg_wait<1>();
    if (g > (QKV ? 1 : 2) && !inx(g - 1)) c.release2(BAR_EMPTYB + 8 * (use(g - 1) % 5));
    if (QKV && g < 13) c.progress(33 + g);
    if (QKV && g == WOG - 1) c.release2(BAR_EMPTYX + 8 * qkv_xslot(17));
    if (QKV && g >= WOG && g < WOG + 4) c.release2(BAR_EMPTYX + 32 + 8 * (g - WOG));
  }
  if (QKV) c.mX = 0x34 ^ 0xf3;
  else { c.sB = 8 * (36 % 5); c.mB = (36 / 5) & 1; }
  wg_wait<0>();
  if (!QKV) c.release2(BAR_EMPTYB + 8 * (use(17) % 5));
  return r;
}

template <int NB, int OFF>
__device__ __forceinline__ void glu(const float (&a)[128], uint32_t (&h)[144]) {
#pragma unroll
  for (int b = 0; b < 2 * NB; b++) {
    if (HMUL) h[OFF + b] = hmul2(pack_bf16(a[2 * b], a[2 * b + 1]), pack_bf16(a[4 * NB + 2 * b], a[4 * NB + 2 * b + 1]));
    else h[OFF + b] = pack_bf16(a[2 * b] * a[4 * NB + 2 * b], a[2 * b + 1] * a[4 * NB + 2 * b + 1]);
  }
}

__global__ void __cluster_dims__(2, 1, 1) __launch_bounds__(384, 1)
fused_kernel(const __nv_bfloat16* __restrict__ x_in, Group* ws, const char* __restrict__ wqkv,
             const char* __restrict__ wo, char* __restrict__ out, uint32_t first, const __grid_constant__ Maps maps,
             const char* __restrict__ wg, const char* __restrict__ wu, const char* __restrict__ wd) {
  extern __shared__ __align__(1024) uint8_t smem_raw[];
  const uint32_t sb = smem_u32(smem_raw);
  const uint32_t bx = blockIdx.x - first;
  if (bx >= NCTA) {
    const int e = blockIdx.x & 3;
    const uint32_t par = ~ld_relaxed(ws->flag + 32) & 1;
    __nanosleep(RDELAY);
    if (threadIdx.x < 16) prefetch_l2(wo + (144 * e + 9 * threadIdx.x) * 1152, 9 * 1152);
#pragma unroll 1
    for (int r = threadIdx.x >> 3; r < 144; r += 48) {
      const uint4* row = (const uint4*)(wo + (144 * e + r) * 1152) + (threadIdx.x & 7);
      float a = 0.f;
      uint4 u;
#pragma unroll
      for (int i = 0; i < 72; i += 8) {
        u = __ldg(row + i);
        a += ((bf_lo(u.x) + bf_hi(u.x)) + (bf_lo(u.y) + bf_hi(u.y))) + ((bf_lo(u.z) + bf_hi(u.z)) + (bf_lo(u.w) + bf_hi(u.w)));
      }
      const int h = r >= 72, k = r - 72 * h;
      ((Scratch*)ws)->woc[threadIdx.x & 7][k < 64 ? 64 + 8 * k + ((2 * e + h) ^ (k & 7)) : 576 * h + 8 * (k & 7) + (e ^ (k & 7))] = u;
      a = quad_sum(a);
      a += __shfl_xor_sync(0xffffffffu, a, 4);
      if ((threadIdx.x & 7) == 0) ((Scratch*)ws)->woc[2 * e + h][640 + k] = make_uint4(pack_bf16(a, a - bf_lo(pack_bf16(a, 0.f))), 0, 0, 0);
    }
    fence_gpu();
    __syncthreads();
    if (threadIdx.x == 0) st_relaxed(((Scratch*)ws)->done + e, par);
    const int cc = threadIdx.x % 54, r0 = threadIdx.x / 54, part = cc / 18, jj = 2 * e + (cc % 18) / 9, c9 = cc % 9;
    if (r0 < 6) {
#pragma unroll 4
      for (int k = r0; k < 576; k += 6) {
        const uint4 u = __ldg((const uint4*)(wqkv + k * 3456 + part * 1152 + 144 * jj) + c9);
        ((Scratch*)ws)->wq[jj][k >> 4][c9 < 8 ? part * 128 + (k & 15) * 8 + (c9 ^ (k & 7)) : 384 + part * 16 + (k & 15)] = u;
      }
    }
    fence_gpu();
    __syncthreads();
    if (threadIdx.x == 0) st_relaxed(((Scratch*)ws)->done + 32 + e, par);
    return;
  }
  if (threadIdx.x == 0) asm volatile("prefetch.tensormap [%0];" ::"l"(&maps.x) : "memory");
  const int warp = __shfl_sync(0xffffffffu, threadIdx.x >> 5, 0);
  const int lane = threadIdx.x & 31;
  const int rank = blockIdx.x & 1;
  if (elect_one()) {
    if (warp >= 8) {
#pragma unroll
      for (int i = 0; i < 9; i++) mbar_init(sb + SM_BAR + 72 * (warp - 8) + 8 * i, warp < 10 ? 1 : 4);
      sts32(sb + SM_PROG + 4 * (warp - 8), 0);
      asm volatile("fence.mbarrier_init.release.cluster;" ::: "memory");
    } else if (warp == 1 || warp == 2) {
      asm volatile("prefetch.tensormap [%0];" ::"l"(&maps.x + warp) : "memory");
    } else if (warp == 3) {
      if (PFMODE & 1) prefetch_l2((const char*)x_in + bx * 18432, 18432);
    } else if (warp == 4) {
      if (PFMODE & 2) prefetch_l2(wqkv + bx * (15552 / PFQ), 15552 / PFQ);
    }
  }
  __syncwarp();
  asm volatile("barrier.cluster.arrive.relaxed.aligned;" ::: "memory");
  if (warp == 8) PROFX(53);
  int lb = bx;
  if (GPCMAP) {
    const int cl = bx >> 1, u = cl - 36;
    lb = (cl < 4 ? cl : cl < 36 ? 8 * ((cl - 4) & 7) + ((cl - 4) >> 3) + (((cl - 4) & 7) ? 0 : 4) : 8 * (1 + u % 7) + 4 + u / 7) * 2 + rank;
  }
#define CTA_J(b) (((b) >> 1) & 7)
#define CTA_RB(b) ((((b) >> 4) << 1) | ((b) & 1))
  const int j = CTA_J(lb), rb = CTA_RB(lb);

  PROF(23);
  if (warp >= 8) {
    asm volatile("setmaxnreg.dec.sync.aligned.u32 " STR(REGS_P) ";");
    auto x_chunk = [&](int cc) {
      mbar_expect_tx(sb + xin_bar(cc), 16384);
      tma3d(sb + xin_off(cc, 0), &maps.x, 64 * cc, 0, 64 * rb, sb + xin_bar(cc));
      tma3d(sb + xin_off(cc, 1), &maps.x, 64 * cc, 1, 64 * rb, sb + xin_bar(cc));
    };
    if (warp == 9 && elect_one()) {
      fence_async_smem();
#pragma unroll 1
      for (int i = 0; i < 9; i++) x_chunk(i);
    }
    __syncwarp();
    if (warp == 9) PROFX(54);
    asm volatile("barrier.cluster.wait.aligned;" ::: "memory");
    if (warp == 8) PROFX(56);
    const uint64_t pol = W_POLICY(), pola = A_POLICY();
    uint4 (* const wq)[432] = ((Scratch*)ws)->wq[j];
    const uint32_t par = ~ld_relaxed(ws[2 * rb].flag + 32 + 32 * j) & 1;
    auto qkv_group = [&](bool copy, int k, uint32_t dst, uint32_t bar) {
      if (copy) {
        wbulk(dst + rank * 8192, wq[(k >> 4) + rank], 6912, bar, pol);
      } else {
        wtma3d(dst + rank * 8192, &maps.qm, 72 * j, k + 16 * rank, 0, bar, pola);
        wtma3d(dst + rank * 8192 + 6144, &maps.qc, 72 * j + 64, k + 16 * rank, 0, bar, pola);
      }
    };
    auto chore = [&](int i) {
#pragma unroll 1
      for (int it = 0; it < SPIN_MAX; it++)
        if (__all_sync(0xffffffffu, ld_acquire(((Scratch*)ws)->done + i) == par)) break;
      asm volatile("fence.proxy.async.global;" ::: "memory");
    };
    const int ktab = group_k0(lane, j);
    auto qkv_gate = [&](int g) { if (g >= 8) gate(sb + SM_PROG, 33 + ((g - 8) * QPACE >> 4)); };
    if (warp == 8) {
      uint32_t s = 0, ph = 1;
      auto slot = [&](uint32_t bytes, auto&& issue) {
        const uint32_t bar = sb + BAR_FULLB + 8 * s;
        mbar_wait(sb + BAR_EMPTYB + 8 * s, ph);
        if (elect_one()) {
          mbar_expect_tx(bar, bytes);
          issue(sb + SM_B + s * BSLOT, bar);
        }
        if (++s == 5) { s = 0; ph ^= 1; }
      };
#pragma unroll 1
      for (int layer = 0; layer < NLAYERS; layer++) {
        if (layer) chore(32 + (j >> 1));
#pragma unroll 1
        for (int g = 0; g < 18 - layer; g += layer && g == 4 ? 8 : 1) {
          const int k = layer ? __shfl_sync(0xffffffffu, ktab, g) : 32 * g;
          if (layer) qkv_gate(g);
          else if (g == QD) mbar_wait(sb + xin_bar(XH), 0);
          slot(2 * 6912, [&](uint32_t dst, uint32_t bar) { qkv_group(layer, k, dst, bar); });
        }
        if (!FCH) {
          gate(sb + SM_PROG, 32 * layer + 20);
          gate(sb + SM_PROG + 4, 32 * layer + 20);
        }
#pragma unroll 1
        for (int t = 0; t < 5; t++) {
          const CUtensorMap* m = &maps.g + (t < 3 ? rank : 2 + rank);
          asm volatile("" : "+l"(m));
          const int c2 = t < 3 ? 9 * j + 2 * t : 18 * j + 3 + 3 * t;
          const uint32_t half = t < 3 ? 8192 : 6144;
          const uint64_t pt = layer == 0 && ((KEEPW >> t) & 1) ? pola : pol;
          auto tile = [&](int g) {
            const int k = __shfl_sync(0xffffffffu, ktab, g);
            slot(2 * half, [&](uint32_t dst, uint32_t bar) { wtma3d(dst + rank * half, m, 0, k, c2, bar, pt); });
          };
          int g = 0;
          if (t == 0) {
#pragma unroll 1
            for (; g < 5; g++) {
              mbar_wait(sb + BAR_FULLB + 8 * (s < FCH ? s + 5 - FCH : s - FCH), s < FCH ? ph : ph ^ 1);
              if (FG >= 0 && g == FN) gate(sb + SM_PROG + 4, 32 * layer + 20);
              tile(g);
            }
          }
#pragma unroll 1
          for (; g < 18; g++) tile(g);
        }
      }
    } else if (warp == 9) {
      uint32_t mE = 0;
      auto acquire = [&](uint32_t s) { mbar_wait(sb + BAR_EMPTYX + 8 * s, (mE >> s) & 1); mE ^= 1u << s; };
      auto landed = [&](uint32_t s) { mbar_wait(sb + BAR_FULLX + 8 * s, (mE >> s) & 1); };
      auto slot = [&](uint32_t s, const CUtensorMap* m, int col, int row, uint64_t pol) {
        acquire(s);
        if (elect_one()) {
          mbar_expect_tx(sb + BAR_FULLX + 8 * s, XSLOT);
          wtma2d(sb + xslot(s) + rank * 9216, m, col, row + 72 * rank, sb + BAR_FULLX + 8 * s, pol);
        }
      };
#pragma unroll 1
      for (int layer = 0; layer < NLAYERS; layer++) {
        if (layer) chore(32 + (j >> 1));
#pragma unroll 1
        for (int g = 5; g < 18 * layer; g += g == 11 ? 6 : 1) {
          const uint32_t s = qkv_xslot(g);
          const int k = __shfl_sync(0xffffffffu, ktab, g);
          if (g < 12) qkv_gate(g);
          acquire(s);
          if (elect_one()) {
            mbar_expect_tx(sb + BAR_FULLX + 8 * s, 2 * 6912);
            qkv_group(true, k, sb + xslot(s), sb + BAR_FULLX + 8 * s);
          }
          if (XCH & 1) landed(s);
        }
#pragma unroll 1
        for (int i = 0; i < 4; i++) { slot(4 + i, &maps.o, 64 * j, 144 * i, pola); if (XCH & 2) landed(4 + i); }
        if (layer == 0) { chore(lane & 3); PROFX(57); }
        acquire(3);
        if (elect_one()) {
          mbar_expect_tx(sb + BAR_FULLX + 24, 10240 + 1280);
          wbulk(sb + SM_WOC + rank * 5120, ((Scratch*)ws)->woc[j] + rank * 320, 5120, sb + BAR_FULLX + 24, pola);
          wbulk(sb + SM_WSUM + rank * 640, ((Scratch*)ws)->woc[j] + 640 + rank * 40, 640, sb + BAR_FULLX + 24, pola);
        }
#pragma unroll 1
        for (int u = 0; u < 36; u++) {
          const uint32_t s = 4 * (u & 1) + ((u >> 1) & 3);
          slot(s, &maps.d, u < 4 ? 512 : 64 * ((j + (u >> 2)) & 7), 576 * j + 144 * (u & 3), pol);
          if ((XCH & 4) && u < 3) landed(s);
        }
      }
    } else {
      const int w = warp - 10, grp = 2 * rb + w;
      if (PFMODE & 4) {
        mbar_wait(sb + xin_bar(XP), 0);
        if (lane == 0) prefetch_l2(wqkv + (2 * bx + w) * 7776, 7776);
      }
      gate(sb + SM_PROG, 3);
      if (w == 0) PROFX(58);
      auto prefetch_gu = [&](int l0, int n) {
#pragma unroll 1
        for (int i = lane; i < 36 * n; i += 32) {
          asm volatile("prefetch.global.L2 [%0];" ::"l"((w ? wu : wg) + (size_t)(36 * rb + i / n) * 9216 + 1152 * j + 128 * (l0 + i % n)));
          __nanosleep(PFSLEEP);
        }
      };
      auto clear = [&](uint4* p, int n) {
#pragma unroll 1
        for (int i = lane; i < n; i += 64) { st_relaxed4(p + i, 0, 0, 0, 0); st_relaxed4(p + i + 32, 0, 0, 0, 0); __nanosleep(CLRSLEEP); }
      };
      auto exchange = [&](uint32_t v, uint32_t bar) {
        if (FENCE1) { if (lane == 0) fence_gpu(); } else fence_gpu();
        __syncwarp();
        if (w == 0 && v != 1) PROFX(64 + 58 - 2 * v);
        if (lane == 0) st_relaxed(ws[grp].flag + j, v);
#pragma unroll 1
        for (int it = 0; it < SPIN_MAX; it++) {
          const uint32_t f = ld_relaxed(ws[grp].flag + (lane & 7));
          if (__all_sync(0xffffffffu, v ? f >= v : f == 0)) break;
        }
        if (lane == 0) mbar_arrive(sb + bar + 8 * w);
      };
      if (MAPPF && w == 0 && lane < 6) asm volatile("prefetch.tensormap [%0];" ::"l"(&maps.o + lane) : "memory");
#pragma unroll 1
      for (int layer = 0; layer < NLAYERS; layer++) {
        gate(sb + SM_PROG, 32 * layer + 3);
        if ((PFF & 1) && (layer == 0 || !(KEEPW & 1))) prefetch_gu(0, 2);
        gate(sb + SM_PROG, 32 * layer + 22);
        if (PFF & 2) prefetch_gu(2, 2);
        if (layer == 0) {
          clear(ws[grp].inbox[0] + 2 * j * INBOX, 2 * INBOX);
          exchange(1, BAR_CLR);
          if (w == 0) PROFX(59);
        }
        if (PFF & 2) prefetch_gu(4, 2);
        if (PFF & 4) prefetch_gu(6, 3);
#pragma unroll 1
        for (int i = lane; i < ((PFF & 8) ? 162 : 0); i += 32) {
          asm volatile("prefetch.global.L2 [%0];" ::"l"(wd + (size_t)(576 * j + 36 * rb + 18 * w) * 1152 + 128 * i));
          __nanosleep(PFSLEEP);
        }
        if (w == 0 && layer == 0) PROFX(60);
        mbar_wait(sb + BAR_REDDONE + 8 * w, layer);
        if (w == 0) PROFX(64 + 53 + 4 * layer);
        exchange(2 - 2 * layer, BAR_RREADY);
        if (w == 0) PROFX(64 + 56 + 4 * layer);
      }
      mbar_wait(sb + BAR_DONE + 8 * w, 0);
    }
  } else {
    asm volatile("setmaxnreg.inc.sync.aligned.u32 " STR(REGS_C) ";");
#define THREAD_IDS()                                                                   \
    int tid_ = threadIdx.x, bid_ = lb;                                                  \
    asm volatile("" : "+r"(tid_), "+r"(bid_));                                          \
    const int w = warp >> 2, wp = warp & 3;                                             \
    const int lane = tid_ & 31, t = tid_ & 127, g = lane >> 2, q = lane & 3;           \
    const int j = CTA_J(bid_), rb = CTA_RB(bid_), grp = 2 * rb + w;                    \
    const int st0 = wp * 64 + g;                         \
    Group* const G = ws + grp;                                                         \
    const uint32_t dsb = (sb & 0x3FFFF) >> 4;                                          \
    (void)t; (void)g; (void)q; (void)grp; (void)j; (void)st0; (void)dsb; (void)G
    Cons c;
    c.sb = sb; c.sB = 0; c.mB = 0; c.mX = 0; c.elect = (threadIdx.x & 127) == 0;
    asm volatile("mapa.shared::cluster.u32 %0, %1, %2;" : "=r"(c.rem) : "r"(sb), "r"(rank ^ 1));
    float v[36], a1[96], a2[12];
    float2 sum, rs;
    uint32_t res[18], xtag;
    auto qkv_mma = [&](bool acc, uint32_t bb, const uint4& f0, const uint4& f1) {
      wg_fence();
      wgmma_ra<192>(a1, f0, desc_hi(2048, 1024, 1) + bb, acc);
      wgmma_ra<24>(a2, f0, desc_hi(128, 256, 0) + (bb + 384), acc);
      wgmma_ra<192>(a1, f1, desc_hi(2048, 1024, 1) + (bb + 512), true);
      wgmma_ra<24>(a2, f1, desc_hi(128, 256, 0) + (bb + 896), true);
      wg_commit();
    };
    {
      THREAD_IDS();
      if (OPEN) {
        if (q == 0) { st_relaxed2(G->sum + st0 + 8 * j, 0, 0); st_relaxed2(G->sq + st0 + 8 * j, 0, 0); }
        if (wp == 3) {
#pragma unroll
          for (int i = 0; i < 5; i++) st_relaxed4(G->halo + j * 160 + lane + i * 32, 0, 0, 0, 0);
        }
        if (lane >= OPENL) st_relaxed4(G->obox + (8 * WPROBE + j) * 128 + t, 0, 0, 0, 0);
      }
      xtag = __shfl_sync(0xffffffffu, ~ld_relaxed(G->flag + 32 + 32 * j) & 1, 0);
      if (OPEN && EARLY && lane >= OPENL) st_relaxed4(G->xbox + (2 * j + 1) * 128 + t, xtag ^ 1, 0, 0, 0);
      asm volatile("barrier.cluster.wait.aligned;" ::: "memory");
      PROF(0);
#pragma unroll
      for (int i = 0; i < 96; i++) asm volatile("mov.b32 %0, 0;" : "=f"(a1[i]));
#pragma unroll
      for (int i = 0; i < 12; i++) asm volatile("mov.b32 %0, 0;" : "=f"(a2[i]));
      PROF(1);
      rs = ln_gemm_in(c, G, res, sum, w, st0, j, t, [&](int i) { PROF(2 + i); if (i) PROF(4); }, qkv_mma);
    }
#pragma unroll 1
    for (int layer = 0;; layer++) {
      const uint32_t tag = layer ^ 1;
      const int pb = 1 + layer * 30;
      uint4 own[5];
      {
        THREAD_IDS();
        PROF(pb + 4);
        uint32_t kv[3][18];
        auto cvt = [&](int b, float r) {
#pragma unroll
          for (int cc = 0; cc < 18; cc++) {
            const float* a = (cc == 8 ? a2 + 4 : cc == 17 ? a2 + 8 : cc < 8 ? a1 + 32 + 4 * cc : a1 + 28 + 4 * cc) + 2 * (b - 1);
            const uint32_t u = pack_bf16(a[0] * r, a[1] * r);
            kv[b][cc] = cc < 9 ? u : movm(u);
          }
        };
        cvt(2, rs.y);
#pragma unroll
        for (int i = 0; i < 18; i += 4) kv[2][i] = tagged(kv[2][i], tag);
        const uint32_t msg = sb + (w ? xslot(3) : xslot(0) + 24576) + wp * 2304 + lane * 16;
        if (wp == 3) {
          uint4* hp = G->halo + j * 160 + lane;
#pragma unroll
          for (int i = 0; i < 4; i++) st_relaxed4(hp + i * 32, kv[2][4 * i], kv[2][4 * i + 1], kv[2][4 * i + 2], kv[2][4 * i + 3]);
          st_relaxed2((uint2*)(hp + 128), kv[2][16], kv[2][17]);
        } else {
#pragma unroll
          for (int i = 0; i < 4; i++) sts128(msg + i * 512, kv[2][4 * i], kv[2][4 * i + 1], kv[2][4 * i + 2], kv[2][4 * i + 3]);
          sts64f(msg + 2048 - lane * 8, __uint_as_float(kv[2][16]), __uint_as_float(kv[2][17]));
        }
        cvt(1, rs.x);
        uint32_t Q[4][6];
#pragma unroll
        for (int h = 0; h < 4; h++)
#pragma unroll
          for (int i = 0; i < 6; i++) {
            const float* a = 4 * h + i < 16 ? a1 + 8 * h + 2 * i : a2 + 8 * h + 2 * i - 32;
            const uint32_t u = pack_bf16(a[0], a[1]);
            Q[h][i] = i < 2 ? (q >= h ? u : 0) : i < 4 ? u : (q <= h ? u : 0);
          }
        const bool lo0 = 2 * q > g, lo1 = 2 * q + 1 > g;
        const uint32_t M = (lo0 ? 0xffffu : 0u) | (lo1 ? 0xffff0000u : 0u);
        auto scores = [&](int h, int b, float (&s)[4]) {
          mma16816z(s, Q[h][0], Q[h][1], Q[h][2], Q[h][3], kv[b][2 * h], kv[b][2 * h + 1]);
          mma1688(s, Q[h][4], Q[h][5], kv[b][2 * h + 2]);
        };
        auto softmax = [&](float (&l)[4][2], float r, uint32_t (&P)[4]) {
          const float sl = r * (0.23570226039551584f * 1.4426950408889634f);
          float m[4];
#pragma unroll
          for (int h = 0; h < 4; h++) { m[h] = fmaxf(l[h][0], l[h][1]); m[h] = fmaxf(m[h], __shfl_xor_sync(0xffffffffu, m[h], 1)); }
#pragma unroll
          for (int h = 0; h < 4; h++) m[h] = fmaxf(m[h], __shfl_xor_sync(0xffffffffu, m[h], 2)) * sl;
#pragma unroll
          for (int h = 0; h < 4; h++) P[h] = pack_bf16(ex2(fmaf(l[h][0], sl, -m[h])), ex2(fmaf(l[h][1], sl, -m[h])));
        };
        const bool remote = wp == 0 && rb > 0;
        const uint4* hp = (G - 2)->halo + j * 160 + lane;
        auto halo = [&] {
#pragma unroll
          for (int i = 0; i < 4; i++) { const uint4 u = ld_relaxed4(hp + i * 32); kv[0][4 * i] = u.x; kv[0][4 * i + 1] = u.y; kv[0][4 * i + 2] = u.z; kv[0][4 * i + 3] = u.w; }
          const uint2 u = ld_relaxed2((const uint2*)(hp + 128));
          kv[0][16] = u.x; kv[0][17] = u.y;
        };
#pragma unroll
        for (int i = 0; i < 18; i++) kv[0][i] = 0;
        float l0[4][2], l1[4][2];
#pragma unroll
        for (int h = 0; h < 4; h++) {
          float s1[4], s2[4];
          scores(h, 1, s1); scores(h, 2, s2);
          l0[h][0] = s1[0]; l0[h][1] = s1[1];
          l1[h][0] = lo0 ? s1[2] : s2[2]; l1[h][1] = lo1 ? s1[3] : s2[3];
        }
        hp += __float_as_uint(l1[HALOH][0]) & late(sb + BAR_FULLX + 64, 0);
        if (remote) halo();
        uint32_t P0[4], P1[4];
        softmax(l1, rs.y, P1);
        if (remote) {
          while (__any_sync(0xffffffffu, chk(chk2(kv[0][0], kv[0][4], tag) | chk2(kv[0][8], kv[0][12], tag), kv[0][16], tag) & 1)) halo();
        }
        if (FG < 0) c.progress(32 * layer + 20);
        wg_bar(w);
        if (wp > 0) {
          const uint32_t from = msg - 2304;
#pragma unroll
          for (int i = 0; i < 4; i++) { const uint4 u = lds128(from + i * 512); kv[0][4 * i] = u.x; kv[0][4 * i + 1] = u.y; kv[0][4 * i + 2] = u.z; kv[0][4 * i + 3] = u.w; }
          const float2 u = lds64(from + 2048 - lane * 8);
          kv[0][16] = __float_as_uint(u.x); kv[0][17] = __float_as_uint(u.y);
        }
        PROF(pb + 5);
        const bool first = (rb == 0 && wp == 0);
#pragma unroll
        for (int h = 0; h < 4; h++) {
          float s0[4];
          scores(h, 0, s0);
          if (first) s0[0] = s0[1] = -INFINITY;
          l0[h][0] = lo0 ? s0[0] : l0[h][0]; l0[h][1] = lo1 ? s0[1] : l0[h][1];
        }
        softmax(l0, rs.x, P0);
        uint4* ob = G->obox + t;
        uint32_t car0 = 0, car1 = 0;
#pragma unroll
        for (int h = 0; h < 4; h++) {
          float o[3][4], z[4] = {0.f, 0.f, 0.f, 0.f};
          mma1688(z, P0[h], P1[h], 0x3f803f80u);
#pragma unroll
          for (int i = 0; i < 3; i++) {
            mma16816z(o[i], P0[h] & ~M, P1[h] & M, 0u, P1[h] & ~M, kv[1][9 + 2 * h + i], kv[2][9 + 2 * h + i]);
            mma1688(o[i], P0[h] & M, 0u, kv[0][9 + 2 * h + i]);
          }
          const float i0 = rcp(z[0]), i1 = rcp(z[2]);
#pragma unroll
          for (int i = 0; i < 3; i++) { o[i][0] *= i0; o[i][1] *= i0; o[i][2] *= i1; o[i][3] *= i1; }
          const uint32_t o0 = q < h ? car0 : pack_bf16(o[0][0], o[0][1]), o1 = q < h ? car1 : pack_bf16(o[0][2], o[0][3]);
          own[h] = make_uint4(o0 | 1, o1, pack_bf16(o[1][0], o[1][1]), pack_bf16(o[1][2], o[1][3]));
          if (h < OFIRST) st_relaxed4(ob + (8 * h + j) * 128, own[h].x, own[h].y, own[h].z, own[h].w);
          car0 = pack_bf16(o[2][0], o[2][1]); car1 = pack_bf16(o[2][2], o[2][3]);
        }
        car0 = tagged(car0, tag);
        own[4] = make_uint4(car0, car1, 0, 0);
        PROF(pb + 6);
      }
      uint2 sa, sc;
      {
        THREAD_IDS();
        uint4* src = G->obox + t;
        asm volatile("" : "+l"(src));
        uint4 x[32];
        const uint4* from[7];
#pragma unroll
        for (int r = 0; r < 7; r++) { from[r] = src + (r >= j ? 128 : 0); asm volatile("" : "+l"(from[r])); }
        auto at = [&](int i) { return i < 28 ? from[i % 7] + (8 * (i / 7) + i % 7) * 128 : src + (i + 4) * 128; };
        auto load = [&](int i) { x[i] = ld_relaxed4(at(i)); };
        const uint32_t* probe = &(G->obox + (8 * WPROBE + (lane & 7)) * 128 + (t | 31))->x;
        uint32_t pv = ld_relaxed(probe);
#pragma unroll
        for (int i = 3; i < 8; i++) mbar_wait_c(sb + BAR_FULLX + 8 * i, (c.mX >> i) & 1);
        c.mX ^= 0xf8;
        while (__any_sync(0xffffffffu, ~pv & 1)) pv = ld_relaxed(probe);
        if (layer) PROF(24); else PROF(25);
        if (WOBAR && w == 1) asm volatile("bar.sync 7, 256;" ::: "memory");
#pragma unroll
        for (int i = 0; i < WB1; i++) load(i);
        if (WOBAR && w == 0) asm volatile("bar.arrive 7, 256;" ::: "memory");
#pragma unroll
        for (int h = OFIRST; h < 4; h++) st_relaxed4(src + (8 * h + j) * 128, own[h].x, own[h].y, own[h].z, own[h].w);
        st_relaxed2((uint2*)(src + (32 + (j >> 1)) * 128) + (j & 1), own[4].x, own[4].y);
        if (layer) PROF(26); else PROF(27);
        float a[36];
        float e[4];
        constexpr uint32_t NEXT = 576 - (575u << 16);
        auto step = [&](const uint4& f, uint32_t s, int i, uint32_t more, bool acc) {
          const uint32_t r = (xslot(4) >> 4) + (i < 4 ? 72 * s + 16 * i : 144 * s + 64) * 8, c = (SM_WOC >> 4) + (i < 4 ? 64 + 128 * i : 0) + s;
          wgmma_ra<72>(a, f, desc_hi(0, i < 4 ? 1024 : 9216, 1) + (dsb + more + (r + ((c - r) << 16))), acc);
        };
        if (OWNBAR) asm volatile("bar.sync 4, 256;" ::: "memory");
        wg_fence();
        if (EARLY) {
#pragma unroll
          for (int i = 0; i < 5; i++) wgmma_ra<8>(e, own[i], desc_hi(128, 0, 0) + (dsb + (SM_WSUM >> 4) + 16 * i), i > 0);
          wg_commit();
        }
#pragma unroll
        for (int i = 0; i < 4; i++) step(own[i], 0, i, j * NEXT, i > 0);
        wg_commit();
        if (layer) PROF(28); else PROF(29);
        auto batch = [&](auto e0, auto e1, auto e2, int b) {
          constexpr int E0 = decltype(e0)::v, E1 = decltype(e1)::v, E2 = decltype(e2)::v;
          const uint32_t one = (LATE0 || E0 > 0) && E1 > E0 ? late(sb + BAR_FULLX + 64, 1) : 1;
          while (E1 > E0) {
            uint32_t bad = 0;
#pragma unroll
            for (int i = E0; i < E1; i++) bad = i < 28 ? chk(bad, x[i].x, one) : chk(chk(bad, x[i].x, tag), x[i].z, tag);
            if (!__any_sync(0xffffffffu, bad & 1)) break;
#pragma unroll
            for (int i = E0; i < E1; i++) load(i);
          }
          if (b == 0) PROF(pb + 7);
          if (b == FG) c.progress(32 * layer + 20);
          if (b > 0 && E2 > E1) wg_wait<WOW>();
#pragma unroll
          for (int i = E1; i < E2; i++) load(i);
          if (EARLY && b == 0) {
            wg_wait<1>();
            if (q == 0) st_relaxed2(G->sum + st0 + 8 * j, (__float_as_uint(e[0] + e[1]) & ~3u) | ((2 * layer + 2) & 3), __float_as_uint(e[2] + e[3]));
          }
          if (EARLY && b == SUMB) { sa = ld_relaxed2(G->sum + st0 + 16 * q); sc = ld_relaxed2(G->sum + st0 + 16 * q + 8); }
          if (E1 > E0) {
            wg_fence();
#pragma unroll
            for (int i = E0; i < E1; i++) {
              step(x[i], i % 7, i / 7, i < 28 && i % 7 >= j ? NEXT : 0, true);
            }
            wg_commit();
          }
        };
        batch(IC<0>(), IC<WB1>(), IC<WB2>(), 0);
        batch(IC<WB1>(), IC<WB2>(), IC<WB3>(), 1);
        batch(IC<WB2>(), IC<WB3>(), IC<32>(), 2);
        batch(IC<WB3>(), IC<32>(), IC<32>(), 3);
        wg_wait<0>();
        if (w == 0) asm volatile("bar.arrive 3, 256;" ::: "memory");
        PROF(pb + 8);
#pragma unroll
        for (int i = 0; i < 18; i++) {
          v[2 * i] = bf_lo(res[i]) + a[2 * i];
          v[2 * i + 1] = bf_hi(res[i]) + a[2 * i + 1];
        }
      }
      uint32_t lsb;
      uint32_t h[144];
      {
        THREAD_IDS();
        float a[128];
        const uint32_t xd = sb + xslot(4 * w) + (lane >> 4) * 1024 + (16 * wp + (lane & 15)) * 16;
        const float2 rs = ln_gemm<false>(c, G, v, res, sum, st0, j, t, layer, xtag,
          [&](int i) {
            if (i == 0) {
              lsb = ((res[0] & 1) | (res[4] & 1) << 1 | (res[8] & 1) << 2 | (res[12] & 1) << 3 | (res[16] & 1) << 4) ^ (xtag * 31);
              if (EARLY) {
                const uint32_t st = late(sb + BAR_FULLX + 64, (2 * layer + 2) & 3);
                while (__any_sync(0xffffffffu, chk2(sa.x, sc.x, st) & 3)) { sa = ld_relaxed2(G->sum + st0 + 16 * q); sc = ld_relaxed2(G->sum + st0 + 16 * q + 8); }
                sum.x += quad_sum(__uint_as_float(sa.x) + __uint_as_float(sc.x)); sum.y += quad_sum(__uint_as_float(sa.y) + __uint_as_float(sc.y));
              }
              if (w == 1) asm volatile("bar.sync 3, 256;" ::: "memory");
            }
            PROF(pb + 9 + i);
          },
          [&](int gi, uint32_t bb, const uint4& f0, const uint4& f1) {
            if (gi == 0) PROF(pb + 11);
            if (TLEAD0 && gi == 18 - TLEAD0 && w == 1) asm volatile("bar.sync 5, 256;" ::: "memory");
            wg_fence();
            wgmma_ra<256>(a, f0, desc_hi(4096, 1024, 1) + bb, gi > 0);
            wgmma_ra<256>(a, f1, desc_hi(4096, 1024, 1) + (bb + 128), true);
            wg_commit();
            if (TLEAD0 && gi == 17 && w == 0) asm volatile("bar.arrive 5, 256;" ::: "memory");
            stsm4(xd + gi * 4096, f0.x, f0.y, f0.z, f0.w);
            stsm4(xd + gi * 4096 + 2048, f1.x, f1.y, f1.z, f1.w);
            if (gi == 17) { fence_async_smem(); wg_bar(w); }
          });
        sts64f(sb + SM_KEEP + (tid_ >> 2) * 8, rs.x * rs.x, rs.y * rs.y);
        c.progress(32 * layer + 22);
        PROF2(pb + 12);
        glu<16, 0>(a, h);
        const Desc da0 = desc_hi(1024, 128, 0) + (dsb + (xslot(4 * w) >> 4));
        auto tile = [&](auto wide, auto last) {
          const uint32_t xe = BAR_EMPTYX + 32 * (t & 1) + 4 * (t & 6);
          auto group = [&](int gi) {
            uint32_t prev;
            const uint32_t bb = c.nextB(prev);
            const Desc da = da0 + gi * 256;
            wg_fence();
            if (wide()) {
              wgmma_ss<256>(a, da, desc_hi(4096, 1024, 1) + bb, gi);
              wgmma_ss<256>(a, da + 128, desc_hi(4096, 1024, 1) + (bb + 128), 1);
            } else {
              wgmma_ss<192>(*(float(*)[96])a, da, desc_hi(2048, 512, 2) + bb, gi);
              wgmma_ss<192>(*(float(*)[96])a, da + 128, desc_hi(2048, 512, 2) + (bb + 64), 1);
            }
            wg_commit();
            if (gi == 17 && w == 0) asm volatile("bar.arrive 5, 256;" ::: "memory");
            wg_wait<1>();
            if (gi > 0 && !(last() && gi > 13)) c.release2(BAR_EMPTYB + prev);
            if (last() && gi >= XREL && !((gi ^ XREL) & 1)) c.release2(BAR_EMPTYX + 16 * ((gi - XREL) & 2) + 2 * ((gi - XREL) & 12));
          };
          int gi = 0, end = w ? 18 - (wide() ? TLEAD2 : TLEAD) : 18;
#pragma unroll 1
          while (true) {
#pragma unroll 1
            for (; gi < end; gi++) group(gi);
            if (end == 18) break;
            asm volatile("bar.sync 5, 256;" ::: "memory");
            end = 18;
          }
          wg_wait<0>();
          if (!last()) c.releaseLastB();
          if (last() && t >= (19 - XREL) / 2 && t < 8) { mbar_arrive(sb + xe); mbar_arrive_remote(c.rem + xe); }
        };
        auto yes = [] { return true; };
        auto no = [] { return false; };
        tile(yes, no); PROF2(pb + 13); glu<16, 32>(a, h);
        tile(yes, no); PROF2(pb + 14); glu<16, 64>(a, h);
        tile(no, no); PROF2(pb + 15); glu<12, 96>(a, h);
        const uint32_t hole = sb + SM_B + 12288 + tid_ * 16;
#pragma unroll
        for (int i = 0; i < NSPILL; i++) sts128(hole + i * BSLOT, h[96 + 4 * i], h[97 + 4 * i], h[98 + 4 * i], h[99 + 4 * i]);
        if (w == 1) asm volatile("bar.arrive 8, 256;" ::: "memory");
        tile(no, yes); PROF2(pb + 16); glu<12, 120>(a, h);
#pragma unroll
        for (int i = 0; i < NSPILL; i++) { const uint4 u = lds128(hole + i * BSLOT); h[96 + 4 * i] = u.x; h[97 + 4 * i] = u.y; h[98 + 4 * i] = u.z; h[99 + 4 * i] = u.w; }
      }
      {
        THREAD_IDS();
        float d[32];
        uint4* gt = G->obox + t;
        asm volatile("" : "+l"(gt));
        uint4* const ib = gt + 2 * 4608 + layer * 8 * INBOX;
        auto pass = [&](uint32_t s0, bool last, auto&& hook) {
          const Desc db = desc_hi(0, 1024, 1) + (dsb + s0 * (XSLOT >> 4));
          mbar_wait_c(sb + BAR_FULLX + 8 * s0, (c.mX >> s0) & 1);
          if (RHOOK < 0) hook();
          asm volatile("bar.sync %0, 256;" ::"r"(8 + w) : "memory");
#pragma unroll
          for (int i = 0; i < 4; i++) {
            const int si = 4 * (i & 1) + (i >> 1);
            if (i > 0) mbar_wait_c(sb + BAR_FULLX + 8 * (s0 + si), (c.mX >> (s0 + si)) & 1);
            wg_fence();
#pragma unroll
            for (int k = 0; k < 9; k++) {
              const uint32_t* hk = h + 36 * i + 4 * k;
              wgmma_ra<64>(d, make_uint4(hk[0], hk[1], hk[2], hk[3]), db + ((xslot(si) >> 4) + k * 128), last || i + k > 0);
              if (9 * i + k == PPK && !(last && w == 1)) asm volatile("bar.arrive %0, 256;" ::"r"(9 - w) : "memory");
            }
            wg_commit();
            if (i > 0) { wg_wait<1>(); c.release2(BAR_EMPTYX + 8 * (s0 + 4 * ((i - 1) & 1) + ((i - 1) >> 1))); }
            if (i == RHOOK) hook();
          }
          c.mX ^= 0x33u << s0;
        };
        PROF2(pb + 17);
#pragma unroll 1
        for (int p = 0; p < 8; p++) {
          const uint32_t s0 = 2 * (p & 1);
          pass(s0, false, [] {});
          wg_wait<0>();
          c.release2(BAR_EMPTYX + 8 * (s0 + 5));
          if (p == 6 && layer == NLAYERS - 1) c.elect = false;
          uint32_t pk[16];
#pragma unroll
          for (int i = 0; i < 16; i++) pk[i] = pack_bf16(d[2 * i], d[2 * i + 1]);
          if (p >= BREL && p < BREL + 5 && layer < NLAYERS - 1) {
            const uint32_t o = c.sB + 8 * (p - BREL);
            c.release2(BAR_EMPTYB + (o < 40 ? o : o - 40));
          }
          uint4* const dst = ib + ((j + p) & 7) * INBOX;
          if (p == 0) {
            mbar_wait_c(sb + BAR_CLR + 8 * w, 0);
#pragma unroll
            for (int k = 0; k < 8; k++) red2((uint2*)(ib + k * INBOX + 512) - t, pk[2 * k], pk[2 * k + 1]);
          } else if (p < 7) {
#pragma unroll
            for (int k = 0; k < 4; k++) red4(dst + k * 128, pk[4 * k], pk[4 * k + 1], pk[4 * k + 2], pk[4 * k + 3]);
            if (p == 6) { __syncwarp(); if (lane == 0) mbar_arrive(sb + BAR_REDDONE + 8 * w); }
          } else {
#pragma unroll
            for (int k = 0; k < 4; k++) st_relaxed4(gt + ((j + 7) & 7) * 128 + k * 1024, pk[4 * k] & ~1u, pk[4 * k + 1], pk[4 * k + 2], pk[4 * k + 3]);
          }
        }
        PROF2(pb + 18);
        const uint4 *in = ib + j * INBOX, *pin = gt + j * 128;
        const uint2* in9 = (const uint2*)(in + 512) - t;
        asm volatile("" : "+l"(in), "+l"(pin), "+l"(in9));
        const float2 r2 = lds64(sb + SM_KEEP + (tid_ >> 2) * 8);
        uint2 X9;
        {
          uint4 X[4];
          const uint4* box = gt + 4608;
#pragma unroll
          for (int k = 0; k < 4; k++) X[k] = ld_relaxed4(box + 256 * j + ((k & 1) + 8 * (k & 2)) * 128);
          X9 = ld_relaxed2((const uint2*)(box + (32 + (j >> 1)) * 128) + (j & 1));
          const float i0 = rcp(r2.x), i1 = rcp(r2.y);
#pragma unroll
          for (int k = 0; k < 4; k++) {
            float* e = d + 8 * k;
            X[k].x ^= (lsb >> k) & 1;
            e[0] = bf_lo(X[k].x) * i0; e[1] = bf_hi(X[k].x) * i0; e[2] = bf_lo(X[k].y) * i1; e[3] = bf_hi(X[k].y) * i1;
            e[4] = bf_lo(X[k].z) * i0; e[5] = bf_hi(X[k].z) * i0; e[6] = bf_lo(X[k].w) * i1; e[7] = bf_hi(X[k].w) * i1;
          }
        }
        uint4 R[4], P[4];
        uint2 R9;
        PROF2(pb + 19);
        pass(0, true, [&] {
          mbar_wait_c(sb + BAR_RREADY + 8 * w, layer);
#pragma unroll
          for (int k = 0; k < 4; k++) R[k] = ld_relaxed4(in + k * 128);
          R9 = ld_relaxed2(in9);
#pragma unroll
          for (int k = 0; k < 4; k++) P[k] = ld_relaxed4(pin + k * 1024);
        });
        const uint32_t zero = late(sb + BAR_FULLX + 64, 0);
        while (__any_sync(0xffffffffu, (chk2(P[0].x, P[1].x, zero) | chk2(P[2].x, P[3].x, zero)) & 1)) {
#pragma unroll
          for (int k = 0; k < 4; k++) P[k] = ld_relaxed4(pin + k * 1024);
        }
#pragma unroll
        for (int k = 0; k < 4; k++) {
          const uint32_t u[4] = {hadd2(R[k].x, P[k].x), hadd2(R[k].y, P[k].y), hadd2(R[k].z, P[k].z), hadd2(R[k].w, P[k].w)};
#pragma unroll
          for (int i = 0; i < 4; i++) { v[8 * k + 2 * i] = bf_lo(u[i]); v[8 * k + 2 * i + 1] = bf_hi(u[i]); }
        }
        X9.x = chk(zero, X9.x, lsb >> 4);
        v[32] = fmaf(bf_lo(R9.x), r2.x, bf_lo(X9.x)); v[33] = fmaf(bf_hi(R9.x), r2.x, bf_hi(X9.x));
        v[34] = fmaf(bf_lo(R9.y), r2.y, bf_lo(X9.y)); v[35] = fmaf(bf_hi(R9.y), r2.y, bf_hi(X9.y));
        PROF2(pb + 20);
        wg_wait<0>();
        c.release2(BAR_EMPTYX + 40);
        PROF2(pb + 21);
#pragma unroll
        for (int i = 0; i < 32; i++) v[i] = (v[i] + d[i]) * (i & 2 ? r2.y : r2.x);
      }
      if (layer == NLAYERS - 1) break;
      {
        THREAD_IDS();
        PROF(31);
        rs = ln_gemm<true>(c, G, v, res, sum, st0, j, t, 1, xtag ^ 1, [&](int i) { PROF(32 + i); if (i) PROF(34); }, qkv_mma);
      }
    }
    {
      THREAD_IDS();
      const uint32_t stg = sb + SM_B + warp * 4096;
      const uint32_t sd = stg + (lane & 15) * 128;
#pragma unroll
      for (int i = 0; i < 4; i++)
        stsm4(sd + (((2 * i + (lane >> 4)) ^ (lane & 7)) << 4), pack_bf16(v[8 * i], v[8 * i + 1]), pack_bf16(v[8 * i + 2], v[8 * i + 3]),
              pack_bf16(v[8 * i + 4], v[8 * i + 5]), pack_bf16(v[8 * i + 6], v[8 * i + 7]));
      stsm2(stg + 2048 + (lane & 15) * 16, pack_bf16(v[32], v[33]), pack_bf16(v[34], v[35]));
      __syncwarp();
      char* o = out + (128 * rb + 32 * wp + w) * 1152;
#pragma unroll
      for (int i = 0; i < 4; i++) {
        const int r = 4 * i + (lane >> 3);
        *(uint4*)(o + r * 2304 + 128 * j + 16 * (lane & 7)) = lds128(stg + r * 128 + (((lane ^ r) & 7) << 4));
      }
      if (lane < 16) *(uint4*)(o + lane * 2304 + 1024 + 16 * j) = lds128(stg + 2048 + lane * 16);
      if (lane == 0) {
        if (wp == 0) st_relaxed(G->flag + 32 + 32 * j, xtag);
        mbar_arrive(sb + BAR_DONE + 8 * w);
      }
      PROF(61);
    }
  }
}

typedef CUresult (*EncFn)(CUtensorMap*, CUtensorMapDataType, cuuint32_t, void*, const cuuint64_t*, const cuuint64_t*, const cuuint32_t*,
                          const cuuint32_t*, CUtensorMapInterleave, CUtensorMapSwizzle, CUtensorMapL2promotion, CUtensorMapFloatOOBfill);

void make_map(EncFn enc, CUtensorMap* m, const void* p, int rank, uint64_t d0, uint64_t d1, uint64_t d2, uint64_t s1, uint64_t s2, uint32_t b0,
              uint32_t b1, uint32_t b2, CUtensorMapSwizzle sw) {
  cuuint64_t gd[3] = {d0, d1, d2};
  cuuint64_t gs[2] = {s1, s2};
  cuuint32_t bd[3] = {b0, b1, b2};
  cuuint32_t es[3] = {1, 1, 1};
  enc(m, CU_TENSOR_MAP_DATA_TYPE_BFLOAT16, rank, const_cast<void*>(p), gd, gs, bd, es, CU_TENSOR_MAP_INTERLEAVE_NONE, sw,
      CU_TENSOR_MAP_L2_PROMOTION_L2_128B, CU_TENSOR_MAP_FLOAT_OOB_FILL_NONE);
}

}

extern "C" void kernel_launch(void* const* d_in, const int* in_sizes, int n_in, void* d_out, int out_size) {
  const __nv_bfloat16* x = (const __nv_bfloat16*)d_in[0];
  const char *wqkv = (const char*)d_in[1], *wo = (const char*)d_in[2], *wg = (const char*)d_in[4], *wu = (const char*)d_in[5], *wd = (const char*)d_in[6];
  static EncFn enc = nullptr;
  static uint32_t first = 0;
  static Group* ws = nullptr;
  if (!enc) {
    cudaDriverEntryPointQueryResult qr;
    cudaGetDriverEntryPoint("cuTensorMapEncodeTiled", (void**)&enc, cudaEnableDefault, &qr);
    cudaGetSymbolAddress((void**)&ws, g_ws);
    cudaFuncSetAttribute(fused_kernel, cudaFuncAttributeMaxDynamicSharedMemorySize, SMEM_BYTES);
    cudaLaunchConfig_t cfg = {};
    cfg.gridDim = NCTA + 4; cfg.blockDim = 384; cfg.dynamicSmemBytes = SMEM_BYTES;
    int clusters = 0;
    if (XFIRST || cudaOccupancyMaxActiveClusters(&clusters, fused_kernel, &cfg) != cudaSuccess || 2 * clusters < NCTA + 4) first = 4;
    cudaGetLastError();
  }
  const CUtensorMapSwizzle S0 = CU_TENSOR_MAP_SWIZZLE_NONE, S64 = CU_TENSOR_MAP_SWIZZLE_64B, S128 = CU_TENSOR_MAP_SWIZZLE_128B;
  Maps m;
  make_map(enc, &m.x, x, 3, 576, 2, 1024, 1152, 2304, 64, 1, 64, S128);
  make_map(enc, &m.qm, wqkv, 3, 576, 576, 3, 3456, 1152, 64, 16, 3, S128);
  make_map(enc, &m.qc, wqkv, 3, 576, 576, 3, 3456, 1152, 8, 16, 3, S0);
  make_map(enc, &m.o, wo, 2, 576, 576, 1, 1152, 0, 64, 72, 1, S128);
  make_map(enc, &m.g, wg, 3, 64, 576, 72, 9216, 128, 64, 32, 2, S128);
  make_map(enc, &m.u, wu, 3, 64, 576, 72, 9216, 128, 64, 32, 2, S128);
  make_map(enc, &m.g3, wg, 3, 32, 576, 144, 9216, 64, 32, 32, 3, S64);
  make_map(enc, &m.u3, wu, 3, 32, 576, 144, 9216, 64, 32, 32, 3, S64);
  make_map(enc, &m.d, wd, 2, 576, 4608, 1, 1152, 0, 64, 72, 1, S128);
  fused_kernel<<<NCTA + 4, 384, SMEM_BYTES>>>(x, ws, wqkv, wo, (char*)d_out, first, m, wg, wu, wd);
}
```

```cpp
#include <cuda_runtime.h>
#include <cuda_bf16.h>
#include <cuda.h>
#include <stdint.h>
#include <stddef.h>

namespace {

constexpr int NCTA = 128;
#define NLAYERS 2
#define XFIRST 0
constexpr uint32_t SM_X = 0;
constexpr uint32_t XSLOT = 18432;
__host__ __device__ constexpr uint32_t xslot(uint32_t s) { return SM_X + (s ^ 4) * XSLOT; }
constexpr uint32_t SM_WOC = xslot(3) + 8192;
constexpr uint32_t SM_B = 147456;
constexpr uint32_t BSLOT = 16384;
constexpr uint32_t SM_KEEP = 229376;
constexpr uint32_t SM_WSUM = SM_KEEP + 512;
constexpr uint32_t SM_BAR = SM_KEEP + 2048;
constexpr uint32_t BAR_FULLB = SM_BAR;
constexpr uint32_t BAR_RREADY = SM_BAR + 40;
constexpr uint32_t BAR_CLR = SM_BAR + 56;
constexpr uint32_t BAR_FULLX = SM_BAR + 72;
constexpr uint32_t BAR_PAST = BAR_FULLX + 64;
constexpr uint32_t BAR_EMPTYB = SM_BAR + 144;
constexpr uint32_t BAR_EMPTYX = SM_BAR + 184;
constexpr uint32_t BAR_REDDONE = SM_BAR + 248;
constexpr uint32_t BAR_DONE = SM_BAR + 264;
constexpr uint32_t SM_PROG = SM_BAR + 288;
constexpr uint32_t SMEM_BYTES = SM_BAR + 1024;

struct Maps { CUtensorMap x, qm, qc, o, g, u, g3, u3, d; };

constexpr int INBOX = 576;
struct Group {
  uint2 sum[4 * 8 * 8];
  uint2 sq[4 * 8 * 8];
  uint32_t flag[1024];
  uint4 halo[8 * 160];
  uint4 obox[36 * 128];
  uint4 xbox[36 * 128];
  uint4 inbox[2][8 * INBOX];
};
struct Scratch { Group g[32]; uint4 wq[8][36][432]; uint4 woc[8][720]; uint32_t done[64]; };
__device__ __align__(1024) Scratch g_ws;
#define PROF(i)
#define PROFX(i)

struct Desc { uint32_t lo, hi; };
__device__ __forceinline__ constexpr Desc desc_hi(uint32_t lbo, uint32_t sbo, uint32_t sw) { return Desc{(lbo >> 4) << 16, (sbo >> 4) | sw << 30}; }
__device__ __forceinline__ constexpr Desc operator+(Desc d, uint32_t a) { return Desc{d.lo + a, d.hi}; }

template<int N> __device__ __forceinline__ void wgmma_ss(float (&d)[N / 2], Desc da, Desc db, int sc);
template<> __device__ __forceinline__ void wgmma_ss<192>(float (&d)[96], Desc da, Desc db, int sc) {
  asm volatile("{\n.reg .pred p;\n.reg .b64 a, b;\nsetp.ne.b32 p, %100, 0;\nmov.b64 a, {%96, %97};\nmov.b64 b, {%98, %99};\n"
    "wgmma.mma_async.sync.aligned.m64n192k16.f32.bf16.bf16 {%0,%1,%2,%3,%4,%5,%6,%7,%8,%9,%10,%11,%12,%13,%14,%15,%16,%17,%18,%19,%20,%21,%22,%23,%24,%25,%26,%27,%28,%29,%30,%31,%32,%33,%34,%35,%36,%37,%38,%39,%40,%41,%42,%43,%44,%45,%46,%47,%48,%49,%50,%51,%52,%53,%54,%55,%56,%57,%58,%59,%60,%61,%62,%63,%64,%65,%66,%67,%68,%69,%70,%71,%72,%73,%74,%75,%76,%77,%78,%79,%80,%81,%82,%83,%84,%85,%86,%87,%88,%89,%90,%91,%92,%93,%94,%95}, a, b, p, 1, 1, 0, 1;\n}\n"
    : "+f"(d[0]),"+f"(d[1]),"+f"(d[2]),"+f"(d[3]),"+f"(d[4]),"+f"(d[5]),"+f"(d[6]),"+f"(d[7]),"+f"(d[8]),"+f"(d[9]),"+f"(d[10]),"+f"(d[11]),"+f"(d[12]),"+f"(d[13]),"+f"(d[14]),"+f"(d[15]),"+f"(d[16]),"+f"(d[17]),"+f"(d[18]),"+f"(d[19]),"+f"(d[20]),"+f"(d[21]),"+f"(d[22]),"+f"(d[23]),"+f"(d[24]),"+f"(d[25]),"+f"(d[26]),"+f"(d[27]),"+f"(d[28]),"+f"(d[29]),"+f"(d[30]),"+f"(d[31]),"+f"(d[32]),"+f"(d[33]),"+f"(d[34]),"+f"(d[35]),"+f"(d[36]),"+f"(d[37]),"+f"(d[38]),"+f"(d[39]),"+f"(d[40]),"+f"(d[41]),"+f"(d[42]),"+f"(d[43]),"+f"(d[44]),"+f"(d[45]),"+f"(d[46]),"+f"(d[47]),"+f"(d[48]),"+f"(d[49]),"+f"(d[50]),"+f"(d[51]),"+f"(d[52]),"+f"(d[53]),"+f"(d[54]),"+f"(d[55]),"+f"(d[56]),"+f"(d[57]),"+f"(d[58]),"+f"(d[59]),"+f"(d[60]),"+f"(d[61]),"+f"(d[62]),"+f"(d[63]),"+f"(d[64]),"+f"(d[65]),"+f"(d[66]),"+f"(d[67]),"+f"(d[68]),"+f"(d[69]),"+f"(d[70]),"+f"(d[71]),"+f"(d[72]),"+f"(d[73]),"+f"(d[74]),"+f"(d[75]),"+f"(d[76]),"+f"(d[77]),"+f"(d[78]),"+f"(d[79]),"+f"(d[80]),"+f"(d[81]),"+f"(d[82]),"+f"(d[83]),"+f"(d[84]),"+f"(d[85]),"+f"(d[86]),"+f"(d[87]),"+f"(d[88]),"+f"(d[89]),"+f"(d[90]),"+f"(d[91]),"+f"(d[92]),"+f"(d[93]),"+f"(d[94]),"+f"(d[95]) : "r"(da.lo), "r"(da.hi), "r"(db.lo), "r"(db.hi), "r"(sc));
}
template<> __device__ __forceinline__ void wgmma_ss<256>(float (&d)[128], Desc da, Desc db, int sc) {
  asm volatile("{\n.reg .pred p;\n.reg .b64 a, b;\nsetp.ne.b32 p, %132, 0;\nmov.b64 a, {%128, %129};\nmov.b64 b, {%130, %131};\n"
    "wgmma.mma_async.sync.aligned.m64n256k16.f32.bf16.bf16 {%0,%1,%2,%3,%4,%5,%6,%7,%8,%9,%10,%11,%12,%13,%14,%15,%16,%17,%18,%19,%20,%21,%22,%23,%24,%25,%26,%27,%28,%29,%30,%31,%32,%33,%34,%35,%36,%37,%38,%39,%40,%41,%42,%43,%44,%45,%46,%47,%48,%49,%50,%51,%52,%53,%54,%55,%56,%57,%58,%59,%60,%61,%62,%63,%64,%65,%66,%67,%68,%69,%70,%71,%72,%73,%74,%75,%76,%77,%78,%79,%80,%81,%82,%83,%84,%85,%86,%87,%88,%89,%90,%91,%92,%93,%94,%95,%96,%97,%98,%99,%100,%101,%102,%103,%104,%105,%106,%107,%108,%109,%110,%111,%112,%113,%114,%115,%116,%117,%118,%119,%120,%121,%122,%123,%124,%125,%126,%127}, a, b, p, 1, 1, 0, 1;\n}\n"
    : "+f"(d[0]),"+f"(d[1]),"+f"(d[2]),"+f"(d[3]),"+f"(d[4]),"+f"(d[5]),"+f"(d[6]),"+f"(d[7]),"+f"(d[8]),"+f"(d[9]),"+f"(d[10]),"+f"(d[11]),"+f"(d[12]),"+f"(d[13]),"+f"(d[14]),"+f"(d[15]),"+f"(d[16]),"+f"(d[17]),"+f"(d[18]),"+f"(d[19]),"+f"(d[20]),"+f"(d[21]),"+f"(d[22]),"+f"(d[23]),"+f"(d[24]),"+f"(d[25]),"+f"(d[26]),"+f"(d[27]),"+f"(d[28]),"+f"(d[29]),"+f"(d[30]),"+f"(d[31]),"+f"(d[32]),"+f"(d[33]),"+f"(d[34]),"+f"(d[35]),"+f"(d[36]),"+f"(d[37]),"+f"(d[38]),"+f"(d[39]),"+f"(d[40]),"+f"(d[41]),"+f"(d[42]),"+f"(d[43]),"+f"(d[44]),"+f"(d[45]),"+f"(d[46]),"+f"(d[47]),"+f"(d[48]),"+f"(d[49]),"+f"(d[50]),"+f"(d[51]),"+f"(d[52]),"+f"(d[53]),"+f"(d[54]),"+f"(d[55]),"+f"(d[56]),"+f"(d[57]),"+f"(d[58]),"+f"(d[59]),"+f"(d[60]),"+f"(d[61]),"+f"(d[62]),"+f"(d[63]),"+f"(d[64]),"+f"(d[65]),"+f"(d[66]),"+f"(d[67]),"+f"(d[68]),"+f"(d[69]),"+f"(d[70]),"+f"(d[71]),"+f"(d[72]),"+f"(d[73]),"+f"(d[74]),"+f"(d[75]),"+f"(d[76]),"+f"(d[77]),"+f"(d[78]),"+f"(d[79]),"+f"(d[80]),"+f"(d[81]),"+f"(d[82]),"+f"(d[83]),"+f"(d[84]),"+f"(d[85]),"+f"(d[86]),"+f"(d[87]),"+f"(d[88]),"+f"(d[89]),"+f"(d[90]),"+f"(d[91]),"+f"(d[92]),"+f"(d[93]),"+f"(d[94]),"+f"(d[95]),"+f"(d[96]),"+f"(d[97]),"+f"(d[98]),"+f"(d[99]),"+f"(d[100]),"+f"(d[101]),"+f"(d[102]),"+f"(d[103]),"+f"(d[104]),"+f"(d[105]),"+f"(d[106]),"+f"(d[107]),"+f"(d[108]),"+f"(d[109]),"+f"(d[110]),"+f"(d[111]),"+f"(d[112]),"+f"(d[113]),"+f"(d[114]),"+f"(d[115]),"+f"(d[116]),"+f"(d[117]),"+f"(d[118]),"+f"(d[119]),"+f"(d[120]),"+f"(d[121]),"+f"(d[122]),"+f"(d[123]),"+f"(d[124]),"+f"(d[125]),"+f"(d[126]),"+f"(d[127]) : "r"(da.lo), "r"(da.hi), "r"(db.lo), "r"(db.hi), "r"(sc));
}
template<int N, int ACC> __device__ __forceinline__ void wgmma_rs(float (&d)[N / 2], const uint4& a, Desc db);
template<> __device__ __forceinline__ void wgmma_rs<8, 1>(float (&d)[4], const uint4& a, Desc db) {
  asm volatile("{\n.reg .pred p;\n.reg .b64 b;\nsetp.ne.b32 p, 1, 0;\nmov.b64 b, {%8, %9};\n"
    "wgmma.mma_async.sync.aligned.m64n8k16.f32.bf16.bf16 {%0,%1,%2,%3}, {%4,%5,%6,%7}, b, p, 1, 1, 1;\n}\n"
    : "+f"(d[0]),"+f"(d[1]),"+f"(d[2]),"+f"(d[3]) : "r"(a.x), "r"(a.y), "r"(a.z), "r"(a.w), "r"(db.lo), "r"(db.hi));
}
template<> __device__ __forceinline__ void wgmma_rs<8, 0>(float (&d)[4], const uint4& a, Desc db) {
  asm volatile("{\n.reg .pred p;\n.reg .b64 b;\nsetp.ne.b32 p, 0, 0;\nmov.b64 b, {%8, %9};\n"
    "wgmma.mma_async.sync.aligned.m64n8k16.f32.bf16.bf16 {%0,%1,%2,%3}, {%4,%5,%6,%7}, b, p, 1, 1, 1;\n}\n"
    : "=f"(d[0]),"=f"(d[1]),"=f"(d[2]),"=f"(d[3]) : "r"(a.x), "r"(a.y), "r"(a.z), "r"(a.w), "r"(db.lo), "r"(db.hi));
}
template<> __device__ __forceinline__ void wgmma_rs<24, 1>(float (&d)[12], const uint4& a, Desc db) {
  asm volatile("{\n.reg .pred p;\n.reg .b64 b;\nsetp.ne.b32 p, 1, 0;\nmov.b64 b, {%16, %17};\n"
    "wgmma.mma_async.sync.aligned.m64n24k16.f32.bf16.bf16 {%0,%1,%2,%3,%4,%5,%6,%7,%8,%9,%10,%11}, {%12,%13,%14,%15}, b, p, 1, 1, 1;\n}\n"
    : "+f"(d[0]),"+f"(d[1]),"+f"(d[2]),"+f"(d[3]),"+f"(d[4]),"+f"(d[5]),"+f"(d[6]),"+f"(d[7]),"+f"(d[8]),"+f"(d[9]),"+f"(d[10]),"+f"(d[11]) : "r"(a.x), "r"(a.y), "r"(a.z), "r"(a.w), "r"(db.lo), "r"(db.hi));
}
template<> __device__ __forceinline__ void wgmma_rs<24, 0>(float (&d)[12], const uint4& a, Desc db) {
  asm volatile("{\n.reg .pred p;\n.reg .b64 b;\nsetp.ne.b32 p, 0, 0;\nmov.b64 b, {%16, %17};\n"
    "wgmma.mma_async.sync.aligned.m64n24k16.f32.bf16.bf16 {%0,%1,%2,%3,%4,%5,%6,%7,%8,%9,%10,%11}, {%12,%13,%14,%15}, b, p, 1, 1, 1;\n}\n"
    : "=f"(d[0]),"=f"(d[1]),"=f"(d[2]),"=f"(d[3]),"=f"(d[4]),"=f"(d[5]),"=f"(d[6]),"=f"(d[7]),"=f"(d[8]),"=f"(d[9]),"=f"(d[10]),"=f"(d[11]) : "r"(a.x), "r"(a.y), "r"(a.z), "r"(a.w), "r"(db.lo), "r"(db.hi));
}
template<> __device__ __forceinline__ void wgmma_rs<64, 1>(float (&d)[32], const uint4& a, Desc db) {
  asm volatile("{\n.reg .pred p;\n.reg .b64 b;\nsetp.ne.b32 p, 1, 0;\nmov.b64 b, {%36, %37};\n"
    "wgmma.mma_async.sync.aligned.m64n64k16.f32.bf16.bf16 {%0,%1,%2,%3,%4,%5,%6,%7,%8,%9,%10,%11,%12,%13,%14,%15,%16,%17,%18,%19,%20,%21,%22,%23,%24,%25,%26,%27,%28,%29,%30,%31}, {%32,%33,%34,%35}, b, p, 1, 1, 1;\n}\n"
    : "+f"(d[0]),"+f"(d[1]),"+f"(d[2]),"+f"(d[3]),"+f"(d[4]),"+f"(d[5]),"+f"(d[6]),"+f"(d[7]),"+f"(d[8]),"+f"(d[9]),"+f"(d[10]),"+f"(d[11]),"+f"(d[12]),"+f"(d[13]),"+f"(d[14]),"+f"(d[15]),"+f"(d[16]),"+f"(d[17]),"+f"(d[18]),"+f"(d[19]),"+f"(d[20]),"+f"(d[21]),"+f"(d[22]),"+f"(d[23]),"+f"(d[24]),"+f"(d[25]),"+f"(d[26]),"+f"(d[27]),"+f"(d[28]),"+f"(d[29]),"+f"(d[30]),"+f"(d[31]) : "r"(a.x), "r"(a.y), "r"(a.z), "r"(a.w), "r"(db.lo), "r"(db.hi));
}
template<> __device__ __forceinline__ void wgmma_rs<64, 0>(float (&d)[32], const uint4& a, Desc db) {
  asm volatile("{\n.reg .pred p;\n.reg .b64 b;\nsetp.ne.b32 p, 0, 0;\nmov.b64 b, {%36, %37};\n"
    "wgmma.mma_async.sync.aligned.m64n64k16.f32.bf16.bf16 {%0,%1,%2,%3,%4,%5,%6,%7,%8,%9,%10,%11,%12,%13,%14,%15,%16,%17,%18,%19,%20,%21,%22,%23,%24,%25,%26,%27,%28,%29,%30,%31}, {%32,%33,%34,%35}, b, p, 1, 1, 1;\n}\n"
    : "=f"(d[0]),"=f"(d[1]),"=f"(d[2]),"=f"(d[3]),"=f"(d[4]),"=f"(d[5]),"=f"(d[6]),"=f"(d[7]),"=f"(d[8]),"=f"(d[9]),"=f"(d[10]),"=f"(d[11]),"=f"(d[12]),"=f"(d[13]),"=f"(d[14]),"=f"(d[15]),"=f"(d[16]),"=f"(d[17]),"=f"(d[18]),"=f"(d[19]),"=f"(d[20]),"=f"(d[21]),"=f"(d[22]),"=f"(d[23]),"=f"(d[24]),"=f"(d[25]),"=f"(d[26]),"=f"(d[27]),"=f"(d[28]),"=f"(d[29]),"=f"(d[30]),"=f"(d[31]) : "r"(a.x), "r"(a.y), "r"(a.z), "r"(a.w), "r"(db.lo), "r"(db.hi));
}
template<> __device__ __forceinline__ void wgmma_rs<72, 1>(float (&d)[36], const uint4& a, Desc db) {
  asm volatile("{\n.reg .pred p;\n.reg .b64 b;\nsetp.ne.b32 p, 1, 0;\nmov.b64 b, {%40, %41};\n"
    "wgmma.mma_async.sync.aligned.m64n72k16.f32.bf16.bf16 {%0,%1,%2,%3,%4,%5,%6,%7,%8,%9,%10,%11,%12,%13,%14,%15,%16,%17,%18,%19,%20,%21,%22,%23,%24,%25,%26,%27,%28,%29,%30,%31,%32,%33,%34,%35}, {%36,%37,%38,%39}, b, p, 1, 1, 1;\n}\n"
    : "+f"(d[0]),"+f"(d[1]),"+f"(d[2]),"+f"(d[3]),"+f"(d[4]),"+f"(d[5]),"+f"(d[6]),"+f"(d[7]),"+f"(d[8]),"+f"(d[9]),"+f"(d[10]),"+f"(d[11]),"+f"(d[12]),"+f"(d[13]),"+f"(d[14]),"+f"(d[15]),"+f"(d[16]),"+f"(d[17]),"+f"(d[18]),"+f"(d[19]),"+f"(d[20]),"+f"(d[21]),"+f"(d[22]),"+f"(d[23]),"+f"(d[24]),"+f"(d[25]),"+f"(d[26]),"+f"(d[27]),"+f"(d[28]),"+f"(d[29]),"+f"(d[30]),"+f"(d[31]),"+f"(d[32]),"+f"(d[33]),"+f"(d[34]),"+f"(d[35]) : "r"(a.x), "r"(a.y), "r"(a.z), "r"(a.w), "r"(db.lo), "r"(db.hi));
}
template<> __device__ __forceinline__ void wgmma_rs<72, 0>(float (&d)[36], const uint4& a, Desc db) {
  asm volatile("{\n.reg .pred p;\n.reg .b64 b;\nsetp.ne.b32 p, 0, 0;\nmov.b64 b, {%40, %41};\n"
    "wgmma.mma_async.sync.aligned.m64n72k16.f32.bf16.bf16 {%0,%1,%2,%3,%4,%5,%6,%7,%8,%9,%10,%11,%12,%13,%14,%15,%16,%17,%18,%19,%20,%21,%22,%23,%24,%25,%26,%27,%28,%29,%30,%31,%32,%33,%34,%35}, {%36,%37,%38,%39}, b, p, 1, 1, 1;\n}\n"
    : "=f"(d[0]),"=f"(d[1]),"=f"(d[2]),"=f"(d[3]),"=f"(d[4]),"=f"(d[5]),"=f"(d[6]),"=f"(d[7]),"=f"(d[8]),"=f"(d[9]),"=f"(d[10]),"=f"(d[11]),"=f"(d[12]),"=f"(d[13]),"=f"(d[14]),"=f"(d[15]),"=f"(d[16]),"=f"(d[17]),"=f"(d[18]),"=f"(d[19]),"=f"(d[20]),"=f"(d[21]),"=f"(d[22]),"=f"(d[23]),"=f"(d[24]),"=f"(d[25]),"=f"(d[26]),"=f"(d[27]),"=f"(d[28]),"=f"(d[29]),"=f"(d[30]),"=f"(d[31]),"=f"(d[32]),"=f"(d[33]),"=f"(d[34]),"=f"(d[35]) : "r"(a.x), "r"(a.y), "r"(a.z), "r"(a.w), "r"(db.lo), "r"(db.hi));
}
template<> __device__ __forceinline__ void wgmma_rs<192, 1>(float (&d)[96], const uint4& a, Desc db) {
  asm volatile("{\n.reg .pred p;\n.reg .b64 b;\nsetp.ne.b32 p, 1, 0;\nmov.b64 b, {%100, %101};\n"
    "wgmma.mma_async.sync.aligned.m64n192k16.f32.bf16.bf16 {%0,%1,%2,%3,%4,%5,%6,%7,%8,%9,%10,%11,%12,%13,%14,%15,%16,%17,%18,%19,%20,%21,%22,%23,%24,%25,%26,%27,%28,%29,%30,%31,%32,%33,%34,%35,%36,%37,%38,%39,%40,%41,%42,%43,%44,%45,%46,%47,%48,%49,%50,%51,%52,%53,%54,%55,%56,%57,%58,%59,%60,%61,%62,%63,%64,%65,%66,%67,%68,%69,%70,%71,%72,%73,%74,%75,%76,%77,%78,%79,%80,%81,%82,%83,%84,%85,%86,%87,%88,%89,%90,%91,%92,%93,%94,%95}, {%96,%97,%98,%99}, b, p, 1, 1, 1;\n}\n"
    : "+f"(d[0]),"+f"(d[1]),"+f"(d[2]),"+f"(d[3]),"+f"(d[4]),"+f"(d[5]),"+f"(d[6]),"+f"(d[7]),"+f"(d[8]),"+f"(d[9]),"+f"(d[10]),"+f"(d[11]),"+f"(d[12]),"+f"(d[13]),"+f"(d[14]),"+f"(d[15]),"+f"(d[16]),"+f"(d[17]),"+f"(d[18]),"+f"(d[19]),"+f"(d[20]),"+f"(d[21]),"+f"(d[22]),"+f"(d[23]),"+f"(d[24]),"+f"(d[25]),"+f"(d[26]),"+f"(d[27]),"+f"(d[28]),"+f"(d[29]),"+f"(d[30]),"+f"(d[31]),"+f"(d[32]),"+f"(d[33]),"+f"(d[34]),"+f"(d[35]),"+f"(d[36]),"+f"(d[37]),"+f"(d[38]),"+f"(d[39]),"+f"(d[40]),"+f"(d[41]),"+f"(d[42]),"+f"(d[43]),"+f"(d[44]),"+f"(d[45]),"+f"(d[46]),"+f"(d[47]),"+f"(d[48]),"+f"(d[49]),"+f"(d[50]),"+f"(d[51]),"+f"(d[52]),"+f"(d[53]),"+f"(d[54]),"+f"(d[55]),"+f"(d[56]),"+f"(d[57]),"+f"(d[58]),"+f"(d[59]),"+f"(d[60]),"+f"(d[61]),"+f"(d[62]),"+f"(d[63]),"+f"(d[64]),"+f"(d[65]),"+f"(d[66]),"+f"(d[67]),"+f"(d[68]),"+f"(d[69]),"+f"(d[70]),"+f"(d[71]),"+f"(d[72]),"+f"(d[73]),"+f"(d[74]),"+f"(d[75]),"+f"(d[76]),"+f"(d[77]),"+f"(d[78]),"+f"(d[79]),"+f"(d[80]),"+f"(d[81]),"+f"(d[82]),"+f"(d[83]),"+f"(d[84]),"+f"(d[85]),"+f"(d[86]),"+f"(d[87]),"+f"(d[88]),"+f"(d[89]),"+f"(d[90]),"+f"(d[91]),"+f"(d[92]),"+f"(d[93]),"+f"(d[94]),"+f"(d[95]) : "r"(a.x), "r"(a.y), "r"(a.z), "r"(a.w), "r"(db.lo), "r"(db.hi));
}
template<> __device__ __forceinline__ void wgmma_rs<192, 0>(float (&d)[96], const uint4& a, Desc db) {
  asm volatile("{\n.reg .pred p;\n.reg .b64 b;\nsetp.ne.b32 p, 0, 0;\nmov.b64 b, {%100, %101};\n"
    "wgmma.mma_async.sync.aligned.m64n192k16.f32.bf16.bf16 {%0,%1,%2,%3,%4,%5,%6,%7,%8,%9,%10,%11,%12,%13,%14,%15,%16,%17,%18,%19,%20,%21,%22,%23,%24,%25,%26,%27,%28,%29,%30,%31,%32,%33,%34,%35,%36,%37,%38,%39,%40,%41,%42,%43,%44,%45,%46,%47,%48,%49,%50,%51,%52,%53,%54,%55,%56,%57,%58,%59,%60,%61,%62,%63,%64,%65,%66,%67,%68,%69,%70,%71,%72,%73,%74,%75,%76,%77,%78,%79,%80,%81,%82,%83,%84,%85,%86,%87,%88,%89,%90,%91,%92,%93,%94,%95}, {%96,%97,%98,%99}, b, p, 1, 1, 1;\n}\n"
    : "=f"(d[0]),"=f"(d[1]),"=f"(d[2]),"=f"(d[3]),"=f"(d[4]),"=f"(d[5]),"=f"(d[6]),"=f"(d[7]),"=f"(d[8]),"=f"(d[9]),"=f"(d[10]),"=f"(d[11]),"=f"(d[12]),"=f"(d[13]),"=f"(d[14]),"=f"(d[15]),"=f"(d[16]),"=f"(d[17]),"=f"(d[18]),"=f"(d[19]),"=f"(d[20]),"=f"(d[21]),"=f"(d[22]),"=f"(d[23]),"=f"(d[24]),"=f"(d[25]),"=f"(d[26]),"=f"(d[27]),"=f"(d[28]),"=f"(d[29]),"=f"(d[30]),"=f"(d[31]),"=f"(d[32]),"=f"(d[33]),"=f"(d[34]),"=f"(d[35]),"=f"(d[36]),"=f"(d[37]),"=f"(d[38]),"=f"(d[39]),"=f"(d[40]),"=f"(d[41]),"=f"(d[42]),"=f"(d[43]),"=f"(d[44]),"=f"(d[45]),"=f"(d[46]),"=f"(d[47]),"=f"(d[48]),"=f"(d[49]),"=f"(d[50]),"=f"(d[51]),"=f"(d[52]),"=f"(d[53]),"=f"(d[54]),"=f"(d[55]),"=f"(d[56]),"=f"(d[57]),"=f"(d[58]),"=f"(d[59]),"=f"(d[60]),"=f"(d[61]),"=f"(d[62]),"=f"(d[63]),"=f"(d[64]),"=f"(d[65]),"=f"(d[66]),"=f"(d[67]),"=f"(d[68]),"=f"(d[69]),"=f"(d[70]),"=f"(d[71]),"=f"(d[72]),"=f"(d[73]),"=f"(d[74]),"=f"(d[75]),"=f"(d[76]),"=f"(d[77]),"=f"(d[78]),"=f"(d[79]),"=f"(d[80]),"=f"(d[81]),"=f"(d[82]),"=f"(d[83]),"=f"(d[84]),"=f"(d[85]),"=f"(d[86]),"=f"(d[87]),"=f"(d[88]),"=f"(d[89]),"=f"(d[90]),"=f"(d[91]),"=f"(d[92]),"=f"(d[93]),"=f"(d[94]),"=f"(d[95]) : "r"(a.x), "r"(a.y), "r"(a.z), "r"(a.w), "r"(db.lo), "r"(db.hi));
}
template<> __device__ __forceinline__ void wgmma_rs<256, 1>(float (&d)[128], const uint4& a, Desc db) {
  asm volatile("{\n.reg .pred p;\n.reg .b64 b;\nsetp.ne.b32 p, 1, 0;\nmov.b64 b, {%132, %133};\n"
    "wgmma.mma_async.sync.aligned.m64n256k16.f32.bf16.bf16 {%0,%1,%2,%3,%4,%5,%6,%7,%8,%9,%10,%11,%12,%13,%14,%15,%16,%17,%18,%19,%20,%21,%22,%23,%24,%25,%26,%27,%28,%29,%30,%31,%32,%33,%34,%35,%36,%37,%38,%39,%40,%41,%42,%43,%44,%45,%46,%47,%48,%49,%50,%51,%52,%53,%54,%55,%56,%57,%58,%59,%60,%61,%62,%63,%64,%65,%66,%67,%68,%69,%70,%71,%72,%73,%74,%75,%76,%77,%78,%79,%80,%81,%82,%83,%84,%85,%86,%87,%88,%89,%90,%91,%92,%93,%94,%95,%96,%97,%98,%99,%100,%101,%102,%103,%104,%105,%106,%107,%108,%109,%110,%111,%112,%113,%114,%115,%116,%117,%118,%119,%120,%121,%122,%123,%124,%125,%126,%127}, {%128,%129,%130,%131}, b, p, 1, 1, 1;\n}\n"
    : "+f"(d[0]),"+f"(d[1]),"+f"(d[2]),"+f"(d[3]),"+f"(d[4]),"+f"(d[5]),"+f"(d[6]),"+f"(d[7]),"+f"(d[8]),"+f"(d[9]),"+f"(d[10]),"+f"(d[11]),"+f"(d[12]),"+f"(d[13]),"+f"(d[14]),"+f"(d[15]),"+f"(d[16]),"+f"(d[17]),"+f"(d[18]),"+f"(d[19]),"+f"(d[20]),"+f"(d[21]),"+f"(d[22]),"+f"(d[23]),"+f"(d[24]),"+f"(d[25]),"+f"(d[26]),"+f"(d[27]),"+f"(d[28]),"+f"(d[29]),"+f"(d[30]),"+f"(d[31]),"+f"(d[32]),"+f"(d[33]),"+f"(d[34]),"+f"(d[35]),"+f"(d[36]),"+f"(d[37]),"+f"(d[38]),"+f"(d[39]),"+f"(d[40]),"+f"(d[41]),"+f"(d[42]),"+f"(d[43]),"+f"(d[44]),"+f"(d[45]),"+f"(d[46]),"+f"(d[47]),"+f"(d[48]),"+f"(d[49]),"+f"(d[50]),"+f"(d[51]),"+f"(d[52]),"+f"(d[53]),"+f"(d[54]),"+f"(d[55]),"+f"(d[56]),"+f"(d[57]),"+f"(d[58]),"+f"(d[59]),"+f"(d[60]),"+f"(d[61]),"+f"(d[62]),"+f"(d[63]),"+f"(d[64]),"+f"(d[65]),"+f"(d[66]),"+f"(d[67]),"+f"(d[68]),"+f"(d[69]),"+f"(d[70]),"+f"(d[71]),"+f"(d[72]),"+f"(d[73]),"+f"(d[74]),"+f"(d[75]),"+f"(d[76]),"+f"(d[77]),"+f"(d[78]),"+f"(d[79]),"+f"(d[80]),"+f"(d[81]),"+f"(d[82]),"+f"(d[83]),"+f"(d[84]),"+f"(d[85]),"+f"(d[86]),"+f"(d[87]),"+f"(d[88]),"+f"(d[89]),"+f"(d[90]),"+f"(d[91]),"+f"(d[92]),"+f"(d[93]),"+f"(d[94]),"+f"(d[95]),"+f"(d[96]),"+f"(d[97]),"+f"(d[98]),"+f"(d[99]),"+f"(d[100]),"+f"(d[101]),"+f"(d[102]),"+f"(d[103]),"+f"(d[104]),"+f"(d[105]),"+f"(d[106]),"+f"(d[107]),"+f"(d[108]),"+f"(d[109]),"+f"(d[110]),"+f"(d[111]),"+f"(d[112]),"+f"(d[113]),"+f"(d[114]),"+f"(d[115]),"+f"(d[116]),"+f"(d[117]),"+f"(d[118]),"+f"(d[119]),"+f"(d[120]),"+f"(d[121]),"+f"(d[122]),"+f"(d[123]),"+f"(d[124]),"+f"(d[125]),"+f"(d[126]),"+f"(d[127]) : "r"(a.x), "r"(a.y), "r"(a.z), "r"(a.w), "r"(db.lo), "r"(db.hi));
}
template<> __device__ __forceinline__ void wgmma_rs<256, 0>(float (&d)[128], const uint4& a, Desc db) {
  asm volatile("{\n.reg .pred p;\n.reg .b64 b;\nsetp.ne.b32 p, 0, 0;\nmov.b64 b, {%132, %133};\n"
    "wgmma.mma_async.sync.aligned.m64n256k16.f32.bf16.bf16 {%0,%1,%2,%3,%4,%5,%6,%7,%8,%9,%10,%11,%12,%13,%14,%15,%16,%17,%18,%19,%20,%21,%22,%23,%24,%25,%26,%27,%28,%29,%30,%31,%32,%33,%34,%35,%36,%37,%38,%39,%40,%41,%42,%43,%44,%45,%46,%47,%48,%49,%50,%51,%52,%53,%54,%55,%56,%57,%58,%59,%60,%61,%62,%63,%64,%65,%66,%67,%68,%69,%70,%71,%72,%73,%74,%75,%76,%77,%78,%79,%80,%81,%82,%83,%84,%85,%86,%87,%88,%89,%90,%91,%92,%93,%94,%95,%96,%97,%98,%99,%100,%101,%102,%103,%104,%105,%106,%107,%108,%109,%110,%111,%112,%113,%114,%115,%116,%117,%118,%119,%120,%121,%122,%123,%124,%125,%126,%127}, {%128,%129,%130,%131}, b, p, 1, 1, 1;\n}\n"
    : "=f"(d[0]),"=f"(d[1]),"=f"(d[2]),"=f"(d[3]),"=f"(d[4]),"=f"(d[5]),"=f"(d[6]),"=f"(d[7]),"=f"(d[8]),"=f"(d[9]),"=f"(d[10]),"=f"(d[11]),"=f"(d[12]),"=f"(d[13]),"=f"(d[14]),"=f"(d[15]),"=f"(d[16]),"=f"(d[17]),"=f"(d[18]),"=f"(d[19]),"=f"(d[20]),"=f"(d[21]),"=f"(d[22]),"=f"(d[23]),"=f"(d[24]),"=f"(d[25]),"=f"(d[26]),"=f"(d[27]),"=f"(d[28]),"=f"(d[29]),"=f"(d[30]),"=f"(d[31]),"=f"(d[32]),"=f"(d[33]),"=f"(d[34]),"=f"(d[35]),"=f"(d[36]),"=f"(d[37]),"=f"(d[38]),"=f"(d[39]),"=f"(d[40]),"=f"(d[41]),"=f"(d[42]),"=f"(d[43]),"=f"(d[44]),"=f"(d[45]),"=f"(d[46]),"=f"(d[47]),"=f"(d[48]),"=f"(d[49]),"=f"(d[50]),"=f"(d[51]),"=f"(d[52]),"=f"(d[53]),"=f"(d[54]),"=f"(d[55]),"=f"(d[56]),"=f"(d[57]),"=f"(d[58]),"=f"(d[59]),"=f"(d[60]),"=f"(d[61]),"=f"(d[62]),"=f"(d[63]),"=f"(d[64]),"=f"(d[65]),"=f"(d[66]),"=f"(d[67]),"=f"(d[68]),"=f"(d[69]),"=f"(d[70]),"=f"(d[71]),"=f"(d[72]),"=f"(d[73]),"=f"(d[74]),"=f"(d[75]),"=f"(d[76]),"=f"(d[77]),"=f"(d[78]),"=f"(d[79]),"=f"(d[80]),"=f"(d[81]),"=f"(d[82]),"=f"(d[83]),"=f"(d[84]),"=f"(d[85]),"=f"(d[86]),"=f"(d[87]),"=f"(d[88]),"=f"(d[89]),"=f"(d[90]),"=f"(d[91]),"=f"(d[92]),"=f"(d[93]),"=f"(d[94]),"=f"(d[95]),"=f"(d[96]),"=f"(d[97]),"=f"(d[98]),"=f"(d[99]),"=f"(d[100]),"=f"(d[101]),"=f"(d[102]),"=f"(d[103]),"=f"(d[104]),"=f"(d[105]),"=f"(d[106]),"=f"(d[107]),"=f"(d[108]),"=f"(d[109]),"=f"(d[110]),"=f"(d[111]),"=f"(d[112]),"=f"(d[113]),"=f"(d[114]),"=f"(d[115]),"=f"(d[116]),"=f"(d[117]),"=f"(d[118]),"=f"(d[119]),"=f"(d[120]),"=f"(d[121]),"=f"(d[122]),"=f"(d[123]),"=f"(d[124]),"=f"(d[125]),"=f"(d[126]),"=f"(d[127]) : "r"(a.x), "r"(a.y), "r"(a.z), "r"(a.w), "r"(db.lo), "r"(db.hi));
}
template<int N> __device__ __forceinline__ void wgmma_ra(float (&d)[N / 2], const uint4& a, Desc db, bool acc) {
  if (acc) wgmma_rs<N, 1>(d, a, db); else wgmma_rs<N, 0>(d, a, db);
}

__device__ __forceinline__ uint32_t smem_u32(const void* p) { return (uint32_t)__cvta_generic_to_shared(p); }
__device__ __forceinline__ void mbar_init(uint32_t bar, uint32_t cnt) { asm volatile("mbarrier.init.shared::cta.b64 [%0], %1;" ::"r"(bar), "r"(cnt)); }
__device__ __forceinline__ void mbar_expect_tx(uint32_t bar, uint32_t bytes) { asm volatile("mbarrier.arrive.expect_tx.shared::cta.b64 _, [%0], %1;" ::"r"(bar), "r"(bytes) : "memory"); }
__device__ __forceinline__ void mbar_arrive(uint32_t bar) { asm volatile("mbarrier.arrive.shared::cta.b64 _, [%0];" ::"r"(bar) : "memory"); }
__device__ __forceinline__ void mbar_arrive_remote(uint32_t rbar) { asm volatile("mbarrier.arrive.shared::cluster.b64 _, [%0];" ::"r"(rbar) : "memory"); }
__device__ __forceinline__ void mbar_wait(uint32_t bar, uint32_t parity) {
  asm volatile(
      "{\n.reg .pred p;\n.reg .u32 c;\nmov.u32 c, 0;\nLAB_WAIT:\nmbarrier.try_wait.parity.shared::cta.b64 p, [%0], %1;\n@p bra DONE;\n"
      "add.u32 c, c, 1;\nsetp.lt.u32 p, c, 1000000;\n@p bra LAB_WAIT;\ntrap;\nDONE:\n}\n" ::"r"(bar), "r"(parity) : "memory");
}
__device__ __forceinline__ void mbar_wait_c(uint32_t bar, uint32_t parity) {
  asm volatile("{\n.reg .pred p;\nLAB_WAIT:\nmbarrier.try_wait.parity.shared::cta.b64 p, [%0], %1;\n@!p bra LAB_WAIT;\n}\n" ::"r"(bar), "r"(parity) : "memory");
}
__device__ __forceinline__ uint32_t late(uint32_t bar, uint32_t v) {
  uint32_t r;
  asm volatile("{\n.reg .pred p;\nmbarrier.test_wait.parity.shared::cta.b64 p, [%1], 0;\nselp.b32 %0, %2, %1, p;\n}\n" : "=r"(r) : "r"(bar), "r"(v) : "memory");
  return r;
}
__device__ __forceinline__ void wtma2d(uint32_t dst, const CUtensorMap* m, int c0, int c1, uint32_t bar, uint64_t pol) {
  asm volatile("cp.async.bulk.tensor.2d.shared::cluster.global.mbarrier::complete_tx::bytes.multicast::cluster.L2::cache_hint [%0], [%1, {%3, %4}], [%2], %5, %6;"
               ::"r"(dst), "l"(m), "r"(bar), "r"(c0), "r"(c1), "h"((uint16_t)3), "l"(pol) : "memory");
}
__device__ __forceinline__ void wtma3d(uint32_t dst, const CUtensorMap* m, int c0, int c1, int c2, uint32_t bar, uint64_t pol) {
  asm volatile("cp.async.bulk.tensor.3d.shared::cluster.global.mbarrier::complete_tx::bytes.multicast::cluster.L2::cache_hint [%0], [%1, {%3, %4, %5}], [%2], %6, %7;"
               ::"r"(dst), "l"(m), "r"(bar), "r"(c0), "r"(c1), "r"(c2), "h"((uint16_t)3), "l"(pol) : "memory");
}
__device__ __forceinline__ void wbulk(uint32_t dst, const void* src, uint32_t bytes, uint32_t bar, uint64_t pol) {
  asm volatile("cp.async.bulk.shared::cluster.global.mbarrier::complete_tx::bytes.multicast::cluster.L2::cache_hint [%0], [%1], %2, [%3], %4, %5;"
               ::"r"(dst), "l"(src), "r"(bytes), "r"(bar), "h"((uint16_t)3), "l"(pol) : "memory");
}
__device__ __forceinline__ void tma3d(uint32_t dst, const CUtensorMap* m, int c0, int c1, int c2, uint32_t bar) {
  asm volatile("cp.async.bulk.tensor.3d.shared::cluster.global.mbarrier::complete_tx::bytes [%0], [%1, {%3, %4, %5}], [%2];"
               ::"r"(dst), "l"(m), "r"(bar), "r"(c0), "r"(c1), "r"(c2) : "memory");
}
__device__ __forceinline__ void prefetch_l2(const void* p, uint32_t bytes) { asm volatile("cp.async.bulk.prefetch.L2.global [%0], %1;" ::"l"(p), "r"(bytes) : "memory"); }
__device__ __forceinline__ uint64_t policy_evict_first() { uint64_t p; asm volatile("createpolicy.fractional.L2::evict_first.b64 %0, 1.0;" : "=l"(p)); return p; }
__device__ __forceinline__ uint64_t policy_evict_normal() { uint64_t p; asm volatile("createpolicy.fractional.L2::evict_normal.b64 %0, 1.0;" : "=l"(p)); return p; }
__device__ __forceinline__ void fence_async_smem() { asm volatile("fence.proxy.async.shared::cta;" ::: "memory"); }
__device__ __forceinline__ bool elect_one() {
  uint32_t p;
  asm volatile("{\n.reg .pred P;\nelect.sync _|P, 0xffffffff;\nselp.u32 %0, 1, 0, P;\n}\n" : "=r"(p));
  return p;
}
__device__ __forceinline__ void wg_fence() { asm volatile("wgmma.fence.sync.aligned;" ::: "memory"); }
__device__ __forceinline__ void wg_commit() { asm volatile("wgmma.commit_group.sync.aligned;" ::: "memory"); }
template <int n> __device__ __forceinline__ void wg_wait() { asm volatile("wgmma.wait_group.sync.aligned %0;" ::"n"(n) : "memory"); }
__device__ __forceinline__ void wg_bar(int w) { asm volatile("bar.sync %0, 128;" ::"r"(w + 1) : "memory"); }
__device__ __forceinline__ void fence_gpu() { asm volatile("fence.acq_rel.gpu;" ::: "memory"); }
__device__ __forceinline__ uint32_t ld_relaxed(const uint32_t* p) { uint32_t v; asm volatile("ld.relaxed.gpu.global.u32 %0, [%1];" : "=r"(v) : "l"(p) : "memory"); return v; }
__device__ __forceinline__ uint32_t ld_acquire(const uint32_t* p) { uint32_t v; asm volatile("ld.acquire.gpu.global.u32 %0, [%1];" : "=r"(v) : "l"(p) : "memory"); return v; }
__device__ __forceinline__ uint4 ld_relaxed4(const uint4* p) {
  uint4 v; asm volatile("ld.relaxed.gpu.global.v4.u32 {%0,%1,%2,%3}, [%4];" : "=r"(v.x), "=r"(v.y), "=r"(v.z), "=r"(v.w) : "l"(p) : "memory"); return v;
}
__device__ __forceinline__ uint2 ld_relaxed2(const uint2* p) {
  uint2 v; asm volatile("ld.relaxed.gpu.global.v2.u32 {%0,%1}, [%2];" : "=r"(v.x), "=r"(v.y) : "l"(p) : "memory"); return v;
}
__device__ __forceinline__ void st_relaxed(uint32_t* p, uint32_t a) { asm volatile("st.relaxed.gpu.global.u32 [%0], %1;" ::"l"(p), "r"(a) : "memory"); }
__device__ __forceinline__ void st_relaxed4(uint4* p, uint32_t a, uint32_t b, uint32_t c, uint32_t d) {
  asm volatile("st.relaxed.gpu.global.v4.u32 [%0], {%1,%2,%3,%4};" ::"l"(p), "r"(a), "r"(b), "r"(c), "r"(d) : "memory");
}
__device__ __forceinline__ void st_relaxed2(uint2* p, uint32_t a, uint32_t b) {
  asm volatile("st.relaxed.gpu.global.v2.u32 [%0], {%1,%2};" ::"l"(p), "r"(a), "r"(b) : "memory");
}
__device__ __forceinline__ void red4(uint4* p, uint32_t a, uint32_t b, uint32_t c, uint32_t d) {
  asm volatile("red.relaxed.gpu.global.add.noftz.v4.bf16x2 [%0], {%1,%2,%3,%4};" ::"l"(p), "r"(a), "r"(b), "r"(c), "r"(d) : "memory");
}
__device__ __forceinline__ void red2(uint2* p, uint32_t a, uint32_t b) {
  asm volatile("red.relaxed.gpu.global.add.noftz.v2.bf16x2 [%0], {%1,%2};" ::"l"(p), "r"(a), "r"(b) : "memory");
}
constexpr int SPIN_MAX = 1 << 21;
__device__ __forceinline__ uint32_t pack_bf16(float lo, float hi) { uint32_t r; asm("cvt.rn.bf16x2.f32 %0, %1, %2;" : "=r"(r) : "f"(hi), "f"(lo)); return r; }
__device__ __forceinline__ float bf_lo(uint32_t v) { return __uint_as_float(v << 16); }
__device__ __forceinline__ float bf_hi(uint32_t v) { return __uint_as_float(v & 0xffff0000u); }
__device__ __forceinline__ float2 lds64(uint32_t a) { float2 v; asm volatile("ld.shared.v2.f32 {%0,%1}, [%2];" : "=f"(v.x), "=f"(v.y) : "r"(a)); return v; }
__device__ __forceinline__ void sts64f(uint32_t a, float x, float y) { asm volatile("st.shared.v2.f32 [%0], {%1,%2};" ::"r"(a), "f"(x), "f"(y) : "memory"); }
__device__ __forceinline__ void sts32(uint32_t a, uint32_t x) { asm volatile("st.volatile.shared.b32 [%0], %1;" ::"r"(a), "r"(x) : "memory"); }
__device__ __forceinline__ void gate(uint32_t a, int need) {
#pragma unroll 1
  for (int it = 0; it < SPIN_MAX; it++) {
    int v; asm volatile("ld.volatile.shared.b32 %0, [%1];" : "=r"(v) : "r"(a) : "memory");
    if (v >= need) break;
    __nanosleep(32);
  }
}
__device__ __forceinline__ void sts128(uint32_t a, uint32_t x, uint32_t y, uint32_t z, uint32_t u) { asm volatile("st.shared.v4.b32 [%0], {%1,%2,%3,%4};" ::"r"(a), "r"(x), "r"(y), "r"(z), "r"(u) : "memory"); }
__device__ __forceinline__ uint4 lds128(uint32_t a) { uint4 v; asm volatile("ld.shared.v4.u32 {%0,%1,%2,%3}, [%4];" : "=r"(v.x), "=r"(v.y), "=r"(v.z), "=r"(v.w) : "r"(a) : "memory"); return v; }
__device__ __forceinline__ uint32_t hmul2(uint32_t a, uint32_t b) { uint32_t r; asm("mul.rn.bf16x2 %0, %1, %2;" : "=r"(r) : "r"(a), "r"(b)); return r; }
__device__ __forceinline__ uint32_t hadd2(uint32_t a, uint32_t b) { uint32_t r; asm("add.rn.bf16x2 %0, %1, %2;" : "=r"(r) : "r"(a), "r"(b)); return r; }
__device__ __forceinline__ void stsm4(uint32_t a, uint32_t r0, uint32_t r1, uint32_t r2, uint32_t r3) {
  asm volatile("stmatrix.sync.aligned.m8n8.x4.shared.b16 [%0], {%1,%2,%3,%4};" ::"r"(a), "r"(r0), "r"(r1), "r"(r2), "r"(r3) : "memory");
}
__device__ __forceinline__ void stsm2(uint32_t a, uint32_t r0, uint32_t r1) {
  asm volatile("stmatrix.sync.aligned.m8n8.x2.shared.b16 [%0], {%1,%2};" ::"r"(a), "r"(r0), "r"(r1) : "memory");
}
__device__ __forceinline__ uint4 ldsm4(uint32_t a) {
  uint4 r; asm volatile("ldmatrix.sync.aligned.m8n8.x4.shared.b16 {%0,%1,%2,%3}, [%4];" : "=r"(r.x), "=r"(r.y), "=r"(r.z), "=r"(r.w) : "r"(a) : "memory"); return r;
}
__device__ __forceinline__ uint32_t movm(uint32_t a) { uint32_t r; asm("movmatrix.sync.aligned.m8n8.trans.b16 %0, %1;" : "=r"(r) : "r"(a)); return r; }
__device__ __forceinline__ void mma16816z(float (&d)[4], uint32_t a0, uint32_t a1, uint32_t a2, uint32_t a3, uint32_t b0, uint32_t b1) {
  asm("mma.sync.aligned.m16n8k16.row.col.f32.bf16.bf16.f32 {%0,%1,%2,%3}, {%4,%5,%6,%7}, {%8,%9}, {%10,%10,%10,%10};"
      : "=f"(d[0]), "=f"(d[1]), "=f"(d[2]), "=f"(d[3]) : "r"(a0), "r"(a1), "r"(a2), "r"(a3), "r"(b0), "r"(b1), "f"(0.f));
}
__device__ __forceinline__ void mma16816(float (&d)[4], const uint4& a, uint32_t b0, uint32_t b1) {
  asm("mma.sync.aligned.m16n8k16.row.col.f32.bf16.bf16.f32 {%0,%1,%2,%3}, {%4,%5,%6,%7}, {%8,%9}, {%0,%1,%2,%3};"
      : "+f"(d[0]), "+f"(d[1]), "+f"(d[2]), "+f"(d[3]) : "r"(a.x), "r"(a.y), "r"(a.z), "r"(a.w), "r"(b0), "r"(b1));
}
__device__ __forceinline__ void mma1688(float (&d)[4], uint32_t a0, uint32_t a1, uint32_t b0) {
  asm("mma.sync.aligned.m16n8k8.row.col.f32.bf16.bf16.f32 {%0,%1,%2,%3}, {%4,%5}, {%6}, {%0,%1,%2,%3};"
      : "+f"(d[0]), "+f"(d[1]), "+f"(d[2]), "+f"(d[3]) : "r"(a0), "r"(a1), "r"(b0));
}
__device__ __forceinline__ float quad_sum(float v) { v += __shfl_xor_sync(0xffffffffu, v, 1); v += __shfl_xor_sync(0xffffffffu, v, 2); return v; }
__device__ __forceinline__ float rcp(float x) { float r; asm("rcp.approx.ftz.f32 %0, %1;" : "=f"(r) : "f"(x)); return r; }
__device__ __forceinline__ float rsq(float x) { float r; asm("rsqrt.approx.ftz.f32 %0, %1;" : "=f"(r) : "f"(x)); return r; }
__device__ __forceinline__ float ex2(float x) { float r; asm("ex2.approx.ftz.f32 %0, %1;" : "=f"(r) : "f"(x)); return r; }
__device__ __forceinline__ uint32_t chk(uint32_t acc, uint32_t v, uint32_t tag) { uint32_t r; asm("lop3.b32 %0, %1, %2, %3, 0xF6;" : "=r"(r) : "r"(acc), "r"(v), "r"(tag)); return r; }
__device__ __forceinline__ uint32_t chk2(uint32_t a, uint32_t b, uint32_t tag) { uint32_t r; asm("lop3.b32 %0, %1, %2, %3, 0x7E;" : "=r"(r) : "r"(a), "r"(b), "r"(tag)); return r; }
__device__ __forceinline__ uint32_t tagged(uint32_t v, uint32_t tag) { return (v & ~1u) | tag; }

__device__ __forceinline__ int group_k0(int g, int j) {
  const int h = g >= 9, r = g - 2 - 7 * h;
  return g < 2 ? 64 * j + 32 * g : g < 16 ? 64 * (r + (r >= j)) + 32 * h : 32 * g;
}
__device__ __forceinline__ uint32_t xin_off(int c, int w) { return SM_X + (2 * c + w) * 8192; }
__device__ __forceinline__ uint32_t xin_bar(int c) { return BAR_FULLX + 8 * (c < 8 ? c ^ 4 : c); }
__device__ __forceinline__ constexpr uint32_t qkv_xslot(int g) { return g < 5 || g > 11 ? 2 : (0x5140762u >> (4 * (g - 5))) & 15; }

template <int N> struct IC { static constexpr int v = N; };

struct Cons {
  uint32_t sb;
  uint32_t rem;
  uint32_t sB, mB;
  uint32_t mX;
  bool elect;
  __device__ __forceinline__ void release2(uint32_t bar) const { if (elect) { mbar_arrive(sb + bar); mbar_arrive_remote(rem + bar); } }
  __device__ __forceinline__ uint32_t nextB(uint32_t& prev) {
    mbar_wait_c(sb + BAR_FULLB + sB, mB);
    const uint32_t a = (((sb & 0x3FFFF) + SM_B) >> 4) + sB * (BSLOT / 128);
    prev = sB == 0 ? 32 : sB - 8;
    sB += 8;
    if (sB == 40) { sB = 0; mB ^= 1; }
    return a;
  }
  __device__ __forceinline__ void progress(uint32_t v) const { if (elect) sts32(sb + SM_PROG + (threadIdx.x >> 5), v); }
  __device__ __forceinline__ void releaseLastB() const { release2(BAR_EMPTYB + (sB == 0 ? 32 : sB - 8)); }
};

__device__ __forceinline__ float2 gather_sums(const uint2* a, uint32_t stag) {
  uint2 sa, sc;
  do { sa = ld_relaxed2(a); sc = ld_relaxed2(a + 8); } while (__any_sync(0xffffffffu, chk2(sa.x, sc.x, stag) & 3));
  return make_float2(quad_sum(__uint_as_float(sa.x) + __uint_as_float(sc.x)), quad_sum(__uint_as_float(sa.y) + __uint_as_float(sc.y)));
}

struct Norm {
  float m0, m1;
  uint32_t nm0, nm1;
  float d0, d1;
  uint2 u0, u1;
  __device__ __forceinline__ Norm(float2 sum) : m0(sum.x * (-1.f / 576)), m1(sum.y * (-1.f / 576)), nm0(pack_bf16(m0, m0)), nm1(pack_bf16(m1, m1)), d0(0.f), d1(0.f) {}
  __device__ __forceinline__ uint4 centre(const uint4& a) const { return make_uint4(hadd2(a.x, nm0), hadd2(a.y, nm1), hadd2(a.z, nm0), hadd2(a.w, nm1)); }
  __device__ __forceinline__ void sqr(uint32_t a, uint32_t b) {
    d0 = fmaf(bf_lo(a), bf_lo(a), fmaf(bf_hi(a), bf_hi(a), d0)); d1 = fmaf(bf_lo(b), bf_lo(b), fmaf(bf_hi(b), bf_hi(b), d1));
  }
  __device__ __forceinline__ void send(uint2* a, int t, uint32_t stag) {
    d0 = quad_sum(d0); d1 = quad_sum(d1);
    if ((t & 3) == 0) st_relaxed2(a, (__float_as_uint(d0) & ~3u) | stag, __float_as_uint(d1));
  }
  __device__ __forceinline__ void fetch(const uint2* a) { u0 = ld_relaxed2(a); u1 = ld_relaxed2(a + 8); }
  __device__ __forceinline__ float2 rstd(const uint2* a, uint32_t stag) {
    while (__any_sync(0xffffffffu, chk2(u0.x, u1.x, stag) & 3)) fetch(a);
    const float e0 = bf_lo(nm0) - m0, e1 = bf_lo(nm1) - m1;
    const float v0 = fmaf(quad_sum(__uint_as_float(u0.x) + __uint_as_float(u1.x)), 1.f / 576, -e0 * e0);
    const float v1 = fmaf(quad_sum(__uint_as_float(u0.y) + __uint_as_float(u1.y)), 1.f / 576, -e1 * e1);
    uint32_t u = pack_bf16(fmaxf(v0, 0.f), fmaxf(v1, 0.f));
    u = pack_bf16(bf_lo(u) + 1e-5f, bf_hi(u) + 1e-5f);
    u = pack_bf16(bf_lo(u) * rsq(bf_lo(u)), bf_hi(u) * rsq(bf_hi(u)));
    float2 r = make_float2(rcp(bf_lo(u)), rcp(bf_hi(u)));
    asm volatile("" : "+f"(r.x), "+f"(r.y));
    return r;
  }
};

template <class Pre, class Mma>
__device__ __forceinline__ float2 ln_gemm_in(Cons& c, Group* G, uint32_t (&p)[18], float2& sum, int w, int st0, int j, int t, Pre&& pre, Mma&& mma) {
  const uint32_t xa = c.sb + (t >> 5) * 2048 + (t & 15) * 128, sw = (((t >> 4) & 1) ^ (t & 7)) * 16;
  float ra[4] = {0.f, 0.f, 0.f, 0.f}, rb[4] = {0.f, 0.f, 0.f, 0.f};
#pragma unroll 1
  for (int cc = 0; cc < 9; cc++) {
    const uint32_t a = xa + xin_off(cc, w);
    mbar_wait_c(c.sb + xin_bar(cc), 0);
    const uint4 u0 = ldsm4(a + sw), u1 = ldsm4(a + (sw ^ 32)), u2 = ldsm4(a + (sw ^ 64)), u3 = ldsm4(a + (sw ^ 96));
    mma16816(ra, u0, 0x3f803f80u, 0x3f803f80u); mma16816(rb, u1, 0x3f803f80u, 0x3f803f80u);
    mma16816(ra, u2, 0x3f803f80u, 0x3f803f80u); mma16816(rb, u3, 0x3f803f80u, 0x3f803f80u);
  }
  sum = make_float2(ra[0] + rb[0], ra[2] + rb[2]);
  pre(0);
  Norm n(sum);
  n.u0 = n.u1 = make_uint2(0, 0);
#pragma unroll
  for (int k = 0; k < 5; k++) {
    const uint4 u = ldsm4(xa + (k < 4 ? xin_off(j, w) + (sw ^ (32 * k)) : xin_off(8, w) + ((j ^ (t & 7)) << 4))), e = n.centre(u);
    p[4 * k] = u.x; p[4 * k + 1] = u.y;
    n.sqr(e.x, e.y);
    if (k < 4) { p[4 * k + 2] = u.z; p[4 * k + 3] = u.w; n.sqr(e.z, e.w); }
  }
  n.send(G->sq + st0 + 8 * j, t, 1);
  pre(1);
  float2 r = make_float2(0.f, 0.f);
  uint4 y0 = ldsm4(xa + xin_off(0, w) + sw), y1 = ldsm4(xa + xin_off(0, w) + (sw ^ 32));
#pragma unroll 1
  for (int cc = 0; cc < 9; cc++) {
#pragma unroll
    for (int i = 0; i < 2; i++) {
      const uint4 f0 = n.centre(y0), f1 = n.centre(y1);
      const uint32_t a = xa + xin_off(min(cc + i, 8), w);
      y0 = ldsm4(a + (sw ^ (64 - 64 * i))); y1 = ldsm4(a + (sw ^ (96 - 64 * i)));
      uint32_t prev;
      const uint32_t bb = c.nextB(prev);
      mma(true, bb, f0, f1);
      if (i == 1) {
        if (cc == 1) c.progress(3);
        if (cc == 5) n.fetch(G->sq + st0 + 16 * (t & 3));
        if (cc == 7) r = n.rstd(G->sq + st0 + 16 * (t & 3), 1);
        if (cc == 8 && w == 0) asm volatile("bar.arrive 6, 256;" ::: "memory");
      }
      wg_wait<1>();
      if (i + cc > 0) c.release2(BAR_EMPTYB + prev);
      if (2 * cc + i >= 13 && 2 * cc + i < 17) c.release2(BAR_EMPTYX + 32 + 8 * (2 * cc + i - 13));
    }
  }
  c.mX = 0xff;
  if (w == 1) asm volatile("bar.sync 6, 256;" ::: "memory");
  wg_wait<0>();
  c.releaseLastB();
  c.release2(BAR_EMPTYX + 24);
  return r;
}

template <bool QKV, class Pre, class Mma>
__device__ __forceinline__ float2 ln_gemm(Cons& c, Group* G, const float (&v)[36], uint32_t (&p)[18], float2& sum, int st0, int j, int t,
                                          int layer, uint32_t tag, Pre&& pre, Mma&& mma) {
  const uint32_t stag = (2 * layer + (QKV ? 1 : 2)) & 3;
  uint4 x[6][2];
  uint4* src = G->xbox + t;
  asm volatile("" : "+l"(src));
  auto buf = [&](int g) -> uint4 (&)[2] { return x[g < 16 ? (g - 2) % 6 : g - 13]; };
  auto load = [&](int g0) {
#pragma unroll
    for (int g = g0; g < g0 + (g0 < 14 ? 3 : 2); g++) {
      const uint4* a = g < 16 ? src + ((g - 2) % 7 >= j ? 256 : 0) + (2 * ((g - 2) % 7) + 16 * (g >= 9)) * 128 : src + 2 * g * 128;
      buf(g)[0] = ld_relaxed4(a); buf(g)[1] = ld_relaxed4(a + 128);
    }
  };
  auto invalid = [&](int g, uint32_t tag) {
    uint32_t bad = chk(chk(chk2(buf(g)[0].x, buf(g)[1].x, tag), buf(g + 1)[0].x, tag), buf(g + 1)[1].x, tag);
    if (g < 14) bad = chk(chk(bad, buf(g + 2)[0].x, tag), buf(g + 2)[1].x, tag);
    if (g == 16) bad = chk(chk(chk(chk(bad, buf(g)[0].z, tag), buf(g)[1].z, tag), buf(g + 1)[0].z, tag), buf(g + 1)[1].z, tag);
    return __any_sync(0xffffffffu, bad & 1);
  };
  uint4* const d = src + 2 * j * 128;
  const int sq = st0 + 16 * (t & 3);
  if (QKV) {
    float s0 = v[0] + v[1], s1 = v[2] + v[3];
#pragma unroll
    for (int i = 1; i < 9; i++) { s0 += v[4 * i] + v[4 * i + 1]; s1 += v[4 * i + 2] + v[4 * i + 3]; }
    s0 = quad_sum(s0); s1 = quad_sum(s1);
    if ((t & 3) == 0) st_relaxed2(G->sum + st0 + 8 * j, (__float_as_uint(s0) & ~3u) | stag, __float_as_uint(s1));
  }
#pragma unroll
  for (int i = 0; i < 18; i++) p[i] = pack_bf16(v[2 * i], v[2 * i + 1]);
#pragma unroll
  for (int i = 0; i < 2; i++) st_relaxed4(d + i * 128, tagged(p[4 * i], tag), p[4 * i + 1], p[4 * i + 2], p[4 * i + 3]);
  pre(0);
  if (QKV) {
    sum = gather_sums(G->sum + sq, stag);
    load(2);
  }
  Norm n(sum);
  pre(1);
  const uint32_t* probe = &(G->xbox + (2 * (t & 3) + 1) * 128 + (t | 31))->x;
  uint32_t pv;
  float2 r;
  auto inx = [](int g) { return QKV && ((g >= 5 && g < 12) || g == 17); };
  auto use = [](int g) { return QKV ? (g < 5 ? 108 : 101) + g : 18 + g; };
#pragma unroll
  for (int g = 0; g < 18; g++) {
    if (g < 16 ? g % 3 == 2 : g == 16) {
      const uint32_t lt = late(c.sb + BAR_PAST, tag);
      while (invalid(g, lt)) load(g);
      if (g < 16) load(g < 14 ? g + 3 : 16);
    }
    const uint4 f0 = n.centre(g < 2 ? make_uint4(p[8 * g], p[8 * g + 1], p[8 * g + 2], p[8 * g + 3]) : buf(g)[0]);
    const uint4 f1 = n.centre(g < 2 ? make_uint4(p[8 * g + 4], p[8 * g + 5], p[8 * g + 6], p[8 * g + 7]) : buf(g)[1]);
    if (g == 11) n.fetch(G->sq + sq);
    if (g == 16) r = n.rstd(G->sq + sq, stag);
    if (inx(g)) mbar_wait_c(c.sb + BAR_FULLX + 8 * qkv_xslot(g), ((0x34 >> qkv_xslot(g)) & 1) ^ (g == 17));
    else mbar_wait_c(c.sb + BAR_FULLB + 8 * (use(g) % 5), (use(g) / 5) & 1);
    mma(g, ((c.sb & 0x3FFFF) >> 4) + ((inx(g) ? xslot(qkv_xslot(g)) : SM_B + (use(g) % 5) * BSLOT) >> 4), f0, f1);
    if (g == 1) { wg_wait<1>(); c.release2(BAR_EMPTYB + 8 * (use(0) % 5)); }
    if (g < 2) {
      if (!QKV) {
        if (g == 0) {
          pv = ld_relaxed(probe);
        } else {
          const uint32_t lt = late(c.sb + BAR_PAST, tag);
          while (__any_sync(0xffffffffu, (pv ^ lt) & 1)) pv = ld_relaxed(probe);
          load(2);
        }
      }
      if (g == (QKV ? 0 : 1)) {
#pragma unroll
        for (int i = 2; i < 4; i++) st_relaxed4(d + (14 + i) * 128, tagged(p[4 * i], tag), p[4 * i + 1], p[4 * i + 2], p[4 * i + 3]);
        st_relaxed2((uint2*)(src + (32 + (j >> 1)) * 128) + (j & 1), tagged(p[16], tag), p[17]);
      }
      n.sqr(f0.x, f0.y); n.sqr(f0.z, f0.w); n.sqr(f1.x, f1.y); n.sqr(f1.z, f1.w);
      if (g == 1) {
        n.sqr(hadd2(p[16], n.nm0), hadd2(p[17], n.nm1));
        n.send(G->sq + st0 + 8 * j, t, stag);
      }
    }
    if (g == 1 && !QKV) { wg_wait<0>(); c.release2(BAR_EMPTYB + 8 * (use(1) % 5)); }
    else wg_wait<1>();
    if (g > (QKV ? 1 : 2) && !inx(g - 1)) c.release2(BAR_EMPTYB + 8 * (use(g - 1) % 5));
    if (QKV && g < 13) c.progress(33 + g);
    if (QKV && g == 12) c.release2(BAR_EMPTYX + 8 * qkv_xslot(17));
    if (QKV && g >= 13 && g < 17) c.release2(BAR_EMPTYX + 32 + 8 * (g - 13));
  }
  if (QKV) c.mX = 0x34 ^ 0xf3;
  else { c.sB = 8 * (36 % 5); c.mB = (36 / 5) & 1; }
  wg_wait<0>();
  if (!QKV) c.release2(BAR_EMPTYB + 8 * (use(17) % 5));
  return r;
}

template <int NB, int OFF>
__device__ __forceinline__ void glu(const float (&a)[128], uint32_t (&h)[144]) {
#pragma unroll
  for (int b = 0; b < 2 * NB; b++) {
    h[OFF + b] = hmul2(pack_bf16(a[2 * b], a[2 * b + 1]), pack_bf16(a[4 * NB + 2 * b], a[4 * NB + 2 * b + 1]));
  }
}

__global__ void __cluster_dims__(2, 1, 1) __launch_bounds__(384, 1)
fused_kernel(const __nv_bfloat16* __restrict__ x_in, Group* ws, const char* __restrict__ wqkv,
             const char* __restrict__ wo, char* __restrict__ out, uint32_t first, const __grid_constant__ Maps maps,
             const char* __restrict__ wg, const char* __restrict__ wu) {
  extern __shared__ __align__(1024) uint8_t smem_raw[];
  const uint32_t sb = smem_u32(smem_raw);
  const uint32_t bx = blockIdx.x - first;
  if (bx >= NCTA) {
    const int e = blockIdx.x & 3;
    const uint32_t par = ~ld_relaxed(ws->flag + 32) & 1;
    __nanosleep(1000);
    if (threadIdx.x < 16) prefetch_l2(wo + (144 * e + 9 * threadIdx.x) * 1152, 9 * 1152);
#pragma unroll 1
    for (int r = threadIdx.x >> 3; r < 144; r += 48) {
      const uint4* row = (const uint4*)(wo + (144 * e + r) * 1152) + (threadIdx.x & 7);
      float a = 0.f;
      uint4 u;
#pragma unroll
      for (int i = 0; i < 72; i += 8) {
        u = __ldg(row + i);
        a += ((bf_lo(u.x) + bf_hi(u.x)) + (bf_lo(u.y) + bf_hi(u.y))) + ((bf_lo(u.z) + bf_hi(u.z)) + (bf_lo(u.w) + bf_hi(u.w)));
      }
      const int h = r >= 72, k = r - 72 * h;
      ((Scratch*)ws)->woc[threadIdx.x & 7][k < 64 ? 64 + 8 * k + ((2 * e + h) ^ (k & 7)) : 576 * h + 8 * (k & 7) + (e ^ (k & 7))] = u;
      a = quad_sum(a);
      a += __shfl_xor_sync(0xffffffffu, a, 4);
      if ((threadIdx.x & 7) == 0) ((Scratch*)ws)->woc[2 * e + h][640 + k] = make_uint4(pack_bf16(a, a - bf_lo(pack_bf16(a, 0.f))), 0, 0, 0);
    }
    fence_gpu();
    __syncthreads();
    if (threadIdx.x == 0) st_relaxed(((Scratch*)ws)->done + e, par);
    const int cc = threadIdx.x % 54, r0 = threadIdx.x / 54, part = cc / 18, jj = 2 * e + (cc % 18) / 9, c9 = cc % 9;
    if (r0 < 6) {
#pragma unroll 4
      for (int k = r0; k < 576; k += 6) {
        const uint4 u = __ldg((const uint4*)(wqkv + k * 3456 + part * 1152 + 144 * jj) + c9);
        ((Scratch*)ws)->wq[jj][k >> 4][c9 < 8 ? part * 128 + (k & 15) * 8 + (c9 ^ (k & 7)) : 384 + part * 16 + (k & 15)] = u;
      }
    }
    fence_gpu();
    __syncthreads();
    if (threadIdx.x == 0) st_relaxed(((Scratch*)ws)->done + 32 + e, par);
    return;
  }
  if (threadIdx.x == 0) asm volatile("prefetch.tensormap [%0];" ::"l"(&maps.x) : "memory");
  const int warp = __shfl_sync(0xffffffffu, threadIdx.x >> 5, 0);
  const int lane = threadIdx.x & 31;
  const int rank = blockIdx.x & 1;
  if (elect_one()) {
    if (warp >= 8) {
#pragma unroll
      for (int i = 0; i < 9; i++) mbar_init(sb + SM_BAR + 72 * (warp - 8) + 8 * i, warp < 10 ? 1 : 4);
      sts32(sb + SM_PROG + 4 * (warp - 8), 0);
      asm volatile("fence.mbarrier_init.release.cluster;" ::: "memory");
    } else if (warp == 1 || warp == 2) {
      asm volatile("prefetch.tensormap [%0];" ::"l"(&maps.x + warp) : "memory");
    } else if (warp == 3) {
      prefetch_l2((const char*)x_in + bx * 18432, 18432);
    }
  }
  __syncwarp();
  asm volatile("barrier.cluster.arrive.relaxed.aligned;" ::: "memory");
  if (warp == 8) PROFX(53);
  const int cl = bx >> 1, u = cl - 36;
  const int lb = (cl < 4 ? cl : cl < 36 ? 8 * ((cl - 4) & 7) + ((cl - 4) >> 3) + (((cl - 4) & 7) ? 0 : 4) : 8 * (1 + u % 7) + 4 + u / 7) * 2 + rank;
#define CTA_J(b) (((b) >> 1) & 7)
#define CTA_RB(b) ((((b) >> 4) << 1) | ((b) & 1))
  const int j = CTA_J(lb), rb = CTA_RB(lb);

  PROF(23);
  if (warp >= 8) {
    asm volatile("setmaxnreg.dec.sync.aligned.u32 40;");
    auto x_chunk = [&](int cc) {
      mbar_expect_tx(sb + xin_bar(cc), 16384);
      tma3d(sb + xin_off(cc, 0), &maps.x, 64 * cc, 0, 64 * rb, sb + xin_bar(cc));
      tma3d(sb + xin_off(cc, 1), &maps.x, 64 * cc, 1, 64 * rb, sb + xin_bar(cc));
    };
    if (warp == 9 && elect_one()) {
      fence_async_smem();
#pragma unroll 1
      for (int i = 0; i < 9; i++) x_chunk(i);
    }
    __syncwarp();
    if (warp == 9) PROFX(54);
    asm volatile("barrier.cluster.wait.aligned;" ::: "memory");
    if (warp == 8) PROFX(56);
    const uint64_t pol = policy_evict_first(), pola = policy_evict_normal();
    uint4 (* const wq)[432] = ((Scratch*)ws)->wq[j];
    const uint32_t par = ~ld_relaxed(ws[2 * rb].flag + 32 + 32 * j) & 1;
    auto qkv_group = [&](bool copy, int k, uint32_t dst, uint32_t bar) {
      if (copy) {
        wbulk(dst + rank * 8192, wq[(k >> 4) + rank], 6912, bar, pol);
      } else {
        wtma3d(dst + rank * 8192, &maps.qm, 72 * j, k + 16 * rank, 0, bar, pola);
        wtma3d(dst + rank * 8192 + 6144, &maps.qc, 72 * j + 64, k + 16 * rank, 0, bar, pola);
      }
    };
    auto chore = [&](int i) {
#pragma unroll 1
      for (int it = 0; __any_sync(0xffffffffu, ld_acquire(((Scratch*)ws)->done + i) != par); it++) if (it == SPIN_MAX) asm volatile("trap;");
      asm volatile("fence.proxy.async.global;" ::: "memory");
    };
    const int ktab = group_k0(lane, j);
    auto qkv_gate = [&](int g) { if (g >= 8) gate(sb + SM_PROG, 33 + ((g - 8) * 23 >> 4)); };
    if (warp == 8) {
      uint32_t s = 0, ph = 1;
      auto slot = [&](uint32_t bytes, auto&& issue) {
        const uint32_t bar = sb + BAR_FULLB + 8 * s;
        mbar_wait(sb + BAR_EMPTYB + 8 * s, ph);
        if (elect_one()) {
          mbar_expect_tx(bar, bytes);
          issue(sb + SM_B + s * BSLOT, bar);
        }
        if (++s == 5) { s = 0; ph ^= 1; }
      };
#pragma unroll 1
      for (int layer = 0; layer < NLAYERS; layer++) {
        if (layer) chore(32 + (j >> 1));
#pragma unroll 1
        for (int g = 0; g < 18 - layer; g += layer && g == 4 ? 8 : 1) {
          const int k = layer ? __shfl_sync(0xffffffffu, ktab, g) : 32 * g;
          if (layer) qkv_gate(g);
          else if (g == 0) mbar_wait(sb + xin_bar(3), 0);
          slot(2 * 6912, [&](uint32_t dst, uint32_t bar) { qkv_group(layer, k, dst, bar); });
        }
#pragma unroll 1
        for (int t = 0; t < 5; t++) {
          const CUtensorMap* m = &maps.g + (t < 3 ? rank : 2 + rank);
          asm volatile("" : "+l"(m));
          const int c2 = t < 3 ? 9 * j + 2 * t : 18 * j + 3 + 3 * t;
          const uint32_t half = t < 3 ? 8192 : 6144;
          const uint64_t pt = layer == 0 && (t == 0 || t > 2) ? pola : pol;
          auto tile = [&](int g) {
            const int k = __shfl_sync(0xffffffffu, ktab, g);
            slot(2 * half, [&](uint32_t dst, uint32_t bar) { wtma3d(dst + rank * half, m, 0, k, c2, bar, pt); });
          };
          int g = 0;
          if (t == 0) {
#pragma unroll 1
            for (; g < 5; g++) {
              mbar_wait(sb + BAR_FULLB + 8 * (s == 0 ? 4 : s - 1), s == 0 ? ph : ph ^ 1);
              if (g == 3) gate(sb + SM_PROG + 4, 32 * layer + 20);
              tile(g);
            }
          }
#pragma unroll 1
          for (; g < 18; g++) tile(g);
        }
      }
    } else if (warp == 9) {
      uint32_t mE = 0;
      auto acquire = [&](uint32_t s) { mbar_wait(sb + BAR_EMPTYX + 8 * s, (mE >> s) & 1); mE ^= 1u << s; };
      auto slot = [&](uint32_t s, const CUtensorMap* m, int col, int row, uint64_t pol) {
        acquire(s);
        if (elect_one()) {
          mbar_expect_tx(sb + BAR_FULLX + 8 * s, XSLOT);
          wtma2d(sb + xslot(s) + rank * 9216, m, col, row + 72 * rank, sb + BAR_FULLX + 8 * s, pol);
        }
      };
#pragma unroll 1
      for (int layer = 0; layer < NLAYERS; layer++) {
        if (layer) chore(32 + (j >> 1));
#pragma unroll 1
        for (int g = 5; g < 18 * layer; g += g == 11 ? 6 : 1) {
          const uint32_t s = qkv_xslot(g);
          const int k = __shfl_sync(0xffffffffu, ktab, g);
          if (g < 12) qkv_gate(g);
          acquire(s);
          if (elect_one()) {
            mbar_expect_tx(sb + BAR_FULLX + 8 * s, 2 * 6912);
            qkv_group(true, k, sb + xslot(s), sb + BAR_FULLX + 8 * s);
          }
          mbar_wait(sb + BAR_FULLX + 8 * s, (mE >> s) & 1);
        }
#pragma unroll 1
        for (int i = 0; i < 4; i++) slot(4 + i, &maps.o, 64 * j, 144 * i, pola);
        if (layer == 0) { chore(lane & 3); PROFX(57); }
        acquire(3);
        if (elect_one()) {
          mbar_expect_tx(sb + BAR_FULLX + 24, 10240 + 1280);
          wbulk(sb + SM_WOC + rank * 5120, ((Scratch*)ws)->woc[j] + rank * 320, 5120, sb + BAR_FULLX + 24, pola);
          wbulk(sb + SM_WSUM + rank * 640, ((Scratch*)ws)->woc[j] + 640 + rank * 40, 640, sb + BAR_FULLX + 24, pola);
        }
#pragma unroll 1
        for (int u = 0; u < 36; u++) slot(4 * (u & 1) + ((u >> 1) & 3), &maps.d, u < 4 ? 512 : 64 * ((j + (u >> 2)) & 7), 576 * j + 144 * (u & 3), pol);
      }
    } else {
      const int w = warp - 10, grp = 2 * rb + w;
      auto exchange = [&](uint32_t v, uint32_t bar) {
        fence_gpu();
        __syncwarp();
        if (w == 0 && v != 1) PROFX(64 + 58 - 2 * v);
        if (lane == 0) st_relaxed(ws[grp].flag + j, v);
#pragma unroll 1
        for (int it = 0;; it++) {
          const uint32_t f = ld_relaxed(ws[grp].flag + (lane & 7));
          if (__all_sync(0xffffffffu, v ? f >= v : f == 0)) break;
          if (it == SPIN_MAX) asm volatile("trap;");
        }
        if (lane == 0) mbar_arrive(sb + bar + 8 * w);
      };
      mbar_wait(sb + xin_bar(0), 0);
      if (lane == 0) prefetch_l2(wqkv + (2 * bx + w) * 7776, 7776);
      gate(sb + SM_PROG, 3);
      if (w == 0 && lane < 6) asm volatile("prefetch.tensormap [%0];" ::"l"(&maps.o + lane) : "memory");
#pragma unroll 1
      for (int i = lane; i < 72; i += 32) {
        asm volatile("prefetch.global.L2 [%0];" ::"l"((w ? wu : wg) + (size_t)(36 * rb + (i >> 1)) * 9216 + 1152 * j + 128 * (i & 1)));
        __nanosleep(700);
      }
      gate(sb + SM_PROG, 22);
#pragma unroll 1
      for (int i = lane; i < 2 * INBOX; i += 64) {
        uint4* p = ws[grp].inbox[0] + 2 * j * INBOX + i;
        st_relaxed4(p, 0, 0, 0, 0); st_relaxed4(p + 32, 0, 0, 0, 0);
        __nanosleep(300);
      }
      exchange(1, BAR_CLR);
      if (w == 0) PROFX(59);
#pragma unroll 1
      for (int layer = 0; layer < NLAYERS; layer++) {
        mbar_wait(sb + BAR_REDDONE + 8 * w, layer);
        if (w == 0) PROFX(64 + 53 + 4 * layer);
        exchange(2 - 2 * layer, BAR_RREADY);
        if (w == 0) PROFX(64 + 56 + 4 * layer);
      }
      mbar_wait(sb + BAR_DONE + 8 * w, 0);
    }
  } else {
    asm volatile("setmaxnreg.inc.sync.aligned.u32 232;");
#define THREAD_IDS()                                                                   \
    int tid_ = threadIdx.x, bid_ = lb;                                                  \
    asm volatile("" : "+r"(tid_), "+r"(bid_));                                          \
    const int w = warp >> 2, wp = warp & 3;                                             \
    const int lane = tid_ & 31, t = tid_ & 127, g = lane >> 2, q = lane & 3;           \
    const int j = CTA_J(bid_), rb = CTA_RB(bid_), grp = 2 * rb + w;                    \
    const int st0 = wp * 64 + g;                         \
    Group* const G = ws + grp;                                                         \
    const uint32_t dsb = (sb & 0x3FFFF) >> 4;                                          \
    (void)t; (void)g; (void)q; (void)grp; (void)j; (void)st0; (void)dsb; (void)G
    Cons c;
    c.sb = sb; c.sB = 0; c.mB = 0; c.mX = 0; c.elect = (threadIdx.x & 127) == 0;
    asm volatile("mapa.shared::cluster.u32 %0, %1, %2;" : "=r"(c.rem) : "r"(sb), "r"(rank ^ 1));
    float v[36], a1[96], a2[12];
    float2 sum, rs;
    uint32_t res[18], xtag;
    auto qkv_mma = [&](bool acc, uint32_t bb, const uint4& f0, const uint4& f1) {
      wg_fence();
      wgmma_ra<192>(a1, f0, desc_hi(2048, 1024, 1) + bb, acc);
      wgmma_ra<24>(a2, f0, desc_hi(128, 256, 0) + (bb + 384), acc);
      wgmma_ra<192>(a1, f1, desc_hi(2048, 1024, 1) + (bb + 512), true);
      wgmma_ra<24>(a2, f1, desc_hi(128, 256, 0) + (bb + 896), true);
      wg_commit();
    };
    {
      THREAD_IDS();
      {
        if (q == 0) { st_relaxed2(G->sum + st0 + 8 * j, 0, 0); st_relaxed2(G->sq + st0 + 8 * j, 0, 0); }
        if (wp == 3) {
#pragma unroll
          for (int i = 0; i < 5; i++) st_relaxed4(G->halo + j * 160 + lane + i * 32, 0, 0, 0, 0);
        }
        if (lane >= 24) st_relaxed4(G->obox + (8 + j) * 128 + t, 0, 0, 0, 0);
      }
      xtag = __shfl_sync(0xffffffffu, ~ld_relaxed(G->flag + 32 + 32 * j) & 1, 0);
      if (lane >= 24) st_relaxed4(G->xbox + (2 * j + 1) * 128 + t, xtag ^ 1, 0, 0, 0);
      asm volatile("barrier.cluster.wait.aligned;" ::: "memory");
      PROF(0);
#pragma unroll
      for (int i = 0; i < 96; i++) asm volatile("mov.b32 %0, 0;" : "=f"(a1[i]));
#pragma unroll
      for (int i = 0; i < 12; i++) asm volatile("mov.b32 %0, 0;" : "=f"(a2[i]));
      PROF(1);
      rs = ln_gemm_in(c, G, res, sum, w, st0, j, t, [&](int i) { PROF(2 + i); if (i) PROF(4); }, qkv_mma);
    }
#pragma unroll 1
    for (int layer = 0;; layer++) {
      const uint32_t tag = layer ^ 1;
      uint4 own[5];
      {
        THREAD_IDS();
        PROF(pb + 4);
        uint32_t kv[3][18];
        auto cvt = [&](int b, float r) {
#pragma unroll
          for (int cc = 0; cc < 18; cc++) {
            const float* a = (cc == 8 ? a2 + 4 : cc == 17 ? a2 + 8 : cc < 8 ? a1 + 32 + 4 * cc : a1 + 28 + 4 * cc) + 2 * (b - 1);
            const uint32_t u = pack_bf16(a[0] * r, a[1] * r);
            kv[b][cc] = cc < 9 ? u : movm(u);
          }
        };
        cvt(2, rs.y);
#pragma unroll
        for (int i = 0; i < 18; i += 4) kv[2][i] = tagged(kv[2][i], tag);
        const uint32_t msg = sb + (w ? xslot(3) : xslot(0) + 24576) + wp * 2304 + lane * 16;
        if (wp == 3) {
          uint4* hp = G->halo + j * 160 + lane;
#pragma unroll
          for (int i = 0; i < 4; i++) st_relaxed4(hp + i * 32, kv[2][4 * i], kv[2][4 * i + 1], kv[2][4 * i + 2], kv[2][4 * i + 3]);
          st_relaxed2((uint2*)(hp + 128), kv[2][16], kv[2][17]);
        } else {
#pragma unroll
          for (int i = 0; i < 4; i++) sts128(msg + i * 512, kv[2][4 * i], kv[2][4 * i + 1], kv[2][4 * i + 2], kv[2][4 * i + 3]);
          sts64f(msg + 2048 - lane * 8, __uint_as_float(kv[2][16]), __uint_as_float(kv[2][17]));
        }
        cvt(1, rs.x);
        uint32_t Q[4][6];
#pragma unroll
        for (int h = 0; h < 4; h++)
#pragma unroll
          for (int i = 0; i < 6; i++) {
            const float* a = 4 * h + i < 16 ? a1 + 8 * h + 2 * i : a2 + 8 * h + 2 * i - 32;
            const uint32_t u = pack_bf16(a[0], a[1]);
            Q[h][i] = i < 2 ? (q >= h ? u : 0) : i < 4 ? u : (q <= h ? u : 0);
          }
        const bool lo0 = 2 * q > g, lo1 = 2 * q + 1 > g;
        const uint32_t M = (lo0 ? 0xffffu : 0u) | (lo1 ? 0xffff0000u : 0u);
        auto scores = [&](int h, int b, float (&s)[4]) {
          mma16816z(s, Q[h][0], Q[h][1], Q[h][2], Q[h][3], kv[b][2 * h], kv[b][2 * h + 1]);
          mma1688(s, Q[h][4], Q[h][5], kv[b][2 * h + 2]);
        };
        auto softmax = [&](float (&l)[4][2], float r, uint32_t (&P)[4]) {
          const float sl = r * (0.23570226039551584f * 1.4426950408889634f);
          float m[4];
#pragma unroll
          for (int h = 0; h < 4; h++) { m[h] = fmaxf(l[h][0], l[h][1]); m[h] = fmaxf(m[h], __shfl_xor_sync(0xffffffffu, m[h], 1)); }
#pragma unroll
          for (int h = 0; h < 4; h++) m[h] = fmaxf(m[h], __shfl_xor_sync(0xffffffffu, m[h], 2)) * sl;
#pragma unroll
          for (int h = 0; h < 4; h++) P[h] = pack_bf16(ex2(fmaf(l[h][0], sl, -m[h])), ex2(fmaf(l[h][1], sl, -m[h])));
        };
        const bool remote = wp == 0 && rb > 0;
        const uint4* hp = (G - 2)->halo + j * 160 + lane;
        auto halo = [&] {
#pragma unroll
          for (int i = 0; i < 4; i++) { const uint4 u = ld_relaxed4(hp + i * 32); kv[0][4 * i] = u.x; kv[0][4 * i + 1] = u.y; kv[0][4 * i + 2] = u.z; kv[0][4 * i + 3] = u.w; }
          const uint2 u = ld_relaxed2((const uint2*)(hp + 128));
          kv[0][16] = u.x; kv[0][17] = u.y;
        };
#pragma unroll
        for (int i = 0; i < 18; i++) kv[0][i] = 0;
        float l0[4][2], l1[4][2];
#pragma unroll
        for (int h = 0; h < 4; h++) {
          float s1[4], s2[4];
          scores(h, 1, s1); scores(h, 2, s2);
          l0[h][0] = s1[0]; l0[h][1] = s1[1];
          l1[h][0] = lo0 ? s1[2] : s2[2]; l1[h][1] = lo1 ? s1[3] : s2[3];
        }
        hp += __float_as_uint(l1[0][0]) & late(sb + BAR_PAST, 0);
        if (remote) halo();
        uint32_t P0[4], P1[4];
        softmax(l1, rs.y, P1);
        if (remote) {
          while (__any_sync(0xffffffffu, chk(chk2(kv[0][0], kv[0][4], tag) | chk2(kv[0][8], kv[0][12], tag), kv[0][16], tag) & 1)) halo();
        }
        wg_bar(w);
        if (wp > 0) {
          const uint32_t from = msg - 2304;
#pragma unroll
          for (int i = 0; i < 4; i++) { const uint4 u = lds128(from + i * 512); kv[0][4 * i] = u.x; kv[0][4 * i + 1] = u.y; kv[0][4 * i + 2] = u.z; kv[0][4 * i + 3] = u.w; }
          const float2 u = lds64(from + 2048 - lane * 8);
          kv[0][16] = __float_as_uint(u.x); kv[0][17] = __float_as_uint(u.y);
        }
        PROF(pb + 5);
        const bool first = (rb == 0 && wp == 0);
#pragma unroll
        for (int h = 0; h < 4; h++) {
          float s0[4];
          scores(h, 0, s0);
          if (first) s0[0] = s0[1] = -INFINITY;
          l0[h][0] = lo0 ? s0[0] : l0[h][0]; l0[h][1] = lo1 ? s0[1] : l0[h][1];
        }
        softmax(l0, rs.x, P0);
        uint4* ob = G->obox + t;
        uint32_t car0 = 0, car1 = 0;
#pragma unroll
        for (int h = 0; h < 4; h++) {
          float o[3][4], z[4] = {0.f, 0.f, 0.f, 0.f};
          mma1688(z, P0[h], P1[h], 0x3f803f80u);
#pragma unroll
          for (int i = 0; i < 3; i++) {
            mma16816z(o[i], P0[h] & ~M, P1[h] & M, 0u, P1[h] & ~M, kv[1][9 + 2 * h + i], kv[2][9 + 2 * h + i]);
            mma1688(o[i], P0[h] & M, 0u, kv[0][9 + 2 * h + i]);
          }
          const float i0 = rcp(z[0]), i1 = rcp(z[2]);
#pragma unroll
          for (int i = 0; i < 3; i++) { o[i][0] *= i0; o[i][1] *= i0; o[i][2] *= i1; o[i][3] *= i1; }
          const uint32_t o0 = q < h ? car0 : pack_bf16(o[0][0], o[0][1]), o1 = q < h ? car1 : pack_bf16(o[0][2], o[0][3]);
          own[h] = make_uint4(o0 | 1, o1, pack_bf16(o[1][0], o[1][1]), pack_bf16(o[1][2], o[1][3]));
          if (h < 3) st_relaxed4(ob + (8 * h + j) * 128, own[h].x, own[h].y, own[h].z, own[h].w);
          car0 = pack_bf16(o[2][0], o[2][1]); car1 = pack_bf16(o[2][2], o[2][3]);
        }
        car0 = tagged(car0, tag);
        own[4] = make_uint4(car0, car1, 0, 0);
        PROF(pb + 6);
      }
      uint2 sa, sc;
      {
        THREAD_IDS();
        uint4* src = G->obox + t;
        asm volatile("" : "+l"(src));
        uint4 x[32];
        const uint4* from[7];
#pragma unroll
        for (int r = 0; r < 7; r++) { from[r] = src + (r >= j ? 128 : 0); asm volatile("" : "+l"(from[r])); }
        auto load = [&](int i) { x[i] = ld_relaxed4(i < 28 ? from[i % 7] + (8 * (i / 7) + i % 7) * 128 : src + (i + 4) * 128); };
        const uint32_t* probe = &(G->obox + (8 + (lane & 7)) * 128 + (t | 31))->x;
        uint32_t pv = ld_relaxed(probe);
#pragma unroll
        for (int i = 3; i < 8; i++) mbar_wait_c(sb + BAR_FULLX + 8 * i, (c.mX >> i) & 1);
        c.mX ^= 0xf8;
        while (__any_sync(0xffffffffu, ~pv & 1)) pv = ld_relaxed(probe);
        PROF(25 - layer);
        if (w == 1) asm volatile("bar.sync 7, 256;" ::: "memory");
#pragma unroll
        for (int i = 0; i < 11; i++) load(i);
        if (w == 0) asm volatile("bar.arrive 7, 256;" ::: "memory");
        st_relaxed4(src + (24 + j) * 128, own[3].x, own[3].y, own[3].z, own[3].w);
        st_relaxed2((uint2*)(src + (32 + (j >> 1)) * 128) + (j & 1), own[4].x, own[4].y);
        PROF(27 - layer);
        float a[36];
        float e[4];
        constexpr uint32_t NEXT = 576 - (575u << 16);
        auto step = [&](const uint4& f, uint32_t s, int i, uint32_t more, bool acc) {
          const uint32_t r = (xslot(4) >> 4) + (i < 4 ? 72 * s + 16 * i : 144 * s + 64) * 8, c = (SM_WOC >> 4) + (i < 4 ? 64 + 128 * i : 0) + s;
          wgmma_ra<72>(a, f, desc_hi(0, i < 4 ? 1024 : 9216, 1) + (dsb + more + (r + ((c - r) << 16))), acc);
        };
        wg_fence();
#pragma unroll
        for (int i = 0; i < 5; i++) wgmma_ra<8>(e, own[i], desc_hi(128, 0, 0) + (dsb + (SM_WSUM >> 4) + 16 * i), i > 0);
        wg_commit();
#pragma unroll
        for (int i = 0; i < 4; i++) step(own[i], 0, i, j * NEXT, i > 0);
        wg_commit();
        PROF(29 - layer);
        auto batch = [&](auto e0, auto e1, auto e2, int b) {
          constexpr int E0 = decltype(e0)::v, E1 = decltype(e1)::v, E2 = decltype(e2)::v;
          const uint32_t one = late(sb + BAR_PAST, 1);
          while (true) {
            uint32_t bad = 0;
#pragma unroll
            for (int i = E0; i < E1; i++) bad = i < 28 ? chk(bad, x[i].x, one) : chk(chk(bad, x[i].x, tag), x[i].z, tag);
            if (!__any_sync(0xffffffffu, bad & 1)) break;
#pragma unroll
            for (int i = E0; i < E1; i++) load(i);
          }
          if (b == 0) PROF(pb + 7);
          if (b == 1) { c.progress(32 * layer + 20); wg_wait<1>(); }
#pragma unroll
          for (int i = E1; i < E2; i++) load(i);
          if (b == 0) {
            wg_wait<1>();
            if (q == 0) st_relaxed2(G->sum + st0 + 8 * j, (__float_as_uint(e[0] + e[1]) & ~3u) | ((2 * layer + 2) & 3), __float_as_uint(e[2] + e[3]));
          }
          if (b == 2) { sa = ld_relaxed2(G->sum + st0 + 16 * q); sc = ld_relaxed2(G->sum + st0 + 16 * q + 8); }
          wg_fence();
#pragma unroll
          for (int i = E0; i < E1; i++) step(x[i], i % 7, i / 7, i < 28 && i % 7 >= j ? NEXT : 0, true);
          wg_commit();
        };
        batch(IC<0>(), IC<11>(), IC<21>(), 0);
        batch(IC<11>(), IC<21>(), IC<32>(), 1);
        batch(IC<21>(), IC<32>(), IC<32>(), 2);
        wg_wait<0>();
        if (w == 0) asm volatile("bar.arrive 3, 256;" ::: "memory");
        PROF(pb + 8);
#pragma unroll
        for (int i = 0; i < 18; i++) {
          v[2 * i] = bf_lo(res[i]) + a[2 * i];
          v[2 * i + 1] = bf_hi(res[i]) + a[2 * i + 1];
        }
      }
      uint32_t lsb;
      uint32_t h[144];
      {
        THREAD_IDS();
        float a[128];
        const uint32_t xd = sb + xslot(4 * w) + (lane >> 4) * 1024 + (16 * wp + (lane & 15)) * 16;
        const float2 rs = ln_gemm<false>(c, G, v, res, sum, st0, j, t, layer, xtag,
          [&](int i) {
            if (i == 0) {
              lsb = ((res[0] & 1) | (res[4] & 1) << 1 | (res[8] & 1) << 2 | (res[12] & 1) << 3 | (res[16] & 1) << 4) ^ (xtag * 31);
              const uint32_t st = late(sb + BAR_PAST, (2 * layer + 2) & 3);
              while (__any_sync(0xffffffffu, chk2(sa.x, sc.x, st) & 3)) { sa = ld_relaxed2(G->sum + st0 + 16 * q); sc = ld_relaxed2(G->sum + st0 + 16 * q + 8); }
              sum.x += quad_sum(__uint_as_float(sa.x) + __uint_as_float(sc.x)); sum.y += quad_sum(__uint_as_float(sa.y) + __uint_as_float(sc.y));
              if (w == 1) asm volatile("bar.sync 3, 256;" ::: "memory");
            }
            PROF(pb + 9 + i);
          },
          [&](int gi, uint32_t bb, const uint4& f0, const uint4& f1) {
            if (gi == 0) PROF(pb + 11);
            if (gi == 16 && w == 1) asm volatile("bar.sync 5, 256;" ::: "memory");
            wg_fence();
            wgmma_ra<256>(a, f0, desc_hi(4096, 1024, 1) + bb, gi > 0);
            wgmma_ra<256>(a, f1, desc_hi(4096, 1024, 1) + (bb + 128), true);
            wg_commit();
            if (gi == 17 && w == 0) asm volatile("bar.arrive 5, 256;" ::: "memory");
            stsm4(xd + gi * 4096, f0.x, f0.y, f0.z, f0.w);
            stsm4(xd + gi * 4096 + 2048, f1.x, f1.y, f1.z, f1.w);
            if (gi == 17) { fence_async_smem(); wg_bar(w); }
          });
        sts64f(sb + SM_KEEP + (tid_ >> 2) * 8, rs.x * rs.x, rs.y * rs.y);
        c.progress(32 * layer + 22);
        PROF(pb + 12);
        glu<16, 0>(a, h);
        const Desc da0 = desc_hi(1024, 128, 0) + (dsb + (xslot(4 * w) >> 4));
        auto tile = [&](auto wide, auto last) {
          const uint32_t xe = BAR_EMPTYX + 32 * (t & 1) + 4 * (t & 6);
          auto group = [&](int gi) {
            uint32_t prev;
            const uint32_t bb = c.nextB(prev);
            const Desc da = da0 + gi * 256;
            wg_fence();
            if (wide()) {
              wgmma_ss<256>(a, da, desc_hi(4096, 1024, 1) + bb, gi);
              wgmma_ss<256>(a, da + 128, desc_hi(4096, 1024, 1) + (bb + 128), 1);
            } else {
              wgmma_ss<192>(*(float(*)[96])a, da, desc_hi(2048, 512, 2) + bb, gi);
              wgmma_ss<192>(*(float(*)[96])a, da + 128, desc_hi(2048, 512, 2) + (bb + 64), 1);
            }
            wg_commit();
            if (gi == 17 && w == 0) asm volatile("bar.arrive 5, 256;" ::: "memory");
            wg_wait<1>();
            if (gi > 0 && !(last() && gi > 13)) c.release2(BAR_EMPTYB + prev);
            if (last() && gi >= 8 && !(gi & 1)) c.release2(BAR_EMPTYX + 16 * ((gi - 8) & 2) + 2 * ((gi - 8) & 12));
          };
          int gi = 0, end = w ? 16 : 18;
#pragma unroll 1
          while (true) {
#pragma unroll 1
            for (; gi < end; gi++) group(gi);
            if (end == 18) break;
            asm volatile("bar.sync 5, 256;" ::: "memory");
            end = 18;
          }
          wg_wait<0>();
          if (!last()) c.releaseLastB();
          if (last() && t >= 5 && t < 8) { mbar_arrive(sb + xe); mbar_arrive_remote(c.rem + xe); }
        };
        auto yes = [] { return true; };
        auto no = [] { return false; };
        tile(yes, no); PROF(pb + 13); glu<16, 32>(a, h);
        tile(yes, no); PROF(pb + 14); glu<16, 64>(a, h);
        tile(no, no); PROF(pb + 15); glu<12, 96>(a, h);
        const uint32_t hole = sb + SM_B + 12288 + tid_ * 16;
#pragma unroll
        for (int i = 0; i < 4; i++) sts128(hole + i * BSLOT, h[96 + 4 * i], h[97 + 4 * i], h[98 + 4 * i], h[99 + 4 * i]);
        if (w == 1) asm volatile("bar.arrive 8, 256;" ::: "memory");
        tile(no, yes); PROF(pb + 16); glu<12, 120>(a, h);
#pragma unroll
        for (int i = 0; i < 4; i++) { const uint4 u = lds128(hole + i * BSLOT); h[96 + 4 * i] = u.x; h[97 + 4 * i] = u.y; h[98 + 4 * i] = u.z; h[99 + 4 * i] = u.w; }
      }
      {
        THREAD_IDS();
        float d[32];
        uint4* gt = G->obox + t;
        asm volatile("" : "+l"(gt));
        uint4* const ib = gt + 2 * 4608 + layer * 8 * INBOX;
        auto pass = [&](uint32_t s0, bool last, auto&& hook) {
          const Desc db = desc_hi(0, 1024, 1) + (dsb + s0 * (XSLOT >> 4));
          mbar_wait_c(sb + BAR_FULLX + 8 * s0, (c.mX >> s0) & 1);
          hook();
          asm volatile("bar.sync %0, 256;" ::"r"(8 + w) : "memory");
#pragma unroll
          for (int i = 0; i < 4; i++) {
            const int si = 4 * (i & 1) + (i >> 1);
            if (i > 0) mbar_wait_c(sb + BAR_FULLX + 8 * (s0 + si), (c.mX >> (s0 + si)) & 1);
            wg_fence();
#pragma unroll
            for (int k = 0; k < 9; k++) {
              const uint32_t* hk = h + 36 * i + 4 * k;
              wgmma_ra<64>(d, make_uint4(hk[0], hk[1], hk[2], hk[3]), db + ((xslot(si) >> 4) + k * 128), last || i + k > 0);
            }
            if (i == 3 && !(last && w == 1)) asm volatile("bar.arrive %0, 256;" ::"r"(9 - w) : "memory");
            wg_commit();
            if (i > 0) { wg_wait<1>(); c.release2(BAR_EMPTYX + 8 * (s0 + 4 * ((i - 1) & 1) + ((i - 1) >> 1))); }
          }
          c.mX ^= 0x33u << s0;
        };
        PROF(pb + 17);
#pragma unroll 1
        for (int p = 0; p < 8; p++) {
          const uint32_t s0 = 2 * (p & 1);
          pass(s0, false, [] {});
          wg_wait<0>();
          c.release2(BAR_EMPTYX + 8 * (s0 + 5));
          if (p == 6 && layer == NLAYERS - 1) c.elect = false;
          uint32_t pk[16];
#pragma unroll
          for (int i = 0; i < 16; i++) pk[i] = pack_bf16(d[2 * i], d[2 * i + 1]);
          if (p >= 1 && p < 6 && layer < NLAYERS - 1) {
            const uint32_t o = c.sB + 8 * (p - 1);
            c.release2(BAR_EMPTYB + (o < 40 ? o : o - 40));
          }
          uint4* const dst = ib + ((j + p) & 7) * INBOX;
          if (p == 0) {
            mbar_wait_c(sb + BAR_CLR + 8 * w, 0);
#pragma unroll
            for (int k = 0; k < 8; k++) red2((uint2*)(ib + k * INBOX + 512) - t, pk[2 * k], pk[2 * k + 1]);
          } else if (p < 7) {
#pragma unroll
            for (int k = 0; k < 4; k++) red4(dst + k * 128, pk[4 * k], pk[4 * k + 1], pk[4 * k + 2], pk[4 * k + 3]);
            if (p == 6) { __syncwarp(); if (lane == 0) mbar_arrive(sb + BAR_REDDONE + 8 * w); }
          } else {
#pragma unroll
            for (int k = 0; k < 4; k++) st_relaxed4(gt + ((j + 7) & 7) * 128 + k * 1024, pk[4 * k] & ~1u, pk[4 * k + 1], pk[4 * k + 2], pk[4 * k + 3]);
          }
        }
        PROF(pb + 18);
        const uint4 *in = ib + j * INBOX, *pin = gt + j * 128;
        const uint2* in9 = (const uint2*)(in + 512) - t;
        asm volatile("" : "+l"(in), "+l"(pin), "+l"(in9));
        const float2 r2 = lds64(sb + SM_KEEP + (tid_ >> 2) * 8);
        uint2 X9;
        {
          uint4 X[4];
          const uint4* box = gt + 4608;
#pragma unroll
          for (int k = 0; k < 4; k++) X[k] = ld_relaxed4(box + 256 * j + ((k & 1) + 8 * (k & 2)) * 128);
          X9 = ld_relaxed2((const uint2*)(box + (32 + (j >> 1)) * 128) + (j & 1));
          const float i0 = rcp(r2.x), i1 = rcp(r2.y);
#pragma unroll
          for (int k = 0; k < 4; k++) {
            float* e = d + 8 * k;
            X[k].x ^= (lsb >> k) & 1;
            e[0] = bf_lo(X[k].x) * i0; e[1] = bf_hi(X[k].x) * i0; e[2] = bf_lo(X[k].y) * i1; e[3] = bf_hi(X[k].y) * i1;
            e[4] = bf_lo(X[k].z) * i0; e[5] = bf_hi(X[k].z) * i0; e[6] = bf_lo(X[k].w) * i1; e[7] = bf_hi(X[k].w) * i1;
          }
        }
        uint4 R[4], P[4];
        uint2 R9;
        PROF(pb + 19);
        pass(0, true, [&] {
          mbar_wait_c(sb + BAR_RREADY + 8 * w, layer);
#pragma unroll
          for (int k = 0; k < 4; k++) R[k] = ld_relaxed4(in + k * 128);
          R9 = ld_relaxed2(in9);
#pragma unroll
          for (int k = 0; k < 4; k++) P[k] = ld_relaxed4(pin + k * 1024);
        });
        const uint32_t zero = late(sb + BAR_PAST, 0);
        while (__any_sync(0xffffffffu, (chk2(P[0].x, P[1].x, zero) | chk2(P[2].x, P[3].x, zero)) & 1)) {
#pragma unroll
          for (int k = 0; k < 4; k++) P[k] = ld_relaxed4(pin + k * 1024);
        }
#pragma unroll
        for (int k = 0; k < 4; k++) {
          const uint32_t u[4] = {hadd2(R[k].x, P[k].x), hadd2(R[k].y, P[k].y), hadd2(R[k].z, P[k].z), hadd2(R[k].w, P[k].w)};
#pragma unroll
          for (int i = 0; i < 4; i++) { v[8 * k + 2 * i] = bf_lo(u[i]); v[8 * k + 2 * i + 1] = bf_hi(u[i]); }
        }
        X9.x = chk(zero, X9.x, lsb >> 4);
        v[32] = fmaf(bf_lo(R9.x), r2.x, bf_lo(X9.x)); v[33] = fmaf(bf_hi(R9.x), r2.x, bf_hi(X9.x));
        v[34] = fmaf(bf_lo(R9.y), r2.y, bf_lo(X9.y)); v[35] = fmaf(bf_hi(R9.y), r2.y, bf_hi(X9.y));
        PROF(pb + 20);
        wg_wait<0>();
        c.release2(BAR_EMPTYX + 40);
        PROF(pb + 21);
#pragma unroll
        for (int i = 0; i < 32; i++) v[i] = (v[i] + d[i]) * (i & 2 ? r2.y : r2.x);
      }
      if (layer == NLAYERS - 1) break;
      {
        THREAD_IDS();
        PROF(31);
        rs = ln_gemm<true>(c, G, v, res, sum, st0, j, t, 1, xtag ^ 1, [&](int i) { PROF(32 + i); if (i) PROF(34); }, qkv_mma);
      }
    }
    {
      THREAD_IDS();
      const uint32_t stg = sb + SM_B + warp * 4096;
      const uint32_t sd = stg + (lane & 15) * 128;
#pragma unroll
      for (int i = 0; i < 4; i++)
        stsm4(sd + (((2 * i + (lane >> 4)) ^ (lane & 7)) << 4), pack_bf16(v[8 * i], v[8 * i + 1]), pack_bf16(v[8 * i + 2], v[8 * i + 3]),
              pack_bf16(v[8 * i + 4], v[8 * i + 5]), pack_bf16(v[8 * i + 6], v[8 * i + 7]));
      stsm2(stg + 2048 + (lane & 15) * 16, pack_bf16(v[32], v[33]), pack_bf16(v[34], v[35]));
      __syncwarp();
      char* o = out + (128 * rb + 32 * wp + w) * 1152;
#pragma unroll
      for (int i = 0; i < 4; i++) {
        const int r = 4 * i + (lane >> 3);
        *(uint4*)(o + r * 2304 + 128 * j + 16 * (lane & 7)) = lds128(stg + r * 128 + (((lane ^ r) & 7) << 4));
      }
      if (lane < 16) *(uint4*)(o + lane * 2304 + 1024 + 16 * j) = lds128(stg + 2048 + lane * 16);
      if (lane == 0) {
        if (wp == 0) st_relaxed(G->flag + 32 + 32 * j, xtag);
        mbar_arrive(sb + BAR_DONE + 8 * w);
      }
      PROF(61);
    }
  }
}

typedef CUresult (*EncFn)(CUtensorMap*, CUtensorMapDataType, cuuint32_t, void*, const cuuint64_t*, const cuuint64_t*, const cuuint32_t*,
                          const cuuint32_t*, CUtensorMapInterleave, CUtensorMapSwizzle, CUtensorMapL2promotion, CUtensorMapFloatOOBfill);

void make_map(EncFn enc, CUtensorMap* m, const void* p, int rank, uint64_t d0, uint64_t d1, uint64_t d2, uint64_t s1, uint64_t s2, uint32_t b0,
              uint32_t b1, uint32_t b2, CUtensorMapSwizzle sw) {
  cuuint64_t gd[3] = {d0, d1, d2};
  cuuint64_t gs[2] = {s1, s2};
  cuuint32_t bd[3] = {b0, b1, b2};
  cuuint32_t es[3] = {1, 1, 1};
  enc(m, CU_TENSOR_MAP_DATA_TYPE_BFLOAT16, rank, const_cast<void*>(p), gd, gs, bd, es, CU_TENSOR_MAP_INTERLEAVE_NONE, sw,
      CU_TENSOR_MAP_L2_PROMOTION_L2_128B, CU_TENSOR_MAP_FLOAT_OOB_FILL_NONE);
}

}

extern "C" void kernel_launch(void* const* d_in, const int* in_sizes, int n_in, void* d_out, int out_size) {
  const __nv_bfloat16* x = (const __nv_bfloat16*)d_in[0];
  const char *wqkv = (const char*)d_in[1], *wo = (const char*)d_in[2], *wg = (const char*)d_in[4], *wu = (const char*)d_in[5], *wd = (const char*)d_in[6];
  static EncFn enc = nullptr;
  static uint32_t first = 0;
  static Group* ws = nullptr;
  if (!enc) {
    cudaDriverEntryPointQueryResult qr;
    cudaGetDriverEntryPoint("cuTensorMapEncodeTiled", (void**)&enc, cudaEnableDefault, &qr);
    cudaGetSymbolAddress((void**)&ws, g_ws);
    cudaFuncSetAttribute(fused_kernel, cudaFuncAttributeMaxDynamicSharedMemorySize, SMEM_BYTES);
    cudaLaunchConfig_t cfg = {};
    cfg.gridDim = NCTA + 4; cfg.blockDim = 384; cfg.dynamicSmemBytes = SMEM_BYTES;
    int clusters = 0;
    if (XFIRST || cudaOccupancyMaxActiveClusters(&clusters, fused_kernel, &cfg) != cudaSuccess || 2 * clusters < NCTA + 4) first = 4;
    cudaGetLastError();
  }
  const CUtensorMapSwizzle S0 = CU_TENSOR_MAP_SWIZZLE_NONE, S64 = CU_TENSOR_MAP_SWIZZLE_64B, S128 = CU_TENSOR_MAP_SWIZZLE_128B;
  Maps m;
  make_map(enc, &m.x, x, 3, 576, 2, 1024, 1152, 2304, 64, 1, 64, S128);
  make_map(enc, &m.qm, wqkv, 3, 576, 576, 3, 3456, 1152, 64, 16, 3, S128);
  make_map(enc, &m.qc, wqkv, 3, 576, 576, 3, 3456, 1152, 8, 16, 3, S0);
  make_map(enc, &m.o, wo, 2, 576, 576, 1, 1152, 0, 64, 72, 1, S128);
  make_map(enc, &m.g, wg, 3, 64, 576, 72, 9216, 128, 64, 32, 2, S128);
  make_map(enc, &m.u, wu, 3, 64, 576, 72, 9216, 128, 64, 32, 2, S128);
  make_map(enc, &m.g3, wg, 3, 32, 576, 144, 9216, 64, 32, 32, 3, S64);
  make_map(enc, &m.u3, wu, 3, 32, 576, 144, 9216, 64, 32, 32, 3, S64);
  make_map(enc, &m.d, wd, 2, 576, 4608, 1, 1152, 0, 64, 72, 1, S128);
  fused_kernel<<<NCTA + 4, 384, SMEM_BYTES>>>(x, ws, wqkv, wo, (char*)d_out, first, m, wg, wu);
}
```

```cpp
#include <cuda_runtime.h>
#include <cuda_bf16.h>
#include <cuda.h>
#include <stdint.h>
#include <stddef.h>

namespace {

constexpr int NCTA = 128;
#define NLAYERS 2
#define XFIRST 0
constexpr uint32_t SM_X = 0;
constexpr uint32_t XSLOT = 18432;
__host__ __device__ constexpr uint32_t xslot(uint32_t s) { return SM_X + (s ^ 4) * XSLOT; }
constexpr uint32_t SM_WOC = xslot(3) + 8192;
constexpr uint32_t SM_B = 147456;
constexpr uint32_t BSLOT = 16384;
constexpr uint32_t SM_KEEP = 229376;
constexpr uint32_t SM_WSUM = SM_KEEP + 512;
constexpr uint32_t SM_BAR = SM_KEEP + 2048;
constexpr uint32_t BAR_FULLB = SM_BAR;
constexpr uint32_t BAR_RREADY = SM_BAR + 40;
constexpr uint32_t BAR_CLR = SM_BAR + 56;
constexpr uint32_t BAR_FULLX = SM_BAR + 72;
constexpr uint32_t BAR_PAST = BAR_FULLX + 64;
constexpr uint32_t BAR_EMPTYB = SM_BAR + 144;
constexpr uint32_t BAR_EMPTYX = SM_BAR + 184;
constexpr uint32_t BAR_REDDONE = SM_BAR + 248;
constexpr uint32_t BAR_DONE = SM_BAR + 264;
constexpr uint32_t SM_PROG = SM_BAR + 288;
constexpr uint32_t SMEM_BYTES = SM_BAR + 1024;

struct Maps { CUtensorMap x, qm, qc, o, g, u, g3, u3, d; };

constexpr int INBOX = 576;
struct Group {
  uint2 sum[4 * 8 * 8];
  uint2 sq[4 * 8 * 8];
  uint32_t flag[1024];
  uint4 halo[8 * 160];
  uint4 obox[36 * 128];
  uint4 xbox[36 * 128];
  uint4 inbox[2][8 * INBOX];
};
struct Scratch { Group g[32]; uint4 wq[8][36][432]; uint4 woc[8][720]; uint32_t done[64]; };
__device__ __align__(1024) Scratch g_ws;
#define PROF(i)
#define PROFX(i)

struct Desc { uint32_t lo, hi; };
__device__ __forceinline__ constexpr Desc desc_hi(uint32_t lbo, uint32_t sbo, uint32_t sw) { return Desc{(lbo >> 4) << 16, (sbo >> 4) | sw << 30}; }
__device__ __forceinline__ constexpr Desc operator+(Desc d, uint32_t a) { return Desc{d.lo + a, d.hi}; }

template<int N> __device__ __forceinline__ void wgmma_ss(float (&d)[N / 2], Desc da, Desc db, int sc);
template<> __device__ __forceinline__ void wgmma_ss<192>(float (&d)[96], Desc da, Desc db, int sc) {
  asm volatile("{\n.reg .pred p;\n.reg .b64 a, b;\nsetp.ne.b32 p, %100, 0;\nmov.b64 a, {%96, %97};\nmov.b64 b, {%98, %99};\n"
    "wgmma.mma_async.sync.aligned.m64n192k16.f32.bf16.bf16 {%0,%1,%2,%3,%4,%5,%6,%7,%8,%9,%10,%11,%12,%13,%14,%15,%16,%17,%18,%19,%20,%21,%22,%23,%24,%25,%26,%27,%28,%29,%30,%31,%32,%33,%34,%35,%36,%37,%38,%39,%40,%41,%42,%43,%44,%45,%46,%47,%48,%49,%50,%51,%52,%53,%54,%55,%56,%57,%58,%59,%60,%61,%62,%63,%64,%65,%66,%67,%68,%69,%70,%71,%72,%73,%74,%75,%76,%77,%78,%79,%80,%81,%82,%83,%84,%85,%86,%87,%88,%89,%90,%91,%92,%93,%94,%95}, a, b, p, 1, 1, 0, 1;\n}\n"
    : "+f"(d[0]),"+f"(d[1]),"+f"(d[2]),"+f"(d[3]),"+f"(d[4]),"+f"(d[5]),"+f"(d[6]),"+f"(d[7]),"+f"(d[8]),"+f"(d[9]),"+f"(d[10]),"+f"(d[11]),"+f"(d[12]),"+f"(d[13]),"+f"(d[14]),"+f"(d[15]),"+f"(d[16]),"+f"(d[17]),"+f"(d[18]),"+f"(d[19]),"+f"(d[20]),"+f"(d[21]),"+f"(d[22]),"+f"(d[23]),"+f"(d[24]),"+f"(d[25]),"+f"(d[26]),"+f"(d[27]),"+f"(d[28]),"+f"(d[29]),"+f"(d[30]),"+f"(d[31]),"+f"(d[32]),"+f"(d[33]),"+f"(d[34]),"+f"(d[35]),"+f"(d[36]),"+f"(d[37]),"+f"(d[38]),"+f"(d[39]),"+f"(d[40]),"+f"(d[41]),"+f"(d[42]),"+f"(d[43]),"+f"(d[44]),"+f"(d[45]),"+f"(d[46]),"+f"(d[47]),"+f"(d[48]),"+f"(d[49]),"+f"(d[50]),"+f"(d[51]),"+f"(d[52]),"+f"(d[53]),"+f"(d[54]),"+f"(d[55]),"+f"(d[56]),"+f"(d[57]),"+f"(d[58]),"+f"(d[59]),"+f"(d[60]),"+f"(d[61]),"+f"(d[62]),"+f"(d[63]),"+f"(d[64]),"+f"(d[65]),"+f"(d[66]),"+f"(d[67]),"+f"(d[68]),"+f"(d[69]),"+f"(d[70]),"+f"(d[71]),"+f"(d[72]),"+f"(d[73]),"+f"(d[74]),"+f"(d[75]),"+f"(d[76]),"+f"(d[77]),"+f"(d[78]),"+f"(d[79]),"+f"(d[80]),"+f"(d[81]),"+f"(d[82]),"+f"(d[83]),"+f"(d[84]),"+f"(d[85]),"+f"(d[86]),"+f"(d[87]),"+f"(d[88]),"+f"(d[89]),"+f"(d[90]),"+f"(d[91]),"+f"(d[92]),"+f"(d[93]),"+f"(d[94]),"+f"(d[95]) : "r"(da.lo), "r"(da.hi), "r"(db.lo), "r"(db.hi), "r"(sc));
}
template<> __device__ __forceinline__ void wgmma_ss<256>(float (&d)[128], Desc da, Desc db, int sc) {
  asm volatile("{\n.reg .pred p;\n.reg .b64 a, b;\nsetp.ne.b32 p, %132, 0;\nmov.b64 a, {%128, %129};\nmov.b64 b, {%130, %131};\n"
    "wgmma.mma_async.sync.aligned.m64n256k16.f32.bf16.bf16 {%0,%1,%2,%3,%4,%5,%6,%7,%8,%9,%10,%11,%12,%13,%14,%15,%16,%17,%18,%19,%20,%21,%22,%23,%24,%25,%26,%27,%28,%29,%30,%31,%32,%33,%34,%35,%36,%37,%38,%39,%40,%41,%42,%43,%44,%45,%46,%47,%48,%49,%50,%51,%52,%53,%54,%55,%56,%57,%58,%59,%60,%61,%62,%63,%64,%65,%66,%67,%68,%69,%70,%71,%72,%73,%74,%75,%76,%77,%78,%79,%80,%81,%82,%83,%84,%85,%86,%87,%88,%89,%90,%91,%92,%93,%94,%95,%96,%97,%98,%99,%100,%101,%102,%103,%104,%105,%106,%107,%108,%109,%110,%111,%112,%113,%114,%115,%116,%117,%118,%119,%120,%121,%122,%123,%124,%125,%126,%127}, a, b, p, 1, 1, 0, 1;\n}\n"
    : "+f"(d[0]),"+f"(d[1]),"+f"(d[2]),"+f"(d[3]),"+f"(d[4]),"+f"(d[5]),"+f"(d[6]),"+f"(d[7]),"+f"(d[8]),"+f"(d[9]),"+f"(d[10]),"+f"(d[11]),"+f"(d[12]),"+f"(d[13]),"+f"(d[14]),"+f"(d[15]),"+f"(d[16]),"+f"(d[17]),"+f"(d[18]),"+f"(d[19]),"+f"(d[20]),"+f"(d[21]),"+f"(d[22]),"+f"(d[23]),"+f"(d[24]),"+f"(d[25]),"+f"(d[26]),"+f"(d[27]),"+f"(d[28]),"+f"(d[29]),"+f"(d[30]),"+f"(d[31]),"+f"(d[32]),"+f"(d[33]),"+f"(d[34]),"+f"(d[35]),"+f"(d[36]),"+f"(d[37]),"+f"(d[38]),"+f"(d[39]),"+f"(d[40]),"+f"(d[41]),"+f"(d[42]),"+f"(d[43]),"+f"(d[44]),"+f"(d[45]),"+f"(d[46]),"+f"(d[47]),"+f"(d[48]),"+f"(d[49]),"+f"(d[50]),"+f"(d[51]),"+f"(d[52]),"+f"(d[53]),"+f"(d[54]),"+f"(d[55]),"+f"(d[56]),"+f"(d[57]),"+f"(d[58]),"+f"(d[59]),"+f"(d[60]),"+f"(d[61]),"+f"(d[62]),"+f"(d[63]),"+f"(d[64]),"+f"(d[65]),"+f"(d[66]),"+f"(d[67]),"+f"(d[68]),"+f"(d[69]),"+f"(d[70]),"+f"(d[71]),"+f"(d[72]),"+f"(d[73]),"+f"(d[74]),"+f"(d[75]),"+f"(d[76]),"+f"(d[77]),"+f"(d[78]),"+f"(d[79]),"+f"(d[80]),"+f"(d[81]),"+f"(d[82]),"+f"(d[83]),"+f"(d[84]),"+f"(d[85]),"+f"(d[86]),"+f"(d[87]),"+f"(d[88]),"+f"(d[89]),"+f"(d[90]),"+f"(d[91]),"+f"(d[92]),"+f"(d[93]),"+f"(d[94]),"+f"(d[95]),"+f"(d[96]),"+f"(d[97]),"+f"(d[98]),"+f"(d[99]),"+f"(d[100]),"+f"(d[101]),"+f"(d[102]),"+f"(d[103]),"+f"(d[104]),"+f"(d[105]),"+f"(d[106]),"+f"(d[107]),"+f"(d[108]),"+f"(d[109]),"+f"(d[110]),"+f"(d[111]),"+f"(d[112]),"+f"(d[113]),"+f"(d[114]),"+f"(d[115]),"+f"(d[116]),"+f"(d[117]),"+f"(d[118]),"+f"(d[119]),"+f"(d[120]),"+f"(d[121]),"+f"(d[122]),"+f"(d[123]),"+f"(d[124]),"+f"(d[125]),"+f"(d[126]),"+f"(d[127]) : "r"(da.lo), "r"(da.hi), "r"(db.lo), "r"(db.hi), "r"(sc));
}
template<int N, int ACC> __device__ __forceinline__ void wgmma_rs(float (&d)[N / 2], const uint4& a, Desc db);
template<> __device__ __forceinline__ void wgmma_rs<8, 1>(float (&d)[4], const uint4& a, Desc db) {
  asm volatile("{\n.reg .pred p;\n.reg .b64 b;\nsetp.ne.b32 p, 1, 0;\nmov.b64 b, {%8, %9};\n"
    "wgmma.mma_async.sync.aligned.m64n8k16.f32.bf16.bf16 {%0,%1,%2,%3}, {%4,%5,%6,%7}, b, p, 1, 1, 1;\n}\n"
    : "+f"(d[0]),"+f"(d[1]),"+f"(d[2]),"+f"(d[3]) : "r"(a.x), "r"(a.y), "r"(a.z), "r"(a.w), "r"(db.lo), "r"(db.hi));
}
template<> __device__ __forceinline__ void wgmma_rs<8, 0>(float (&d)[4], const uint4& a, Desc db) {
  asm volatile("{\n.reg .pred p;\n.reg .b64 b;\nsetp.ne.b32 p, 0, 0;\nmov.b64 b, {%8, %9};\n"
    "wgmma.mma_async.sync.aligned.m64n8k16.f32.bf16.bf16 {%0,%1,%2,%3}, {%4,%5,%6,%7}, b, p, 1, 1, 1;\n}\n"
    : "=f"(d[0]),"=f"(d[1]),"=f"(d[2]),"=f"(d[3]) : "r"(a.x), "r"(a.y), "r"(a.z), "r"(a.w), "r"(db.lo), "r"(db.hi));
}
template<> __device__ __forceinline__ void wgmma_rs<24, 1>(float (&d)[12], const uint4& a, Desc db) {
  asm volatile("{\n.reg .pred p;\n.reg .b64 b;\nsetp.ne.b32 p, 1, 0;\nmov.b64 b, {%16, %17};\n"
    "wgmma.mma_async.sync.aligned.m64n24k16.f32.bf16.bf16 {%0,%1,%2,%3,%4,%5,%6,%7,%8,%9,%10,%11}, {%12,%13,%14,%15}, b, p, 1, 1, 1;\n}\n"
    : "+f"(d[0]),"+f"(d[1]),"+f"(d[2]),"+f"(d[3]),"+f"(d[4]),"+f"(d[5]),"+f"(d[6]),"+f"(d[7]),"+f"(d[8]),"+f"(d[9]),"+f"(d[10]),"+f"(d[11]) : "r"(a.x), "r"(a.y), "r"(a.z), "r"(a.w), "r"(db.lo), "r"(db.hi));
}
template<> __device__ __forceinline__ void wgmma_rs<24, 0>(float (&d)[12], const uint4& a, Desc db) {
  asm volatile("{\n.reg .pred p;\n.reg .b64 b;\nsetp.ne.b32 p, 0, 0;\nmov.b64 b, {%16, %17};\n"
    "wgmma.mma_async.sync.aligned.m64n24k16.f32.bf16.bf16 {%0,%1,%2,%3,%4,%5,%6,%7,%8,%9,%10,%11}, {%12,%13,%14,%15}, b, p, 1, 1, 1;\n}\n"
    : "=f"(d[0]),"=f"(d[1]),"=f"(d[2]),"=f"(d[3]),"=f"(d[4]),"=f"(d[5]),"=f"(d[6]),"=f"(d[7]),"=f"(d[8]),"=f"(d[9]),"=f"(d[10]),"=f"(d[11]) : "r"(a.x), "r"(a.y), "r"(a.z), "r"(a.w), "r"(db.lo), "r"(db.hi));
}
template<> __device__ __forceinline__ void wgmma_rs<64, 1>(float (&d)[32], const uint4& a, Desc db) {
  asm volatile("{\n.reg .pred p;\n.reg .b64 b;\nsetp.ne.b32 p, 1, 0;\nmov.b64 b, {%36, %37};\n"
    "wgmma.mma_async.sync.aligned.m64n64k16.f32.bf16.bf16 {%0,%1,%2,%3,%4,%5,%6,%7,%8,%9,%10,%11,%12,%13,%14,%15,%16,%17,%18,%19,%20,%21,%22,%23,%24,%25,%26,%27,%28,%29,%30,%31}, {%32,%33,%34,%35}, b, p, 1, 1, 1;\n}\n"
    : "+f"(d[0]),"+f"(d[1]),"+f"(d[2]),"+f"(d[3]),"+f"(d[4]),"+f"(d[5]),"+f"(d[6]),"+f"(d[7]),"+f"(d[8]),"+f"(d[9]),"+f"(d[10]),"+f"(d[11]),"+f"(d[12]),"+f"(d[13]),"+f"(d[14]),"+f"(d[15]),"+f"(d[16]),"+f"(d[17]),"+f"(d[18]),"+f"(d[19]),"+f"(d[20]),"+f"(d[21]),"+f"(d[22]),"+f"(d[23]),"+f"(d[24]),"+f"(d[25]),"+f"(d[26]),"+f"(d[27]),"+f"(d[28]),"+f"(d[29]),"+f"(d[30]),"+f"(d[31]) : "r"(a.x), "r"(a.y), "r"(a.z), "r"(a.w), "r"(db.lo), "r"(db.hi));
}
template<> __device__ __forceinline__ void wgmma_rs<64, 0>(float (&d)[32], const uint4& a, Desc db) {
  asm volatile("{\n.reg .pred p;\n.reg .b64 b;\nsetp.ne.b32 p, 0, 0;\nmov.b64 b, {%36, %37};\n"
    "wgmma.mma_async.sync.aligned.m64n64k16.f32.bf16.bf16 {%0,%1,%2,%3,%4,%5,%6,%7,%8,%9,%10,%11,%12,%13,%14,%15,%16,%17,%18,%19,%20,%21,%22,%23,%24,%25,%26,%27,%28,%29,%30,%31}, {%32,%33,%34,%35}, b, p, 1, 1, 1;\n}\n"
    : "=f"(d[0]),"=f"(d[1]),"=f"(d[2]),"=f"(d[3]),"=f"(d[4]),"=f"(d[5]),"=f"(d[6]),"=f"(d[7]),"=f"(d[8]),"=f"(d[9]),"=f"(d[10]),"=f"(d[11]),"=f"(d[12]),"=f"(d[13]),"=f"(d[14]),"=f"(d[15]),"=f"(d[16]),"=f"(d[17]),"=f"(d[18]),"=f"(d[19]),"=f"(d[20]),"=f"(d[21]),"=f"(d[22]),"=f"(d[23]),"=f"(d[24]),"=f"(d[25]),"=f"(d[26]),"=f"(d[27]),"=f"(d[28]),"=f"(d[29]),"=f"(d[30]),"=f"(d[31]) : "r"(a.x), "r"(a.y), "r"(a.z), "r"(a.w), "r"(db.lo), "r"(db.hi));
}
template<> __device__ __forceinline__ void wgmma_rs<72, 1>(float (&d)[36], const uint4& a, Desc db) {
  asm volatile("{\n.reg .pred p;\n.reg .b64 b;\nsetp.ne.b32 p, 1, 0;\nmov.b64 b, {%40, %41};\n"
    "wgmma.mma_async.sync.aligned.m64n72k16.f32.bf16.bf16 {%0,%1,%2,%3,%4,%5,%6,%7,%8,%9,%10,%11,%12,%13,%14,%15,%16,%17,%18,%19,%20,%21,%22,%23,%24,%25,%26,%27,%28,%29,%30,%31,%32,%33,%34,%35}, {%36,%37,%38,%39}, b, p, 1, 1, 1;\n}\n"
    : "+f"(d[0]),"+f"(d[1]),"+f"(d[2]),"+f"(d[3]),"+f"(d[4]),"+f"(d[5]),"+f"(d[6]),"+f"(d[7]),"+f"(d[8]),"+f"(d[9]),"+f"(d[10]),"+f"(d[11]),"+f"(d[12]),"+f"(d[13]),"+f"(d[14]),"+f"(d[15]),"+f"(d[16]),"+f"(d[17]),"+f"(d[18]),"+f"(d[19]),"+f"(d[20]),"+f"(d[21]),"+f"(d[22]),"+f"(d[23]),"+f"(d[24]),"+f"(d[25]),"+f"(d[26]),"+f"(d[27]),"+f"(d[28]),"+f"(d[29]),"+f"(d[30]),"+f"(d[31]),"+f"(d[32]),"+f"(d[33]),"+f"(d[34]),"+f"(d[35]) : "r"(a.x), "r"(a.y), "r"(a.z), "r"(a.w), "r"(db.lo), "r"(db.hi));
}
template<> __device__ __forceinline__ void wgmma_rs<72, 0>(float (&d)[36], const uint4& a, Desc db) {
  asm volatile("{\n.reg .pred p;\n.reg .b64 b;\nsetp.ne.b32 p, 0, 0;\nmov.b64 b, {%40, %41};\n"
    "wgmma.mma_async.sync.aligned.m64n72k16.f32.bf16.bf16 {%0,%1,%2,%3,%4,%5,%6,%7,%8,%9,%10,%11,%12,%13,%14,%15,%16,%17,%18,%19,%20,%21,%22,%23,%24,%25,%26,%27,%28,%29,%30,%31,%32,%33,%34,%35}, {%36,%37,%38,%39}, b, p, 1, 1, 1;\n}\n"
    : "=f"(d[0]),"=f"(d[1]),"=f"(d[2]),"=f"(d[3]),"=f"(d[4]),"=f"(d[5]),"=f"(d[6]),"=f"(d[7]),"=f"(d[8]),"=f"(d[9]),"=f"(d[10]),"=f"(d[11]),"=f"(d[12]),"=f"(d[13]),"=f"(d[14]),"=f"(d[15]),"=f"(d[16]),"=f"(d[17]),"=f"(d[18]),"=f"(d[19]),"=f"(d[20]),"=f"(d[21]),"=f"(d[22]),"=f"(d[23]),"=f"(d[24]),"=f"(d[25]),"=f"(d[26]),"=f"(d[27]),"=f"(d[28]),"=f"(d[29]),"=f"(d[30]),"=f"(d[31]),"=f"(d[32]),"=f"(d[33]),"=f"(d[34]),"=f"(d[35]) : "r"(a.x), "r"(a.y), "r"(a.z), "r"(a.w), "r"(db.lo), "r"(db.hi));
}
template<> __device__ __forceinline__ void wgmma_rs<192, 1>(float (&d)[96], const uint4& a, Desc db) {
  asm volatile("{\n.reg .pred p;\n.reg .b64 b;\nsetp.ne.b32 p, 1, 0;\nmov.b64 b, {%100, %101};\n"
    "wgmma.mma_async.sync.aligned.m64n192k16.f32.bf16.bf16 {%0,%1,%2,%3,%4,%5,%6,%7,%8,%9,%10,%11,%12,%13,%14,%15,%16,%17,%18,%19,%20,%21,%22,%23,%24,%25,%26,%27,%28,%29,%30,%31,%32,%33,%34,%35,%36,%37,%38,%39,%40,%41,%42,%43,%44,%45,%46,%47,%48,%49,%50,%51,%52,%53,%54,%55,%56,%57,%58,%59,%60,%61,%62,%63,%64,%65,%66,%67,%68,%69,%70,%71,%72,%73,%74,%75,%76,%77,%78,%79,%80,%81,%82,%83,%84,%85,%86,%87,%88,%89,%90,%91,%92,%93,%94,%95}, {%96,%97,%98,%99}, b, p, 1, 1, 1;\n}\n"
    : "+f"(d[0]),"+f"(d[1]),"+f"(d[2]),"+f"(d[3]),"+f"(d[4]),"+f"(d[5]),"+f"(d[6]),"+f"(d[7]),"+f"(d[8]),"+f"(d[9]),"+f"(d[10]),"+f"(d[11]),"+f"(d[12]),"+f"(d[13]),"+f"(d[14]),"+f"(d[15]),"+f"(d[16]),"+f"(d[17]),"+f"(d[18]),"+f"(d[19]),"+f"(d[20]),"+f"(d[21]),"+f"(d[22]),"+f"(d[23]),"+f"(d[24]),"+f"(d[25]),"+f"(d[26]),"+f"(d[27]),"+f"(d[28]),"+f"(d[29]),"+f"(d[30]),"+f"(d[31]),"+f"(d[32]),"+f"(d[33]),"+f"(d[34]),"+f"(d[35]),"+f"(d[36]),"+f"(d[37]),"+f"(d[38]),"+f"(d[39]),"+f"(d[40]),"+f"(d[41]),"+f"(d[42]),"+f"(d[43]),"+f"(d[44]),"+f"(d[45]),"+f"(d[46]),"+f"(d[47]),"+f"(d[48]),"+f"(d[49]),"+f"(d[50]),"+f"(d[51]),"+f"(d[52]),"+f"(d[53]),"+f"(d[54]),"+f"(d[55]),"+f"(d[56]),"+f"(d[57]),"+f"(d[58]),"+f"(d[59]),"+f"(d[60]),"+f"(d[61]),"+f"(d[62]),"+f"(d[63]),"+f"(d[64]),"+f"(d[65]),"+f"(d[66]),"+f"(d[67]),"+f"(d[68]),"+f"(d[69]),"+f"(d[70]),"+f"(d[71]),"+f"(d[72]),"+f"(d[73]),"+f"(d[74]),"+f"(d[75]),"+f"(d[76]),"+f"(d[77]),"+f"(d[78]),"+f"(d[79]),"+f"(d[80]),"+f"(d[81]),"+f"(d[82]),"+f"(d[83]),"+f"(d[84]),"+f"(d[85]),"+f"(d[86]),"+f"(d[87]),"+f"(d[88]),"+f"(d[89]),"+f"(d[90]),"+f"(d[91]),"+f"(d[92]),"+f"(d[93]),"+f"(d[94]),"+f"(d[95]) : "r"(a.x), "r"(a.y), "r"(a.z), "r"(a.w), "r"(db.lo), "r"(db.hi));
}
template<> __device__ __forceinline__ void wgmma_rs<192, 0>(float (&d)[96], const uint4& a, Desc db) {
  asm volatile("{\n.reg .pred p;\n.reg .b64 b;\nsetp.ne.b32 p, 0, 0;\nmov.b64 b, {%100, %101};\n"
    "wgmma.mma_async.sync.aligned.m64n192k16.f32.bf16.bf16 {%0,%1,%2,%3,%4,%5,%6,%7,%8,%9,%10,%11,%12,%13,%14,%15,%16,%17,%18,%19,%20,%21,%22,%23,%24,%25,%26,%27,%28,%29,%30,%31,%32,%33,%34,%35,%36,%37,%38,%39,%40,%41,%42,%43,%44,%45,%46,%47,%48,%49,%50,%51,%52,%53,%54,%55,%56,%57,%58,%59,%60,%61,%62,%63,%64,%65,%66,%67,%68,%69,%70,%71,%72,%73,%74,%75,%76,%77,%78,%79,%80,%81,%82,%83,%84,%85,%86,%87,%88,%89,%90,%91,%92,%93,%94,%95}, {%96,%97,%98,%99}, b, p, 1, 1, 1;\n}\n"
    : "=f"(d[0]),"=f"(d[1]),"=f"(d[2]),"=f"(d[3]),"=f"(d[4]),"=f"(d[5]),"=f"(d[6]),"=f"(d[7]),"=f"(d[8]),"=f"(d[9]),"=f"(d[10]),"=f"(d[11]),"=f"(d[12]),"=f"(d[13]),"=f"(d[14]),"=f"(d[15]),"=f"(d[16]),"=f"(d[17]),"=f"(d[18]),"=f"(d[19]),"=f"(d[20]),"=f"(d[21]),"=f"(d[22]),"=f"(d[23]),"=f"(d[24]),"=f"(d[25]),"=f"(d[26]),"=f"(d[27]),"=f"(d[28]),"=f"(d[29]),"=f"(d[30]),"=f"(d[31]),"=f"(d[32]),"=f"(d[33]),"=f"(d[34]),"=f"(d[35]),"=f"(d[36]),"=f"(d[37]),"=f"(d[38]),"=f"(d[39]),"=f"(d[40]),"=f"(d[41]),"=f"(d[42]),"=f"(d[43]),"=f"(d[44]),"=f"(d[45]),"=f"(d[46]),"=f"(d[47]),"=f"(d[48]),"=f"(d[49]),"=f"(d[50]),"=f"(d[51]),"=f"(d[52]),"=f"(d[53]),"=f"(d[54]),"=f"(d[55]),"=f"(d[56]),"=f"(d[57]),"=f"(d[58]),"=f"(d[59]),"=f"(d[60]),"=f"(d[61]),"=f"(d[62]),"=f"(d[63]),"=f"(d[64]),"=f"(d[65]),"=f"(d[66]),"=f"(d[67]),"=f"(d[68]),"=f"(d[69]),"=f"(d[70]),"=f"(d[71]),"=f"(d[72]),"=f"(d[73]),"=f"(d[74]),"=f"(d[75]),"=f"(d[76]),"=f"(d[77]),"=f"(d[78]),"=f"(d[79]),"=f"(d[80]),"=f"(d[81]),"=f"(d[82]),"=f"(d[83]),"=f"(d[84]),"=f"(d[85]),"=f"(d[86]),"=f"(d[87]),"=f"(d[88]),"=f"(d[89]),"=f"(d[90]),"=f"(d[91]),"=f"(d[92]),"=f"(d[93]),"=f"(d[94]),"=f"(d[95]) : "r"(a.x), "r"(a.y), "r"(a.z), "r"(a.w), "r"(db.lo), "r"(db.hi));
}
template<> __device__ __forceinline__ void wgmma_rs<256, 1>(float (&d)[128], const uint4& a, Desc db) {
  asm volatile("{\n.reg .pred p;\n.reg .b64 b;\nsetp.ne.b32 p, 1, 0;\nmov.b64 b, {%132, %133};\n"
    "wgmma.mma_async.sync.aligned.m64n256k16.f32.bf16.bf16 {%0,%1,%2,%3,%4,%5,%6,%7,%8,%9,%10,%11,%12,%13,%14,%15,%16,%17,%18,%19,%20,%21,%22,%23,%24,%25,%26,%27,%28,%29,%30,%31,%32,%33,%34,%35,%36,%37,%38,%39,%40,%41,%42,%43,%44,%45,%46,%47,%48,%49,%50,%51,%52,%53,%54,%55,%56,%57,%58,%59,%60,%61,%62,%63,%64,%65,%66,%67,%68,%69,%70,%71,%72,%73,%74,%75,%76,%77,%78,%79,%80,%81,%82,%83,%84,%85,%86,%87,%88,%89,%90,%91,%92,%93,%94,%95,%96,%97,%98,%99,%100,%101,%102,%103,%104,%105,%106,%107,%108,%109,%110,%111,%112,%113,%114,%115,%116,%117,%118,%119,%120,%121,%122,%123,%124,%125,%126,%127}, {%128,%129,%130,%131}, b, p, 1, 1, 1;\n}\n"
    : "+f"(d[0]),"+f"(d[1]),"+f"(d[2]),"+f"(d[3]),"+f"(d[4]),"+f"(d[5]),"+f"(d[6]),"+f"(d[7]),"+f"(d[8]),"+f"(d[9]),"+f"(d[10]),"+f"(d[11]),"+f"(d[12]),"+f"(d[13]),"+f"(d[14]),"+f"(d[15]),"+f"(d[16]),"+f"(d[17]),"+f"(d[18]),"+f"(d[19]),"+f"(d[20]),"+f"(d[21]),"+f"(d[22]),"+f"(d[23]),"+f"(d[24]),"+f"(d[25]),"+f"(d[26]),"+f"(d[27]),"+f"(d[28]),"+f"(d[29]),"+f"(d[30]),"+f"(d[31]),"+f"(d[32]),"+f"(d[33]),"+f"(d[34]),"+f"(d[35]),"+f"(d[36]),"+f"(d[37]),"+f"(d[38]),"+f"(d[39]),"+f"(d[40]),"+f"(d[41]),"+f"(d[42]),"+f"(d[43]),"+f"(d[44]),"+f"(d[45]),"+f"(d[46]),"+f"(d[47]),"+f"(d[48]),"+f"(d[49]),"+f"(d[50]),"+f"(d[51]),"+f"(d[52]),"+f"(d[53]),"+f"(d[54]),"+f"(d[55]),"+f"(d[56]),"+f"(d[57]),"+f"(d[58]),"+f"(d[59]),"+f"(d[60]),"+f"(d[61]),"+f"(d[62]),"+f"(d[63]),"+f"(d[64]),"+f"(d[65]),"+f"(d[66]),"+f"(d[67]),"+f"(d[68]),"+f"(d[69]),"+f"(d[70]),"+f"(d[71]),"+f"(d[72]),"+f"(d[73]),"+f"(d[74]),"+f"(d[75]),"+f"(d[76]),"+f"(d[77]),"+f"(d[78]),"+f"(d[79]),"+f"(d[80]),"+f"(d[81]),"+f"(d[82]),"+f"(d[83]),"+f"(d[84]),"+f"(d[85]),"+f"(d[86]),"+f"(d[87]),"+f"(d[88]),"+f"(d[89]),"+f"(d[90]),"+f"(d[91]),"+f"(d[92]),"+f"(d[93]),"+f"(d[94]),"+f"(d[95]),"+f"(d[96]),"+f"(d[97]),"+f"(d[98]),"+f"(d[99]),"+f"(d[100]),"+f"(d[101]),"+f"(d[102]),"+f"(d[103]),"+f"(d[104]),"+f"(d[105]),"+f"(d[106]),"+f"(d[107]),"+f"(d[108]),"+f"(d[109]),"+f"(d[110]),"+f"(d[111]),"+f"(d[112]),"+f"(d[113]),"+f"(d[114]),"+f"(d[115]),"+f"(d[116]),"+f"(d[117]),"+f"(d[118]),"+f"(d[119]),"+f"(d[120]),"+f"(d[121]),"+f"(d[122]),"+f"(d[123]),"+f"(d[124]),"+f"(d[125]),"+f"(d[126]),"+f"(d[127]) : "r"(a.x), "r"(a.y), "r"(a.z), "r"(a.w), "r"(db.lo), "r"(db.hi));
}
template<> __device__ __forceinline__ void wgmma_rs<256, 0>(float (&d)[128], const uint4& a, Desc db) {
  asm volatile("{\n.reg .pred p;\n.reg .b64 b;\nsetp.ne.b32 p, 0, 0;\nmov.b64 b, {%132, %133};\n"
    "wgmma.mma_async.sync.aligned.m64n256k16.f32.bf16.bf16 {%0,%1,%2,%3,%4,%5,%6,%7,%8,%9,%10,%11,%12,%13,%14,%15,%16,%17,%18,%19,%20,%21,%22,%23,%24,%25,%26,%27,%28,%29,%30,%31,%32,%33,%34,%35,%36,%37,%38,%39,%40,%41,%42,%43,%44,%45,%46,%47,%48,%49,%50,%51,%52,%53,%54,%55,%56,%57,%58,%59,%60,%61,%62,%63,%64,%65,%66,%67,%68,%69,%70,%71,%72,%73,%74,%75,%76,%77,%78,%79,%80,%81,%82,%83,%84,%85,%86,%87,%88,%89,%90,%91,%92,%93,%94,%95,%96,%97,%98,%99,%100,%101,%102,%103,%104,%105,%106,%107,%108,%109,%110,%111,%112,%113,%114,%115,%116,%117,%118,%119,%120,%121,%122,%123,%124,%125,%126,%127}, {%128,%129,%130,%131}, b, p, 1, 1, 1;\n}\n"
    : "=f"(d[0]),"=f"(d[1]),"=f"(d[2]),"=f"(d[3]),"=f"(d[4]),"=f"(d[5]),"=f"(d[6]),"=f"(d[7]),"=f"(d[8]),"=f"(d[9]),"=f"(d[10]),"=f"(d[11]),"=f"(d[12]),"=f"(d[13]),"=f"(d[14]),"=f"(d[15]),"=f"(d[16]),"=f"(d[17]),"=f"(d[18]),"=f"(d[19]),"=f"(d[20]),"=f"(d[21]),"=f"(d[22]),"=f"(d[23]),"=f"(d[24]),"=f"(d[25]),"=f"(d[26]),"=f"(d[27]),"=f"(d[28]),"=f"(d[29]),"=f"(d[30]),"=f"(d[31]),"=f"(d[32]),"=f"(d[33]),"=f"(d[34]),"=f"(d[35]),"=f"(d[36]),"=f"(d[37]),"=f"(d[38]),"=f"(d[39]),"=f"(d[40]),"=f"(d[41]),"=f"(d[42]),"=f"(d[43]),"=f"(d[44]),"=f"(d[45]),"=f"(d[46]),"=f"(d[47]),"=f"(d[48]),"=f"(d[49]),"=f"(d[50]),"=f"(d[51]),"=f"(d[52]),"=f"(d[53]),"=f"(d[54]),"=f"(d[55]),"=f"(d[56]),"=f"(d[57]),"=f"(d[58]),"=f"(d[59]),"=f"(d[60]),"=f"(d[61]),"=f"(d[62]),"=f"(d[63]),"=f"(d[64]),"=f"(d[65]),"=f"(d[66]),"=f"(d[67]),"=f"(d[68]),"=f"(d[69]),"=f"(d[70]),"=f"(d[71]),"=f"(d[72]),"=f"(d[73]),"=f"(d[74]),"=f"(d[75]),"=f"(d[76]),"=f"(d[77]),"=f"(d[78]),"=f"(d[79]),"=f"(d[80]),"=f"(d[81]),"=f"(d[82]),"=f"(d[83]),"=f"(d[84]),"=f"(d[85]),"=f"(d[86]),"=f"(d[87]),"=f"(d[88]),"=f"(d[89]),"=f"(d[90]),"=f"(d[91]),"=f"(d[92]),"=f"(d[93]),"=f"(d[94]),"=f"(d[95]),"=f"(d[96]),"=f"(d[97]),"=f"(d[98]),"=f"(d[99]),"=f"(d[100]),"=f"(d[101]),"=f"(d[102]),"=f"(d[103]),"=f"(d[104]),"=f"(d[105]),"=f"(d[106]),"=f"(d[107]),"=f"(d[108]),"=f"(d[109]),"=f"(d[110]),"=f"(d[111]),"=f"(d[112]),"=f"(d[113]),"=f"(d[114]),"=f"(d[115]),"=f"(d[116]),"=f"(d[117]),"=f"(d[118]),"=f"(d[119]),"=f"(d[120]),"=f"(d[121]),"=f"(d[122]),"=f"(d[123]),"=f"(d[124]),"=f"(d[125]),"=f"(d[126]),"=f"(d[127]) : "r"(a.x), "r"(a.y), "r"(a.z), "r"(a.w), "r"(db.lo), "r"(db.hi));
}
template<int N> __device__ __forceinline__ void wgmma_ra(float (&d)[N / 2], const uint4& a, Desc db, bool acc) {
  if (acc) wgmma_rs<N, 1>(d, a, db); else wgmma_rs<N, 0>(d, a, db);
}

__device__ __forceinline__ uint32_t smem_u32(const void* p) { return (uint32_t)__cvta_generic_to_shared(p); }
__device__ __forceinline__ void mbar_init(uint32_t bar, uint32_t cnt) { asm volatile("mbarrier.init.shared::cta.b64 [%0], %1;" ::"r"(bar), "r"(cnt)); }
__device__ __forceinline__ void mbar_expect_tx(uint32_t bar, uint32_t bytes) { asm volatile("mbarrier.arrive.expect_tx.shared::cta.b64 _, [%0], %1;" ::"r"(bar), "r"(bytes) : "memory"); }
__device__ __forceinline__ void mbar_arrive(uint32_t bar) { asm volatile("mbarrier.arrive.shared::cta.b64 _, [%0];" ::"r"(bar) : "memory"); }
__device__ __forceinline__ void mbar_arrive_remote(uint32_t rbar) { asm volatile("mbarrier.arrive.shared::cluster.b64 _, [%0];" ::"r"(rbar) : "memory"); }
__device__ __forceinline__ void mbar_wait(uint32_t bar, uint32_t parity) {
  asm volatile(
      "{\n.reg .pred p;\n.reg .u32 c;\nmov.u32 c, 0;\nLAB_WAIT:\nmbarrier.try_wait.parity.shared::cta.b64 p, [%0], %1;\n@p bra DONE;\n"
      "add.u32 c, c, 1;\nsetp.lt.u32 p, c, 1000000;\n@p bra LAB_WAIT;\ntrap;\nDONE:\n}\n" ::"r"(bar), "r"(parity) : "memory");
}
__device__ __forceinline__ void mbar_wait_c(uint32_t bar, uint32_t parity) {
  asm volatile("{\n.reg .pred p;\nLAB_WAIT:\nmbarrier.try_wait.parity.shared::cta.b64 p, [%0], %1;\n@!p bra LAB_WAIT;\n}\n" ::"r"(bar), "r"(parity) : "memory");
}
__device__ __forceinline__ uint32_t late(uint32_t bar, uint32_t v) {
  uint32_t r;
  asm volatile("{\n.reg .pred p;\nmbarrier.test_wait.parity.shared::cta.b64 p, [%1], 0;\nselp.b32 %0, %2, %1, p;\n}\n" : "=r"(r) : "r"(bar), "r"(v) : "memory");
  return r;
}
__device__ __forceinline__ void wtma2d(uint32_t dst, const CUtensorMap* m, int c0, int c1, uint32_t bar, uint64_t pol) {
  asm volatile("cp.async.bulk.tensor.2d.shared::cluster.global.mbarrier::complete_tx::bytes.multicast::cluster.L2::cache_hint [%0], [%1, {%3, %4}], [%2], %5, %6;"
               ::"r"(dst), "l"(m), "r"(bar), "r"(c0), "r"(c1), "h"((uint16_t)3), "l"(pol) : "memory");
}
__device__ __forceinline__ void wtma3d(uint32_t dst, const CUtensorMap* m, int c0, int c1, int c2, uint32_t bar, uint64_t pol) {
  asm volatile("cp.async.bulk.tensor.3d.shared::cluster.global.mbarrier::complete_tx::bytes.multicast::cluster.L2::cache_hint [%0], [%1, {%3, %4, %5}], [%2], %6, %7;"
               ::"r"(dst), "l"(m), "r"(bar), "r"(c0), "r"(c1), "r"(c2), "h"((uint16_t)3), "l"(pol) : "memory");
}
__device__ __forceinline__ void wbulk(uint32_t dst, const void* src, uint32_t bytes, uint32_t bar, uint64_t pol) {
  asm volatile("cp.async.bulk.shared::cluster.global.mbarrier::complete_tx::bytes.multicast::cluster.L2::cache_hint [%0], [%1], %2, [%3], %4, %5;"
               ::"r"(dst), "l"(src), "r"(bytes), "r"(bar), "h"((uint16_t)3), "l"(pol) : "memory");
}
__device__ __forceinline__ void tma3d(uint32_t dst, const CUtensorMap* m, int c0, int c1, int c2, uint32_t bar) {
  asm volatile("cp.async.bulk.tensor.3d.shared::cluster.global.mbarrier::complete_tx::bytes [%0], [%1, {%3, %4, %5}], [%2];"
               ::"r"(dst), "l"(m), "r"(bar), "r"(c0), "r"(c1), "r"(c2) : "memory");
}
__device__ __forceinline__ void prefetch_l2(const void* p, uint32_t bytes) { asm volatile("cp.async.bulk.prefetch.L2.global [%0], %1;" ::"l"(p), "r"(bytes) : "memory"); }
__device__ __forceinline__ uint64_t policy_evict_first() { uint64_t p; asm volatile("createpolicy.fractional.L2::evict_first.b64 %0, 1.0;" : "=l"(p)); return p; }
__device__ __forceinline__ uint64_t policy_evict_normal() { uint64_t p; asm volatile("createpolicy.fractional.L2::evict_normal.b64 %0, 1.0;" : "=l"(p)); return p; }
__device__ __forceinline__ void fence_async_smem() { asm volatile("fence.proxy.async.shared::cta;" ::: "memory"); }
__device__ __forceinline__ bool elect_one() {
  uint32_t p;
  asm volatile("{\n.reg .pred P;\nelect.sync _|P, 0xffffffff;\nselp.u32 %0, 1, 0, P;\n}\n" : "=r"(p));
  return p;
}
__device__ __forceinline__ void wg_fence() { asm volatile("wgmma.fence.sync.aligned;" ::: "memory"); }
__device__ __forceinline__ void wg_commit() { asm volatile("wgmma.commit_group.sync.aligned;" ::: "memory"); }
template <int n> __device__ __forceinline__ void wg_wait() { asm volatile("wgmma.wait_group.sync.aligned %0;" ::"n"(n) : "memory"); }
__device__ __forceinline__ void wg_bar(int w) { asm volatile("bar.sync %0, 128;" ::"r"(w + 1) : "memory"); }
__device__ __forceinline__ void fence_gpu() { asm volatile("fence.acq_rel.gpu;" ::: "memory"); }
__device__ __forceinline__ uint32_t ld_relaxed(const uint32_t* p) { uint32_t v; asm volatile("ld.relaxed.gpu.global.u32 %0, [%1];" : "=r"(v) : "l"(p) : "memory"); return v; }
__device__ __forceinline__ uint32_t ld_acquire(const uint32_t* p) { uint32_t v; asm volatile("ld.acquire.gpu.global.u32 %0, [%1];" : "=r"(v) : "l"(p) : "memory"); return v; }
__device__ __forceinline__ uint4 ld_relaxed4(const uint4* p) {
  uint4 v; asm volatile("ld.relaxed.gpu.global.v4.u32 {%0,%1,%2,%3}, [%4];" : "=r"(v.x), "=r"(v.y), "=r"(v.z), "=r"(v.w) : "l"(p) : "memory"); return v;
}
__device__ __forceinline__ uint2 ld_relaxed2(const uint2* p) {
  uint2 v; asm volatile("ld.relaxed.gpu.global.v2.u32 {%0,%1}, [%2];" : "=r"(v.x), "=r"(v.y) : "l"(p) : "memory"); return v;
}
__device__ __forceinline__ void st_relaxed(uint32_t* p, uint32_t a) { asm volatile("st.relaxed.gpu.global.u32 [%0], %1;" ::"l"(p), "r"(a) : "memory"); }
__device__ __forceinline__ void st_relaxed4(uint4* p, uint32_t a, uint32_t b, uint32_t c, uint32_t d) {
  asm volatile("st.relaxed.gpu.global.v4.u32 [%0], {%1,%2,%3,%4};" ::"l"(p), "r"(a), "r"(b), "r"(c), "r"(d) : "memory");
}
__device__ __forceinline__ void st_relaxed2(uint2* p, uint32_t a, uint32_t b) {
  asm volatile("st.relaxed.gpu.global.v2.u32 [%0], {%1,%2};" ::"l"(p), "r"(a), "r"(b) : "memory");
}
__device__ __forceinline__ void red4(uint4* p, uint32_t a, uint32_t b, uint32_t c, uint32_t d) {
  asm volatile("red.relaxed.gpu.global.add.noftz.v4.bf16x2 [%0], {%1,%2,%3,%4};" ::"l"(p), "r"(a), "r"(b), "r"(c), "r"(d) : "memory");
}
__device__ __forceinline__ void red2(uint2* p, uint32_t a, uint32_t b) {
  asm volatile("red.relaxed.gpu.global.add.noftz.v2.bf16x2 [%0], {%1,%2};" ::"l"(p), "r"(a), "r"(b) : "memory");
}
constexpr int SPIN_MAX = 1 << 21;
__device__ __forceinline__ uint32_t pack_bf16(float lo, float hi) { uint32_t r; asm("cvt.rn.bf16x2.f32 %0, %1, %2;" : "=r"(r) : "f"(hi), "f"(lo)); return r; }
__device__ __forceinline__ float bf_lo(uint32_t v) { return __uint_as_float(v << 16); }
__device__ __forceinline__ float bf_hi(uint32_t v) { return __uint_as_float(v & 0xffff0000u); }
__device__ __forceinline__ float2 lds64(uint32_t a) { float2 v; asm volatile("ld.shared.v2.f32 {%0,%1}, [%2];" : "=f"(v.x), "=f"(v.y) : "r"(a)); return v; }
__device__ __forceinline__ void sts64f(uint32_t a, float x, float y) { asm volatile("st.shared.v2.f32 [%0], {%1,%2};" ::"r"(a), "f"(x), "f"(y) : "memory"); }
__device__ __forceinline__ void sts32(uint32_t a, uint32_t x) { asm volatile("st.volatile.shared.b32 [%0], %1;" ::"r"(a), "r"(x) : "memory"); }
__device__ __forceinline__ void gate(uint32_t a, int need) {
#pragma unroll 1
  for (int it = 0; it < SPIN_MAX; it++) {
    int v; asm volatile("ld.volatile.shared.b32 %0, [%1];" : "=r"(v) : "r"(a) : "memory");
    if (v >= need) break;
    __nanosleep(200);
  }
}
__device__ __forceinline__ void sts128(uint32_t a, uint32_t x, uint32_t y, uint32_t z, uint32_t u) { asm volatile("st.shared.v4.b32 [%0], {%1,%2,%3,%4};" ::"r"(a), "r"(x), "r"(y), "r"(z), "r"(u) : "memory"); }
__device__ __forceinline__ uint4 lds128(uint32_t a) { uint4 v; asm volatile("ld.shared.v4.u32 {%0,%1,%2,%3}, [%4];" : "=r"(v.x), "=r"(v.y), "=r"(v.z), "=r"(v.w) : "r"(a) : "memory"); return v; }
__device__ __forceinline__ uint32_t hmul2(uint32_t a, uint32_t b) { uint32_t r; asm("mul.rn.bf16x2 %0, %1, %2;" : "=r"(r) : "r"(a), "r"(b)); return r; }
__device__ __forceinline__ uint32_t hadd2(uint32_t a, uint32_t b) { uint32_t r; asm("add.rn.bf16x2 %0, %1, %2;" : "=r"(r) : "r"(a), "r"(b)); return r; }
__device__ __forceinline__ void stsm4(uint32_t a, uint32_t r0, uint32_t r1, uint32_t r2, uint32_t r3) {
  asm volatile("stmatrix.sync.aligned.m8n8.x4.shared.b16 [%0], {%1,%2,%3,%4};" ::"r"(a), "r"(r0), "r"(r1), "r"(r2), "r"(r3) : "memory");
}
__device__ __forceinline__ void stsm2(uint32_t a, uint32_t r0, uint32_t r1) {
  asm volatile("stmatrix.sync.aligned.m8n8.x2.shared.b16 [%0], {%1,%2};" ::"r"(a), "r"(r0), "r"(r1) : "memory");
}
__device__ __forceinline__ uint4 ldsm4(uint32_t a) {
  uint4 r; asm volatile("ldmatrix.sync.aligned.m8n8.x4.shared.b16 {%0,%1,%2,%3}, [%4];" : "=r"(r.x), "=r"(r.y), "=r"(r.z), "=r"(r.w) : "r"(a) : "memory"); return r;
}
__device__ __forceinline__ uint32_t movm(uint32_t a) { uint32_t r; asm("movmatrix.sync.aligned.m8n8.trans.b16 %0, %1;" : "=r"(r) : "r"(a)); return r; }
__device__ __forceinline__ void mma16816z(float (&d)[4], uint32_t a0, uint32_t a1, uint32_t a2, uint32_t a3, uint32_t b0, uint32_t b1) {
  asm("mma.sync.aligned.m16n8k16.row.col.f32.bf16.bf16.f32 {%0,%1,%2,%3}, {%4,%5,%6,%7}, {%8,%9}, {%10,%10,%10,%10};"
      : "=f"(d[0]), "=f"(d[1]), "=f"(d[2]), "=f"(d[3]) : "r"(a0), "r"(a1), "r"(a2), "r"(a3), "r"(b0), "r"(b1), "f"(0.f));
}
__device__ __forceinline__ void mma16816(float (&d)[4], const uint4& a, uint32_t b0, uint32_t b1) {
  asm("mma.sync.aligned.m16n8k16.row.col.f32.bf16.bf16.f32 {%0,%1,%2,%3}, {%4,%5,%6,%7}, {%8,%9}, {%0,%1,%2,%3};"
      : "+f"(d[0]), "+f"(d[1]), "+f"(d[2]), "+f"(d[3]) : "r"(a.x), "r"(a.y), "r"(a.z), "r"(a.w), "r"(b0), "r"(b1));
}
__device__ __forceinline__ void mma1688(float (&d)[4], uint32_t a0, uint32_t a1, uint32_t b0) {
  asm("mma.sync.aligned.m16n8k8.row.col.f32.bf16.bf16.f32 {%0,%1,%2,%3}, {%4,%5}, {%6}, {%0,%1,%2,%3};"
      : "+f"(d[0]), "+f"(d[1]), "+f"(d[2]), "+f"(d[3]) : "r"(a0), "r"(a1), "r"(b0));
}
__device__ __forceinline__ float quad_sum(float v) { v += __shfl_xor_sync(0xffffffffu, v, 1); v += __shfl_xor_sync(0xffffffffu, v, 2); return v; }
__device__ __forceinline__ float rcp(float x) { float r; asm("rcp.approx.ftz.f32 %0, %1;" : "=f"(r) : "f"(x)); return r; }
__device__ __forceinline__ float rsq(float x) { float r; asm("rsqrt.approx.ftz.f32 %0, %1;" : "=f"(r) : "f"(x)); return r; }
__device__ __forceinline__ float ex2(float x) { float r; asm("ex2.approx.ftz.f32 %0, %1;" : "=f"(r) : "f"(x)); return r; }
__device__ __forceinline__ uint32_t chk(uint32_t acc, uint32_t v, uint32_t tag) { uint32_t r; asm("lop3.b32 %0, %1, %2, %3, 0xF6;" : "=r"(r) : "r"(acc), "r"(v), "r"(tag)); return r; }
__device__ __forceinline__ uint32_t chk2(uint32_t a, uint32_t b, uint32_t tag) { uint32_t r; asm("lop3.b32 %0, %1, %2, %3, 0x7E;" : "=r"(r) : "r"(a), "r"(b), "r"(tag)); return r; }
__device__ __forceinline__ uint32_t tagged(uint32_t v, uint32_t tag) { return (v & ~1u) | tag; }

__device__ __forceinline__ int group_k0(int g, int j) {
  const int h = g >= 9, r = g - 2 - 7 * h;
  return g < 2 ? 64 * j + 32 * g : g < 16 ? 64 * (r + (r >= j)) + 32 * h : 32 * g;
}
__device__ __forceinline__ uint32_t xin_off(int c, int w) { return SM_X + (2 * c + w) * 8192; }
__device__ __forceinline__ uint32_t xin_bar(int c) { return BAR_FULLX + 8 * (c < 8 ? c ^ 4 : c); }
__device__ __forceinline__ constexpr uint32_t qkv_xslot(int g) { return g < 5 || g > 11 ? 2 : (0x5140762u >> (4 * (g - 5))) & 15; }

template <int N> struct IC { static constexpr int v = N; };

struct Cons {
  uint32_t sb;
  uint32_t rem;
  uint32_t sB, mB;
  uint32_t mX;
  bool elect;
  __device__ __forceinline__ void release2(uint32_t bar) const { if (elect) { mbar_arrive(sb + bar); mbar_arrive_remote(rem + bar); } }
  __device__ __forceinline__ uint32_t nextB(uint32_t& prev) {
    mbar_wait_c(sb + BAR_FULLB + sB, mB);
    const uint32_t a = (((sb & 0x3FFFF) + SM_B) >> 4) + sB * (BSLOT / 128);
    prev = sB == 0 ? 32 : sB - 8;
    sB += 8;
    if (sB == 40) { sB = 0; mB ^= 1; }
    return a;
  }
  __device__ __forceinline__ void progress(uint32_t v) const { if (elect) sts32(sb + SM_PROG + (threadIdx.x >> 5), v); }
  __device__ __forceinline__ void releaseLastB() const { release2(BAR_EMPTYB + (sB == 0 ? 32 : sB - 8)); }
};

__device__ __forceinline__ float2 gather_sums(const uint2* a, uint32_t stag) {
  uint2 sa, sc;
  do { sa = ld_relaxed2(a); sc = ld_relaxed2(a + 8); } while (__any_sync(0xffffffffu, chk2(sa.x, sc.x, stag) & 3));
  return make_float2(quad_sum(__uint_as_float(sa.x) + __uint_as_float(sc.x)), quad_sum(__uint_as_float(sa.y) + __uint_as_float(sc.y)));
}

struct Norm {
  float m0, m1;
  uint32_t nm0, nm1;
  float d0, d1;
  uint2 u0, u1;
  __device__ __forceinline__ Norm(float2 sum) : m0(sum.x * (-1.f / 576)), m1(sum.y * (-1.f / 576)), nm0(pack_bf16(m0, m0)), nm1(pack_bf16(m1, m1)), d0(0.f), d1(0.f) {}
  __device__ __forceinline__ uint4 centre(const uint4& a) const { return make_uint4(hadd2(a.x, nm0), hadd2(a.y, nm1), hadd2(a.z, nm0), hadd2(a.w, nm1)); }
  __device__ __forceinline__ void sqr(uint32_t a, uint32_t b) {
    d0 = fmaf(bf_lo(a), bf_lo(a), fmaf(bf_hi(a), bf_hi(a), d0)); d1 = fmaf(bf_lo(b), bf_lo(b), fmaf(bf_hi(b), bf_hi(b), d1));
  }
  __device__ __forceinline__ void send(uint2* a, int t, uint32_t stag) {
    d0 = quad_sum(d0); d1 = quad_sum(d1);
    if ((t & 3) == 0) st_relaxed2(a, (__float_as_uint(d0) & ~3u) | stag, __float_as_uint(d1));
  }
  __device__ __forceinline__ void fetch(const uint2* a) { u0 = ld_relaxed2(a); u1 = ld_relaxed2(a + 8); }
  __device__ __forceinline__ float2 rstd(const uint2* a, uint32_t stag) {
    while (__any_sync(0xffffffffu, chk2(u0.x, u1.x, stag) & 3)) fetch(a);
    const float e0 = bf_lo(nm0) - m0, e1 = bf_lo(nm1) - m1;
    const float v0 = fmaf(quad_sum(__uint_as_float(u0.x) + __uint_as_float(u1.x)), 1.f / 576, -e0 * e0);
    const float v1 = fmaf(quad_sum(__uint_as_float(u0.y) + __uint_as_float(u1.y)), 1.f / 576, -e1 * e1);
    uint32_t u = pack_bf16(fmaxf(v0, 0.f), fmaxf(v1, 0.f));
    u = pack_bf16(bf_lo(u) + 1e-5f, bf_hi(u) + 1e-5f);
    u = pack_bf16(bf_lo(u) * rsq(bf_lo(u)), bf_hi(u) * rsq(bf_hi(u)));
    float2 r = make_float2(rcp(bf_lo(u)), rcp(bf_hi(u)));
    asm volatile("" : "+f"(r.x), "+f"(r.y));
    return r;
  }
};

template <class Pre, class Mma>
__device__ __forceinline__ float2 ln_gemm_in(Cons& c, Group* G, uint32_t (&p)[18], float2& sum, int w, int st0, int j, int t, Pre&& pre, Mma&& mma) {
  const uint32_t xa = c.sb + (t >> 5) * 2048 + (t & 15) * 128, sw = (((t >> 4) & 1) ^ (t & 7)) * 16;
  float ra[4] = {0.f, 0.f, 0.f, 0.f}, rb[4] = {0.f, 0.f, 0.f, 0.f};
#pragma unroll 1
  for (int cc = 0; cc < 9; cc++) {
    const uint32_t a = xa + xin_off(cc, w);
    mbar_wait_c(c.sb + xin_bar(cc), 0);
    const uint4 u0 = ldsm4(a + sw), u1 = ldsm4(a + (sw ^ 32)), u2 = ldsm4(a + (sw ^ 64)), u3 = ldsm4(a + (sw ^ 96));
    mma16816(ra, u0, 0x3f803f80u, 0x3f803f80u); mma16816(rb, u1, 0x3f803f80u, 0x3f803f80u);
    mma16816(ra, u2, 0x3f803f80u, 0x3f803f80u); mma16816(rb, u3, 0x3f803f80u, 0x3f803f80u);
  }
  sum = make_float2(ra[0] + rb[0], ra[2] + rb[2]);
  pre(0);
  Norm n(sum);
  n.u0 = n.u1 = make_uint2(0, 0);
#pragma unroll
  for (int k = 0; k < 5; k++) {
    const uint4 u = ldsm4(xa + (k < 4 ? xin_off(j, w) + (sw ^ (32 * k)) : xin_off(8, w) + ((j ^ (t & 7)) << 4))), e = n.centre(u);
    p[4 * k] = u.x; p[4 * k + 1] = u.y;
    n.sqr(e.x, e.y);
    if (k < 4) { p[4 * k + 2] = u.z; p[4 * k + 3] = u.w; n.sqr(e.z, e.w); }
  }
  n.send(G->sq + st0 + 8 * j, t, 1);
  pre(1);
  float2 r = make_float2(0.f, 0.f);
  uint4 y0 = ldsm4(xa + xin_off(0, w) + sw), y1 = ldsm4(xa + xin_off(0, w) + (sw ^ 32));
#pragma unroll 1
  for (int cc = 0; cc < 9; cc++) {
#pragma unroll
    for (int i = 0; i < 2; i++) {
      const uint4 f0 = n.centre(y0), f1 = n.centre(y1);
      const uint32_t a = xa + xin_off(min(cc + i, 8), w);
      y0 = ldsm4(a + (sw ^ (64 - 64 * i))); y1 = ldsm4(a + (sw ^ (96 - 64 * i)));
      uint32_t prev;
      const uint32_t bb = c.nextB(prev);
      mma(true, bb, f0, f1);
      if (i == 1) {
        if (cc == 1) c.progress(3);
        if (cc == 5) n.fetch(G->sq + st0 + 16 * (t & 3));
        if (cc == 7) r = n.rstd(G->sq + st0 + 16 * (t & 3), 1);
        if (cc == 8 && w == 0) asm volatile("bar.arrive 6, 256;" ::: "memory");
      }
      wg_wait<1>();
      if (i + cc > 0) c.release2(BAR_EMPTYB + prev);
      if (cc >= 7) c.release2(BAR_EMPTYX + 32 + 8 * (2 * cc + i - 14));
    }
  }
  c.mX = 0xff;
  if (w == 1) asm volatile("bar.sync 6, 256;" ::: "memory");
  wg_wait<0>();
  c.releaseLastB();
  c.release2(BAR_EMPTYX + 24);
  return r;
}

template <bool QKV, class Pre, class Mma>
__device__ __forceinline__ float2 ln_gemm(Cons& c, Group* G, const float (&v)[36], uint32_t (&p)[18], float2& sum, int st0, int j, int t,
                                          int layer, uint32_t tag, Pre&& pre, Mma&& mma) {
  const uint32_t stag = (2 * layer + (QKV ? 1 : 2)) & 3;
  uint4 x[6][2];
  uint4* src = G->xbox + t;
  asm volatile("" : "+l"(src));
  auto buf = [&](int g) -> uint4 (&)[2] { return x[g < 16 ? (g - 2) % 6 : g - 13]; };
  auto load = [&](int g0) {
#pragma unroll
    for (int g = g0; g < g0 + (g0 < 14 ? 3 : 2); g++) {
      const uint4* a = g < 16 ? src + ((g - 2) % 7 >= j ? 256 : 0) + (2 * ((g - 2) % 7) + 16 * (g >= 9)) * 128 : src + 2 * g * 128;
      buf(g)[0] = ld_relaxed4(a); buf(g)[1] = ld_relaxed4(a + 128);
    }
  };
  auto invalid = [&](int g, uint32_t tag) {
    uint32_t bad = chk(chk(chk2(buf(g)[0].x, buf(g)[1].x, tag), buf(g + 1)[0].x, tag), buf(g + 1)[1].x, tag);
    if (g < 14) bad = chk(chk(bad, buf(g + 2)[0].x, tag), buf(g + 2)[1].x, tag);
    if (g == 16) bad = chk(chk(chk(chk(bad, buf(g)[0].z, tag), buf(g)[1].z, tag), buf(g + 1)[0].z, tag), buf(g + 1)[1].z, tag);
    return __any_sync(0xffffffffu, bad & 1);
  };
  uint4* const d = src + 2 * j * 128;
  const int sq = st0 + 16 * (t & 3);
  if (QKV) {
    float s0 = v[0] + v[1], s1 = v[2] + v[3];
#pragma unroll
    for (int i = 1; i < 9; i++) { s0 += v[4 * i] + v[4 * i + 1]; s1 += v[4 * i + 2] + v[4 * i + 3]; }
    s0 = quad_sum(s0); s1 = quad_sum(s1);
    if ((t & 3) == 0) st_relaxed2(G->sum + st0 + 8 * j, (__float_as_uint(s0) & ~3u) | stag, __float_as_uint(s1));
  }
#pragma unroll
  for (int i = 0; i < 18; i++) p[i] = pack_bf16(v[2 * i], v[2 * i + 1]);
#pragma unroll
  for (int i = 0; i < 2; i++) st_relaxed4(d + i * 128, tagged(p[4 * i], tag), p[4 * i + 1], p[4 * i + 2], p[4 * i + 3]);
  pre(0);
  if (QKV) {
    sum = gather_sums(G->sum + sq, stag);
    load(2);
  }
  Norm n(sum);
  pre(1);
  const uint32_t* probe = &(G->xbox + (2 * (t & 3) + 1) * 128 + (t | 31))->x;
  uint32_t pv;
  float2 r;
  auto inx = [](int g) { return QKV && ((g >= 5 && g < 12) || g == 17); };
  auto use = [](int g) { return QKV ? (g < 5 ? 108 : 101) + g : 18 + g; };
#pragma unroll
  for (int g = 0; g < 18; g++) {
    if (g < 16 ? g % 3 == 2 : g == 16) {
      const uint32_t lt = late(c.sb + BAR_PAST, tag);
      while (invalid(g, lt)) load(g);
      if (g < 16) load(g < 14 ? g + 3 : 16);
    }
    const uint4 f0 = n.centre(g < 2 ? make_uint4(p[8 * g], p[8 * g + 1], p[8 * g + 2], p[8 * g + 3]) : buf(g)[0]);
    const uint4 f1 = n.centre(g < 2 ? make_uint4(p[8 * g + 4], p[8 * g + 5], p[8 * g + 6], p[8 * g + 7]) : buf(g)[1]);
    if (g == 11) n.fetch(G->sq + sq);
    if (g == 16) r = n.rstd(G->sq + sq, stag);
    if (inx(g)) mbar_wait_c(c.sb + BAR_FULLX + 8 * qkv_xslot(g), ((0x34 >> qkv_xslot(g)) & 1) ^ (g == 17));
    else mbar_wait_c(c.sb + BAR_FULLB + 8 * (use(g) % 5), (use(g) / 5) & 1);
    mma(g, ((c.sb & 0x3FFFF) >> 4) + ((inx(g) ? xslot(qkv_xslot(g)) : SM_B + (use(g) % 5) * BSLOT) >> 4), f0, f1);
    if (g == 1) { wg_wait<1>(); c.release2(BAR_EMPTYB + 8 * (use(0) % 5)); }
    if (g < 2) {
      if (!QKV) {
        if (g == 0) {
          pv = ld_relaxed(probe);
        } else {
          const uint32_t lt = late(c.sb + BAR_PAST, tag);
          while (__any_sync(0xffffffffu, (pv ^ lt) & 1)) pv = ld_relaxed(probe);
          load(2);
        }
      }
      if (g == (QKV ? 0 : 1)) {
#pragma unroll
        for (int i = 2; i < 4; i++) st_relaxed4(d + (14 + i) * 128, tagged(p[4 * i], tag), p[4 * i + 1], p[4 * i + 2], p[4 * i + 3]);
        st_relaxed2((uint2*)(src + (32 + (j >> 1)) * 128) + (j & 1), tagged(p[16], tag), p[17]);
      }
      n.sqr(f0.x, f0.y); n.sqr(f0.z, f0.w); n.sqr(f1.x, f1.y); n.sqr(f1.z, f1.w);
      if (g == 1) {
        n.sqr(hadd2(p[16], n.nm0), hadd2(p[17], n.nm1));
        n.send(G->sq + st0 + 8 * j, t, stag);
      }
    }
    if (g == 1 && !QKV) { wg_wait<0>(); c.release2(BAR_EMPTYB + 8 * (use(1) % 5)); }
    else wg_wait<1>();
    if (g > (QKV ? 1 : 2) && !inx(g - 1)) c.release2(BAR_EMPTYB + 8 * (use(g - 1) % 5));
    if (QKV && g < 13) c.progress(33 + g);
    if (QKV && g == 11) c.release2(BAR_EMPTYX + 8 * qkv_xslot(17));
    if (QKV && g >= 12 && g < 16) c.release2(BAR_EMPTYX + 32 + 8 * (g - 12));
  }
  if (QKV) c.mX = 0x34 ^ 0xf3;
  else { c.sB = 8 * (36 % 5); c.mB = (36 / 5) & 1; }
  wg_wait<0>();
  if (!QKV) c.release2(BAR_EMPTYB + 8 * (use(17) % 5));
  return r;
}

template <int NB, int OFF>
__device__ __forceinline__ void glu(const float (&a)[128], uint32_t (&h)[144]) {
#pragma unroll
  for (int b = 0; b < 2 * NB; b++) {
    if (OFF == 120) h[OFF + b] = pack_bf16(a[2 * b] * a[4 * NB + 2 * b], a[2 * b + 1] * a[4 * NB + 2 * b + 1]);
    else h[OFF + b] = hmul2(pack_bf16(a[2 * b], a[2 * b + 1]), pack_bf16(a[4 * NB + 2 * b], a[4 * NB + 2 * b + 1]));
  }
}

__global__ void __cluster_dims__(2, 1, 1) __launch_bounds__(384, 1)
fused_kernel(const __nv_bfloat16* __restrict__ x_in, Group* ws, const char* __restrict__ wqkv,
             const char* __restrict__ wo, char* __restrict__ out, uint32_t first, const __grid_constant__ Maps maps,
             const char* __restrict__ wg, const char* __restrict__ wu) {
  extern __shared__ __align__(1024) uint8_t smem_raw[];
  const uint32_t sb = smem_u32(smem_raw);
  const uint32_t bx = blockIdx.x - first;
  if (bx >= NCTA) {
    const int e = blockIdx.x & 3;
    const uint32_t par = ~ld_relaxed(ws->flag + 32) & 1;
    __nanosleep(1000);
    if (threadIdx.x < 16) prefetch_l2(wo + (144 * e + 9 * threadIdx.x) * 1152, 9 * 1152);
#pragma unroll 1
    for (int r = threadIdx.x >> 3; r < 144; r += 48) {
      const uint4* row = (const uint4*)(wo + (144 * e + r) * 1152) + (threadIdx.x & 7);
      float a = 0.f;
      uint4 u;
#pragma unroll
      for (int i = 0; i < 72; i += 8) {
        u = __ldg(row + i);
        a += ((bf_lo(u.x) + bf_hi(u.x)) + (bf_lo(u.y) + bf_hi(u.y))) + ((bf_lo(u.z) + bf_hi(u.z)) + (bf_lo(u.w) + bf_hi(u.w)));
      }
      const int h = r >= 72, k = r - 72 * h;
      ((Scratch*)ws)->woc[threadIdx.x & 7][k < 64 ? 64 + 8 * k + ((2 * e + h) ^ (k & 7)) : 576 * h + 8 * (k & 7) + (e ^ (k & 7))] = u;
      a = quad_sum(a);
      a += __shfl_xor_sync(0xffffffffu, a, 4);
      if ((threadIdx.x & 7) == 0) ((Scratch*)ws)->woc[2 * e + h][640 + k] = make_uint4(pack_bf16(a, a - bf_lo(pack_bf16(a, 0.f))), 0, 0, 0);
    }
    fence_gpu();
    __syncthreads();
    if (threadIdx.x == 0) st_relaxed(((Scratch*)ws)->done + e, par);
    const int cc = threadIdx.x % 54, r0 = threadIdx.x / 54, part = cc / 18, jj = 2 * e + (cc % 18) / 9, c9 = cc % 9;
    if (r0 < 6) {
#pragma unroll 4
      for (int k = r0; k < 576; k += 6) {
        const uint4 u = __ldg((const uint4*)(wqkv + k * 3456 + part * 1152 + 144 * jj) + c9);
        ((Scratch*)ws)->wq[jj][k >> 4][c9 < 8 ? part * 128 + (k & 15) * 8 + (c9 ^ (k & 7)) : 384 + part * 16 + (k & 15)] = u;
      }
    }
    fence_gpu();
    __syncthreads();
    if (threadIdx.x == 0) st_relaxed(((Scratch*)ws)->done + 32 + e, par);
    return;
  }
  if (threadIdx.x == 0) asm volatile("prefetch.tensormap [%0];" ::"l"(&maps.x) : "memory");
  const int warp = __shfl_sync(0xffffffffu, threadIdx.x >> 5, 0);
  const int lane = threadIdx.x & 31;
  const int rank = blockIdx.x & 1;
  if (elect_one()) {
    if (warp >= 8) {
#pragma unroll
      for (int i = 0; i < 9; i++) mbar_init(sb + SM_BAR + 72 * (warp - 8) + 8 * i, warp < 10 ? 1 : 4);
      sts32(sb + SM_PROG + 4 * (warp - 8), 0);
      asm volatile("fence.mbarrier_init.release.cluster;" ::: "memory");
    } else if (warp == 1 || warp == 2) {
      asm volatile("prefetch.tensormap [%0];" ::"l"(&maps.x + warp) : "memory");
    } else if (warp == 3) {
      prefetch_l2((const char*)x_in + bx * 18432, 18432);
    }
  }
  __syncwarp();
  asm volatile("barrier.cluster.arrive.relaxed.aligned;" ::: "memory");
  if (warp == 8) PROFX(53);
  const int cl = bx >> 1, u = cl - 36;
  const int lb = (cl < 4 ? cl : cl < 36 ? 8 * ((cl - 4) & 7) + ((cl - 4) >> 3) + (((cl - 4) & 7) ? 0 : 4) : 8 * (1 + u % 7) + 4 + u / 7) * 2 + rank;
#define CTA_J(b) (((b) >> 1) & 7)
#define CTA_RB(b) ((((b) >> 4) << 1) | ((b) & 1))
  const int j = CTA_J(lb), rb = CTA_RB(lb);

  PROF(23);
  if (warp >= 8) {
    asm volatile("setmaxnreg.dec.sync.aligned.u32 40;");
    auto x_chunk = [&](int cc) {
      mbar_expect_tx(sb + xin_bar(cc), 16384);
      tma3d(sb + xin_off(cc, 0), &maps.x, 64 * cc, 0, 64 * rb, sb + xin_bar(cc));
      tma3d(sb + xin_off(cc, 1), &maps.x, 64 * cc, 1, 64 * rb, sb + xin_bar(cc));
    };
    if (warp == 9 && elect_one()) {
      fence_async_smem();
#pragma unroll 1
      for (int i = 0; i < 9; i++) x_chunk(i);
    }
    __syncwarp();
    if (warp == 9) PROFX(54);
    asm volatile("barrier.cluster.wait.aligned;" ::: "memory");
    if (warp == 8) PROFX(56);
    const uint64_t pol = policy_evict_first(), pola = policy_evict_normal();
    uint4 (* const wq)[432] = ((Scratch*)ws)->wq[j];
    const uint32_t par = ~ld_relaxed(ws[2 * rb].flag + 32 + 32 * j) & 1;
    auto qkv_group = [&](bool copy, int k, uint32_t dst, uint32_t bar) {
      if (copy) {
        wbulk(dst + rank * 8192, wq[(k >> 4) + rank], 6912, bar, pol);
      } else {
        wtma3d(dst + rank * 8192, &maps.qm, 72 * j, k + 16 * rank, 0, bar, pola);
        wtma3d(dst + rank * 8192 + 6144, &maps.qc, 72 * j + 64, k + 16 * rank, 0, bar, pola);
      }
    };
    auto chore = [&](int i) {
#pragma unroll 1
      for (int it = 0; __any_sync(0xffffffffu, ld_acquire(((Scratch*)ws)->done + i) != par); it++) if (it == SPIN_MAX) asm volatile("trap;");
      asm volatile("fence.proxy.async.global;" ::: "memory");
    };
    const int ktab = group_k0(lane, j);
    auto qkv_gate = [&](int g) { if (g >= 8) gate(sb + SM_PROG, 33 + ((g - 8) * 23 >> 4)); };
    if (warp == 8) {
      uint32_t s = 0, ph = 1;
      auto slot = [&](uint32_t bytes, auto&& issue) {
        const uint32_t bar = sb + BAR_FULLB + 8 * s;
        mbar_wait(sb + BAR_EMPTYB + 8 * s, ph);
        if (elect_one()) {
          mbar_expect_tx(bar, bytes);
          issue(sb + SM_B + s * BSLOT, bar);
        }
        if (++s == 5) { s = 0; ph ^= 1; }
      };
#pragma unroll 1
      for (int layer = 0; layer < NLAYERS; layer++) {
        if (layer) chore(32 + (j >> 1));
#pragma unroll 1
        for (int g = 0; g < 18 - layer; g += layer && g == 4 ? 8 : 1) {
          const int k = layer ? __shfl_sync(0xffffffffu, ktab, g) : 32 * g;
          if (layer) qkv_gate(g);
          else if (g == 0) mbar_wait(sb + xin_bar(3), 0);
          slot(2 * 6912, [&](uint32_t dst, uint32_t bar) { qkv_group(layer, k, dst, bar); });
        }
#pragma unroll 1
        for (int t = 0; t < 5; t++) {
          const CUtensorMap* m = &maps.g + (t < 3 ? rank : 2 + rank);
          asm volatile("" : "+l"(m));
          const int c2 = t < 3 ? 9 * j + 2 * t : 18 * j + 3 + 3 * t;
          const uint32_t half = t < 3 ? 8192 : 6144;
          const uint64_t pt = layer == 0 && (t == 0 || t > 2) ? pola : pol;
          auto tile = [&](int g) {
            const int k = __shfl_sync(0xffffffffu, ktab, g);
            slot(2 * half, [&](uint32_t dst, uint32_t bar) { wtma3d(dst + rank * half, m, 0, k, c2, bar, pt); });
          };
          int g = 0;
          if (t == 0) {
#pragma unroll 1
            for (; g < 5; g++) {
              mbar_wait(sb + BAR_FULLB + 8 * (s == 0 ? 4 : s - 1), s == 0 ? ph : ph ^ 1);
              if (g == 2) gate(sb + SM_PROG + 4, 32 * layer + 20);
              tile(g);
            }
          }
#pragma unroll 1
          for (; g < 18; g++) tile(g);
        }
      }
    } else if (warp == 9) {
      uint32_t mE = 0;
      auto acquire = [&](uint32_t s) { mbar_wait(sb + BAR_EMPTYX + 8 * s, (mE >> s) & 1); mE ^= 1u << s; };
      auto slot = [&](uint32_t s, const CUtensorMap* m, int col, int row, uint64_t pol) {
        acquire(s);
        if (elect_one()) {
          mbar_expect_tx(sb + BAR_FULLX + 8 * s, XSLOT);
          wtma2d(sb + xslot(s) + rank * 9216, m, col, row + 72 * rank, sb + BAR_FULLX + 8 * s, pol);
        }
      };
#pragma unroll 1
      for (int layer = 0; layer < NLAYERS; layer++) {
        if (layer) chore(32 + (j >> 1));
#pragma unroll 1
        for (int g = 5; g < 18 * layer; g += g == 11 ? 6 : 1) {
          const uint32_t s = qkv_xslot(g);
          const int k = __shfl_sync(0xffffffffu, ktab, g);
          if (g < 12) qkv_gate(g);
          acquire(s);
          if (elect_one()) {
            mbar_expect_tx(sb + BAR_FULLX + 8 * s, 2 * 6912);
            qkv_group(true, k, sb + xslot(s), sb + BAR_FULLX + 8 * s);
          }
          mbar_wait(sb + BAR_FULLX + 8 * s, (mE >> s) & 1);
        }
#pragma unroll 1
        for (int i = 0; i < 4; i++) slot(4 + i, &maps.o, 64 * j, 144 * i, pola);
        if (layer == 0) { chore(lane & 3); PROFX(57); }
        acquire(3);
        if (elect_one()) {
          mbar_expect_tx(sb + BAR_FULLX + 24, 10240 + 1280);
          wbulk(sb + SM_WOC + rank * 5120, ((Scratch*)ws)->woc[j] + rank * 320, 5120, sb + BAR_FULLX + 24, pola);
          wbulk(sb + SM_WSUM + rank * 640, ((Scratch*)ws)->woc[j] + 640 + rank * 40, 640, sb + BAR_FULLX + 24, pola);
        }
#pragma unroll 1
        for (int u = 0; u < 36; u++) slot(4 * (u & 1) + ((u >> 1) & 3), &maps.d, u < 4 ? 512 : 64 * ((j + (u >> 2)) & 7), 576 * j + 144 * (u & 3), pol);
      }
    } else {
      const int w = warp - 10, grp = 2 * rb + w;
      auto exchange = [&](uint32_t v, uint32_t bar) {
        fence_gpu();
        __syncwarp();
        if (w == 0 && v != 1) PROFX(64 + 58 - 2 * v);
        if (lane == 0) st_relaxed(ws[grp].flag + j, v);
#pragma unroll 1
        for (int it = 0;; it++) {
          const uint32_t f = ld_relaxed(ws[grp].flag + (lane & 7));
          if (__all_sync(0xffffffffu, v ? f >= v : f == 0)) break;
          if (it == SPIN_MAX) asm volatile("trap;");
        }
        if (lane == 0) mbar_arrive(sb + bar + 8 * w);
      };
      mbar_wait(sb + xin_bar(0), 0);
      if (lane == 0) prefetch_l2(wqkv + (2 * bx + w) * 7776, 7776);
      gate(sb + SM_PROG, 3);
      if (w == 0 && lane < 6) asm volatile("prefetch.tensormap [%0];" ::"l"(&maps.o + lane) : "memory");
#pragma unroll 1
      for (int i = lane; i < 72; i += 32) {
        asm volatile("prefetch.global.L2 [%0];" ::"l"((w ? wu : wg) + (size_t)(36 * rb + (i >> 1)) * 9216 + 1152 * j + 128 * (i & 1)));
        __nanosleep(700);
      }
      gate(sb + SM_PROG, 22);
#pragma unroll 1
      for (int i = lane; i < 2 * INBOX; i += 64) {
        uint4* p = ws[grp].inbox[0] + 2 * j * INBOX + i;
        st_relaxed4(p, 0, 0, 0, 0); st_relaxed4(p + 32, 0, 0, 0, 0);
        __nanosleep(150);
      }
      exchange(1, BAR_CLR);
      if (w == 0) PROFX(59);
#pragma unroll 1
      for (int layer = 0; layer < NLAYERS; layer++) {
        mbar_wait(sb + BAR_REDDONE + 8 * w, layer);
        if (w == 0) PROFX(64 + 53 + 4 * layer);
        exchange(2 - 2 * layer, BAR_RREADY);
        if (w == 0) PROFX(64 + 56 + 4 * layer);
      }
      mbar_wait(sb + BAR_DONE + 8 * w, 0);
    }
  } else {
    asm volatile("setmaxnreg.inc.sync.aligned.u32 232;");
#define THREAD_IDS()                                                                   \
    int tid_ = threadIdx.x, bid_ = lb;                                                  \
    asm volatile("" : "+r"(tid_), "+r"(bid_));                                          \
    const int w = warp >> 2, wp = warp & 3;                                             \
    const int lane = tid_ & 31, t = tid_ & 127, g = lane >> 2, q = lane & 3;           \
    const int j = CTA_J(bid_), rb = CTA_RB(bid_), grp = 2 * rb + w;                    \
    const int st0 = wp * 64 + g;                         \
    Group* const G = ws + grp;                                                         \
    const uint32_t dsb = (sb & 0x3FFFF) >> 4;                                          \
    (void)t; (void)g; (void)q; (void)grp; (void)j; (void)st0; (void)dsb; (void)G
    Cons c;
    c.sb = sb; c.sB = 0; c.mB = 0; c.mX = 0; c.elect = (threadIdx.x & 127) == 0;
    asm volatile("mapa.shared::cluster.u32 %0, %1, %2;" : "=r"(c.rem) : "r"(sb), "r"(rank ^ 1));
    float v[36], a1[96], a2[12];
    float2 sum, rs;
    uint32_t res[18], xtag;
    auto qkv_mma = [&](bool acc, uint32_t bb, const uint4& f0, const uint4& f1) {
      wg_fence();
      wgmma_ra<192>(a1, f0, desc_hi(2048, 1024, 1) + bb, acc);
      wgmma_ra<24>(a2, f0, desc_hi(128, 256, 0) + (bb + 384), acc);
      wgmma_ra<192>(a1, f1, desc_hi(2048, 1024, 1) + (bb + 512), true);
      wgmma_ra<24>(a2, f1, desc_hi(128, 256, 0) + (bb + 896), true);
      wg_commit();
    };
    {
      THREAD_IDS();
      {
        if (q == 0) { st_relaxed2(G->sum + st0 + 8 * j, 0, 0); st_relaxed2(G->sq + st0 + 8 * j, 0, 0); }
        if (wp == 3) {
#pragma unroll
          for (int i = 0; i < 5; i++) st_relaxed4(G->halo + j * 160 + lane + i * 32, 0, 0, 0, 0);
        }
        if (lane >= 24) st_relaxed4(G->obox + (8 + j) * 128 + t, 0, 0, 0, 0);
      }
      xtag = __shfl_sync(0xffffffffu, ~ld_relaxed(G->flag + 32 + 32 * j) & 1, 0);
      if (lane >= 24) st_relaxed4(G->xbox + (2 * j + 1) * 128 + t, xtag ^ 1, 0, 0, 0);
      asm volatile("barrier.cluster.wait.aligned;" ::: "memory");
      PROF(0);
#pragma unroll
      for (int i = 0; i < 96; i++) asm volatile("mov.b32 %0, 0;" : "=f"(a1[i]));
#pragma unroll
      for (int i = 0; i < 12; i++) asm volatile("mov.b32 %0, 0;" : "=f"(a2[i]));
      PROF(1);
      rs = ln_gemm_in(c, G, res, sum, w, st0, j, t, [&](int i) { PROF(2 + i); if (i) PROF(4); }, qkv_mma);
    }
#pragma unroll 1
    for (int layer = 0;; layer++) {
      const uint32_t tag = layer ^ 1;
      uint4 own[5];
      {
        THREAD_IDS();
        PROF(pb + 4);
        uint32_t kv[3][18];
        auto cvt = [&](int b, float r) {
#pragma unroll
          for (int cc = 0; cc < 18; cc++) {
            const float* a = (cc == 8 ? a2 + 4 : cc == 17 ? a2 + 8 : cc < 8 ? a1 + 32 + 4 * cc : a1 + 28 + 4 * cc) + 2 * (b - 1);
            const uint32_t u = pack_bf16(a[0] * r, a[1] * r);
            kv[b][cc] = cc < 9 ? u : movm(u);
          }
        };
        cvt(2, rs.y);
#pragma unroll
        for (int i = 0; i < 18; i += 4) kv[2][i] = tagged(kv[2][i], tag);
        const uint32_t msg = sb + (w ? xslot(3) : xslot(0) + 24576) + wp * 2304 + lane * 16;
        if (wp == 3) {
          uint4* hp = G->halo + j * 160 + lane;
#pragma unroll
          for (int i = 0; i < 4; i++) st_relaxed4(hp + i * 32, kv[2][4 * i], kv[2][4 * i + 1], kv[2][4 * i + 2], kv[2][4 * i + 3]);
          st_relaxed2((uint2*)(hp + 128), kv[2][16], kv[2][17]);
        } else {
#pragma unroll
          for (int i = 0; i < 4; i++) sts128(msg + i * 512, kv[2][4 * i], kv[2][4 * i + 1], kv[2][4 * i + 2], kv[2][4 * i + 3]);
          sts64f(msg + 2048 - lane * 8, __uint_as_float(kv[2][16]), __uint_as_float(kv[2][17]));
        }
        cvt(1, rs.x);
        uint32_t Q[4][6];
#pragma unroll
        for (int h = 0; h < 4; h++)
#pragma unroll
          for (int i = 0; i < 6; i++) {
            const float* a = 4 * h + i < 16 ? a1 + 8 * h + 2 * i : a2 + 8 * h + 2 * i - 32;
            const uint32_t u = pack_bf16(a[0], a[1]);
            Q[h][i] = i < 2 ? (q >= h ? u : 0) : i < 4 ? u : (q <= h ? u : 0);
          }
        const bool lo0 = 2 * q > g, lo1 = 2 * q + 1 > g;
        const uint32_t M = (lo0 ? 0xffffu : 0u) | (lo1 ? 0xffff0000u : 0u);
        auto scores = [&](int h, int b, float (&s)[4]) {
          mma16816z(s, Q[h][0], Q[h][1], Q[h][2], Q[h][3], kv[b][2 * h], kv[b][2 * h + 1]);
          mma1688(s, Q[h][4], Q[h][5], kv[b][2 * h + 2]);
        };
        auto softmax = [&](float (&l)[4][2], float r, uint32_t (&P)[4]) {
          const float sl = r * (0.23570226039551584f * 1.4426950408889634f);
          float m[4];
#pragma unroll
          for (int h = 0; h < 4; h++) { m[h] = fmaxf(l[h][0], l[h][1]); m[h] = fmaxf(m[h], __shfl_xor_sync(0xffffffffu, m[h], 1)); }
#pragma unroll
          for (int h = 0; h < 4; h++) m[h] = fmaxf(m[h], __shfl_xor_sync(0xffffffffu, m[h], 2)) * sl;
#pragma unroll
          for (int h = 0; h < 4; h++) P[h] = pack_bf16(ex2(fmaf(l[h][0], sl, -m[h])), ex2(fmaf(l[h][1], sl, -m[h])));
        };
        const bool remote = wp == 0 && rb > 0;
        const uint4* hp = (G - 2)->halo + j * 160 + lane;
        auto halo = [&] {
#pragma unroll
          for (int i = 0; i < 4; i++) { const uint4 u = ld_relaxed4(hp + i * 32); kv[0][4 * i] = u.x; kv[0][4 * i + 1] = u.y; kv[0][4 * i + 2] = u.z; kv[0][4 * i + 3] = u.w; }
          const uint2 u = ld_relaxed2((const uint2*)(hp + 128));
          kv[0][16] = u.x; kv[0][17] = u.y;
        };
#pragma unroll
        for (int i = 0; i < 18; i++) kv[0][i] = 0;
        float l0[4][2], l1[4][2];
#pragma unroll
        for (int h = 0; h < 4; h++) {
          float s1[4], s2[4];
          scores(h, 1, s1); scores(h, 2, s2);
          l0[h][0] = s1[0]; l0[h][1] = s1[1];
          l1[h][0] = lo0 ? s1[2] : s2[2]; l1[h][1] = lo1 ? s1[3] : s2[3];
        }
        hp += __float_as_uint(l1[0][0]) & late(sb + BAR_PAST, 0);
        if (remote) halo();
        uint32_t P0[4], P1[4];
        softmax(l1, rs.y, P1);
        if (remote) {
          while (__any_sync(0xffffffffu, chk(chk(chk(chk2(kv[0][0], kv[0][4], tag), kv[0][8], tag), kv[0][12], tag), kv[0][16], tag) & 1)) halo();
        }
        wg_bar(w);
        if (wp > 0) {
          const uint32_t from = msg - 2304;
#pragma unroll
          for (int i = 0; i < 4; i++) { const uint4 u = lds128(from + i * 512); kv[0][4 * i] = u.x; kv[0][4 * i + 1] = u.y; kv[0][4 * i + 2] = u.z; kv[0][4 * i + 3] = u.w; }
          const float2 u = lds64(from + 2048 - lane * 8);
          kv[0][16] = __float_as_uint(u.x); kv[0][17] = __float_as_uint(u.y);
        }
        PROF(pb + 5);
        const bool first = (rb == 0 && wp == 0);
#pragma unroll
        for (int h = 0; h < 4; h++) {
          float s0[4];
          scores(h, 0, s0);
          if (first) s0[0] = s0[1] = -INFINITY;
          l0[h][0] = lo0 ? s0[0] : l0[h][0]; l0[h][1] = lo1 ? s0[1] : l0[h][1];
        }
        softmax(l0, rs.x, P0);
        uint4* ob = G->obox + t;
        uint32_t car0 = 0, car1 = 0;
#pragma unroll
        for (int h = 0; h < 4; h++) {
          float o[3][4], z[4] = {0.f, 0.f, 0.f, 0.f};
          mma1688(z, P0[h], P1[h], 0x3f803f80u);
#pragma unroll
          for (int i = 0; i < 3; i++) {
            mma16816z(o[i], P0[h] & ~M, P1[h] & M, 0u, P1[h] & ~M, kv[1][9 + 2 * h + i], kv[2][9 + 2 * h + i]);
            mma1688(o[i], P0[h] & M, 0u, kv[0][9 + 2 * h + i]);
          }
          const float i0 = rcp(z[0]), i1 = rcp(z[2]);
#pragma unroll
          for (int i = 0; i < 3; i++) { o[i][0] *= i0; o[i][1] *= i0; o[i][2] *= i1; o[i][3] *= i1; }
          const uint32_t o0 = q < h ? car0 : pack_bf16(o[0][0], o[0][1]), o1 = q < h ? car1 : pack_bf16(o[0][2], o[0][3]);
          own[h] = make_uint4(o0 | 1, o1, pack_bf16(o[1][0], o[1][1]), pack_bf16(o[1][2], o[1][3]));
          if (h < 3) st_relaxed4(ob + (8 * h + j) * 128, own[h].x, own[h].y, own[h].z, own[h].w);
          car0 = pack_bf16(o[2][0], o[2][1]); car1 = pack_bf16(o[2][2], o[2][3]);
        }
        car0 = tagged(car0, tag);
        own[4] = make_uint4(car0, car1, 0, 0);
        PROF(pb + 6);
      }
      uint2 sa, sc;
      {
        THREAD_IDS();
        uint4* src = G->obox + t;
        asm volatile("" : "+l"(src));
        uint4 x[32];
        const uint4* from[7];
#pragma unroll
        for (int r = 0; r < 7; r++) { from[r] = src + (r >= j ? 128 : 0); asm volatile("" : "+l"(from[r])); }
        auto load = [&](int i) { x[i] = ld_relaxed4(i < 28 ? from[i % 7] + (8 * (i / 7) + i % 7) * 128 : src + (i + 4) * 128); };
        const uint32_t* probe = &(G->obox + (8 + (lane & 7)) * 128 + (t | 31))->x;
        uint32_t pv = ld_relaxed(probe);
#pragma unroll
        for (int i = 3; i < 8; i++) mbar_wait_c(sb + BAR_FULLX + 8 * i, (c.mX >> i) & 1);
        c.mX ^= 0xf8;
        while (__any_sync(0xffffffffu, ~pv & 1)) pv = ld_relaxed(probe);
        PROF(25 - layer);
        if (w == 1) asm volatile("bar.sync 7, 256;" ::: "memory");
#pragma unroll
        for (int i = 0; i < 10; i++) load(i);
        if (w == 0) asm volatile("bar.arrive 7, 256;" ::: "memory");
        st_relaxed4(src + (24 + j) * 128, own[3].x, own[3].y, own[3].z, own[3].w);
        st_relaxed2((uint2*)(src + (32 + (j >> 1)) * 128) + (j & 1), own[4].x, own[4].y);
        PROF(27 - layer);
        float a[36];
        float e[4];
        constexpr uint32_t NEXT = 576 - (575u << 16);
        auto step = [&](const uint4& f, uint32_t s, int i, uint32_t more, bool acc) {
          const uint32_t r = (xslot(4) >> 4) + (i < 4 ? 72 * s + 16 * i : 144 * s + 64) * 8, c = (SM_WOC >> 4) + (i < 4 ? 64 + 128 * i : 0) + s;
          wgmma_ra<72>(a, f, desc_hi(0, i < 4 ? 1024 : 9216, 1) + (dsb + more + (r + ((c - r) << 16))), acc);
        };
        wg_fence();
#pragma unroll
        for (int i = 0; i < 5; i++) wgmma_ra<8>(e, own[i], desc_hi(128, 0, 0) + (dsb + (SM_WSUM >> 4) + 16 * i), i > 0);
        wg_commit();
#pragma unroll
        for (int i = 0; i < 4; i++) step(own[i], 0, i, j * NEXT, i > 0);
        wg_commit();
        PROF(29 - layer);
        auto batch = [&](auto e0, auto e1, auto e2, int b) {
          constexpr int E0 = decltype(e0)::v, E1 = decltype(e1)::v, E2 = decltype(e2)::v;
          const uint32_t one = late(sb + BAR_PAST, 1);
          while (true) {
            uint32_t bad = 0;
#pragma unroll
            for (int i = E0; i < E1; i++) bad = i < 28 ? chk(bad, x[i].x, one) : chk(chk(bad, x[i].x, tag), x[i].z, tag);
            if (!__any_sync(0xffffffffu, bad & 1)) break;
#pragma unroll
            for (int i = E0; i < E1; i++) load(i);
          }
          if (b == 0) PROF(pb + 7);
          if (b == 1) { c.progress(32 * layer + 20); wg_wait<1>(); }
#pragma unroll
          for (int i = E1; i < E2; i++) load(i);
          if (b == 2) { sa = ld_relaxed2(G->sum + st0 + 16 * q); sc = ld_relaxed2(G->sum + st0 + 16 * q + 8); }
          wg_fence();
#pragma unroll
          for (int i = E0; i < E1; i++) step(x[i], i % 7, i / 7, i < 28 && i % 7 >= j ? NEXT : 0, true);
          wg_commit();
          if (b == 0) {
            wg_wait<2>();
            if (q == 0) st_relaxed2(G->sum + st0 + 8 * j, (__float_as_uint(e[0] + e[1]) & ~3u) | ((2 * layer + 2) & 3), __float_as_uint(e[2] + e[3]));
          }
        };
        batch(IC<0>(), IC<10>(), IC<21>(), 0);
        batch(IC<10>(), IC<21>(), IC<32>(), 1);
        batch(IC<21>(), IC<32>(), IC<32>(), 2);
        wg_wait<0>();
        if (w == 0) asm volatile("bar.arrive 3, 256;" ::: "memory");
        PROF(pb + 8);
#pragma unroll
        for (int i = 0; i < 18; i++) {
          v[2 * i] = bf_lo(res[i]) + a[2 * i];
          v[2 * i + 1] = bf_hi(res[i]) + a[2 * i + 1];
        }
      }
      uint32_t lsb;
      uint32_t h[144];
      {
        THREAD_IDS();
        float a[128];
        const uint32_t xd = sb + xslot(4 * w) + (lane >> 4) * 1024 + (16 * wp + (lane & 15)) * 16;
        const float2 rs = ln_gemm<false>(c, G, v, res, sum, st0, j, t, layer, xtag,
          [&](int i) {
            if (i == 0) {
              lsb = ((res[0] & 1) | (res[4] & 1) << 1 | (res[8] & 1) << 2 | (res[12] & 1) << 3 | (res[16] & 1) << 4) ^ (xtag * 31);
              const uint32_t st = late(sb + BAR_PAST, (2 * layer + 2) & 3);
              while (__any_sync(0xffffffffu, chk2(sa.x, sc.x, st) & 3)) { sa = ld_relaxed2(G->sum + st0 + 16 * q); sc = ld_relaxed2(G->sum + st0 + 16 * q + 8); }
              sum.x += quad_sum(__uint_as_float(sa.x) + __uint_as_float(sc.x)); sum.y += quad_sum(__uint_as_float(sa.y) + __uint_as_float(sc.y));
              if (w == 1) asm volatile("bar.sync 3, 256;" ::: "memory");
            }
            PROF(pb + 9 + i);
          },
          [&](int gi, uint32_t bb, const uint4& f0, const uint4& f1) {
            if (gi == 0) PROF(pb + 11);
            if (gi == 16 && w == 1) asm volatile("bar.sync 5, 256;" ::: "memory");
            wg_fence();
            wgmma_ra<256>(a, f0, desc_hi(4096, 1024, 1) + bb, gi > 0);
            wgmma_ra<256>(a, f1, desc_hi(4096, 1024, 1) + (bb + 128), true);
            wg_commit();
            if (gi == 17 && w == 0) asm volatile("bar.arrive 5, 256;" ::: "memory");
            stsm4(xd + gi * 4096, f0.x, f0.y, f0.z, f0.w);
            stsm4(xd + gi * 4096 + 2048, f1.x, f1.y, f1.z, f1.w);
            if (gi == 17) { fence_async_smem(); wg_bar(w); }
          });
        sts64f(sb + SM_KEEP + (tid_ >> 2) * 8, rs.x * rs.x, rs.y * rs.y);
        c.progress(32 * layer + 22);
        PROF(pb + 12);
        glu<16, 0>(a, h);
        const Desc da0 = desc_hi(1024, 128, 0) + (dsb + (xslot(4 * w) >> 4));
        auto tile = [&](auto wide, auto last) {
          const uint32_t xe = BAR_EMPTYX + 32 * (t & 1) + 4 * (t & 6);
          auto group = [&](int gi) {
            uint32_t prev;
            const uint32_t bb = c.nextB(prev);
            const Desc da = da0 + gi * 256;
            wg_fence();
            if (wide()) {
              wgmma_ss<256>(a, da, desc_hi(4096, 1024, 1) + bb, gi);
              wgmma_ss<256>(a, da + 128, desc_hi(4096, 1024, 1) + (bb + 128), 1);
            } else {
              wgmma_ss<192>(*(float(*)[96])a, da, desc_hi(2048, 512, 2) + bb, gi);
              wgmma_ss<192>(*(float(*)[96])a, da + 128, desc_hi(2048, 512, 2) + (bb + 64), 1);
            }
            wg_commit();
            if (gi == 17 && w == 0) asm volatile("bar.arrive 5, 256;" ::: "memory");
            wg_wait<1>();
            if (gi > 0 && !(last() && gi > 13)) c.release2(BAR_EMPTYB + prev);
            if (last() && gi >= 8 && !(gi & 1)) c.release2(BAR_EMPTYX + 16 * ((gi - 8) & 2) + 2 * ((gi - 8) & 12));
          };
          int gi = 0, end = w ? 16 : 18;
#pragma unroll 1
          while (true) {
#pragma unroll 1
            for (; gi < end; gi++) group(gi);
            if (end == 18) break;
            asm volatile("bar.sync 5, 256;" ::: "memory");
            end = 18;
          }
          wg_wait<0>();
          if (!last()) c.releaseLastB();
          if (last() && t >= 5 && t < 8) { mbar_arrive(sb + xe); mbar_arrive_remote(c.rem + xe); }
        };
        auto yes = [] { return true; };
        auto no = [] { return false; };
        tile(yes, no); PROF(pb + 13); glu<16, 32>(a, h);
        tile(yes, no); PROF(pb + 14); glu<16, 64>(a, h);
        tile(no, no); PROF(pb + 15); glu<12, 96>(a, h);
        const uint32_t hole = sb + SM_B + 12288 + tid_ * 16;
#pragma unroll
        for (int i = 0; i < 4; i++) sts128(hole + i * BSLOT, h[96 + 4 * i], h[97 + 4 * i], h[98 + 4 * i], h[99 + 4 * i]);
        if (w == 1) asm volatile("bar.arrive 8, 256;" ::: "memory");
        tile(no, yes); PROF(pb + 16); glu<12, 120>(a, h);
#pragma unroll
        for (int i = 0; i < 4; i++) { const uint4 u = lds128(hole + i * BSLOT); h[96 + 4 * i] = u.x; h[97 + 4 * i] = u.y; h[98 + 4 * i] = u.z; h[99 + 4 * i] = u.w; }
      }
      {
        THREAD_IDS();
        float d[32];
        uint4* gt = G->obox + t;
        asm volatile("" : "+l"(gt));
        uint4* const ib = gt + 2 * 4608 + layer * 8 * INBOX;
        auto pass = [&](uint32_t s0, bool last, auto&& hook) {
          const Desc db = desc_hi(0, 1024, 1) + (dsb + s0 * (XSLOT >> 4));
          mbar_wait_c(sb + BAR_FULLX + 8 * s0, (c.mX >> s0) & 1);
          hook();
          asm volatile("bar.sync %0, 256;" ::"r"(8 + w) : "memory");
#pragma unroll
          for (int i = 0; i < 4; i++) {
            const int si = 4 * (i & 1) + (i >> 1);
            if (i > 0) mbar_wait_c(sb + BAR_FULLX + 8 * (s0 + si), (c.mX >> (s0 + si)) & 1);
            wg_fence();
#pragma unroll
            for (int k = 0; k < 9; k++) {
              const uint32_t* hk = h + 36 * i + 4 * k;
              wgmma_ra<64>(d, make_uint4(hk[0], hk[1], hk[2], hk[3]), db + ((xslot(si) >> 4) + k * 128), last || i + k > 0);
            }
            if (i == 3 && !(last && w == 1)) asm volatile("bar.arrive %0, 256;" ::"r"(9 - w) : "memory");
            wg_commit();
            if (i > 0) { wg_wait<1>(); c.release2(BAR_EMPTYX + 8 * (s0 + 4 * ((i - 1) & 1) + ((i - 1) >> 1))); }
          }
          c.mX ^= 0x33u << s0;
        };
        PROF(pb + 17);
#pragma unroll 1
        for (int p = 0; p < 8; p++) {
          const uint32_t s0 = 2 * (p & 1);
          pass(s0, false, [] {});
          wg_wait<0>();
          c.release2(BAR_EMPTYX + 8 * (s0 + 5));
          if (p == 6 && layer == NLAYERS - 1) c.elect = false;
          uint32_t pk[16];
#pragma unroll
          for (int i = 0; i < 16; i++) pk[i] = pack_bf16(d[2 * i], d[2 * i + 1]);
          if (p >= 1 && p < 6 && layer < NLAYERS - 1) {
            const uint32_t o = c.sB + 8 * (p - 1);
            c.release2(BAR_EMPTYB + (o < 40 ? o : o - 40));
          }
          uint4* const dst = ib + ((j + p) & 7) * INBOX;
          if (p == 0) {
            mbar_wait_c(sb + BAR_CLR + 8 * w, 0);
#pragma unroll
            for (int k = 0; k < 8; k++) red2((uint2*)(ib + k * INBOX + 512) - t, pk[2 * k], pk[2 * k + 1]);
          } else if (p < 7) {
#pragma unroll
            for (int k = 0; k < 4; k++) red4(dst + k * 128, pk[4 * k], pk[4 * k + 1], pk[4 * k + 2], pk[4 * k + 3]);
            if (p == 6) { __syncwarp(); if (lane == 0) mbar_arrive(sb + BAR_REDDONE + 8 * w); }
          } else {
#pragma unroll
            for (int k = 0; k < 4; k++) st_relaxed4(gt + ((j + 7) & 7) * 128 + k * 1024, pk[4 * k] & ~1u, pk[4 * k + 1], pk[4 * k + 2], pk[4 * k + 3]);
          }
        }
        PROF(pb + 18);
        const uint4 *in = ib + j * INBOX, *pin = gt + j * 128;
        const uint2* in9 = (const uint2*)(in + 512) - t;
        asm volatile("" : "+l"(in), "+l"(pin), "+l"(in9));
        const float2 r2 = lds64(sb + SM_KEEP + (tid_ >> 2) * 8);
        uint2 X9;
        {
          uint4 X[4];
          const uint4* box = gt + 4608;
#pragma unroll
          for (int k = 0; k < 4; k++) X[k] = ld_relaxed4(box + 256 * j + ((k & 1) + 8 * (k & 2)) * 128);
          X9 = ld_relaxed2((const uint2*)(box + (32 + (j >> 1)) * 128) + (j & 1));
          const float i0 = rcp(r2.x), i1 = rcp(r2.y);
#pragma unroll
          for (int k = 0; k < 4; k++) {
            float* e = d + 8 * k;
            X[k].x ^= (lsb >> k) & 1;
            e[0] = bf_lo(X[k].x) * i0; e[1] = bf_hi(X[k].x) * i0; e[2] = bf_lo(X[k].y) * i1; e[3] = bf_hi(X[k].y) * i1;
            e[4] = bf_lo(X[k].z) * i0; e[5] = bf_hi(X[k].z) * i0; e[6] = bf_lo(X[k].w) * i1; e[7] = bf_hi(X[k].w) * i1;
          }
        }
        uint4 R[4], P[4];
        uint2 R9;
        PROF(pb + 19);
        pass(0, true, [&] {
          mbar_wait_c(sb + BAR_RREADY + 8 * w, layer);
#pragma unroll
          for (int k = 0; k < 4; k++) R[k] = ld_relaxed4(in + k * 128);
          R9 = ld_relaxed2(in9);
#pragma unroll
          for (int k = 0; k < 4; k++) P[k] = ld_relaxed4(pin + k * 1024);
        });
        const uint32_t zero = late(sb + BAR_PAST, 0);
        while (__any_sync(0xffffffffu, (chk2(P[0].x, P[1].x, zero) | chk2(P[2].x, P[3].x, zero)) & 1)) {
#pragma unroll
          for (int k = 0; k < 4; k++) P[k] = ld_relaxed4(pin + k * 1024);
        }
#pragma unroll
        for (int k = 0; k < 4; k++) {
          const uint32_t u[4] = {hadd2(R[k].x, P[k].x), hadd2(R[k].y, P[k].y), hadd2(R[k].z, P[k].z), hadd2(R[k].w, P[k].w)};
#pragma unroll
          for (int i = 0; i < 4; i++) { v[8 * k + 2 * i] = bf_lo(u[i]); v[8 * k + 2 * i + 1] = bf_hi(u[i]); }
        }
        X9.x = chk(zero, X9.x, lsb >> 4);
        v[32] = fmaf(bf_lo(R9.x), r2.x, bf_lo(X9.x)); v[33] = fmaf(bf_hi(R9.x), r2.x, bf_hi(X9.x));
        v[34] = fmaf(bf_lo(R9.y), r2.y, bf_lo(X9.y)); v[35] = fmaf(bf_hi(R9.y), r2.y, bf_hi(X9.y));
        PROF(pb + 20);
        wg_wait<0>();
        c.release2(BAR_EMPTYX + 40);
        PROF(pb + 21);
#pragma unroll
        for (int i = 0; i < 32; i++) v[i] = (v[i] + d[i]) * (i & 2 ? r2.y : r2.x);
      }
      if (layer == NLAYERS - 1) break;
      {
        THREAD_IDS();
        PROF(31);
        rs = ln_gemm<true>(c, G, v, res, sum, st0, j, t, 1, xtag ^ 1, [&](int i) { PROF(32 + i); if (i) PROF(34); }, qkv_mma);
      }
    }
    {
      THREAD_IDS();
      const uint32_t stg = sb + SM_B + warp * 4096;
      const uint32_t sd = stg + (lane & 15) * 128;
#pragma unroll
      for (int i = 0; i < 4; i++)
        stsm4(sd + (((2 * i + (lane >> 4)) ^ (lane & 7)) << 4), pack_bf16(v[8 * i], v[8 * i + 1]), pack_bf16(v[8 * i + 2], v[8 * i + 3]),
              pack_bf16(v[8 * i + 4], v[8 * i + 5]), pack_bf16(v[8 * i + 6], v[8 * i + 7]));
      stsm2(stg + 2048 + (lane & 15) * 16, pack_bf16(v[32], v[33]), pack_bf16(v[34], v[35]));
      __syncwarp();
      char* o = out + (128 * rb + 32 * wp + w) * 1152;
#pragma unroll
      for (int i = 0; i < 4; i++) {
        const int r = 4 * i + (lane >> 3);
        *(uint4*)(o + r * 2304 + 128 * j + 16 * (lane & 7)) = lds128(stg + r * 128 + (((lane ^ r) & 7) << 4));
      }
      if (lane < 16) *(uint4*)(o + lane * 2304 + 1024 + 16 * j) = lds128(stg + 2048 + lane * 16);
      if (lane == 0) {
        if (wp == 0) st_relaxed(G->flag + 32 + 32 * j, xtag);
        mbar_arrive(sb + BAR_DONE + 8 * w);
      }
      PROF(61);
    }
  }
}

typedef CUresult (*EncFn)(CUtensorMap*, CUtensorMapDataType, cuuint32_t, void*, const cuuint64_t*, const cuuint64_t*, const cuuint32_t*,
                          const cuuint32_t*, CUtensorMapInterleave, CUtensorMapSwizzle, CUtensorMapL2promotion, CUtensorMapFloatOOBfill);

void make_map(EncFn enc, CUtensorMap* m, const void* p, int rank, uint64_t d0, uint64_t d1, uint64_t d2, uint64_t s1, uint64_t s2, uint32_t b0,
              uint32_t b1, uint32_t b2, CUtensorMapSwizzle sw) {
  cuuint64_t gd[3] = {d0, d1, d2};
  cuuint64_t gs[2] = {s1, s2};
  cuuint32_t bd[3] = {b0, b1, b2};
  cuuint32_t es[3] = {1, 1, 1};
  enc(m, CU_TENSOR_MAP_DATA_TYPE_BFLOAT16, rank, const_cast<void*>(p), gd, gs, bd, es, CU_TENSOR_MAP_INTERLEAVE_NONE, sw,
      CU_TENSOR_MAP_L2_PROMOTION_L2_128B, CU_TENSOR_MAP_FLOAT_OOB_FILL_NONE);
}

}

extern "C" void kernel_launch(void* const* d_in, const int* in_sizes, int n_in, void* d_out, int out_size) {
  const __nv_bfloat16* x = (const __nv_bfloat16*)d_in[0];
  const char *wqkv = (const char*)d_in[1], *wo = (const char*)d_in[2], *wg = (const char*)d_in[4], *wu = (const char*)d_in[5], *wd = (const char*)d_in[6];
  static EncFn enc = nullptr;
  static uint32_t first = 0;
  static Group* ws = nullptr;
  if (!enc) {
    cudaDriverEntryPointQueryResult qr;
    cudaGetDriverEntryPoint("cuTensorMapEncodeTiled", (void**)&enc, cudaEnableDefault, &qr);
    cudaGetSymbolAddress((void**)&ws, g_ws);
    cudaFuncSetAttribute(fused_kernel, cudaFuncAttributeMaxDynamicSharedMemorySize, SMEM_BYTES);
    cudaLaunchConfig_t cfg = {};
    cfg.gridDim = NCTA + 4; cfg.blockDim = 384; cfg.dynamicSmemBytes = SMEM_BYTES;
    int clusters = 0;
    if (XFIRST || cudaOccupancyMaxActiveClusters(&clusters, fused_kernel, &cfg) != cudaSuccess || 2 * clusters < NCTA + 4) first = 4;
    cudaGetLastError();
  }
  const CUtensorMapSwizzle S0 = CU_TENSOR_MAP_SWIZZLE_NONE, S64 = CU_TENSOR_MAP_SWIZZLE_64B, S128 = CU_TENSOR_MAP_SWIZZLE_128B;
  Maps m;
  make_map(enc, &m.x, x, 3, 576, 2, 1024, 1152, 2304, 64, 1, 64, S128);
  make_map(enc, &m.qm, wqkv, 3, 576, 576, 3, 3456, 1152, 64, 16, 3, S128);
  make_map(enc, &m.qc, wqkv, 3, 576, 576, 3, 3456, 1152, 8, 16, 3, S0);
  make_map(enc, &m.o, wo, 2, 576, 576, 1, 1152, 0, 64, 72, 1, S128);
  make_map(enc, &m.g, wg, 3, 64, 576, 72, 9216, 128, 64, 32, 2, S128);
  make_map(enc, &m.u, wu, 3, 64, 576, 72, 9216, 128, 64, 32, 2, S128);
  make_map(enc, &m.g3, wg, 3, 32, 576, 144, 9216, 64, 32, 32, 3, S64);
  make_map(enc, &m.u3, wu, 3, 32, 576, 144, 9216, 64, 32, 32, 3, S64);
  make_map(enc, &m.d, wd, 2, 576, 4608, 1, 1152, 0, 64, 72, 1, S128);
  fused_kernel<<<NCTA + 4, 384, SMEM_BYTES>>>(x, ws, wqkv, wo, (char*)d_out, first, m, wg, wu);
}
```

```cpp
#include <cuda_runtime.h>
#include <cuda_bf16.h>
#include <cuda.h>
#include <stdint.h>
#include <stddef.h>

namespace {

constexpr int NCTA = 128;
#define NLAYERS 2
#define XFIRST 0
constexpr uint32_t SM_X = 0;
constexpr uint32_t XSLOT = 18432;
__host__ __device__ constexpr uint32_t xslot(uint32_t s) { return SM_X + (s ^ 4) * XSLOT; }
constexpr uint32_t SM_WOC = xslot(3) + 8192;
constexpr uint32_t SM_B = 147456;
constexpr uint32_t BSLOT = 16384;
constexpr uint32_t SM_KEEP = 229376;
constexpr uint32_t SM_WSUM = SM_KEEP + 512;
constexpr uint32_t SM_BAR = SM_KEEP + 2048;
constexpr uint32_t BAR_FULLB = SM_BAR;
constexpr uint32_t BAR_RREADY = SM_BAR + 40;
constexpr uint32_t BAR_CLR = SM_BAR + 56;
constexpr uint32_t BAR_FULLX = SM_BAR + 72;
constexpr uint32_t BAR_PAST = BAR_FULLX + 64;
constexpr uint32_t BAR_EMPTYB = SM_BAR + 144;
constexpr uint32_t BAR_EMPTYX = SM_BAR + 184;
constexpr uint32_t BAR_REDDONE = SM_BAR + 248;
constexpr uint32_t BAR_DONE = SM_BAR + 264;
constexpr uint32_t SM_PROG = SM_BAR + 288;
constexpr uint32_t SMEM_BYTES = SM_BAR + 1024;

struct Maps { CUtensorMap x, qm, qc, o, g, u, g3, u3, d; };

constexpr int INBOX = 576;
struct Group {
  uint2 sum[4 * 8 * 8];
  uint2 sq[4 * 8 * 8];
  uint32_t flag[1024];
  uint4 halo[8 * 160];
  uint4 obox[36 * 128];
  uint4 xbox[36 * 128];
  uint4 inbox[2][8 * INBOX];
};
struct Scratch { Group g[32]; uint4 wq[8][36][432]; uint4 woc[8][720]; uint32_t done[64]; };
__device__ __align__(1024) Scratch g_ws;
#define PROF(i)
#define PROFX(i)

struct Desc { uint32_t lo, hi; };
__device__ __forceinline__ constexpr Desc desc_hi(uint32_t lbo, uint32_t sbo, uint32_t sw) { return Desc{(lbo >> 4) << 16, (sbo >> 4) | sw << 30}; }
__device__ __forceinline__ constexpr Desc operator+(Desc d, uint32_t a) { return Desc{d.lo + a, d.hi}; }

template<int N> __device__ __forceinline__ void wgmma_ss(float (&d)[N / 2], Desc da, Desc db, int sc);
template<> __device__ __forceinline__ void wgmma_ss<192>(float (&d)[96], Desc da, Desc db, int sc) {
  asm volatile("{\n.reg .pred p;\n.reg .b64 a, b;\nsetp.ne.b32 p, %100, 0;\nmov.b64 a, {%96, %97};\nmov.b64 b, {%98, %99};\n"
    "wgmma.mma_async.sync.aligned.m64n192k16.f32.bf16.bf16 {%0,%1,%2,%3,%4,%5,%6,%7,%8,%9,%10,%11,%12,%13,%14,%15,%16,%17,%18,%19,%20,%21,%22,%23,%24,%25,%26,%27,%28,%29,%30,%31,%32,%33,%34,%35,%36,%37,%38,%39,%40,%41,%42,%43,%44,%45,%46,%47,%48,%49,%50,%51,%52,%53,%54,%55,%56,%57,%58,%59,%60,%61,%62,%63,%64,%65,%66,%67,%68,%69,%70,%71,%72,%73,%74,%75,%76,%77,%78,%79,%80,%81,%82,%83,%84,%85,%86,%87,%88,%89,%90,%91,%92,%93,%94,%95}, a, b, p, 1, 1, 0, 1;\n}\n"
    : "+f"(d[0]),"+f"(d[1]),"+f"(d[2]),"+f"(d[3]),"+f"(d[4]),"+f"(d[5]),"+f"(d[6]),"+f"(d[7]),"+f"(d[8]),"+f"(d[9]),"+f"(d[10]),"+f"(d[11]),"+f"(d[12]),"+f"(d[13]),"+f"(d[14]),"+f"(d[15]),"+f"(d[16]),"+f"(d[17]),"+f"(d[18]),"+f"(d[19]),"+f"(d[20]),"+f"(d[21]),"+f"(d[22]),"+f"(d[23]),"+f"(d[24]),"+f"(d[25]),"+f"(d[26]),"+f"(d[27]),"+f"(d[28]),"+f"(d[29]),"+f"(d[30]),"+f"(d[31]),"+f"(d[32]),"+f"(d[33]),"+f"(d[34]),"+f"(d[35]),"+f"(d[36]),"+f"(d[37]),"+f"(d[38]),"+f"(d[39]),"+f"(d[40]),"+f"(d[41]),"+f"(d[42]),"+f"(d[43]),"+f"(d[44]),"+f"(d[45]),"+f"(d[46]),"+f"(d[47]),"+f"(d[48]),"+f"(d[49]),"+f"(d[50]),"+f"(d[51]),"+f"(d[52]),"+f"(d[53]),"+f"(d[54]),"+f"(d[55]),"+f"(d[56]),"+f"(d[57]),"+f"(d[58]),"+f"(d[59]),"+f"(d[60]),"+f"(d[61]),"+f"(d[62]),"+f"(d[63]),"+f"(d[64]),"+f"(d[65]),"+f"(d[66]),"+f"(d[67]),"+f"(d[68]),"+f"(d[69]),"+f"(d[70]),"+f"(d[71]),"+f"(d[72]),"+f"(d[73]),"+f"(d[74]),"+f"(d[75]),"+f"(d[76]),"+f"(d[77]),"+f"(d[78]),"+f"(d[79]),"+f"(d[80]),"+f"(d[81]),"+f"(d[82]),"+f"(d[83]),"+f"(d[84]),"+f"(d[85]),"+f"(d[86]),"+f"(d[87]),"+f"(d[88]),"+f"(d[89]),"+f"(d[90]),"+f"(d[91]),"+f"(d[92]),"+f"(d[93]),"+f"(d[94]),"+f"(d[95]) : "r"(da.lo), "r"(da.hi), "r"(db.lo), "r"(db.hi), "r"(sc));
}
template<> __device__ __forceinline__ void wgmma_ss<256>(float (&d)[128], Desc da, Desc db, int sc) {
  asm volatile("{\n.reg .pred p;\n.reg .b64 a, b;\nsetp.ne.b32 p, %132, 0;\nmov.b64 a, {%128, %129};\nmov.b64 b, {%130, %131};\n"
    "wgmma.mma_async.sync.aligned.m64n256k16.f32.bf16.bf16 {%0,%1,%2,%3,%4,%5,%6,%7,%8,%9,%10,%11,%12,%13,%14,%15,%16,%17,%18,%19,%20,%21,%22,%23,%24,%25,%26,%27,%28,%29,%30,%31,%32,%33,%34,%35,%36,%37,%38,%39,%40,%41,%42,%43,%44,%45,%46,%47,%48,%49,%50,%51,%52,%53,%54,%55,%56,%57,%58,%59,%60,%61,%62,%63,%64,%65,%66,%67,%68,%69,%70,%71,%72,%73,%74,%75,%76,%77,%78,%79,%80,%81,%82,%83,%84,%85,%86,%87,%88,%89,%90,%91,%92,%93,%94,%95,%96,%97,%98,%99,%100,%101,%102,%103,%104,%105,%106,%107,%108,%109,%110,%111,%112,%113,%114,%115,%116,%117,%118,%119,%120,%121,%122,%123,%124,%125,%126,%127}, a, b, p, 1, 1, 0, 1;\n}\n"
    : "+f"(d[0]),"+f"(d[1]),"+f"(d[2]),"+f"(d[3]),"+f"(d[4]),"+f"(d[5]),"+f"(d[6]),"+f"(d[7]),"+f"(d[8]),"+f"(d[9]),"+f"(d[10]),"+f"(d[11]),"+f"(d[12]),"+f"(d[13]),"+f"(d[14]),"+f"(d[15]),"+f"(d[16]),"+f"(d[17]),"+f"(d[18]),"+f"(d[19]),"+f"(d[20]),"+f"(d[21]),"+f"(d[22]),"+f"(d[23]),"+f"(d[24]),"+f"(d[25]),"+f"(d[26]),"+f"(d[27]),"+f"(d[28]),"+f"(d[29]),"+f"(d[30]),"+f"(d[31]),"+f"(d[32]),"+f"(d[33]),"+f"(d[34]),"+f"(d[35]),"+f"(d[36]),"+f"(d[37]),"+f"(d[38]),"+f"(d[39]),"+f"(d[40]),"+f"(d[41]),"+f"(d[42]),"+f"(d[43]),"+f"(d[44]),"+f"(d[45]),"+f"(d[46]),"+f"(d[47]),"+f"(d[48]),"+f"(d[49]),"+f"(d[50]),"+f"(d[51]),"+f"(d[52]),"+f"(d[53]),"+f"(d[54]),"+f"(d[55]),"+f"(d[56]),"+f"(d[57]),"+f"(d[58]),"+f"(d[59]),"+f"(d[60]),"+f"(d[61]),"+f"(d[62]),"+f"(d[63]),"+f"(d[64]),"+f"(d[65]),"+f"(d[66]),"+f"(d[67]),"+f"(d[68]),"+f"(d[69]),"+f"(d[70]),"+f"(d[71]),"+f"(d[72]),"+f"(d[73]),"+f"(d[74]),"+f"(d[75]),"+f"(d[76]),"+f"(d[77]),"+f"(d[78]),"+f"(d[79]),"+f"(d[80]),"+f"(d[81]),"+f"(d[82]),"+f"(d[83]),"+f"(d[84]),"+f"(d[85]),"+f"(d[86]),"+f"(d[87]),"+f"(d[88]),"+f"(d[89]),"+f"(d[90]),"+f"(d[91]),"+f"(d[92]),"+f"(d[93]),"+f"(d[94]),"+f"(d[95]),"+f"(d[96]),"+f"(d[97]),"+f"(d[98]),"+f"(d[99]),"+f"(d[100]),"+f"(d[101]),"+f"(d[102]),"+f"(d[103]),"+f"(d[104]),"+f"(d[105]),"+f"(d[106]),"+f"(d[107]),"+f"(d[108]),"+f"(d[109]),"+f"(d[110]),"+f"(d[111]),"+f"(d[112]),"+f"(d[113]),"+f"(d[114]),"+f"(d[115]),"+f"(d[116]),"+f"(d[117]),"+f"(d[118]),"+f"(d[119]),"+f"(d[120]),"+f"(d[121]),"+f"(d[122]),"+f"(d[123]),"+f"(d[124]),"+f"(d[125]),"+f"(d[126]),"+f"(d[127]) : "r"(da.lo), "r"(da.hi), "r"(db.lo), "r"(db.hi), "r"(sc));
}
template<int N, int ACC> __device__ __forceinline__ void wgmma_rs(float (&d)[N / 2], const uint4& a, Desc db);
template<> __device__ __forceinline__ void wgmma_rs<8, 1>(float (&d)[4], const uint4& a, Desc db) {
  asm volatile("{\n.reg .pred p;\n.reg .b64 b;\nsetp.ne.b32 p, 1, 0;\nmov.b64 b, {%8, %9};\n"
    "wgmma.mma_async.sync.aligned.m64n8k16.f32.bf16.bf16 {%0,%1,%2,%3}, {%4,%5,%6,%7}, b, p, 1, 1, 1;\n}\n"
    : "+f"(d[0]),"+f"(d[1]),"+f"(d[2]),"+f"(d[3]) : "r"(a.x), "r"(a.y), "r"(a.z), "r"(a.w), "r"(db.lo), "r"(db.hi));
}
template<> __device__ __forceinline__ void wgmma_rs<8, 0>(float (&d)[4], const uint4& a, Desc db) {
  asm volatile("{\n.reg .pred p;\n.reg .b64 b;\nsetp.ne.b32 p, 0, 0;\nmov.b64 b, {%8, %9};\n"
    "wgmma.mma_async.sync.aligned.m64n8k16.f32.bf16.bf16 {%0,%1,%2,%3}, {%4,%5,%6,%7}, b, p, 1, 1, 1;\n}\n"
    : "=f"(d[0]),"=f"(d[1]),"=f"(d[2]),"=f"(d[3]) : "r"(a.x), "r"(a.y), "r"(a.z), "r"(a.w), "r"(db.lo), "r"(db.hi));
}
template<> __device__ __forceinline__ void wgmma_rs<24, 1>(float (&d)[12], const uint4& a, Desc db) {
  asm volatile("{\n.reg .pred p;\n.reg .b64 b;\nsetp.ne.b32 p, 1, 0;\nmov.b64 b, {%16, %17};\n"
    "wgmma.mma_async.sync.aligned.m64n24k16.f32.bf16.bf16 {%0,%1,%2,%3,%4,%5,%6,%7,%8,%9,%10,%11}, {%12,%13,%14,%15}, b, p, 1, 1, 1;\n}\n"
    : "+f"(d[0]),"+f"(d[1]),"+f"(d[2]),"+f"(d[3]),"+f"(d[4]),"+f"(d[5]),"+f"(d[6]),"+f"(d[7]),"+f"(d[8]),"+f"(d[9]),"+f"(d[10]),"+f"(d[11]) : "r"(a.x), "r"(a.y), "r"(a.z), "r"(a.w), "r"(db.lo), "r"(db.hi));
}
template<> __device__ __forceinline__ void wgmma_rs<24, 0>(float (&d)[12], const uint4& a, Desc db) {
  asm volatile("{\n.reg .pred p;\n.reg .b64 b;\nsetp.ne.b32 p, 0, 0;\nmov.b64 b, {%16, %17};\n"
    "wgmma.mma_async.sync.aligned.m64n24k16.f32.bf16.bf16 {%0,%1,%2,%3,%4,%5,%6,%7,%8,%9,%10,%11}, {%12,%13,%14,%15}, b, p, 1, 1, 1;\n}\n"
    : "=f"(d[0]),"=f"(d[1]),"=f"(d[2]),"=f"(d[3]),"=f"(d[4]),"=f"(d[5]),"=f"(d[6]),"=f"(d[7]),"=f"(d[8]),"=f"(d[9]),"=f"(d[10]),"=f"(d[11]) : "r"(a.x), "r"(a.y), "r"(a.z), "r"(a.w), "r"(db.lo), "r"(db.hi));
}
template<> __device__ __forceinline__ void wgmma_rs<64, 1>(float (&d)[32], const uint4& a, Desc db) {
  asm volatile("{\n.reg .pred p;\n.reg .b64 b;\nsetp.ne.b32 p, 1, 0;\nmov.b64 b, {%36, %37};\n"
    "wgmma.mma_async.sync.aligned.m64n64k16.f32.bf16.bf16 {%0,%1,%2,%3,%4,%5,%6,%7,%8,%9,%10,%11,%12,%13,%14,%15,%16,%17,%18,%19,%20,%21,%22,%23,%24,%25,%26,%27,%28,%29,%30,%31}, {%32,%33,%34,%35}, b, p, 1, 1, 1;\n}\n"
    : "+f"(d[0]),"+f"(d[1]),"+f"(d[2]),"+f"(d[3]),"+f"(d[4]),"+f"(d[5]),"+f"(d[6]),"+f"(d[7]),"+f"(d[8]),"+f"(d[9]),"+f"(d[10]),"+f"(d[11]),"+f"(d[12]),"+f"(d[13]),"+f"(d[14]),"+f"(d[15]),"+f"(d[16]),"+f"(d[17]),"+f"(d[18]),"+f"(d[19]),"+f"(d[20]),"+f"(d[21]),"+f"(d[22]),"+f"(d[23]),"+f"(d[24]),"+f"(d[25]),"+f"(d[26]),"+f"(d[27]),"+f"(d[28]),"+f"(d[29]),"+f"(d[30]),"+f"(d[31]) : "r"(a.x), "r"(a.y), "r"(a.z), "r"(a.w), "r"(db.lo), "r"(db.hi));
}
template<> __device__ __forceinline__ void wgmma_rs<64, 0>(float (&d)[32], const uint4& a, Desc db) {
  asm volatile("{\n.reg .pred p;\n.reg .b64 b;\nsetp.ne.b32 p, 0, 0;\nmov.b64 b, {%36, %37};\n"
    "wgmma.mma_async.sync.aligned.m64n64k16.f32.bf16.bf16 {%0,%1,%2,%3,%4,%5,%6,%7,%8,%9,%10,%11,%12,%13,%14,%15,%16,%17,%18,%19,%20,%21,%22,%23,%24,%25,%26,%27,%28,%29,%30,%31}, {%32,%33,%34,%35}, b, p, 1, 1, 1;\n}\n"
    : "=f"(d[0]),"=f"(d[1]),"=f"(d[2]),"=f"(d[3]),"=f"(d[4]),"=f"(d[5]),"=f"(d[6]),"=f"(d[7]),"=f"(d[8]),"=f"(d[9]),"=f"(d[10]),"=f"(d[11]),"=f"(d[12]),"=f"(d[13]),"=f"(d[14]),"=f"(d[15]),"=f"(d[16]),"=f"(d[17]),"=f"(d[18]),"=f"(d[19]),"=f"(d[20]),"=f"(d[21]),"=f"(d[22]),"=f"(d[23]),"=f"(d[24]),"=f"(d[25]),"=f"(d[26]),"=f"(d[27]),"=f"(d[28]),"=f"(d[29]),"=f"(d[30]),"=f"(d[31]) : "r"(a.x), "r"(a.y), "r"(a.z), "r"(a.w), "r"(db.lo), "r"(db.hi));
}
template<> __device__ __forceinline__ void wgmma_rs<72, 1>(float (&d)[36], const uint4& a, Desc db) {
  asm volatile("{\n.reg .pred p;\n.reg .b64 b;\nsetp.ne.b32 p, 1, 0;\nmov.b64 b, {%40, %41};\n"
    "wgmma.mma_async.sync.aligned.m64n72k16.f32.bf16.bf16 {%0,%1,%2,%3,%4,%5,%6,%7,%8,%9,%10,%11,%12,%13,%14,%15,%16,%17,%18,%19,%20,%21,%22,%23,%24,%25,%26,%27,%28,%29,%30,%31,%32,%33,%34,%35}, {%36,%37,%38,%39}, b, p, 1, 1, 1;\n}\n"
    : "+f"(d[0]),"+f"(d[1]),"+f"(d[2]),"+f"(d[3]),"+f"(d[4]),"+f"(d[5]),"+f"(d[6]),"+f"(d[7]),"+f"(d[8]),"+f"(d[9]),"+f"(d[10]),"+f"(d[11]),"+f"(d[12]),"+f"(d[13]),"+f"(d[14]),"+f"(d[15]),"+f"(d[16]),"+f"(d[17]),"+f"(d[18]),"+f"(d[19]),"+f"(d[20]),"+f"(d[21]),"+f"(d[22]),"+f"(d[23]),"+f"(d[24]),"+f"(d[25]),"+f"(d[26]),"+f"(d[27]),"+f"(d[28]),"+f"(d[29]),"+f"(d[30]),"+f"(d[31]),"+f"(d[32]),"+f"(d[33]),"+f"(d[34]),"+f"(d[35]) : "r"(a.x), "r"(a.y), "r"(a.z), "r"(a.w), "r"(db.lo), "r"(db.hi));
}
template<> __device__ __forceinline__ void wgmma_rs<72, 0>(float (&d)[36], const uint4& a, Desc db) {
  asm volatile("{\n.reg .pred p;\n.reg .b64 b;\nsetp.ne.b32 p, 0, 0;\nmov.b64 b, {%40, %41};\n"
    "wgmma.mma_async.sync.aligned.m64n72k16.f32.bf16.bf16 {%0,%1,%2,%3,%4,%5,%6,%7,%8,%9,%10,%11,%12,%13,%14,%15,%16,%17,%18,%19,%20,%21,%22,%23,%24,%25,%26,%27,%28,%29,%30,%31,%32,%33,%34,%35}, {%36,%37,%38,%39}, b, p, 1, 1, 1;\n}\n"
    : "=f"(d[0]),"=f"(d[1]),"=f"(d[2]),"=f"(d[3]),"=f"(d[4]),"=f"(d[5]),"=f"(d[6]),"=f"(d[7]),"=f"(d[8]),"=f"(d[9]),"=f"(d[10]),"=f"(d[11]),"=f"(d[12]),"=f"(d[13]),"=f"(d[14]),"=f"(d[15]),"=f"(d[16]),"=f"(d[17]),"=f"(d[18]),"=f"(d[19]),"=f"(d[20]),"=f"(d[21]),"=f"(d[22]),"=f"(d[23]),"=f"(d[24]),"=f"(d[25]),"=f"(d[26]),"=f"(d[27]),"=f"(d[28]),"=f"(d[29]),"=f"(d[30]),"=f"(d[31]),"=f"(d[32]),"=f"(d[33]),"=f"(d[34]),"=f"(d[35]) : "r"(a.x), "r"(a.y), "r"(a.z), "r"(a.w), "r"(db.lo), "r"(db.hi));
}
template<> __device__ __forceinline__ void wgmma_rs<192, 1>(float (&d)[96], const uint4& a, Desc db) {
  asm volatile("{\n.reg .pred p;\n.reg .b64 b;\nsetp.ne.b32 p, 1, 0;\nmov.b64 b, {%100, %101};\n"
    "wgmma.mma_async.sync.aligned.m64n192k16.f32.bf16.bf16 {%0,%1,%2,%3,%4,%5,%6,%7,%8,%9,%10,%11,%12,%13,%14,%15,%16,%17,%18,%19,%20,%21,%22,%23,%24,%25,%26,%27,%28,%29,%30,%31,%32,%33,%34,%35,%36,%37,%38,%39,%40,%41,%42,%43,%44,%45,%46,%47,%48,%49,%50,%51,%52,%53,%54,%55,%56,%57,%58,%59,%60,%61,%62,%63,%64,%65,%66,%67,%68,%69,%70,%71,%72,%73,%74,%75,%76,%77,%78,%79,%80,%81,%82,%83,%84,%85,%86,%87,%88,%89,%90,%91,%92,%93,%94,%95}, {%96,%97,%98,%99}, b, p, 1, 1, 1;\n}\n"
    : "+f"(d[0]),"+f"(d[1]),"+f"(d[2]),"+f"(d[3]),"+f"(d[4]),"+f"(d[5]),"+f"(d[6]),"+f"(d[7]),"+f"(d[8]),"+f"(d[9]),"+f"(d[10]),"+f"(d[11]),"+f"(d[12]),"+f"(d[13]),"+f"(d[14]),"+f"(d[15]),"+f"(d[16]),"+f"(d[17]),"+f"(d[18]),"+f"(d[19]),"+f"(d[20]),"+f"(d[21]),"+f"(d[22]),"+f"(d[23]),"+f"(d[24]),"+f"(d[25]),"+f"(d[26]),"+f"(d[27]),"+f"(d[28]),"+f"(d[29]),"+f"(d[30]),"+f"(d[31]),"+f"(d[32]),"+f"(d[33]),"+f"(d[34]),"+f"(d[35]),"+f"(d[36]),"+f"(d[37]),"+f"(d[38]),"+f"(d[39]),"+f"(d[40]),"+f"(d[41]),"+f"(d[42]),"+f"(d[43]),"+f"(d[44]),"+f"(d[45]),"+f"(d[46]),"+f"(d[47]),"+f"(d[48]),"+f"(d[49]),"+f"(d[50]),"+f"(d[51]),"+f"(d[52]),"+f"(d[53]),"+f"(d[54]),"+f"(d[55]),"+f"(d[56]),"+f"(d[57]),"+f"(d[58]),"+f"(d[59]),"+f"(d[60]),"+f"(d[61]),"+f"(d[62]),"+f"(d[63]),"+f"(d[64]),"+f"(d[65]),"+f"(d[66]),"+f"(d[67]),"+f"(d[68]),"+f"(d[69]),"+f"(d[70]),"+f"(d[71]),"+f"(d[72]),"+f"(d[73]),"+f"(d[74]),"+f"(d[75]),"+f"(d[76]),"+f"(d[77]),"+f"(d[78]),"+f"(d[79]),"+f"(d[80]),"+f"(d[81]),"+f"(d[82]),"+f"(d[83]),"+f"(d[84]),"+f"(d[85]),"+f"(d[86]),"+f"(d[87]),"+f"(d[88]),"+f"(d[89]),"+f"(d[90]),"+f"(d[91]),"+f"(d[92]),"+f"(d[93]),"+f"(d[94]),"+f"(d[95]) : "r"(a.x), "r"(a.y), "r"(a.z), "r"(a.w), "r"(db.lo), "r"(db.hi));
}
template<> __device__ __forceinline__ void wgmma_rs<192, 0>(float (&d)[96], const uint4& a, Desc db) {
  asm volatile("{\n.reg .pred p;\n.reg .b64 b;\nsetp.ne.b32 p, 0, 0;\nmov.b64 b, {%100, %101};\n"
    "wgmma.mma_async.sync.aligned.m64n192k16.f32.bf16.bf16 {%0,%1,%2,%3,%4,%5,%6,%7,%8,%9,%10,%11,%12,%13,%14,%15,%16,%17,%18,%19,%20,%21,%22,%23,%24,%25,%26,%27,%28,%29,%30,%31,%32,%33,%34,%35,%36,%37,%38,%39,%40,%41,%42,%43,%44,%45,%46,%47,%48,%49,%50,%51,%52,%53,%54,%55,%56,%57,%58,%59,%60,%61,%62,%63,%64,%65,%66,%67,%68,%69,%70,%71,%72,%73,%74,%75,%76,%77,%78,%79,%80,%81,%82,%83,%84,%85,%86,%87,%88,%89,%90,%91,%92,%93,%94,%95}, {%96,%97,%98,%99}, b, p, 1, 1, 1;\n}\n"
    : "=f"(d[0]),"=f"(d[1]),"=f"(d[2]),"=f"(d[3]),"=f"(d[4]),"=f"(d[5]),"=f"(d[6]),"=f"(d[7]),"=f"(d[8]),"=f"(d[9]),"=f"(d[10]),"=f"(d[11]),"=f"(d[12]),"=f"(d[13]),"=f"(d[14]),"=f"(d[15]),"=f"(d[16]),"=f"(d[17]),"=f"(d[18]),"=f"(d[19]),"=f"(d[20]),"=f"(d[21]),"=f"(d[22]),"=f"(d[23]),"=f"(d[24]),"=f"(d[25]),"=f"(d[26]),"=f"(d[27]),"=f"(d[28]),"=f"(d[29]),"=f"(d[30]),"=f"(d[31]),"=f"(d[32]),"=f"(d[33]),"=f"(d[34]),"=f"(d[35]),"=f"(d[36]),"=f"(d[37]),"=f"(d[38]),"=f"(d[39]),"=f"(d[40]),"=f"(d[41]),"=f"(d[42]),"=f"(d[43]),"=f"(d[44]),"=f"(d[45]),"=f"(d[46]),"=f"(d[47]),"=f"(d[48]),"=f"(d[49]),"=f"(d[50]),"=f"(d[51]),"=f"(d[52]),"=f"(d[53]),"=f"(d[54]),"=f"(d[55]),"=f"(d[56]),"=f"(d[57]),"=f"(d[58]),"=f"(d[59]),"=f"(d[60]),"=f"(d[61]),"=f"(d[62]),"=f"(d[63]),"=f"(d[64]),"=f"(d[65]),"=f"(d[66]),"=f"(d[67]),"=f"(d[68]),"=f"(d[69]),"=f"(d[70]),"=f"(d[71]),"=f"(d[72]),"=f"(d[73]),"=f"(d[74]),"=f"(d[75]),"=f"(d[76]),"=f"(d[77]),"=f"(d[78]),"=f"(d[79]),"=f"(d[80]),"=f"(d[81]),"=f"(d[82]),"=f"(d[83]),"=f"(d[84]),"=f"(d[85]),"=f"(d[86]),"=f"(d[87]),"=f"(d[88]),"=f"(d[89]),"=f"(d[90]),"=f"(d[91]),"=f"(d[92]),"=f"(d[93]),"=f"(d[94]),"=f"(d[95]) : "r"(a.x), "r"(a.y), "r"(a.z), "r"(a.w), "r"(db.lo), "r"(db.hi));
}
template<> __device__ __forceinline__ void wgmma_rs<256, 1>(float (&d)[128], const uint4& a, Desc db) {
  asm volatile("{\n.reg .pred p;\n.reg .b64 b;\nsetp.ne.b32 p, 1, 0;\nmov.b64 b, {%132, %133};\n"
    "wgmma.mma_async.sync.aligned.m64n256k16.f32.bf16.bf16 {%0,%1,%2,%3,%4,%5,%6,%7,%8,%9,%10,%11,%12,%13,%14,%15,%16,%17,%18,%19,%20,%21,%22,%23,%24,%25,%26,%27,%28,%29,%30,%31,%32,%33,%34,%35,%36,%37,%38,%39,%40,%41,%42,%43,%44,%45,%46,%47,%48,%49,%50,%51,%52,%53,%54,%55,%56,%57,%58,%59,%60,%61,%62,%63,%64,%65,%66,%67,%68,%69,%70,%71,%72,%73,%74,%75,%76,%77,%78,%79,%80,%81,%82,%83,%84,%85,%86,%87,%88,%89,%90,%91,%92,%93,%94,%95,%96,%97,%98,%99,%100,%101,%102,%103,%104,%105,%106,%107,%108,%109,%110,%111,%112,%113,%114,%115,%116,%117,%118,%119,%120,%121,%122,%123,%124,%125,%126,%127}, {%128,%129,%130,%131}, b, p, 1, 1, 1;\n}\n"
    : "+f"(d[0]),"+f"(d[1]),"+f"(d[2]),"+f"(d[3]),"+f"(d[4]),"+f"(d[5]),"+f"(d[6]),"+f"(d[7]),"+f"(d[8]),"+f"(d[9]),"+f"(d[10]),"+f"(d[11]),"+f"(d[12]),"+f"(d[13]),"+f"(d[14]),"+f"(d[15]),"+f"(d[16]),"+f"(d[17]),"+f"(d[18]),"+f"(d[19]),"+f"(d[20]),"+f"(d[21]),"+f"(d[22]),"+f"(d[23]),"+f"(d[24]),"+f"(d[25]),"+f"(d[26]),"+f"(d[27]),"+f"(d[28]),"+f"(d[29]),"+f"(d[30]),"+f"(d[31]),"+f"(d[32]),"+f"(d[33]),"+f"(d[34]),"+f"(d[35]),"+f"(d[36]),"+f"(d[37]),"+f"(d[38]),"+f"(d[39]),"+f"(d[40]),"+f"(d[41]),"+f"(d[42]),"+f"(d[43]),"+f"(d[44]),"+f"(d[45]),"+f"(d[46]),"+f"(d[47]),"+f"(d[48]),"+f"(d[49]),"+f"(d[50]),"+f"(d[51]),"+f"(d[52]),"+f"(d[53]),"+f"(d[54]),"+f"(d[55]),"+f"(d[56]),"+f"(d[57]),"+f"(d[58]),"+f"(d[59]),"+f"(d[60]),"+f"(d[61]),"+f"(d[62]),"+f"(d[63]),"+f"(d[64]),"+f"(d[65]),"+f"(d[66]),"+f"(d[67]),"+f"(d[68]),"+f"(d[69]),"+f"(d[70]),"+f"(d[71]),"+f"(d[72]),"+f"(d[73]),"+f"(d[74]),"+f"(d[75]),"+f"(d[76]),"+f"(d[77]),"+f"(d[78]),"+f"(d[79]),"+f"(d[80]),"+f"(d[81]),"+f"(d[82]),"+f"(d[83]),"+f"(d[84]),"+f"(d[85]),"+f"(d[86]),"+f"(d[87]),"+f"(d[88]),"+f"(d[89]),"+f"(d[90]),"+f"(d[91]),"+f"(d[92]),"+f"(d[93]),"+f"(d[94]),"+f"(d[95]),"+f"(d[96]),"+f"(d[97]),"+f"(d[98]),"+f"(d[99]),"+f"(d[100]),"+f"(d[101]),"+f"(d[102]),"+f"(d[103]),"+f"(d[104]),"+f"(d[105]),"+f"(d[106]),"+f"(d[107]),"+f"(d[108]),"+f"(d[109]),"+f"(d[110]),"+f"(d[111]),"+f"(d[112]),"+f"(d[113]),"+f"(d[114]),"+f"(d[115]),"+f"(d[116]),"+f"(d[117]),"+f"(d[118]),"+f"(d[119]),"+f"(d[120]),"+f"(d[121]),"+f"(d[122]),"+f"(d[123]),"+f"(d[124]),"+f"(d[125]),"+f"(d[126]),"+f"(d[127]) : "r"(a.x), "r"(a.y), "r"(a.z), "r"(a.w), "r"(db.lo), "r"(db.hi));
}
template<> __device__ __forceinline__ void wgmma_rs<256, 0>(float (&d)[128], const uint4& a, Desc db) {
  asm volatile("{\n.reg .pred p;\n.reg .b64 b;\nsetp.ne.b32 p, 0, 0;\nmov.b64 b, {%132, %133};\n"
    "wgmma.mma_async.sync.aligned.m64n256k16.f32.bf16.bf16 {%0,%1,%2,%3,%4,%5,%6,%7,%8,%9,%10,%11,%12,%13,%14,%15,%16,%17,%18,%19,%20,%21,%22,%23,%24,%25,%26,%27,%28,%29,%30,%31,%32,%33,%34,%35,%36,%37,%38,%39,%40,%41,%42,%43,%44,%45,%46,%47,%48,%49,%50,%51,%52,%53,%54,%55,%56,%57,%58,%59,%60,%61,%62,%63,%64,%65,%66,%67,%68,%69,%70,%71,%72,%73,%74,%75,%76,%77,%78,%79,%80,%81,%82,%83,%84,%85,%86,%87,%88,%89,%90,%91,%92,%93,%94,%95,%96,%97,%98,%99,%100,%101,%102,%103,%104,%105,%106,%107,%108,%109,%110,%111,%112,%113,%114,%115,%116,%117,%118,%119,%120,%121,%122,%123,%124,%125,%126,%127}, {%128,%129,%130,%131}, b, p, 1, 1, 1;\n}\n"
    : "=f"(d[0]),"=f"(d[1]),"=f"(d[2]),"=f"(d[3]),"=f"(d[4]),"=f"(d[5]),"=f"(d[6]),"=f"(d[7]),"=f"(d[8]),"=f"(d[9]),"=f"(d[10]),"=f"(d[11]),"=f"(d[12]),"=f"(d[13]),"=f"(d[14]),"=f"(d[15]),"=f"(d[16]),"=f"(d[17]),"=f"(d[18]),"=f"(d[19]),"=f"(d[20]),"=f"(d[21]),"=f"(d[22]),"=f"(d[23]),"=f"(d[24]),"=f"(d[25]),"=f"(d[26]),"=f"(d[27]),"=f"(d[28]),"=f"(d[29]),"=f"(d[30]),"=f"(d[31]),"=f"(d[32]),"=f"(d[33]),"=f"(d[34]),"=f"(d[35]),"=f"(d[36]),"=f"(d[37]),"=f"(d[38]),"=f"(d[39]),"=f"(d[40]),"=f"(d[41]),"=f"(d[42]),"=f"(d[43]),"=f"(d[44]),"=f"(d[45]),"=f"(d[46]),"=f"(d[47]),"=f"(d[48]),"=f"(d[49]),"=f"(d[50]),"=f"(d[51]),"=f"(d[52]),"=f"(d[53]),"=f"(d[54]),"=f"(d[55]),"=f"(d[56]),"=f"(d[57]),"=f"(d[58]),"=f"(d[59]),"=f"(d[60]),"=f"(d[61]),"=f"(d[62]),"=f"(d[63]),"=f"(d[64]),"=f"(d[65]),"=f"(d[66]),"=f"(d[67]),"=f"(d[68]),"=f"(d[69]),"=f"(d[70]),"=f"(d[71]),"=f"(d[72]),"=f"(d[73]),"=f"(d[74]),"=f"(d[75]),"=f"(d[76]),"=f"(d[77]),"=f"(d[78]),"=f"(d[79]),"=f"(d[80]),"=f"(d[81]),"=f"(d[82]),"=f"(d[83]),"=f"(d[84]),"=f"(d[85]),"=f"(d[86]),"=f"(d[87]),"=f"(d[88]),"=f"(d[89]),"=f"(d[90]),"=f"(d[91]),"=f"(d[92]),"=f"(d[93]),"=f"(d[94]),"=f"(d[95]),"=f"(d[96]),"=f"(d[97]),"=f"(d[98]),"=f"(d[99]),"=f"(d[100]),"=f"(d[101]),"=f"(d[102]),"=f"(d[103]),"=f"(d[104]),"=f"(d[105]),"=f"(d[106]),"=f"(d[107]),"=f"(d[108]),"=f"(d[109]),"=f"(d[110]),"=f"(d[111]),"=f"(d[112]),"=f"(d[113]),"=f"(d[114]),"=f"(d[115]),"=f"(d[116]),"=f"(d[117]),"=f"(d[118]),"=f"(d[119]),"=f"(d[120]),"=f"(d[121]),"=f"(d[122]),"=f"(d[123]),"=f"(d[124]),"=f"(d[125]),"=f"(d[126]),"=f"(d[127]) : "r"(a.x), "r"(a.y), "r"(a.z), "r"(a.w), "r"(db.lo), "r"(db.hi));
}
template<int N> __device__ __forceinline__ void wgmma_ra(float (&d)[N / 2], const uint4& a, Desc db, bool acc) {
  if (acc) wgmma_rs<N, 1>(d, a, db); else wgmma_rs<N, 0>(d, a, db);
}

__device__ __forceinline__ uint32_t smem_u32(const void* p) { return (uint32_t)__cvta_generic_to_shared(p); }
__device__ __forceinline__ void mbar_init(uint32_t bar, uint32_t cnt) { asm volatile("mbarrier.init.shared::cta.b64 [%0], %1;" ::"r"(bar), "r"(cnt)); }
__device__ __forceinline__ void mbar_expect_tx(uint32_t bar, uint32_t bytes) { asm volatile("mbarrier.arrive.expect_tx.shared::cta.b64 _, [%0], %1;" ::"r"(bar), "r"(bytes) : "memory"); }
__device__ __forceinline__ void mbar_arrive(uint32_t bar) { asm volatile("mbarrier.arrive.shared::cta.b64 _, [%0];" ::"r"(bar) : "memory"); }
__device__ __forceinline__ void mbar_arrive_remote(uint32_t rbar) { asm volatile("mbarrier.arrive.shared::cluster.b64 _, [%0];" ::"r"(rbar) : "memory"); }
__device__ __forceinline__ void mbar_wait(uint32_t bar, uint32_t parity) {
  asm volatile(
      "{\n.reg .pred p;\n.reg .u32 c;\nmov.u32 c, 0;\nLAB_WAIT:\nmbarrier.try_wait.parity.shared::cta.b64 p, [%0], %1;\n@p bra DONE;\n"
      "add.u32 c, c, 1;\nsetp.lt.u32 p, c, 1000000;\n@p bra LAB_WAIT;\ntrap;\nDONE:\n}\n" ::"r"(bar), "r"(parity) : "memory");
}
__device__ __forceinline__ void mbar_wait_c(uint32_t bar, uint32_t parity) {
  asm volatile("{\n.reg .pred p;\nLAB_WAIT:\nmbarrier.try_wait.parity.shared::cta.b64 p, [%0], %1;\n@!p bra LAB_WAIT;\n}\n" ::"r"(bar), "r"(parity) : "memory");
}
__device__ __forceinline__ uint32_t late(uint32_t bar, uint32_t v) {
  uint32_t r;
  asm volatile("{\n.reg .pred p;\nmbarrier.test_wait.parity.shared::cta.b64 p, [%1], 0;\nselp.b32 %0, %2, %1, p;\n}\n" : "=r"(r) : "r"(bar), "r"(v) : "memory");
  return r;
}
__device__ __forceinline__ void wtma2d(uint32_t dst, const CUtensorMap* m, int c0, int c1, uint32_t bar, uint64_t pol) {
  asm volatile("cp.async.bulk.tensor.2d.shared::cluster.global.mbarrier::complete_tx::bytes.multicast::cluster.L2::cache_hint [%0], [%1, {%3, %4}], [%2], %5, %6;"
               ::"r"(dst), "l"(m), "r"(bar), "r"(c0), "r"(c1), "h"((uint16_t)3), "l"(pol) : "memory");
}
__device__ __forceinline__ void wtma3d(uint32_t dst, const CUtensorMap* m, int c0, int c1, int c2, uint32_t bar, uint64_t pol) {
  asm volatile("cp.async.bulk.tensor.3d.shared::cluster.global.mbarrier::complete_tx::bytes.multicast::cluster.L2::cache_hint [%0], [%1, {%3, %4, %5}], [%2], %6, %7;"
               ::"r"(dst), "l"(m), "r"(bar), "r"(c0), "r"(c1), "r"(c2), "h"((uint16_t)3), "l"(pol) : "memory");
}
__device__ __forceinline__ void wbulk(uint32_t dst, const void* src, uint32_t bytes, uint32_t bar, uint64_t pol) {
  asm volatile("cp.async.bulk.shared::cluster.global.mbarrier::complete_tx::bytes.multicast::cluster.L2::cache_hint [%0], [%1], %2, [%3], %4, %5;"
               ::"r"(dst), "l"(src), "r"(bytes), "r"(bar), "h"((uint16_t)3), "l"(pol) : "memory");
}
__device__ __forceinline__ void tma3d(uint32_t dst, const CUtensorMap* m, int c0, int c1, int c2, uint32_t bar) {
  asm volatile("cp.async.bulk.tensor.3d.shared::cluster.global.mbarrier::complete_tx::bytes [%0], [%1, {%3, %4, %5}], [%2];"
               ::"r"(dst), "l"(m), "r"(bar), "r"(c0), "r"(c1), "r"(c2) : "memory");
}
__device__ __forceinline__ void prefetch_l2(const void* p, uint32_t bytes) { asm volatile("cp.async.bulk.prefetch.L2.global [%0], %1;" ::"l"(p), "r"(bytes) : "memory"); }
__device__ __forceinline__ uint64_t policy_evict_first() { uint64_t p; asm volatile("createpolicy.fractional.L2::evict_first.b64 %0, 1.0;" : "=l"(p)); return p; }
__device__ __forceinline__ uint64_t policy_evict_normal() { uint64_t p; asm volatile("createpolicy.fractional.L2::evict_normal.b64 %0, 1.0;" : "=l"(p)); return p; }
__device__ __forceinline__ void fence_async_smem() { asm volatile("fence.proxy.async.shared::cta;" ::: "memory"); }
__device__ __forceinline__ bool elect_one() {
  uint32_t p;
  asm volatile("{\n.reg .pred P;\nelect.sync _|P, 0xffffffff;\nselp.u32 %0, 1, 0, P;\n}\n" : "=r"(p));
  return p;
}
__device__ __forceinline__ void wg_fence() { asm volatile("wgmma.fence.sync.aligned;" ::: "memory"); }
__device__ __forceinline__ void wg_commit() { asm volatile("wgmma.commit_group.sync.aligned;" ::: "memory"); }
template <int n> __device__ __forceinline__ void wg_wait() { asm volatile("wgmma.wait_group.sync.aligned %0;" ::"n"(n) : "memory"); }
__device__ __forceinline__ void wg_bar(int w) { asm volatile("bar.sync %0, 128;" ::"r"(w + 1) : "memory"); }
__device__ __forceinline__ void fence_gpu() { asm volatile("fence.acq_rel.gpu;" ::: "memory"); }
__device__ __forceinline__ uint32_t ld_relaxed(const uint32_t* p) { uint32_t v; asm volatile("ld.relaxed.gpu.global.u32 %0, [%1];" : "=r"(v) : "l"(p) : "memory"); return v; }
__device__ __forceinline__ uint32_t ld_acquire(const uint32_t* p) { uint32_t v; asm volatile("ld.acquire.gpu.global.u32 %0, [%1];" : "=r"(v) : "l"(p) : "memory"); return v; }
__device__ __forceinline__ uint4 ld_relaxed4(const uint4* p) {
  uint4 v; asm volatile("ld.relaxed.gpu.global.v4.u32 {%0,%1,%2,%3}, [%4];" : "=r"(v.x), "=r"(v.y), "=r"(v.z), "=r"(v.w) : "l"(p) : "memory"); return v;
}
__device__ __forceinline__ uint2 ld_relaxed2(const uint2* p) {
  uint2 v; asm volatile("ld.relaxed.gpu.global.v2.u32 {%0,%1}, [%2];" : "=r"(v.x), "=r"(v.y) : "l"(p) : "memory"); return v;
}
__device__ __forceinline__ void st_relaxed(uint32_t* p, uint32_t a) { asm volatile("st.relaxed.gpu.global.u32 [%0], %1;" ::"l"(p), "r"(a) : "memory"); }
__device__ __forceinline__ void st_relaxed4(uint4* p, uint32_t a, uint32_t b, uint32_t c, uint32_t d) {
  asm volatile("st.relaxed.gpu.global.v4.u32 [%0], {%1,%2,%3,%4};" ::"l"(p), "r"(a), "r"(b), "r"(c), "r"(d) : "memory");
}
__device__ __forceinline__ void st_relaxed2(uint2* p, uint32_t a, uint32_t b) {
  asm volatile("st.relaxed.gpu.global.v2.u32 [%0], {%1,%2};" ::"l"(p), "r"(a), "r"(b) : "memory");
}
__device__ __forceinline__ void red4(uint4* p, uint32_t a, uint32_t b, uint32_t c, uint32_t d) {
  asm volatile("red.relaxed.gpu.global.add.noftz.v4.bf16x2 [%0], {%1,%2,%3,%4};" ::"l"(p), "r"(a), "r"(b), "r"(c), "r"(d) : "memory");
}
__device__ __forceinline__ void red2(uint2* p, uint32_t a, uint32_t b) {
  asm volatile("red.relaxed.gpu.global.add.noftz.v2.bf16x2 [%0], {%1,%2};" ::"l"(p), "r"(a), "r"(b) : "memory");
}
constexpr int SPIN_MAX = 1 << 21;
__device__ __forceinline__ uint32_t pack_bf16(float lo, float hi) { uint32_t r; asm("cvt.rn.bf16x2.f32 %0, %1, %2;" : "=r"(r) : "f"(hi), "f"(lo)); return r; }
__device__ __forceinline__ float bf_lo(uint32_t v) { return __uint_as_float(v << 16); }
__device__ __forceinline__ float bf_hi(uint32_t v) { return __uint_as_float(v & 0xffff0000u); }
__device__ __forceinline__ float2 lds64(uint32_t a) { float2 v; asm volatile("ld.shared.v2.f32 {%0,%1}, [%2];" : "=f"(v.x), "=f"(v.y) : "r"(a)); return v; }
__device__ __forceinline__ void sts64f(uint32_t a, float x, float y) { asm volatile("st.shared.v2.f32 [%0], {%1,%2};" ::"r"(a), "f"(x), "f"(y) : "memory"); }
__device__ __forceinline__ void sts32(uint32_t a, uint32_t x) { asm volatile("st.volatile.shared.b32 [%0], %1;" ::"r"(a), "r"(x) : "memory"); }
__device__ __forceinline__ void gate(uint32_t a, int need) {
#pragma unroll 1
  for (int it = 0; it < SPIN_MAX; it++) {
    int v; asm volatile("ld.volatile.shared.b32 %0, [%1];" : "=r"(v) : "r"(a) : "memory");
    if (v >= need) break;
    __nanosleep(200);
  }
}
__device__ __forceinline__ void sts128(uint32_t a, uint32_t x, uint32_t y, uint32_t z, uint32_t u) { asm volatile("st.shared.v4.b32 [%0], {%1,%2,%3,%4};" ::"r"(a), "r"(x), "r"(y), "r"(z), "r"(u) : "memory"); }
__device__ __forceinline__ uint4 lds128(uint32_t a) { uint4 v; asm volatile("ld.shared.v4.u32 {%0,%1,%2,%3}, [%4];" : "=r"(v.x), "=r"(v.y), "=r"(v.z), "=r"(v.w) : "r"(a) : "memory"); return v; }
__device__ __forceinline__ uint32_t hmul2(uint32_t a, uint32_t b) { uint32_t r; asm("mul.rn.bf16x2 %0, %1, %2;" : "=r"(r) : "r"(a), "r"(b)); return r; }
__device__ __forceinline__ uint32_t hadd2(uint32_t a, uint32_t b) { uint32_t r; asm("add.rn.bf16x2 %0, %1, %2;" : "=r"(r) : "r"(a), "r"(b)); return r; }
__device__ __forceinline__ void stsm4(uint32_t a, uint32_t r0, uint32_t r1, uint32_t r2, uint32_t r3) {
  asm volatile("stmatrix.sync.aligned.m8n8.x4.shared.b16 [%0], {%1,%2,%3,%4};" ::"r"(a), "r"(r0), "r"(r1), "r"(r2), "r"(r3) : "memory");
}
__device__ __forceinline__ void stsm2(uint32_t a, uint32_t r0, uint32_t r1) {
  asm volatile("stmatrix.sync.aligned.m8n8.x2.shared.b16 [%0], {%1,%2};" ::"r"(a), "r"(r0), "r"(r1) : "memory");
}
__device__ __forceinline__ uint4 ldsm4(uint32_t a) {
  uint4 r; asm volatile("ldmatrix.sync.aligned.m8n8.x4.shared.b16 {%0,%1,%2,%3}, [%4];" : "=r"(r.x), "=r"(r.y), "=r"(r.z), "=r"(r.w) : "r"(a) : "memory"); return r;
}
__device__ __forceinline__ uint32_t movm(uint32_t a) { uint32_t r; asm("movmatrix.sync.aligned.m8n8.trans.b16 %0, %1;" : "=r"(r) : "r"(a)); return r; }
__device__ __forceinline__ void mma16816z(float (&d)[4], uint32_t a0, uint32_t a1, uint32_t a2, uint32_t a3, uint32_t b0, uint32_t b1) {
  asm("mma.sync.aligned.m16n8k16.row.col.f32.bf16.bf16.f32 {%0,%1,%2,%3}, {%4,%5,%6,%7}, {%8,%9}, {%10,%10,%10,%10};"
      : "=f"(d[0]), "=f"(d[1]), "=f"(d[2]), "=f"(d[3]) : "r"(a0), "r"(a1), "r"(a2), "r"(a3), "r"(b0), "r"(b1), "f"(0.f));
}
__device__ __forceinline__ void mma16816(float (&d)[4], const uint4& a, uint32_t b0, uint32_t b1) {
  asm("mma.sync.aligned.m16n8k16.row.col.f32.bf16.bf16.f32 {%0,%1,%2,%3}, {%4,%5,%6,%7}, {%8,%9}, {%0,%1,%2,%3};"
      : "+f"(d[0]), "+f"(d[1]), "+f"(d[2]), "+f"(d[3]) : "r"(a.x), "r"(a.y), "r"(a.z), "r"(a.w), "r"(b0), "r"(b1));
}
__device__ __forceinline__ void mma1688(float (&d)[4], uint32_t a0, uint32_t a1, uint32_t b0) {
  asm("mma.sync.aligned.m16n8k8.row.col.f32.bf16.bf16.f32 {%0,%1,%2,%3}, {%4,%5}, {%6}, {%0,%1,%2,%3};"
      : "+f"(d[0]), "+f"(d[1]), "+f"(d[2]), "+f"(d[3]) : "r"(a0), "r"(a1), "r"(b0));
}
__device__ __forceinline__ float quad_sum(float v) { v += __shfl_xor_sync(0xffffffffu, v, 1); v += __shfl_xor_sync(0xffffffffu, v, 2); return v; }
__device__ __forceinline__ float rcp(float x) { float r; asm("rcp.approx.ftz.f32 %0, %1;" : "=f"(r) : "f"(x)); return r; }
__device__ __forceinline__ float rsq(float x) { float r; asm("rsqrt.approx.ftz.f32 %0, %1;" : "=f"(r) : "f"(x)); return r; }
__device__ __forceinline__ float ex2(float x) { float r; asm("ex2.approx.ftz.f32 %0, %1;" : "=f"(r) : "f"(x)); return r; }
__device__ __forceinline__ uint32_t chk(uint32_t acc, uint32_t v, uint32_t tag) { uint32_t r; asm("lop3.b32 %0, %1, %2, %3, 0xF6;" : "=r"(r) : "r"(acc), "r"(v), "r"(tag)); return r; }
__device__ __forceinline__ uint32_t chk2(uint32_t a, uint32_t b, uint32_t tag) { uint32_t r; asm("lop3.b32 %0, %1, %2, %3, 0x7E;" : "=r"(r) : "r"(a), "r"(b), "r"(tag)); return r; }
__device__ __forceinline__ uint32_t tagged(uint32_t v, uint32_t tag) { return (v & ~1u) | tag; }

__device__ __forceinline__ int group_k0(int g, int j) {
  const int h = g >= 9, r = g - 2 - 7 * h;
  return g < 2 ? 64 * j + 32 * g : g < 16 ? 64 * (r + (r >= j)) + 32 * h : 32 * g;
}
__device__ __forceinline__ uint32_t xin_off(int c, int w) { return SM_X + (2 * c + w) * 8192; }
__device__ __forceinline__ uint32_t xin_bar(int c) { return BAR_FULLX + 8 * (c < 8 ? c ^ 4 : c); }
__device__ __forceinline__ constexpr uint32_t qkv_xslot(int g) { return g < 5 || g > 11 ? 2 : (0x5140762u >> (4 * (g - 5))) & 15; }

template <int N> struct IC { static constexpr int v = N; };

struct Cons {
  uint32_t sb;
  uint32_t rem;
  uint32_t sB, mB;
  uint32_t mX;
  bool elect;
  __device__ __forceinline__ void release2(uint32_t bar) const { if (elect) { mbar_arrive(sb + bar); mbar_arrive_remote(rem + bar); } }
  __device__ __forceinline__ uint32_t nextB(uint32_t& prev) {
    mbar_wait_c(sb + BAR_FULLB + sB, mB);
    const uint32_t a = (((sb & 0x3FFFF) + SM_B) >> 4) + sB * (BSLOT / 128);
    prev = sB == 0 ? 32 : sB - 8;
    sB += 8;
    if (sB == 40) { sB = 0; mB ^= 1; }
    return a;
  }
  __device__ __forceinline__ void progress(uint32_t v) const { if (elect) sts32(sb + SM_PROG + (threadIdx.x >> 5), v); }
  __device__ __forceinline__ void releaseLastB() const { release2(BAR_EMPTYB + (sB == 0 ? 32 : sB - 8)); }
};

__device__ __forceinline__ float2 gather_sums(const uint2* a, uint32_t stag) {
  uint2 sa, sc;
  do { sa = ld_relaxed2(a); sc = ld_relaxed2(a + 8); } while (__any_sync(0xffffffffu, chk2(sa.x, sc.x, stag) & 3));
  return make_float2(quad_sum(__uint_as_float(sa.x) + __uint_as_float(sc.x)), quad_sum(__uint_as_float(sa.y) + __uint_as_float(sc.y)));
}

struct Norm {
  float m0, m1;
  uint32_t nm0, nm1;
  float d0, d1;
  uint2 u0, u1;
  __device__ __forceinline__ Norm(float2 sum) : m0(sum.x * (-1.f / 576)), m1(sum.y * (-1.f / 576)), nm0(pack_bf16(m0, m0)), nm1(pack_bf16(m1, m1)), d0(0.f), d1(0.f) {}
  __device__ __forceinline__ uint4 centre(const uint4& a) const { return make_uint4(hadd2(a.x, nm0), hadd2(a.y, nm1), hadd2(a.z, nm0), hadd2(a.w, nm1)); }
  __device__ __forceinline__ void sqr(uint32_t a, uint32_t b) {
    d0 = fmaf(bf_lo(a), bf_lo(a), fmaf(bf_hi(a), bf_hi(a), d0)); d1 = fmaf(bf_lo(b), bf_lo(b), fmaf(bf_hi(b), bf_hi(b), d1));
  }
  __device__ __forceinline__ void send(uint2* a, int t, uint32_t stag) {
    d0 = quad_sum(d0); d1 = quad_sum(d1);
    if ((t & 3) == 0) st_relaxed2(a, (__float_as_uint(d0) & ~3u) | stag, __float_as_uint(d1));
  }
  __device__ __forceinline__ void fetch(const uint2* a) { u0 = ld_relaxed2(a); u1 = ld_relaxed2(a + 8); }
  __device__ __forceinline__ float2 rstd(const uint2* a, uint32_t stag) {
    while (__any_sync(0xffffffffu, chk2(u0.x, u1.x, stag) & 3)) fetch(a);
    const float e0 = bf_lo(nm0) - m0, e1 = bf_lo(nm1) - m1;
    const float v0 = fmaf(quad_sum(__uint_as_float(u0.x) + __uint_as_float(u1.x)), 1.f / 576, -e0 * e0);
    const float v1 = fmaf(quad_sum(__uint_as_float(u0.y) + __uint_as_float(u1.y)), 1.f / 576, -e1 * e1);
    uint32_t u = pack_bf16(fmaxf(v0, 0.f), fmaxf(v1, 0.f));
    u = pack_bf16(bf_lo(u) + 1e-5f, bf_hi(u) + 1e-5f);
    u = pack_bf16(bf_lo(u) * rsq(bf_lo(u)), bf_hi(u) * rsq(bf_hi(u)));
    float2 r = make_float2(rcp(bf_lo(u)), rcp(bf_hi(u)));
    asm volatile("" : "+f"(r.x), "+f"(r.y));
    return r;
  }
};

template <class Pre, class Mma>
__device__ __forceinline__ float2 ln_gemm_in(Cons& c, Group* G, uint32_t (&p)[18], float2& sum, int w, int st0, int j, int t, Pre&& pre, Mma&& mma) {
  const uint32_t xa = c.sb + (t >> 5) * 2048 + (t & 15) * 128, sw = (((t >> 4) & 1) ^ (t & 7)) * 16;
  float ra[4] = {0.f, 0.f, 0.f, 0.f}, rb[4] = {0.f, 0.f, 0.f, 0.f};
#pragma unroll 1
  for (int cc = 0; cc < 9; cc++) {
    const uint32_t a = xa + xin_off(cc, w);
    mbar_wait_c(c.sb + xin_bar(cc), 0);
    const uint4 u0 = ldsm4(a + sw), u1 = ldsm4(a + (sw ^ 32)), u2 = ldsm4(a + (sw ^ 64)), u3 = ldsm4(a + (sw ^ 96));
    mma16816(ra, u0, 0x3f803f80u, 0x3f803f80u); mma16816(rb, u1, 0x3f803f80u, 0x3f803f80u);
    mma16816(ra, u2, 0x3f803f80u, 0x3f803f80u); mma16816(rb, u3, 0x3f803f80u, 0x3f803f80u);
  }
  sum = make_float2(ra[0] + rb[0], ra[2] + rb[2]);
  pre(0);
  Norm n(sum);
  n.u0 = n.u1 = make_uint2(0, 0);
#pragma unroll
  for (int k = 0; k < 5; k++) {
    const uint4 u = ldsm4(xa + (k < 4 ? xin_off(j, w) + (sw ^ (32 * k)) : xin_off(8, w) + ((j ^ (t & 7)) << 4))), e = n.centre(u);
    p[4 * k] = u.x; p[4 * k + 1] = u.y;
    n.sqr(e.x, e.y);
    if (k < 4) { p[4 * k + 2] = u.z; p[4 * k + 3] = u.w; n.sqr(e.z, e.w); }
  }
  n.send(G->sq + st0 + 8 * j, t, 1);
  pre(1);
  float2 r = make_float2(0.f, 0.f);
  uint4 y0 = ldsm4(xa + xin_off(0, w) + sw), y1 = ldsm4(xa + xin_off(0, w) + (sw ^ 32));
#pragma unroll 1
  for (int cc = 0; cc < 9; cc++) {
#pragma unroll
    for (int i = 0; i < 2; i++) {
      const uint4 f0 = n.centre(y0), f1 = n.centre(y1);
      const uint32_t a = xa + xin_off(min(cc + i, 8), w);
      y0 = ldsm4(a + (sw ^ (64 - 64 * i))); y1 = ldsm4(a + (sw ^ (96 - 64 * i)));
      uint32_t prev;
      const uint32_t bb = c.nextB(prev);
      mma(true, bb, f0, f1);
      if (i == 1) {
        if (cc == 1) c.progress(3);
        if (cc == 5) n.fetch(G->sq + st0 + 16 * (t & 3));
        if (cc == 7) r = n.rstd(G->sq + st0 + 16 * (t & 3), 1);
        if (cc == 8 && w == 0) asm volatile("bar.arrive 6, 256;" ::: "memory");
      }
      wg_wait<1>();
      if (i + cc > 0) c.release2(BAR_EMPTYB + prev);
      if (cc >= 7) c.release2(BAR_EMPTYX + 32 + 8 * (2 * cc + i - 14));
    }
  }
  c.mX = 0xff;
  if (w == 1) asm volatile("bar.sync 6, 256;" ::: "memory");
  wg_wait<0>();
  c.releaseLastB();
  c.release2(BAR_EMPTYX + 24);
  return r;
}

template <bool QKV, class Pre, class Mma>
__device__ __forceinline__ float2 ln_gemm(Cons& c, Group* G, const float (&v)[36], uint32_t (&p)[18], float2& sum, int st0, int j, int t,
                                          int layer, uint32_t tag, Pre&& pre, Mma&& mma) {
  const uint32_t stag = (2 * layer + (QKV ? 1 : 2)) & 3;
  uint4 x[6][2];
  uint4* src = G->xbox + t;
  asm volatile("" : "+l"(src));
  auto buf = [&](int g) -> uint4 (&)[2] { return x[g < 16 ? (g - 2) % 6 : g - 13]; };
  auto load = [&](int g0) {
#pragma unroll
    for (int g = g0; g < g0 + (g0 < 14 ? 3 : 2); g++) {
      const uint4* a = g < 16 ? src + ((g - 2) % 7 >= j ? 256 : 0) + (2 * ((g - 2) % 7) + 16 * (g >= 9)) * 128 : src + 2 * g * 128;
      buf(g)[0] = ld_relaxed4(a); buf(g)[1] = ld_relaxed4(a + 128);
    }
  };
  auto invalid = [&](int g, uint32_t tag) {
    uint32_t bad = chk(chk(chk2(buf(g)[0].x, buf(g)[1].x, tag), buf(g + 1)[0].x, tag), buf(g + 1)[1].x, tag);
    if (g < 14) bad = chk(chk(bad, buf(g + 2)[0].x, tag), buf(g + 2)[1].x, tag);
    if (g == 16) bad = chk(chk(chk(chk(bad, buf(g)[0].z, tag), buf(g)[1].z, tag), buf(g + 1)[0].z, tag), buf(g + 1)[1].z, tag);
    return __any_sync(0xffffffffu, bad & 1);
  };
  uint4* const d = src + 2 * j * 128;
  const int sq = st0 + 16 * (t & 3);
  if (QKV) {
    float s0 = v[0] + v[1], s1 = v[2] + v[3];
#pragma unroll
    for (int i = 1; i < 9; i++) { s0 += v[4 * i] + v[4 * i + 1]; s1 += v[4 * i + 2] + v[4 * i + 3]; }
    s0 = quad_sum(s0); s1 = quad_sum(s1);
    if ((t & 3) == 0) st_relaxed2(G->sum + st0 + 8 * j, (__float_as_uint(s0) & ~3u) | stag, __float_as_uint(s1));
  }
#pragma unroll
  for (int i = 0; i < 18; i++) p[i] = pack_bf16(v[2 * i], v[2 * i + 1]);
#pragma unroll
  for (int i = 0; i < 2; i++) st_relaxed4(d + i * 128, tagged(p[4 * i], tag), p[4 * i + 1], p[4 * i + 2], p[4 * i + 3]);
  pre(0);
  if (QKV) {
    sum = gather_sums(G->sum + sq, stag);
    load(2);
  }
  Norm n(sum);
  pre(1);
  const uint32_t* probe = &(G->xbox + (2 * (t & 3) + 1) * 128 + (t | 31))->x;
  uint32_t pv;
  float2 r;
  auto inx = [](int g) { return QKV && ((g >= 5 && g < 12) || g == 17); };
  auto use = [](int g) { return QKV ? (g < 5 ? 108 : 101) + g : 18 + g; };
#pragma unroll
  for (int g = 0; g < 18; g++) {
    if (g < 16 ? g % 3 == 2 : g == 16) {
      const uint32_t lt = late(c.sb + BAR_PAST, tag);
      while (invalid(g, lt)) load(g);
      if (g < 16) load(g < 14 ? g + 3 : 16);
    }
    const uint4 f0 = n.centre(g < 2 ? make_uint4(p[8 * g], p[8 * g + 1], p[8 * g + 2], p[8 * g + 3]) : buf(g)[0]);
    const uint4 f1 = n.centre(g < 2 ? make_uint4(p[8 * g + 4], p[8 * g + 5], p[8 * g + 6], p[8 * g + 7]) : buf(g)[1]);
    if (g == 11) n.fetch(G->sq + sq);
    if (g == 16) r = n.rstd(G->sq + sq, stag);
    if (inx(g)) mbar_wait_c(c.sb + BAR_FULLX + 8 * qkv_xslot(g), ((0x34 >> qkv_xslot(g)) & 1) ^ (g == 17));
    else mbar_wait_c(c.sb + BAR_FULLB + 8 * (use(g) % 5), (use(g) / 5) & 1);
    mma(g, ((c.sb & 0x3FFFF) >> 4) + ((inx(g) ? xslot(qkv_xslot(g)) : SM_B + (use(g) % 5) * BSLOT) >> 4), f0, f1);
    if (g == 1) { wg_wait<1>(); c.release2(BAR_EMPTYB + 8 * (use(0) % 5)); }
    if (g < 2) {
      if (!QKV) {
        if (g == 0) {
          pv = ld_relaxed(probe);
        } else {
          const uint32_t lt = late(c.sb + BAR_PAST, tag);
          while (__any_sync(0xffffffffu, (pv ^ lt) & 1)) pv = ld_relaxed(probe);
          load(2);
        }
      }
      if (g == (QKV ? 0 : 1)) {
#pragma unroll
        for (int i = 2; i < 4; i++) st_relaxed4(d + (14 + i) * 128, tagged(p[4 * i], tag), p[4 * i + 1], p[4 * i + 2], p[4 * i + 3]);
        st_relaxed2((uint2*)(src + (32 + (j >> 1)) * 128) + (j & 1), tagged(p[16], tag), p[17]);
      }
      n.sqr(f0.x, f0.y); n.sqr(f0.z, f0.w); n.sqr(f1.x, f1.y); n.sqr(f1.z, f1.w);
      if (g == 1) {
        n.sqr(hadd2(p[16], n.nm0), hadd2(p[17], n.nm1));
        n.send(G->sq + st0 + 8 * j, t, stag);
      }
    }
    if (g == 1 && !QKV) { wg_wait<0>(); c.release2(BAR_EMPTYB + 8 * (use(1) % 5)); }
    else wg_wait<1>();
    if (g > (QKV ? 1 : 2) && !inx(g - 1)) c.release2(BAR_EMPTYB + 8 * (use(g - 1) % 5));
    if (QKV && g < 13) c.progress(33 + g);
    if (QKV && g == 11) c.release2(BAR_EMPTYX + 8 * qkv_xslot(17));
    if (QKV && g >= 12 && g < 16) c.release2(BAR_EMPTYX + 32 + 8 * (g - 12));
  }
  if (QKV) c.mX = 0x34 ^ 0xf3;
  else { c.sB = 8 * (36 % 5); c.mB = (36 / 5) & 1; }
  wg_wait<0>();
  if (!QKV) c.release2(BAR_EMPTYB + 8 * (use(17) % 5));
  return r;
}

template <int NB, int OFF>
__device__ __forceinline__ void glu(const float (&a)[128], uint32_t (&h)[144]) {
#pragma unroll
  for (int b = 0; b < 2 * NB; b++) {
    if (OFF == 120) h[OFF + b] = pack_bf16(a[2 * b] * a[4 * NB + 2 * b], a[2 * b + 1] * a[4 * NB + 2 * b + 1]);
    else h[OFF + b] = hmul2(pack_bf16(a[2 * b], a[2 * b + 1]), pack_bf16(a[4 * NB + 2 * b], a[4 * NB + 2 * b + 1]));
  }
}

__global__ void __cluster_dims__(2, 1, 1) __launch_bounds__(384, 1)
fused_kernel(const __nv_bfloat16* __restrict__ x_in, Group* ws, const char* __restrict__ wqkv,
             const char* __restrict__ wo, char* __restrict__ out, uint32_t first, const __grid_constant__ Maps maps,
             const char* __restrict__ wg, const char* __restrict__ wu) {
  extern __shared__ __align__(1024) uint8_t smem_raw[];
  const uint32_t sb = smem_u32(smem_raw);
  const uint32_t bx = blockIdx.x - first;
  if (bx >= NCTA) {
    const int e = blockIdx.x & 3;
    const uint32_t par = ~ld_relaxed(ws->flag + 32) & 1;
    __nanosleep(1000);
    if (threadIdx.x < 16) prefetch_l2(wo + (144 * e + 9 * threadIdx.x) * 1152, 9 * 1152);
#pragma unroll 1
    for (int r = threadIdx.x >> 3; r < 144; r += 48) {
      const uint4* row = (const uint4*)(wo + (144 * e + r) * 1152) + (threadIdx.x & 7);
      float a = 0.f;
      uint4 u;
#pragma unroll
      for (int i = 0; i < 72; i += 8) {
        u = __ldg(row + i);
        a += ((bf_lo(u.x) + bf_hi(u.x)) + (bf_lo(u.y) + bf_hi(u.y))) + ((bf_lo(u.z) + bf_hi(u.z)) + (bf_lo(u.w) + bf_hi(u.w)));
      }
      const int h = r >= 72, k = r - 72 * h;
      ((Scratch*)ws)->woc[threadIdx.x & 7][k < 64 ? 64 + 8 * k + ((2 * e + h) ^ (k & 7)) : 576 * h + 8 * (k & 7) + (e ^ (k & 7))] = u;
      a = quad_sum(a);
      a += __shfl_xor_sync(0xffffffffu, a, 4);
      if ((threadIdx.x & 7) == 0) ((Scratch*)ws)->woc[2 * e + h][640 + k] = make_uint4(pack_bf16(a, a - bf_lo(pack_bf16(a, 0.f))), 0, 0, 0);
    }
    fence_gpu();
    __syncthreads();
    if (threadIdx.x == 0) st_relaxed(((Scratch*)ws)->done + e, par);
    const int cc = threadIdx.x % 54, r0 = threadIdx.x / 54, part = cc / 18, jj = 2 * e + (cc % 18) / 9, c9 = cc % 9;
    if (r0 < 6) {
#pragma unroll 4
      for (int k = r0; k < 576; k += 6) {
        const uint4 u = __ldg((const uint4*)(wqkv + k * 3456 + part * 1152 + 144 * jj) + c9);
        ((Scratch*)ws)->wq[jj][k >> 4][c9 < 8 ? part * 128 + (k & 15) * 8 + (c9 ^ (k & 7)) : 384 + part * 16 + (k & 15)] = u;
      }
    }
    fence_gpu();
    __syncthreads();
    if (threadIdx.x == 0) st_relaxed(((Scratch*)ws)->done + 32 + e, par);
    return;
  }
  if (threadIdx.x == 0) asm volatile("prefetch.tensormap [%0];" ::"l"(&maps.x) : "memory");
  const int warp = __shfl_sync(0xffffffffu, threadIdx.x >> 5, 0);
  const int lane = threadIdx.x & 31;
  const int rank = blockIdx.x & 1;
  if (elect_one()) {
    if (warp >= 8) {
#pragma unroll
      for (int i = 0; i < 9; i++) mbar_init(sb + SM_BAR + 72 * (warp - 8) + 8 * i, warp < 10 ? 1 : 4);
      sts32(sb + SM_PROG + 4 * (warp - 8), 0);
      asm volatile("fence.mbarrier_init.release.cluster;" ::: "memory");
    } else if (warp == 1 || warp == 2) {
      asm volatile("prefetch.tensormap [%0];" ::"l"(&maps.x + warp) : "memory");
    } else if (warp == 3) {
      prefetch_l2((const char*)x_in + bx * 18432, 18432);
    }
  }
  __syncwarp();
  asm volatile("barrier.cluster.arrive.relaxed.aligned;" ::: "memory");
  if (warp == 8) PROFX(53);
  const int cl = bx >> 1, u = cl - 36;
  const int lb = (cl < 4 ? cl : cl < 36 ? 8 * ((cl - 4) & 7) + ((cl - 4) >> 3) + (((cl - 4) & 7) ? 0 : 4) : 8 * (1 + u % 7) + 4 + u / 7) * 2 + rank;
#define CTA_J(b) (((b) >> 1) & 7)
#define CTA_RB(b) ((((b) >> 4) << 1) | ((b) & 1))
  const int j = CTA_J(lb), rb = CTA_RB(lb);

  PROF(23);
  if (warp >= 8) {
    asm volatile("setmaxnreg.dec.sync.aligned.u32 40;");
    auto x_chunk = [&](int cc) {
      mbar_expect_tx(sb + xin_bar(cc), 16384);
      tma3d(sb + xin_off(cc, 0), &maps.x, 64 * cc, 0, 64 * rb, sb + xin_bar(cc));
      tma3d(sb + xin_off(cc, 1), &maps.x, 64 * cc, 1, 64 * rb, sb + xin_bar(cc));
    };
    if (warp == 9 && elect_one()) {
      fence_async_smem();
#pragma unroll 1
      for (int i = 0; i < 9; i++) x_chunk(i);
    }
    __syncwarp();
    if (warp == 9) PROFX(54);
    asm volatile("barrier.cluster.wait.aligned;" ::: "memory");
    if (warp == 8) PROFX(56);
    const uint64_t pol = policy_evict_first(), pola = policy_evict_normal();
    uint4 (* const wq)[432] = ((Scratch*)ws)->wq[j];
    const uint32_t par = ~ld_relaxed(ws[2 * rb].flag + 32 + 32 * j) & 1;
    auto qkv_group = [&](bool copy, int k, uint32_t dst, uint32_t bar) {
      if (copy) {
        wbulk(dst + rank * 8192, wq[(k >> 4) + rank], 6912, bar, pol);
      } else {
        wtma3d(dst + rank * 8192, &maps.qm, 72 * j, k + 16 * rank, 0, bar, pola);
        wtma3d(dst + rank * 8192 + 6144, &maps.qc, 72 * j + 64, k + 16 * rank, 0, bar, pola);
      }
    };
    auto chore = [&](int i) {
#pragma unroll 1
      for (int it = 0; __any_sync(0xffffffffu, ld_acquire(((Scratch*)ws)->done + i) != par); it++) if (it == SPIN_MAX) asm volatile("trap;");
      asm volatile("fence.proxy.async.global;" ::: "memory");
    };
    const int ktab = group_k0(lane, j);
    auto qkv_gate = [&](int g) { if (g >= 8) gate(sb + SM_PROG, 33 + ((g - 8) * 23 >> 4)); };
    if (warp == 8) {
      uint32_t s = 0, ph = 1;
      auto slot = [&](uint32_t bytes, auto&& issue) {
        const uint32_t bar = sb + BAR_FULLB + 8 * s;
        mbar_wait(sb + BAR_EMPTYB + 8 * s, ph);
        if (elect_one()) {
          mbar_expect_tx(bar, bytes);
          issue(sb + SM_B + s * BSLOT, bar);
        }
        if (++s == 5) { s = 0; ph ^= 1; }
      };
#pragma unroll 1
      for (int layer = 0; layer < NLAYERS; layer++) {
        if (layer) chore(32 + (j >> 1));
#pragma unroll 1
        for (int g = 0; g < 18 - layer; g += layer && g == 4 ? 8 : 1) {
          const int k = layer ? __shfl_sync(0xffffffffu, ktab, g) : 32 * g;
          if (layer) qkv_gate(g);
          else if (g == 0) mbar_wait(sb + xin_bar(3), 0);
          slot(2 * 6912, [&](uint32_t dst, uint32_t bar) { qkv_group(layer, k, dst, bar); });
        }
#pragma unroll 1
        for (int t = 0; t < 5; t++) {
          const CUtensorMap* m = &maps.g + (t < 3 ? rank : 2 + rank);
          asm volatile("" : "+l"(m));
          const int c2 = t < 3 ? 9 * j + 2 * t : 18 * j + 3 + 3 * t;
          const uint32_t half = t < 3 ? 8192 : 6144;
          const uint64_t pt = layer == 0 && (t == 0 || t > 2) ? pola : pol;
          auto tile = [&](int g) {
            const int k = __shfl_sync(0xffffffffu, ktab, g);
            slot(2 * half, [&](uint32_t dst, uint32_t bar) { wtma3d(dst + rank * half, m, 0, k, c2, bar, pt); });
          };
          int g = 0;
          if (t == 0) {
#pragma unroll 1
            for (; g < 5; g++) {
              mbar_wait(sb + BAR_FULLB + 8 * (s == 0 ? 4 : s - 1), s == 0 ? ph : ph ^ 1);
              if (g == 2) gate(sb + SM_PROG + 4, 32 * layer + 20);
              tile(g);
            }
          }
#pragma unroll 1
          for (; g < 18; g++) tile(g);
        }
      }
    } else if (warp == 9) {
      uint32_t mE = 0;
      auto acquire = [&](uint32_t s) { mbar_wait(sb + BAR_EMPTYX + 8 * s, (mE >> s) & 1); mE ^= 1u << s; };
      auto slot = [&](uint32_t s, const CUtensorMap* m, int col, int row, uint64_t pol) {
        acquire(s);
        if (elect_one()) {
          mbar_expect_tx(sb + BAR_FULLX + 8 * s, XSLOT);
          wtma2d(sb + xslot(s) + rank * 9216, m, col, row + 72 * rank, sb + BAR_FULLX + 8 * s, pol);
        }
      };
#pragma unroll 1
      for (int layer = 0; layer < NLAYERS; layer++) {
        if (layer) chore(32 + (j >> 1));
#pragma unroll 1
        for (int g = 5; g < 18 * layer; g += g == 11 ? 6 : 1) {
          const uint32_t s = qkv_xslot(g);
          const int k = __shfl_sync(0xffffffffu, ktab, g);
          if (g < 12) qkv_gate(g);
          acquire(s);
          if (elect_one()) {
            mbar_expect_tx(sb + BAR_FULLX + 8 * s, 2 * 6912);
            qkv_group(true, k, sb + xslot(s), sb + BAR_FULLX + 8 * s);
          }
          mbar_wait(sb + BAR_FULLX + 8 * s, (mE >> s) & 1);
        }
#pragma unroll 1
        for (int i = 0; i < 4; i++) slot(4 + i, &maps.o, 64 * j, 144 * i, pola);
        if (layer == 0) { chore(lane & 3); PROFX(57); }
        acquire(3);
        if (elect_one()) {
          mbar_expect_tx(sb + BAR_FULLX + 24, 10240 + 1280);
          wbulk(sb + SM_WOC + rank * 5120, ((Scratch*)ws)->woc[j] + rank * 320, 5120, sb + BAR_FULLX + 24, pola);
          wbulk(sb + SM_WSUM + rank * 640, ((Scratch*)ws)->woc[j] + 640 + rank * 40, 640, sb + BAR_FULLX + 24, pola);
        }
#pragma unroll 1
        for (int u = 0; u < 36; u++) slot(4 * (u & 1) + ((u >> 1) & 3), &maps.d, u < 4 ? 512 : 64 * ((j + (u >> 2)) & 7), 576 * j + 144 * (u & 3), pol);
      }
    } else {
      const int w = warp - 10, grp = 2 * rb + w;
      auto exchange = [&](uint32_t v, uint32_t bar) {
        fence_gpu();
        __syncwarp();
        if (w == 0 && v != 1) PROFX(64 + 58 - 2 * v);
        if (lane == 0) st_relaxed(ws[grp].flag + j, v);
#pragma unroll 1
        for (int it = 0;; it++) {
          const uint32_t f = ld_relaxed(ws[grp].flag + (lane & 7));
          if (__all_sync(0xffffffffu, v ? f >= v : f == 0)) break;
          if (it == SPIN_MAX) asm volatile("trap;");
        }
        if (lane == 0) mbar_arrive(sb + bar + 8 * w);
      };
      mbar_wait(sb + xin_bar(0), 0);
      if (lane == 0) prefetch_l2(wqkv + (2 * bx + w) * 7776, 7776);
      gate(sb + SM_PROG, 3);
      if (w == 0 && lane < 6) asm volatile("prefetch.tensormap [%0];" ::"l"(&maps.o + lane) : "memory");
#pragma unroll 1
      for (int i = lane; i < 72; i += 32) {
        asm volatile("prefetch.global.L2 [%0];" ::"l"((w ? wu : wg) + (size_t)(36 * rb + (i >> 1)) * 9216 + 1152 * j + 128 * (i & 1)));
        __nanosleep(700);
      }
      gate(sb + SM_PROG, 22);
#pragma unroll 1
      for (int i = lane; i < 2 * INBOX; i += 64) {
        uint4* p = ws[grp].inbox[0] + 2 * j * INBOX + i;
        st_relaxed4(p, 0, 0, 0, 0); st_relaxed4(p + 32, 0, 0, 0, 0);
        __nanosleep(150);
      }
      exchange(1, BAR_CLR);
      if (w == 0) PROFX(59);
#pragma unroll 1
      for (int layer = 0; layer < NLAYERS; layer++) {
        mbar_wait(sb + BAR_REDDONE + 8 * w, layer);
        if (w == 0) PROFX(64 + 53 + 4 * layer);
        exchange(2 - 2 * layer, BAR_RREADY);
        if (w == 0) PROFX(64 + 56 + 4 * layer);
      }
      mbar_wait(sb + BAR_DONE + 8 * w, 0);
    }
  } else {
    asm volatile("setmaxnreg.inc.sync.aligned.u32 232;");
#define THREAD_IDS()                                                                   \
    int tid_ = threadIdx.x, bid_ = lb;                                                  \
    asm volatile("" : "+r"(tid_), "+r"(bid_));                                          \
    const int w = warp >> 2, wp = warp & 3;                                             \
    const int lane = tid_ & 31, t = tid_ & 127, g = lane >> 2, q = lane & 3;           \
    const int j = CTA_J(bid_), rb = CTA_RB(bid_), grp = 2 * rb + w;                    \
    const int st0 = wp * 64 + g;                         \
    Group* const G = ws + grp;                                                         \
    const uint32_t dsb = (sb & 0x3FFFF) >> 4;                                          \
    (void)t; (void)g; (void)q; (void)grp; (void)j; (void)st0; (void)dsb; (void)G
    Cons c;
    c.sb = sb; c.sB = 0; c.mB = 0; c.mX = 0; c.elect = (threadIdx.x & 127) == 0;
    asm volatile("mapa.shared::cluster.u32 %0, %1, %2;" : "=r"(c.rem) : "r"(sb), "r"(rank ^ 1));
    float v[36], a1[96], a2[12];
    float2 sum, rs;
    uint32_t res[18], xtag;
    auto qkv_mma = [&](bool acc, uint32_t bb, const uint4& f0, const uint4& f1) {
      wg_fence();
      wgmma_ra<192>(a1, f0, desc_hi(2048, 1024, 1) + bb, acc);
      wgmma_ra<24>(a2, f0, desc_hi(128, 256, 0) + (bb + 384), acc);
      wgmma_ra<192>(a1, f1, desc_hi(2048, 1024, 1) + (bb + 512), true);
      wgmma_ra<24>(a2, f1, desc_hi(128, 256, 0) + (bb + 896), true);
      wg_commit();
    };
    {
      THREAD_IDS();
      {
        if (q == 0) { st_relaxed2(G->sum + st0 + 8 * j, 0, 0); st_relaxed2(G->sq + st0 + 8 * j, 0, 0); }
        if (wp == 3) {
#pragma unroll
          for (int i = 0; i < 5; i++) st_relaxed4(G->halo + j * 160 + lane + i * 32, 0, 0, 0, 0);
        }
        if (lane >= 24) st_relaxed4(G->obox + (8 + j) * 128 + t, 0, 0, 0, 0);
      }
      xtag = __shfl_sync(0xffffffffu, ~ld_relaxed(G->flag + 32 + 32 * j) & 1, 0);
      if (lane >= 24) st_relaxed4(G->xbox + (2 * j + 1) * 128 + t, xtag ^ 1, 0, 0, 0);
      asm volatile("barrier.cluster.wait.aligned;" ::: "memory");
      PROF(0);
#pragma unroll
      for (int i = 0; i < 96; i++) asm volatile("mov.b32 %0, 0;" : "=f"(a1[i]));
#pragma unroll
      for (int i = 0; i < 12; i++) asm volatile("mov.b32 %0, 0;" : "=f"(a2[i]));
      PROF(1);
      rs = ln_gemm_in(c, G, res, sum, w, st0, j, t, [&](int i) { PROF(2 + i); if (i) PROF(4); }, qkv_mma);
    }
#pragma unroll 1
    for (int layer = 0;; layer++) {
      const uint32_t tag = layer ^ 1;
      uint4 own[5];
      {
        THREAD_IDS();
        PROF(pb + 4);
        uint32_t kv[3][18];
        auto cvt = [&](int b, float r) {
#pragma unroll
          for (int cc = 0; cc < 18; cc++) {
            const float* a = (cc == 8 ? a2 + 4 : cc == 17 ? a2 + 8 : cc < 8 ? a1 + 32 + 4 * cc : a1 + 28 + 4 * cc) + 2 * (b - 1);
            const uint32_t u = pack_bf16(a[0] * r, a[1] * r);
            kv[b][cc] = cc < 9 ? u : movm(u);
          }
        };
        cvt(2, rs.y);
#pragma unroll
        for (int i = 0; i < 18; i += 4) kv[2][i] = tagged(kv[2][i], tag);
        const uint32_t msg = sb + (w ? xslot(3) : xslot(0) + 24576) + wp * 2304 + lane * 16;
        if (wp == 3) {
          uint4* hp = G->halo + j * 160 + lane;
#pragma unroll
          for (int i = 0; i < 4; i++) st_relaxed4(hp + i * 32, kv[2][4 * i], kv[2][4 * i + 1], kv[2][4 * i + 2], kv[2][4 * i + 3]);
          st_relaxed2((uint2*)(hp + 128), kv[2][16], kv[2][17]);
        } else {
#pragma unroll
          for (int i = 0; i < 4; i++) sts128(msg + i * 512, kv[2][4 * i], kv[2][4 * i + 1], kv[2][4 * i + 2], kv[2][4 * i + 3]);
          sts64f(msg + 2048 - lane * 8, __uint_as_float(kv[2][16]), __uint_as_float(kv[2][17]));
        }
        cvt(1, rs.x);
        uint32_t Q[4][6];
#pragma unroll
        for (int h = 0; h < 4; h++)
#pragma unroll
          for (int i = 0; i < 6; i++) {
            const float* a = 4 * h + i < 16 ? a1 + 8 * h + 2 * i : a2 + 8 * h + 2 * i - 32;
            const uint32_t u = pack_bf16(a[0], a[1]);
            Q[h][i] = i < 2 ? (q >= h ? u : 0) : i < 4 ? u : (q <= h ? u : 0);
          }
        const bool lo0 = 2 * q > g, lo1 = 2 * q + 1 > g;
        const uint32_t M = (lo0 ? 0xffffu : 0u) | (lo1 ? 0xffff0000u : 0u);
        auto scores = [&](int h, int b, float (&s)[4]) {
          mma16816z(s, Q[h][0], Q[h][1], Q[h][2], Q[h][3], kv[b][2 * h], kv[b][2 * h + 1]);
          mma1688(s, Q[h][4], Q[h][5], kv[b][2 * h + 2]);
        };
        auto softmax = [&](float (&l)[4][2], float r, uint32_t (&P)[4]) {
          const float sl = r * (0.23570226039551584f * 1.4426950408889634f);
          float m[4];
#pragma unroll
          for (int h = 0; h < 4; h++) { m[h] = fmaxf(l[h][0], l[h][1]); m[h] = fmaxf(m[h], __shfl_xor_sync(0xffffffffu, m[h], 1)); }
#pragma unroll
          for (int h = 0; h < 4; h++) m[h] = fmaxf(m[h], __shfl_xor_sync(0xffffffffu, m[h], 2)) * sl;
#pragma unroll
          for (int h = 0; h < 4; h++) P[h] = pack_bf16(ex2(fmaf(l[h][0], sl, -m[h])), ex2(fmaf(l[h][1], sl, -m[h])));
        };
        const bool remote = wp == 0 && rb > 0;
        const uint4* hp = (G - 2)->halo + j * 160 + lane;
        auto halo = [&] {
#pragma unroll
          for (int i = 0; i < 4; i++) { const uint4 u = ld_relaxed4(hp + i * 32); kv[0][4 * i] = u.x; kv[0][4 * i + 1] = u.y; kv[0][4 * i + 2] = u.z; kv[0][4 * i + 3] = u.w; }
          const uint2 u = ld_relaxed2((const uint2*)(hp + 128));
          kv[0][16] = u.x; kv[0][17] = u.y;
        };
#pragma unroll
        for (int i = 0; i < 18; i++) kv[0][i] = 0;
        float l0[4][2], l1[4][2];
#pragma unroll
        for (int h = 0; h < 4; h++) {
          float s1[4], s2[4];
          scores(h, 1, s1); scores(h, 2, s2);
          l0[h][0] = s1[0]; l0[h][1] = s1[1];
          l1[h][0] = lo0 ? s1[2] : s2[2]; l1[h][1] = lo1 ? s1[3] : s2[3];
        }
        hp += __float_as_uint(l1[0][0]) & late(sb + BAR_PAST, 0);
        if (remote) halo();
        uint32_t P0[4], P1[4];
        softmax(l1, rs.y, P1);
        if (remote) {
          while (__any_sync(0xffffffffu, chk(chk(chk(chk2(kv[0][0], kv[0][4], tag), kv[0][8], tag), kv[0][12], tag), kv[0][16], tag) & 1)) halo();
        }
        wg_bar(w);
        if (wp > 0) {
          const uint32_t from = msg - 2304;
#pragma unroll
          for (int i = 0; i < 4; i++) { const uint4 u = lds128(from + i * 512); kv[0][4 * i] = u.x; kv[0][4 * i + 1] = u.y; kv[0][4 * i + 2] = u.z; kv[0][4 * i + 3] = u.w; }
          const float2 u = lds64(from + 2048 - lane * 8);
          kv[0][16] = __float_as_uint(u.x); kv[0][17] = __float_as_uint(u.y);
        }
        PROF(pb + 5);
        const bool first = (rb == 0 && wp == 0);
#pragma unroll
        for (int h = 0; h < 4; h++) {
          float s0[4];
          scores(h, 0, s0);
          if (first) s0[0] = s0[1] = -INFINITY;
          l0[h][0] = lo0 ? s0[0] : l0[h][0]; l0[h][1] = lo1 ? s0[1] : l0[h][1];
        }
        softmax(l0, rs.x, P0);
        uint4* ob = G->obox + t;
        uint32_t car0 = 0, car1 = 0;
#pragma unroll
        for (int h = 0; h < 4; h++) {
          float o[3][4], z[4] = {0.f, 0.f, 0.f, 0.f};
          mma1688(z, P0[h], P1[h], 0x3f803f80u);
#pragma unroll
          for (int i = 0; i < 3; i++) {
            mma16816z(o[i], P0[h] & ~M, P1[h] & M, 0u, P1[h] & ~M, kv[1][9 + 2 * h + i], kv[2][9 + 2 * h + i]);
            mma1688(o[i], P0[h] & M, 0u, kv[0][9 + 2 * h + i]);
          }
          const float i0 = rcp(z[0]), i1 = rcp(z[2]);
#pragma unroll
          for (int i = 0; i < 3; i++) { o[i][0] *= i0; o[i][1] *= i0; o[i][2] *= i1; o[i][3] *= i1; }
          const uint32_t o0 = q < h ? car0 : pack_bf16(o[0][0], o[0][1]), o1 = q < h ? car1 : pack_bf16(o[0][2], o[0][3]);
          own[h] = make_uint4(o0 | 1, o1, pack_bf16(o[1][0], o[1][1]), pack_bf16(o[1][2], o[1][3]));
          if (h < 3) st_relaxed4(ob + (8 * h + j) * 128, own[h].x, own[h].y, own[h].z, own[h].w);
          car0 = pack_bf16(o[2][0], o[2][1]); car1 = pack_bf16(o[2][2], o[2][3]);
          if (h == 1) { const uint32_t z = late(sb + BAR_PAST, 0); P0[2] ^= z; P0[3] ^= z; }
        }
        car0 = tagged(car0, tag);
        own[4] = make_uint4(car0, car1, 0, 0);
        PROF(pb + 6);
      }
      uint2 sa, sc;
      {
        THREAD_IDS();
        uint4* src = G->obox + t;
        asm volatile("" : "+l"(src));
        uint4 x[32];
        const uint4* from[7];
#pragma unroll
        for (int r = 0; r < 7; r++) { from[r] = src + (r >= j ? 128 : 0); asm volatile("" : "+l"(from[r])); }
        auto load = [&](int i) { x[i] = ld_relaxed4(i < 28 ? from[i % 7] + (8 * (i / 7) + i % 7) * 128 : src + (i + 4) * 128); };
        const uint32_t* probe = &(G->obox + (8 + (lane & 7)) * 128 + (t | 31))->x;
        uint32_t pv = ld_relaxed(probe);
#pragma unroll
        for (int i = 3; i < 8; i++) mbar_wait_c(sb + BAR_FULLX + 8 * i, (c.mX >> i) & 1);
        c.mX ^= 0xf8;
        while (__any_sync(0xffffffffu, ~pv & 1)) pv = ld_relaxed(probe);
        PROF(25 - layer);
        if (w == 1) asm volatile("bar.sync 7, 256;" ::: "memory");
#pragma unroll
        for (int i = 0; i < 10; i++) load(i);
        if (w == 0) asm volatile("bar.arrive 7, 256;" ::: "memory");
        st_relaxed4(src + (24 + j) * 128, own[3].x, own[3].y, own[3].z, own[3].w);
        st_relaxed2((uint2*)(src + (32 + (j >> 1)) * 128) + (j & 1), own[4].x, own[4].y);
        PROF(27 - layer);
        float a[36];
        float e[4];
        constexpr uint32_t NEXT = 576 - (575u << 16);
        auto step = [&](const uint4& f, uint32_t s, int i, uint32_t more, bool acc) {
          const uint32_t r = (xslot(4) >> 4) + (i < 4 ? 72 * s + 16 * i : 144 * s + 64) * 8, c = (SM_WOC >> 4) + (i < 4 ? 64 + 128 * i : 0) + s;
          wgmma_ra<72>(a, f, desc_hi(0, i < 4 ? 1024 : 9216, 1) + (dsb + more + (r + ((c - r) << 16))), acc);
        };
        wg_fence();
#pragma unroll
        for (int i = 0; i < 5; i++) wgmma_ra<8>(e, own[i], desc_hi(128, 0, 0) + (dsb + (SM_WSUM >> 4) + 16 * i), i > 0);
        wg_commit();
#pragma unroll
        for (int i = 0; i < 4; i++) step(own[i], 0, i, j * NEXT, i > 0);
        wg_commit();
        PROF(29 - layer);
        auto batch = [&](auto e0, auto e1, auto e2, int b) {
          constexpr int E0 = decltype(e0)::v, E1 = decltype(e1)::v, E2 = decltype(e2)::v;
          const uint32_t one = late(sb + BAR_PAST, 1);
          while (true) {
            uint32_t bad = 0;
#pragma unroll
            for (int i = E0; i < E1; i++) bad = i < 28 ? chk(bad, x[i].x, one) : chk(chk(bad, x[i].x, tag), x[i].z, tag);
            if (!__any_sync(0xffffffffu, bad & 1)) break;
#pragma unroll
            for (int i = E0; i < E1; i++) load(i);
          }
          if (b == 0) PROF(pb + 7);
          if (b == 1) { c.progress(32 * layer + 20); wg_wait<1>(); }
#pragma unroll
          for (int i = E1; i < E2; i++) load(i);
          if (b == 2) { sa = ld_relaxed2(G->sum + st0 + 16 * q); sc = ld_relaxed2(G->sum + st0 + 16 * q + 8); }
          wg_fence();
#pragma unroll
          for (int i = E0; i < E1; i++) step(x[i], i % 7, i / 7, i < 28 && i % 7 >= j ? NEXT : 0, true);
          wg_commit();
          if (b == 0) {
            wg_wait<2>();
            if (q == 0) st_relaxed2(G->sum + st0 + 8 * j, (__float_as_uint(e[0] + e[1]) & ~3u) | ((2 * layer + 2) & 3), __float_as_uint(e[2] + e[3]));
          }
        };
        batch(IC<0>(), IC<10>(), IC<21>(), 0);
        batch(IC<10>(), IC<21>(), IC<32>(), 1);
        batch(IC<21>(), IC<32>(), IC<32>(), 2);
        wg_wait<0>();
        if (w == 0) asm volatile("bar.arrive 3, 256;" ::: "memory");
        PROF(pb + 8);
#pragma unroll
        for (int i = 0; i < 18; i++) {
          v[2 * i] = bf_lo(res[i]) + a[2 * i];
          v[2 * i + 1] = bf_hi(res[i]) + a[2 * i + 1];
        }
      }
      uint32_t lsb;
      uint32_t h[144];
      {
        THREAD_IDS();
        float a[128];
        const uint32_t xd = sb + xslot(4 * w) + (lane >> 4) * 1024 + (16 * wp + (lane & 15)) * 16;
        const float2 rs = ln_gemm<false>(c, G, v, res, sum, st0, j, t, layer, xtag,
          [&](int i) {
            if (i == 0) {
              lsb = ((res[0] & 1) | (res[4] & 1) << 1 | (res[8] & 1) << 2 | (res[12] & 1) << 3 | (res[16] & 1) << 4) ^ (xtag * 31);
              const uint32_t st = late(sb + BAR_PAST, (2 * layer + 2) & 3);
              while (__any_sync(0xffffffffu, chk2(sa.x, sc.x, st) & 3)) { sa = ld_relaxed2(G->sum + st0 + 16 * q); sc = ld_relaxed2(G->sum + st0 + 16 * q + 8); }
              sum.x += quad_sum(__uint_as_float(sa.x) + __uint_as_float(sc.x)); sum.y += quad_sum(__uint_as_float(sa.y) + __uint_as_float(sc.y));
              if (w == 1) asm volatile("bar.sync 3, 256;" ::: "memory");
            }
            PROF(pb + 9 + i);
          },
          [&](int gi, uint32_t bb, const uint4& f0, const uint4& f1) {
            if (gi == 0) PROF(pb + 11);
            if (gi == 16 && w == 1) asm volatile("bar.sync 5, 256;" ::: "memory");
            wg_fence();
            wgmma_ra<256>(a, f0, desc_hi(4096, 1024, 1) + bb, gi > 0);
            wgmma_ra<256>(a, f1, desc_hi(4096, 1024, 1) + (bb + 128), true);
            wg_commit();
            if (gi == 17 && w == 0) asm volatile("bar.arrive 5, 256;" ::: "memory");
            stsm4(xd + gi * 4096, f0.x, f0.y, f0.z, f0.w);
            stsm4(xd + gi * 4096 + 2048, f1.x, f1.y, f1.z, f1.w);
            if (gi == 17) { fence_async_smem(); wg_bar(w); }
          });
        sts64f(sb + SM_KEEP + (tid_ >> 2) * 8, rs.x * rs.x, rs.y * rs.y);
        c.progress(32 * layer + 22);
        PROF(pb + 12);
        glu<16, 0>(a, h);
        const Desc da0 = desc_hi(1024, 128, 0) + (dsb + (xslot(4 * w) >> 4));
        auto tile = [&](auto wide, auto last) {
          const uint32_t xe = BAR_EMPTYX + 32 * (t & 1) + 4 * (t & 6);
          auto group = [&](int gi) {
            uint32_t prev;
            const uint32_t bb = c.nextB(prev);
            const Desc da = da0 + gi * 256;
            wg_fence();
            if (wide()) {
              wgmma_ss<256>(a, da, desc_hi(4096, 1024, 1) + bb, gi);
              wgmma_ss<256>(a, da + 128, desc_hi(4096, 1024, 1) + (bb + 128), 1);
            } else {
              wgmma_ss<192>(*(float(*)[96])a, da, desc_hi(2048, 512, 2) + bb, gi);
              wgmma_ss<192>(*(float(*)[96])a, da + 128, desc_hi(2048, 512, 2) + (bb + 64), 1);
            }
            wg_commit();
            if (gi == 17 && w == 0) asm volatile("bar.arrive 5, 256;" ::: "memory");
            wg_wait<1>();
            if (gi > 0 && !(last() && gi > 13)) c.release2(BAR_EMPTYB + prev);
            if (last() && gi >= 8 && !(gi & 1)) c.release2(BAR_EMPTYX + 16 * ((gi - 8) & 2) + 2 * ((gi - 8) & 12));
          };
          int gi = 0, end = w ? 16 : 18;
#pragma unroll 1
          while (true) {
#pragma unroll 1
            for (; gi < end; gi++) group(gi);
            if (end == 18) break;
            asm volatile("bar.sync 5, 256;" ::: "memory");
            end = 18;
          }
          wg_wait<0>();
          if (!last()) c.releaseLastB();
          if (last() && t >= 5 && t < 8) { mbar_arrive(sb + xe); mbar_arrive_remote(c.rem + xe); }
        };
        auto yes = [] { return true; };
        auto no = [] { return false; };
        tile(yes, no); PROF(pb + 13); glu<16, 32>(a, h);
        tile(yes, no); PROF(pb + 14); glu<16, 64>(a, h);
        tile(no, no); PROF(pb + 15); glu<12, 96>(a, h);
        const uint32_t hole = sb + SM_B + 12288 + tid_ * 16;
#pragma unroll
        for (int i = 0; i < 4; i++) sts128(hole + i * BSLOT, h[96 + 4 * i], h[97 + 4 * i], h[98 + 4 * i], h[99 + 4 * i]);
        if (w == 1) asm volatile("bar.arrive 8, 256;" ::: "memory");
        tile(no, yes); PROF(pb + 16); glu<12, 120>(a, h);
#pragma unroll
        for (int i = 0; i < 4; i++) { const uint4 u = lds128(hole + i * BSLOT); h[96 + 4 * i] = u.x; h[97 + 4 * i] = u.y; h[98 + 4 * i] = u.z; h[99 + 4 * i] = u.w; }
      }
      {
        THREAD_IDS();
        float d[32];
        uint4* gt = G->obox + t;
        asm volatile("" : "+l"(gt));
        uint4* const ib = gt + 2 * 4608 + layer * 8 * INBOX;
        auto pass = [&](uint32_t s0, bool last, auto&& hook) {
          const Desc db = desc_hi(0, 1024, 1) + (dsb + s0 * (XSLOT >> 4));
          auto full = [&](int i) { const int si = 4 * (i & 1) + (i >> 1); mbar_wait_c(sb + BAR_FULLX + 8 * (s0 + si), (c.mX >> (s0 + si)) & 1); };
          auto empty = [&](int i) { c.release2(BAR_EMPTYX + 8 * (s0 + 4 * (i & 1) + (i >> 1))); };
          full(0);
          hook();
          asm volatile("bar.sync %0, 256;" ::"r"(8 + w) : "memory");
#pragma unroll
          for (int i = 0; i < 4; i++) {
            const int si = 4 * (i & 1) + (i >> 1);
            if (i > 0) full(i);
            wg_fence();
#pragma unroll
            for (int k = 0; k < 9; k++) {
              const uint32_t* hk = h + 36 * i + 4 * k;
              wgmma_ra<64>(d, make_uint4(hk[0], hk[1], hk[2], hk[3]), db + ((xslot(si) >> 4) + k * 128), last || i + k > 0);
            }
            if (i == 3 && !(last && w == 1)) asm volatile("bar.arrive %0, 256;" ::"r"(9 - w) : "memory");
            if (i > 0) wg_commit();
            if (i > 1) { wg_wait<1>(); empty(i - 1); }
            if (i == 2) empty(0);
          }
          c.mX ^= 0x33u << s0;
        };
        PROF(pb + 17);
#pragma unroll 1
        for (int p = 0; p < 8; p++) {
          const uint32_t s0 = 2 * (p & 1);
          pass(s0, false, [] {});
          wg_wait<0>();
          c.release2(BAR_EMPTYX + 8 * (s0 + 5));
          if (p == 6 && layer == NLAYERS - 1) c.elect = false;
          uint32_t pk[16];
#pragma unroll
          for (int i = 0; i < 16; i++) pk[i] = pack_bf16(d[2 * i], d[2 * i + 1]);
          if (p >= 1 && p < 6 && layer < NLAYERS - 1) {
            const uint32_t o = c.sB + 8 * (p - 1);
            c.release2(BAR_EMPTYB + (o < 40 ? o : o - 40));
          }
          uint4* const dst = ib + ((j + p) & 7) * INBOX;
          if (p == 0) {
            mbar_wait_c(sb + BAR_CLR + 8 * w, 0);
#pragma unroll
            for (int k = 0; k < 8; k++) red2((uint2*)(ib + k * INBOX + 512) - t, pk[2 * k], pk[2 * k + 1]);
          } else if (p < 7) {
#pragma unroll
            for (int k = 0; k < 4; k++) red4(dst + k * 128, pk[4 * k], pk[4 * k + 1], pk[4 * k + 2], pk[4 * k + 3]);
            if (p == 6) { __syncwarp(); if (lane == 0) mbar_arrive(sb + BAR_REDDONE + 8 * w); }
          } else {
#pragma unroll
            for (int k = 0; k < 4; k++) st_relaxed4(gt + ((j + 7) & 7) * 128 + k * 1024, pk[4 * k] & ~1u, pk[4 * k + 1], pk[4 * k + 2], pk[4 * k + 3]);
          }
        }
        PROF(pb + 18);
        const uint4 *in = ib + j * INBOX, *pin = gt + j * 128;
        const uint2* in9 = (const uint2*)(in + 512) - t;
        asm volatile("" : "+l"(in), "+l"(pin), "+l"(in9));
        const float2 r2 = lds64(sb + SM_KEEP + (tid_ >> 2) * 8);
        uint2 X9;
        {
          uint4 X[4];
          const uint4* box = gt + 4608;
#pragma unroll
          for (int k = 0; k < 4; k++) X[k] = ld_relaxed4(box + 256 * j + ((k & 1) + 8 * (k & 2)) * 128);
          X9 = ld_relaxed2((const uint2*)(box + (32 + (j >> 1)) * 128) + (j & 1));
          const float i0 = rcp(r2.x), i1 = rcp(r2.y);
#pragma unroll
          for (int k = 0; k < 4; k++) {
            float* e = d + 8 * k;
            X[k].x ^= (lsb >> k) & 1;
            e[0] = bf_lo(X[k].x) * i0; e[1] = bf_hi(X[k].x) * i0; e[2] = bf_lo(X[k].y) * i1; e[3] = bf_hi(X[k].y) * i1;
            e[4] = bf_lo(X[k].z) * i0; e[5] = bf_hi(X[k].z) * i0; e[6] = bf_lo(X[k].w) * i1; e[7] = bf_hi(X[k].w) * i1;
          }
        }
        uint4 R[4], P[4];
        uint2 R9;
        PROF(pb + 19);
        pass(0, true, [&] {
          mbar_wait_c(sb + BAR_RREADY + 8 * w, layer);
#pragma unroll
          for (int k = 0; k < 4; k++) R[k] = ld_relaxed4(in + k * 128);
          R9 = ld_relaxed2(in9);
#pragma unroll
          for (int k = 0; k < 4; k++) P[k] = ld_relaxed4(pin + k * 1024);
        });
        const uint32_t zero = late(sb + BAR_PAST, 0);
        while (__any_sync(0xffffffffu, (chk2(P[0].x, P[1].x, zero) | chk2(P[2].x, P[3].x, zero)) & 1)) {
#pragma unroll
          for (int k = 0; k < 4; k++) P[k] = ld_relaxed4(pin + k * 1024);
        }
#pragma unroll
        for (int k = 0; k < 4; k++) {
          const uint32_t u[4] = {hadd2(R[k].x, P[k].x), hadd2(R[k].y, P[k].y), hadd2(R[k].z, P[k].z), hadd2(R[k].w, P[k].w)};
#pragma unroll
          for (int i = 0; i < 4; i++) { v[8 * k + 2 * i] = bf_lo(u[i]); v[8 * k + 2 * i + 1] = bf_hi(u[i]); }
        }
        X9.x = chk(zero, X9.x, lsb >> 4);
        v[32] = fmaf(bf_lo(R9.x), r2.x, bf_lo(X9.x)); v[33] = fmaf(bf_hi(R9.x), r2.x, bf_hi(X9.x));
        v[34] = fmaf(bf_lo(R9.y), r2.y, bf_lo(X9.y)); v[35] = fmaf(bf_hi(R9.y), r2.y, bf_hi(X9.y));
        PROF(pb + 20);
        wg_wait<0>();
        c.release2(BAR_EMPTYX + 40);
        PROF(pb + 21);
#pragma unroll
        for (int i = 0; i < 32; i++) v[i] = (v[i] + d[i]) * (i & 2 ? r2.y : r2.x);
      }
      if (layer == NLAYERS - 1) break;
      {
        THREAD_IDS();
        PROF(31);
        rs = ln_gemm<true>(c, G, v, res, sum, st0, j, t, 1, xtag ^ 1, [&](int i) { PROF(32 + i); if (i) PROF(34); }, qkv_mma);
      }
    }
    {
      THREAD_IDS();
      const uint32_t stg = sb + SM_B + warp * 4096;
      const uint32_t sd = stg + (lane & 15) * 128;
#pragma unroll
      for (int i = 0; i < 4; i++)
        stsm4(sd + (((2 * i + (lane >> 4)) ^ (lane & 7)) << 4), pack_bf16(v[8 * i], v[8 * i + 1]), pack_bf16(v[8 * i + 2], v[8 * i + 3]),
              pack_bf16(v[8 * i + 4], v[8 * i + 5]), pack_bf16(v[8 * i + 6], v[8 * i + 7]));
      stsm2(stg + 2048 + (lane & 15) * 16, pack_bf16(v[32], v[33]), pack_bf16(v[34], v[35]));
      __syncwarp();
      char* o = out + (128 * rb + 32 * wp + w) * 1152;
#pragma unroll
      for (int i = 0; i < 4; i++) {
        const int r = 4 * i + (lane >> 3);
        *(uint4*)(o + r * 2304 + 128 * j + 16 * (lane & 7)) = lds128(stg + r * 128 + (((lane ^ r) & 7) << 4));
      }
      if (lane < 16) *(uint4*)(o + lane * 2304 + 1024 + 16 * j) = lds128(stg + 2048 + lane * 16);
      if (lane == 0) {
        if (wp == 0) st_relaxed(G->flag + 32 + 32 * j, xtag);
        mbar_arrive(sb + BAR_DONE + 8 * w);
      }
      PROF(61);
    }
  }
}

typedef CUresult (*EncFn)(CUtensorMap*, CUtensorMapDataType, cuuint32_t, void*, const cuuint64_t*, const cuuint64_t*, const cuuint32_t*,
                          const cuuint32_t*, CUtensorMapInterleave, CUtensorMapSwizzle, CUtensorMapL2promotion, CUtensorMapFloatOOBfill);

void make_map(EncFn enc, CUtensorMap* m, const void* p, int rank, uint64_t d0, uint64_t d1, uint64_t d2, uint64_t s1, uint64_t s2, uint32_t b0,
              uint32_t b1, uint32_t b2, CUtensorMapSwizzle sw) {
  cuuint64_t gd[3] = {d0, d1, d2};
  cuuint64_t gs[2] = {s1, s2};
  cuuint32_t bd[3] = {b0, b1, b2};
  cuuint32_t es[3] = {1, 1, 1};
  enc(m, CU_TENSOR_MAP_DATA_TYPE_BFLOAT16, rank, const_cast<void*>(p), gd, gs, bd, es, CU_TENSOR_MAP_INTERLEAVE_NONE, sw,
      CU_TENSOR_MAP_L2_PROMOTION_L2_128B, CU_TENSOR_MAP_FLOAT_OOB_FILL_NONE);
}

}

extern "C" void kernel_launch(void* const* d_in, const int* in_sizes, int n_in, void* d_out, int out_size) {
  const __nv_bfloat16* x = (const __nv_bfloat16*)d_in[0];
  const char *wqkv = (const char*)d_in[1], *wo = (const char*)d_in[2], *wg = (const char*)d_in[4], *wu = (const char*)d_in[5], *wd = (const char*)d_in[6];
  static EncFn enc = nullptr;
  static uint32_t first = 0;
  static Group* ws = nullptr;
  if (!enc) {
    cudaDriverEntryPointQueryResult qr;
    cudaGetDriverEntryPoint("cuTensorMapEncodeTiled", (void**)&enc, cudaEnableDefault, &qr);
    cudaGetSymbolAddress((void**)&ws, g_ws);
    cudaFuncSetAttribute(fused_kernel, cudaFuncAttributeMaxDynamicSharedMemorySize, SMEM_BYTES);
    cudaLaunchConfig_t cfg = {};
    cfg.gridDim = NCTA + 4; cfg.blockDim = 384; cfg.dynamicSmemBytes = SMEM_BYTES;
    int clusters = 0;
    if (XFIRST || cudaOccupancyMaxActiveClusters(&clusters, fused_kernel, &cfg) != cudaSuccess || 2 * clusters < NCTA + 4) first = 4;
    cudaGetLastError();
  }
  const CUtensorMapSwizzle S0 = CU_TENSOR_MAP_SWIZZLE_NONE, S64 = CU_TENSOR_MAP_SWIZZLE_64B, S128 = CU_TENSOR_MAP_SWIZZLE_128B;
  Maps m;
  make_map(enc, &m.x, x, 3, 576, 2, 1024, 1152, 2304, 64, 1, 64, S128);
  make_map(enc, &m.qm, wqkv, 3, 576, 576, 3, 3456, 1152, 64, 16, 3, S128);
  make_map(enc, &m.qc, wqkv, 3, 576, 576, 3, 3456, 1152, 8, 16, 3, S0);
  make_map(enc, &m.o, wo, 2, 576, 576, 1, 1152, 0, 64, 72, 1, S128);
  make_map(enc, &m.g, wg, 3, 64, 576, 72, 9216, 128, 64, 32, 2, S128);
  make_map(enc, &m.u, wu, 3, 64, 576, 72, 9216, 128, 64, 32, 2, S128);
  make_map(enc, &m.g3, wg, 3, 32, 576, 144, 9216, 64, 32, 32, 3, S64);
  make_map(enc, &m.u3, wu, 3, 32, 576, 144, 9216, 64, 32, 32, 3, S64);
  make_map(enc, &m.d, wd, 2, 576, 4608, 1, 1152, 0, 64, 72, 1, S128);
  fused_kernel<<<NCTA + 4, 384, SMEM_BYTES>>>(x, ws, wqkv, wo, (char*)d_out, first, m, wg, wu);
}
```

```cpp
#include <cuda_runtime.h>
#include <cuda_bf16.h>
#include <cuda.h>
#include <stdint.h>
#include <stddef.h>

namespace {

constexpr int NCTA = 128;
#define NLAYERS 2
#define XFIRST 0
constexpr uint32_t SM_X = 0;
constexpr uint32_t XSLOT = 18432;
__host__ __device__ constexpr uint32_t xslot(uint32_t s) { return SM_X + (s ^ 4) * XSLOT; }
constexpr uint32_t SM_WOC = xslot(3) + 8192;
constexpr uint32_t SM_B = 147456;
constexpr uint32_t BSLOT = 16384;
constexpr uint32_t SM_KEEP = 229376;
constexpr uint32_t SM_WSUM = SM_KEEP + 512;
constexpr uint32_t SM_BAR = SM_KEEP + 2048;
constexpr uint32_t BAR_FULLB = SM_BAR;
constexpr uint32_t BAR_RREADY = SM_BAR + 40;
constexpr uint32_t BAR_CLR = SM_BAR + 56;
constexpr uint32_t BAR_FULLX = SM_BAR + 72;
constexpr uint32_t BAR_PAST = BAR_FULLX + 64;
constexpr uint32_t BAR_EMPTYB = SM_BAR + 144;
constexpr uint32_t BAR_EMPTYX = SM_BAR + 184;
constexpr uint32_t BAR_REDDONE = SM_BAR + 248;
constexpr uint32_t BAR_DONE = SM_BAR + 264;
constexpr uint32_t SM_PROG = SM_BAR + 288;
constexpr uint32_t SMEM_BYTES = SM_BAR + 1024;

struct Maps { CUtensorMap x, qm, qc, o, g, u, g3, u3, d; };

constexpr int INBOX = 576;
struct Group {
  uint2 sum[4 * 8 * 8];
  uint2 sq[4 * 8 * 8];
  uint32_t flag[1024];
  uint4 halo[8 * 160];
  uint4 obox[36 * 128];
  uint4 xbox[36 * 128];
  uint4 inbox[2][8 * INBOX];
};
struct Scratch { Group g[32]; uint4 wq[8][36][432]; uint4 woc[8][720]; uint32_t done[64]; };
__device__ __align__(1024) Scratch g_ws;
#define PROF(i)
#define PROFX(i)

struct Desc { uint32_t lo, hi; };
__device__ __forceinline__ constexpr Desc desc_hi(uint32_t lbo, uint32_t sbo, uint32_t sw) { return Desc{(lbo >> 4) << 16, (sbo >> 4) | sw << 30}; }
__device__ __forceinline__ constexpr Desc operator+(Desc d, uint32_t a) { return Desc{d.lo + a, d.hi}; }

template<int N> __device__ __forceinline__ void wgmma_ss(float (&d)[N / 2], Desc da, Desc db, int sc);
template<> __device__ __forceinline__ void wgmma_ss<192>(float (&d)[96], Desc da, Desc db, int sc) {
  asm volatile("{\n.reg .pred p;\n.reg .b64 a, b;\nsetp.ne.b32 p, %100, 0;\nmov.b64 a, {%96, %97};\nmov.b64 b, {%98, %99};\n"
    "wgmma.mma_async.sync.aligned.m64n192k16.f32.bf16.bf16 {%0,%1,%2,%3,%4,%5,%6,%7,%8,%9,%10,%11,%12,%13,%14,%15,%16,%17,%18,%19,%20,%21,%22,%23,%24,%25,%26,%27,%28,%29,%30,%31,%32,%33,%34,%35,%36,%37,%38,%39,%40,%41,%42,%43,%44,%45,%46,%47,%48,%49,%50,%51,%52,%53,%54,%55,%56,%57,%58,%59,%60,%61,%62,%63,%64,%65,%66,%67,%68,%69,%70,%71,%72,%73,%74,%75,%76,%77,%78,%79,%80,%81,%82,%83,%84,%85,%86,%87,%88,%89,%90,%91,%92,%93,%94,%95}, a, b, p, 1, 1, 0, 1;\n}\n"
    : "+f"(d[0]),"+f"(d[1]),"+f"(d[2]),"+f"(d[3]),"+f"(d[4]),"+f"(d[5]),"+f"(d[6]),"+f"(d[7]),"+f"(d[8]),"+f"(d[9]),"+f"(d[10]),"+f"(d[11]),"+f"(d[12]),"+f"(d[13]),"+f"(d[14]),"+f"(d[15]),"+f"(d[16]),"+f"(d[17]),"+f"(d[18]),"+f"(d[19]),"+f"(d[20]),"+f"(d[21]),"+f"(d[22]),"+f"(d[23]),"+f"(d[24]),"+f"(d[25]),"+f"(d[26]),"+f"(d[27]),"+f"(d[28]),"+f"(d[29]),"+f"(d[30]),"+f"(d[31]),"+f"(d[32]),"+f"(d[33]),"+f"(d[34]),"+f"(d[35]),"+f"(d[36]),"+f"(d[37]),"+f"(d[38]),"+f"(d[39]),"+f"(d[40]),"+f"(d[41]),"+f"(d[42]),"+f"(d[43]),"+f"(d[44]),"+f"(d[45]),"+f"(d[46]),"+f"(d[47]),"+f"(d[48]),"+f"(d[49]),"+f"(d[50]),"+f"(d[51]),"+f"(d[52]),"+f"(d[53]),"+f"(d[54]),"+f"(d[55]),"+f"(d[56]),"+f"(d[57]),"+f"(d[58]),"+f"(d[59]),"+f"(d[60]),"+f"(d[61]),"+f"(d[62]),"+f"(d[63]),"+f"(d[64]),"+f"(d[65]),"+f"(d[66]),"+f"(d[67]),"+f"(d[68]),"+f"(d[69]),"+f"(d[70]),"+f"(d[71]),"+f"(d[72]),"+f"(d[73]),"+f"(d[74]),"+f"(d[75]),"+f"(d[76]),"+f"(d[77]),"+f"(d[78]),"+f"(d[79]),"+f"(d[80]),"+f"(d[81]),"+f"(d[82]),"+f"(d[83]),"+f"(d[84]),"+f"(d[85]),"+f"(d[86]),"+f"(d[87]),"+f"(d[88]),"+f"(d[89]),"+f"(d[90]),"+f"(d[91]),"+f"(d[92]),"+f"(d[93]),"+f"(d[94]),"+f"(d[95]) : "r"(da.lo), "r"(da.hi), "r"(db.lo), "r"(db.hi), "r"(sc));
}
template<> __device__ __forceinline__ void wgmma_ss<256>(float (&d)[128], Desc da, Desc db, int sc) {
  asm volatile("{\n.reg .pred p;\n.reg .b64 a, b;\nsetp.ne.b32 p, %132, 0;\nmov.b64 a, {%128, %129};\nmov.b64 b, {%130, %131};\n"
    "wgmma.mma_async.sync.aligned.m64n256k16.f32.bf16.bf16 {%0,%1,%2,%3,%4,%5,%6,%7,%8,%9,%10,%11,%12,%13,%14,%15,%16,%17,%18,%19,%20,%21,%22,%23,%24,%25,%26,%27,%28,%29,%30,%31,%32,%33,%34,%35,%36,%37,%38,%39,%40,%41,%42,%43,%44,%45,%46,%47,%48,%49,%50,%51,%52,%53,%54,%55,%56,%57,%58,%59,%60,%61,%62,%63,%64,%65,%66,%67,%68,%69,%70,%71,%72,%73,%74,%75,%76,%77,%78,%79,%80,%81,%82,%83,%84,%85,%86,%87,%88,%89,%90,%91,%92,%93,%94,%95,%96,%97,%98,%99,%100,%101,%102,%103,%104,%105,%106,%107,%108,%109,%110,%111,%112,%113,%114,%115,%116,%117,%118,%119,%120,%121,%122,%123,%124,%125,%126,%127}, a, b, p, 1, 1, 0, 1;\n}\n"
    : "+f"(d[0]),"+f"(d[1]),"+f"(d[2]),"+f"(d[3]),"+f"(d[4]),"+f"(d[5]),"+f"(d[6]),"+f"(d[7]),"+f"(d[8]),"+f"(d[9]),"+f"(d[10]),"+f"(d[11]),"+f"(d[12]),"+f"(d[13]),"+f"(d[14]),"+f"(d[15]),"+f"(d[16]),"+f"(d[17]),"+f"(d[18]),"+f"(d[19]),"+f"(d[20]),"+f"(d[21]),"+f"(d[22]),"+f"(d[23]),"+f"(d[24]),"+f"(d[25]),"+f"(d[26]),"+f"(d[27]),"+f"(d[28]),"+f"(d[29]),"+f"(d[30]),"+f"(d[31]),"+f"(d[32]),"+f"(d[33]),"+f"(d[34]),"+f"(d[35]),"+f"(d[36]),"+f"(d[37]),"+f"(d[38]),"+f"(d[39]),"+f"(d[40]),"+f"(d[41]),"+f"(d[42]),"+f"(d[43]),"+f"(d[44]),"+f"(d[45]),"+f"(d[46]),"+f"(d[47]),"+f"(d[48]),"+f"(d[49]),"+f"(d[50]),"+f"(d[51]),"+f"(d[52]),"+f"(d[53]),"+f"(d[54]),"+f"(d[55]),"+f"(d[56]),"+f"(d[57]),"+f"(d[58]),"+f"(d[59]),"+f"(d[60]),"+f"(d[61]),"+f"(d[62]),"+f"(d[63]),"+f"(d[64]),"+f"(d[65]),"+f"(d[66]),"+f"(d[67]),"+f"(d[68]),"+f"(d[69]),"+f"(d[70]),"+f"(d[71]),"+f"(d[72]),"+f"(d[73]),"+f"(d[74]),"+f"(d[75]),"+f"(d[76]),"+f"(d[77]),"+f"(d[78]),"+f"(d[79]),"+f"(d[80]),"+f"(d[81]),"+f"(d[82]),"+f"(d[83]),"+f"(d[84]),"+f"(d[85]),"+f"(d[86]),"+f"(d[87]),"+f"(d[88]),"+f"(d[89]),"+f"(d[90]),"+f"(d[91]),"+f"(d[92]),"+f"(d[93]),"+f"(d[94]),"+f"(d[95]),"+f"(d[96]),"+f"(d[97]),"+f"(d[98]),"+f"(d[99]),"+f"(d[100]),"+f"(d[101]),"+f"(d[102]),"+f"(d[103]),"+f"(d[104]),"+f"(d[105]),"+f"(d[106]),"+f"(d[107]),"+f"(d[108]),"+f"(d[109]),"+f"(d[110]),"+f"(d[111]),"+f"(d[112]),"+f"(d[113]),"+f"(d[114]),"+f"(d[115]),"+f"(d[116]),"+f"(d[117]),"+f"(d[118]),"+f"(d[119]),"+f"(d[120]),"+f"(d[121]),"+f"(d[122]),"+f"(d[123]),"+f"(d[124]),"+f"(d[125]),"+f"(d[126]),"+f"(d[127]) : "r"(da.lo), "r"(da.hi), "r"(db.lo), "r"(db.hi), "r"(sc));
}
template<int N, int ACC> __device__ __forceinline__ void wgmma_rs(float (&d)[N / 2], const uint4& a, Desc db);
template<> __device__ __forceinline__ void wgmma_rs<8, 1>(float (&d)[4], const uint4& a, Desc db) {
  asm volatile("{\n.reg .pred p;\n.reg .b64 b;\nsetp.ne.b32 p, 1, 0;\nmov.b64 b, {%8, %9};\n"
    "wgmma.mma_async.sync.aligned.m64n8k16.f32.bf16.bf16 {%0,%1,%2,%3}, {%4,%5,%6,%7}, b, p, 1, 1, 1;\n}\n"
    : "+f"(d[0]),"+f"(d[1]),"+f"(d[2]),"+f"(d[3]) : "r"(a.x), "r"(a.y), "r"(a.z), "r"(a.w), "r"(db.lo), "r"(db.hi));
}
template<> __device__ __forceinline__ void wgmma_rs<8, 0>(float (&d)[4], const uint4& a, Desc db) {
  asm volatile("{\n.reg .pred p;\n.reg .b64 b;\nsetp.ne.b32 p, 0, 0;\nmov.b64 b, {%8, %9};\n"
    "wgmma.mma_async.sync.aligned.m64n8k16.f32.bf16.bf16 {%0,%1,%2,%3}, {%4,%5,%6,%7}, b, p, 1, 1, 1;\n}\n"
    : "=f"(d[0]),"=f"(d[1]),"=f"(d[2]),"=f"(d[3]) : "r"(a.x), "r"(a.y), "r"(a.z), "r"(a.w), "r"(db.lo), "r"(db.hi));
}
template<> __device__ __forceinline__ void wgmma_rs<24, 1>(float (&d)[12], const uint4& a, Desc db) {
  asm volatile("{\n.reg .pred p;\n.reg .b64 b;\nsetp.ne.b32 p, 1, 0;\nmov.b64 b, {%16, %17};\n"
    "wgmma.mma_async.sync.aligned.m64n24k16.f32.bf16.bf16 {%0,%1,%2,%3,%4,%5,%6,%7,%8,%9,%10,%11}, {%12,%13,%14,%15}, b, p, 1, 1, 1;\n}\n"
    : "+f"(d[0]),"+f"(d[1]),"+f"(d[2]),"+f"(d[3]),"+f"(d[4]),"+f"(d[5]),"+f"(d[6]),"+f"(d[7]),"+f"(d[8]),"+f"(d[9]),"+f"(d[10]),"+f"(d[11]) : "r"(a.x), "r"(a.y), "r"(a.z), "r"(a.w), "r"(db.lo), "r"(db.hi));
}
template<> __device__ __forceinline__ void wgmma_rs<24, 0>(float (&d)[12], const uint4& a, Desc db) {
  asm volatile("{\n.reg .pred p;\n.reg .b64 b;\nsetp.ne.b32 p, 0, 0;\nmov.b64 b, {%16, %17};\n"
    "wgmma.mma_async.sync.aligned.m64n24k16.f32.bf16.bf16 {%0,%1,%2,%3,%4,%5,%6,%7,%8,%9,%10,%11}, {%12,%13,%14,%15}, b, p, 1, 1, 1;\n}\n"
    : "=f"(d[0]),"=f"(d[1]),"=f"(d[2]),"=f"(d[3]),"=f"(d[4]),"=f"(d[5]),"=f"(d[6]),"=f"(d[7]),"=f"(d[8]),"=f"(d[9]),"=f"(d[10]),"=f"(d[11]) : "r"(a.x), "r"(a.y), "r"(a.z), "r"(a.w), "r"(db.lo), "r"(db.hi));
}
template<> __device__ __forceinline__ void wgmma_rs<64, 1>(float (&d)[32], const uint4& a, Desc db) {
  asm volatile("{\n.reg .pred p;\n.reg .b64 b;\nsetp.ne.b32 p, 1, 0;\nmov.b64 b, {%36, %37};\n"
    "wgmma.mma_async.sync.aligned.m64n64k16.f32.bf16.bf16 {%0,%1,%2,%3,%4,%5,%6,%7,%8,%9,%10,%11,%12,%13,%14,%15,%16,%17,%18,%19,%20,%21,%22,%23,%24,%25,%26,%27,%28,%29,%30,%31}, {%32,%33,%34,%35}, b, p, 1, 1, 1;\n}\n"
    : "+f"(d[0]),"+f"(d[1]),"+f"(d[2]),"+f"(d[3]),"+f"(d[4]),"+f"(d[5]),"+f"(d[6]),"+f"(d[7]),"+f"(d[8]),"+f"(d[9]),"+f"(d[10]),"+f"(d[11]),"+f"(d[12]),"+f"(d[13]),"+f"(d[14]),"+f"(d[15]),"+f"(d[16]),"+f"(d[17]),"+f"(d[18]),"+f"(d[19]),"+f"(d[20]),"+f"(d[21]),"+f"(d[22]),"+f"(d[23]),"+f"(d[24]),"+f"(d[25]),"+f"(d[26]),"+f"(d[27]),"+f"(d[28]),"+f"(d[29]),"+f"(d[30]),"+f"(d[31]) : "r"(a.x), "r"(a.y), "r"(a.z), "r"(a.w), "r"(db.lo), "r"(db.hi));
}
template<> __device__ __forceinline__ void wgmma_rs<64, 0>(float (&d)[32], const uint4& a, Desc db) {
  asm volatile("{\n.reg .pred p;\n.reg .b64 b;\nsetp.ne.b32 p, 0, 0;\nmov.b64 b, {%36, %37};\n"
    "wgmma.mma_async.sync.aligned.m64n64k16.f32.bf16.bf16 {%0,%1,%2,%3,%4,%5,%6,%7,%8,%9,%10,%11,%12,%13,%14,%15,%16,%17,%18,%19,%20,%21,%22,%23,%24,%25,%26,%27,%28,%29,%30,%31}, {%32,%33,%34,%35}, b, p, 1, 1, 1;\n}\n"
    : "=f"(d[0]),"=f"(d[1]),"=f"(d[2]),"=f"(d[3]),"=f"(d[4]),"=f"(d[5]),"=f"(d[6]),"=f"(d[7]),"=f"(d[8]),"=f"(d[9]),"=f"(d[10]),"=f"(d[11]),"=f"(d[12]),"=f"(d[13]),"=f"(d[14]),"=f"(d[15]),"=f"(d[16]),"=f"(d[17]),"=f"(d[18]),"=f"(d[19]),"=f"(d[20]),"=f"(d[21]),"=f"(d[22]),"=f"(d[23]),"=f"(d[24]),"=f"(d[25]),"=f"(d[26]),"=f"(d[27]),"=f"(d[28]),"=f"(d[29]),"=f"(d[30]),"=f"(d[31]) : "r"(a.x), "r"(a.y), "r"(a.z), "r"(a.w), "r"(db.lo), "r"(db.hi));
}
template<> __device__ __forceinline__ void wgmma_rs<72, 1>(float (&d)[36], const uint4& a, Desc db) {
  asm volatile("{\n.reg .pred p;\n.reg .b64 b;\nsetp.ne.b32 p, 1, 0;\nmov.b64 b, {%40, %41};\n"
    "wgmma.mma_async.sync.aligned.m64n72k16.f32.bf16.bf16 {%0,%1,%2,%3,%4,%5,%6,%7,%8,%9,%10,%11,%12,%13,%14,%15,%16,%17,%18,%19,%20,%21,%22,%23,%24,%25,%26,%27,%28,%29,%30,%31,%32,%33,%34,%35}, {%36,%37,%38,%39}, b, p, 1, 1, 1;\n}\n"
    : "+f"(d[0]),"+f"(d[1]),"+f"(d[2]),"+f"(d[3]),"+f"(d[4]),"+f"(d[5]),"+f"(d[6]),"+f"(d[7]),"+f"(d[8]),"+f"(d[9]),"+f"(d[10]),"+f"(d[11]),"+f"(d[12]),"+f"(d[13]),"+f"(d[14]),"+f"(d[15]),"+f"(d[16]),"+f"(d[17]),"+f"(d[18]),"+f"(d[19]),"+f"(d[20]),"+f"(d[21]),"+f"(d[22]),"+f"(d[23]),"+f"(d[24]),"+f"(d[25]),"+f"(d[26]),"+f"(d[27]),"+f"(d[28]),"+f"(d[29]),"+f"(d[30]),"+f"(d[31]),"+f"(d[32]),"+f"(d[33]),"+f"(d[34]),"+f"(d[35]) : "r"(a.x), "r"(a.y), "r"(a.z), "r"(a.w), "r"(db.lo), "r"(db.hi));
}
template<> __device__ __forceinline__ void wgmma_rs<72, 0>(float (&d)[36], const uint4& a, Desc db) {
  asm volatile("{\n.reg .pred p;\n.reg .b64 b;\nsetp.ne.b32 p, 0, 0;\nmov.b64 b, {%40, %41};\n"
    "wgmma.mma_async.sync.aligned.m64n72k16.f32.bf16.bf16 {%0,%1,%2,%3,%4,%5,%6,%7,%8,%9,%10,%11,%12,%13,%14,%15,%16,%17,%18,%19,%20,%21,%22,%23,%24,%25,%26,%27,%28,%29,%30,%31,%32,%33,%34,%35}, {%36,%37,%38,%39}, b, p, 1, 1, 1;\n}\n"
    : "=f"(d[0]),"=f"(d[1]),"=f"(d[2]),"=f"(d[3]),"=f"(d[4]),"=f"(d[5]),"=f"(d[6]),"=f"(d[7]),"=f"(d[8]),"=f"(d[9]),"=f"(d[10]),"=f"(d[11]),"=f"(d[12]),"=f"(d[13]),"=f"(d[14]),"=f"(d[15]),"=f"(d[16]),"=f"(d[17]),"=f"(d[18]),"=f"(d[19]),"=f"(d[20]),"=f"(d[21]),"=f"(d[22]),"=f"(d[23]),"=f"(d[24]),"=f"(d[25]),"=f"(d[26]),"=f"(d[27]),"=f"(d[28]),"=f"(d[29]),"=f"(d[30]),"=f"(d[31]),"=f"(d[32]),"=f"(d[33]),"=f"(d[34]),"=f"(d[35]) : "r"(a.x), "r"(a.y), "r"(a.z), "r"(a.w), "r"(db.lo), "r"(db.hi));
}
template<> __device__ __forceinline__ void wgmma_rs<192, 1>(float (&d)[96], const uint4& a, Desc db) {
  asm volatile("{\n.reg .pred p;\n.reg .b64 b;\nsetp.ne.b32 p, 1, 0;\nmov.b64 b, {%100, %101};\n"
    "wgmma.mma_async.sync.aligned.m64n192k16.f32.bf16.bf16 {%0,%1,%2,%3,%4,%5,%6,%7,%8,%9,%10,%11,%12,%13,%14,%15,%16,%17,%18,%19,%20,%21,%22,%23,%24,%25,%26,%27,%28,%29,%30,%31,%32,%33,%34,%35,%36,%37,%38,%39,%40,%41,%42,%43,%44,%45,%46,%47,%48,%49,%50,%51,%52,%53,%54,%55,%56,%57,%58,%59,%60,%61,%62,%63,%64,%65,%66,%67,%68,%69,%70,%71,%72,%73,%74,%75,%76,%77,%78,%79,%80,%81,%82,%83,%84,%85,%86,%87,%88,%89,%90,%91,%92,%93,%94,%95}, {%96,%97,%98,%99}, b, p, 1, 1, 1;\n}\n"
    : "+f"(d[0]),"+f"(d[1]),"+f"(d[2]),"+f"(d[3]),"+f"(d[4]),"+f"(d[5]),"+f"(d[6]),"+f"(d[7]),"+f"(d[8]),"+f"(d[9]),"+f"(d[10]),"+f"(d[11]),"+f"(d[12]),"+f"(d[13]),"+f"(d[14]),"+f"(d[15]),"+f"(d[16]),"+f"(d[17]),"+f"(d[18]),"+f"(d[19]),"+f"(d[20]),"+f"(d[21]),"+f"(d[22]),"+f"(d[23]),"+f"(d[24]),"+f"(d[25]),"+f"(d[26]),"+f"(d[27]),"+f"(d[28]),"+f"(d[29]),"+f"(d[30]),"+f"(d[31]),"+f"(d[32]),"+f"(d[33]),"+f"(d[34]),"+f"(d[35]),"+f"(d[36]),"+f"(d[37]),"+f"(d[38]),"+f"(d[39]),"+f"(d[40]),"+f"(d[41]),"+f"(d[42]),"+f"(d[43]),"+f"(d[44]),"+f"(d[45]),"+f"(d[46]),"+f"(d[47]),"+f"(d[48]),"+f"(d[49]),"+f"(d[50]),"+f"(d[51]),"+f"(d[52]),"+f"(d[53]),"+f"(d[54]),"+f"(d[55]),"+f"(d[56]),"+f"(d[57]),"+f"(d[58]),"+f"(d[59]),"+f"(d[60]),"+f"(d[61]),"+f"(d[62]),"+f"(d[63]),"+f"(d[64]),"+f"(d[65]),"+f"(d[66]),"+f"(d[67]),"+f"(d[68]),"+f"(d[69]),"+f"(d[70]),"+f"(d[71]),"+f"(d[72]),"+f"(d[73]),"+f"(d[74]),"+f"(d[75]),"+f"(d[76]),"+f"(d[77]),"+f"(d[78]),"+f"(d[79]),"+f"(d[80]),"+f"(d[81]),"+f"(d[82]),"+f"(d[83]),"+f"(d[84]),"+f"(d[85]),"+f"(d[86]),"+f"(d[87]),"+f"(d[88]),"+f"(d[89]),"+f"(d[90]),"+f"(d[91]),"+f"(d[92]),"+f"(d[93]),"+f"(d[94]),"+f"(d[95]) : "r"(a.x), "r"(a.y), "r"(a.z), "r"(a.w), "r"(db.lo), "r"(db.hi));
}
template<> __device__ __forceinline__ void wgmma_rs<192, 0>(float (&d)[96], const uint4& a, Desc db) {
  asm volatile("{\n.reg .pred p;\n.reg .b64 b;\nsetp.ne.b32 p, 0, 0;\nmov.b64 b, {%100, %101};\n"
    "wgmma.mma_async.sync.aligned.m64n192k16.f32.bf16.bf16 {%0,%1,%2,%3,%4,%5,%6,%7,%8,%9,%10,%11,%12,%13,%14,%15,%16,%17,%18,%19,%20,%21,%22,%23,%24,%25,%26,%27,%28,%29,%30,%31,%32,%33,%34,%35,%36,%37,%38,%39,%40,%41,%42,%43,%44,%45,%46,%47,%48,%49,%50,%51,%52,%53,%54,%55,%56,%57,%58,%59,%60,%61,%62,%63,%64,%65,%66,%67,%68,%69,%70,%71,%72,%73,%74,%75,%76,%77,%78,%79,%80,%81,%82,%83,%84,%85,%86,%87,%88,%89,%90,%91,%92,%93,%94,%95}, {%96,%97,%98,%99}, b, p, 1, 1, 1;\n}\n"
    : "=f"(d[0]),"=f"(d[1]),"=f"(d[2]),"=f"(d[3]),"=f"(d[4]),"=f"(d[5]),"=f"(d[6]),"=f"(d[7]),"=f"(d[8]),"=f"(d[9]),"=f"(d[10]),"=f"(d[11]),"=f"(d[12]),"=f"(d[13]),"=f"(d[14]),"=f"(d[15]),"=f"(d[16]),"=f"(d[17]),"=f"(d[18]),"=f"(d[19]),"=f"(d[20]),"=f"(d[21]),"=f"(d[22]),"=f"(d[23]),"=f"(d[24]),"=f"(d[25]),"=f"(d[26]),"=f"(d[27]),"=f"(d[28]),"=f"(d[29]),"=f"(d[30]),"=f"(d[31]),"=f"(d[32]),"=f"(d[33]),"=f"(d[34]),"=f"(d[35]),"=f"(d[36]),"=f"(d[37]),"=f"(d[38]),"=f"(d[39]),"=f"(d[40]),"=f"(d[41]),"=f"(d[42]),"=f"(d[43]),"=f"(d[44]),"=f"(d[45]),"=f"(d[46]),"=f"(d[47]),"=f"(d[48]),"=f"(d[49]),"=f"(d[50]),"=f"(d[51]),"=f"(d[52]),"=f"(d[53]),"=f"(d[54]),"=f"(d[55]),"=f"(d[56]),"=f"(d[57]),"=f"(d[58]),"=f"(d[59]),"=f"(d[60]),"=f"(d[61]),"=f"(d[62]),"=f"(d[63]),"=f"(d[64]),"=f"(d[65]),"=f"(d[66]),"=f"(d[67]),"=f"(d[68]),"=f"(d[69]),"=f"(d[70]),"=f"(d[71]),"=f"(d[72]),"=f"(d[73]),"=f"(d[74]),"=f"(d[75]),"=f"(d[76]),"=f"(d[77]),"=f"(d[78]),"=f"(d[79]),"=f"(d[80]),"=f"(d[81]),"=f"(d[82]),"=f"(d[83]),"=f"(d[84]),"=f"(d[85]),"=f"(d[86]),"=f"(d[87]),"=f"(d[88]),"=f"(d[89]),"=f"(d[90]),"=f"(d[91]),"=f"(d[92]),"=f"(d[93]),"=f"(d[94]),"=f"(d[95]) : "r"(a.x), "r"(a.y), "r"(a.z), "r"(a.w), "r"(db.lo), "r"(db.hi));
}
template<> __device__ __forceinline__ void wgmma_rs<256, 1>(float (&d)[128], const uint4& a, Desc db) {
  asm volatile("{\n.reg .pred p;\n.reg .b64 b;\nsetp.ne.b32 p, 1, 0;\nmov.b64 b, {%132, %133};\n"
    "wgmma.mma_async.sync.aligned.m64n256k16.f32.bf16.bf16 {%0,%1,%2,%3,%4,%5,%6,%7,%8,%9,%10,%11,%12,%13,%14,%15,%16,%17,%18,%19,%20,%21,%22,%23,%24,%25,%26,%27,%28,%29,%30,%31,%32,%33,%34,%35,%36,%37,%38,%39,%40,%41,%42,%43,%44,%45,%46,%47,%48,%49,%50,%51,%52,%53,%54,%55,%56,%57,%58,%59,%60,%61,%62,%63,%64,%65,%66,%67,%68,%69,%70,%71,%72,%73,%74,%75,%76,%77,%78,%79,%80,%81,%82,%83,%84,%85,%86,%87,%88,%89,%90,%91,%92,%93,%94,%95,%96,%97,%98,%99,%100,%101,%102,%103,%104,%105,%106,%107,%108,%109,%110,%111,%112,%113,%114,%115,%116,%117,%118,%119,%120,%121,%122,%123,%124,%125,%126,%127}, {%128,%129,%130,%131}, b, p, 1, 1, 1;\n}\n"
    : "+f"(d[0]),"+f"(d[1]),"+f"(d[2]),"+f"(d[3]),"+f"(d[4]),"+f"(d[5]),"+f"(d[6]),"+f"(d[7]),"+f"(d[8]),"+f"(d[9]),"+f"(d[10]),"+f"(d[11]),"+f"(d[12]),"+f"(d[13]),"+f"(d[14]),"+f"(d[15]),"+f"(d[16]),"+f"(d[17]),"+f"(d[18]),"+f"(d[19]),"+f"(d[20]),"+f"(d[21]),"+f"(d[22]),"+f"(d[23]),"+f"(d[24]),"+f"(d[25]),"+f"(d[26]),"+f"(d[27]),"+f"(d[28]),"+f"(d[29]),"+f"(d[30]),"+f"(d[31]),"+f"(d[32]),"+f"(d[33]),"+f"(d[34]),"+f"(d[35]),"+f"(d[36]),"+f"(d[37]),"+f"(d[38]),"+f"(d[39]),"+f"(d[40]),"+f"(d[41]),"+f"(d[42]),"+f"(d[43]),"+f"(d[44]),"+f"(d[45]),"+f"(d[46]),"+f"(d[47]),"+f"(d[48]),"+f"(d[49]),"+f"(d[50]),"+f"(d[51]),"+f"(d[52]),"+f"(d[53]),"+f"(d[54]),"+f"(d[55]),"+f"(d[56]),"+f"(d[57]),"+f"(d[58]),"+f"(d[59]),"+f"(d[60]),"+f"(d[61]),"+f"(d[62]),"+f"(d[63]),"+f"(d[64]),"+f"(d[65]),"+f"(d[66]),"+f"(d[67]),"+f"(d[68]),"+f"(d[69]),"+f"(d[70]),"+f"(d[71]),"+f"(d[72]),"+f"(d[73]),"+f"(d[74]),"+f"(d[75]),"+f"(d[76]),"+f"(d[77]),"+f"(d[78]),"+f"(d[79]),"+f"(d[80]),"+f"(d[81]),"+f"(d[82]),"+f"(d[83]),"+f"(d[84]),"+f"(d[85]),"+f"(d[86]),"+f"(d[87]),"+f"(d[88]),"+f"(d[89]),"+f"(d[90]),"+f"(d[91]),"+f"(d[92]),"+f"(d[93]),"+f"(d[94]),"+f"(d[95]),"+f"(d[96]),"+f"(d[97]),"+f"(d[98]),"+f"(d[99]),"+f"(d[100]),"+f"(d[101]),"+f"(d[102]),"+f"(d[103]),"+f"(d[104]),"+f"(d[105]),"+f"(d[106]),"+f"(d[107]),"+f"(d[108]),"+f"(d[109]),"+f"(d[110]),"+f"(d[111]),"+f"(d[112]),"+f"(d[113]),"+f"(d[114]),"+f"(d[115]),"+f"(d[116]),"+f"(d[117]),"+f"(d[118]),"+f"(d[119]),"+f"(d[120]),"+f"(d[121]),"+f"(d[122]),"+f"(d[123]),"+f"(d[124]),"+f"(d[125]),"+f"(d[126]),"+f"(d[127]) : "r"(a.x), "r"(a.y), "r"(a.z), "r"(a.w), "r"(db.lo), "r"(db.hi));
}
template<> __device__ __forceinline__ void wgmma_rs<256, 0>(float (&d)[128], const uint4& a, Desc db) {
  asm volatile("{\n.reg .pred p;\n.reg .b64 b;\nsetp.ne.b32 p, 0, 0;\nmov.b64 b, {%132, %133};\n"
    "wgmma.mma_async.sync.aligned.m64n256k16.f32.bf16.bf16 {%0,%1,%2,%3,%4,%5,%6,%7,%8,%9,%10,%11,%12,%13,%14,%15,%16,%17,%18,%19,%20,%21,%22,%23,%24,%25,%26,%27,%28,%29,%30,%31,%32,%33,%34,%35,%36,%37,%38,%39,%40,%41,%42,%43,%44,%45,%46,%47,%48,%49,%50,%51,%52,%53,%54,%55,%56,%57,%58,%59,%60,%61,%62,%63,%64,%65,%66,%67,%68,%69,%70,%71,%72,%73,%74,%75,%76,%77,%78,%79,%80,%81,%82,%83,%84,%85,%86,%87,%88,%89,%90,%91,%92,%93,%94,%95,%96,%97,%98,%99,%100,%101,%102,%103,%104,%105,%106,%107,%108,%109,%110,%111,%112,%113,%114,%115,%116,%117,%118,%119,%120,%121,%122,%123,%124,%125,%126,%127}, {%128,%129,%130,%131}, b, p, 1, 1, 1;\n}\n"
    : "=f"(d[0]),"=f"(d[1]),"=f"(d[2]),"=f"(d[3]),"=f"(d[4]),"=f"(d[5]),"=f"(d[6]),"=f"(d[7]),"=f"(d[8]),"=f"(d[9]),"=f"(d[10]),"=f"(d[11]),"=f"(d[12]),"=f"(d[13]),"=f"(d[14]),"=f"(d[15]),"=f"(d[16]),"=f"(d[17]),"=f"(d[18]),"=f"(d[19]),"=f"(d[20]),"=f"(d[21]),"=f"(d[22]),"=f"(d[23]),"=f"(d[24]),"=f"(d[25]),"=f"(d[26]),"=f"(d[27]),"=f"(d[28]),"=f"(d[29]),"=f"(d[30]),"=f"(d[31]),"=f"(d[32]),"=f"(d[33]),"=f"(d[34]),"=f"(d[35]),"=f"(d[36]),"=f"(d[37]),"=f"(d[38]),"=f"(d[39]),"=f"(d[40]),"=f"(d[41]),"=f"(d[42]),"=f"(d[43]),"=f"(d[44]),"=f"(d[45]),"=f"(d[46]),"=f"(d[47]),"=f"(d[48]),"=f"(d[49]),"=f"(d[50]),"=f"(d[51]),"=f"(d[52]),"=f"(d[53]),"=f"(d[54]),"=f"(d[55]),"=f"(d[56]),"=f"(d[57]),"=f"(d[58]),"=f"(d[59]),"=f"(d[60]),"=f"(d[61]),"=f"(d[62]),"=f"(d[63]),"=f"(d[64]),"=f"(d[65]),"=f"(d[66]),"=f"(d[67]),"=f"(d[68]),"=f"(d[69]),"=f"(d[70]),"=f"(d[71]),"=f"(d[72]),"=f"(d[73]),"=f"(d[74]),"=f"(d[75]),"=f"(d[76]),"=f"(d[77]),"=f"(d[78]),"=f"(d[79]),"=f"(d[80]),"=f"(d[81]),"=f"(d[82]),"=f"(d[83]),"=f"(d[84]),"=f"(d[85]),"=f"(d[86]),"=f"(d[87]),"=f"(d[88]),"=f"(d[89]),"=f"(d[90]),"=f"(d[91]),"=f"(d[92]),"=f"(d[93]),"=f"(d[94]),"=f"(d[95]),"=f"(d[96]),"=f"(d[97]),"=f"(d[98]),"=f"(d[99]),"=f"(d[100]),"=f"(d[101]),"=f"(d[102]),"=f"(d[103]),"=f"(d[104]),"=f"(d[105]),"=f"(d[106]),"=f"(d[107]),"=f"(d[108]),"=f"(d[109]),"=f"(d[110]),"=f"(d[111]),"=f"(d[112]),"=f"(d[113]),"=f"(d[114]),"=f"(d[115]),"=f"(d[116]),"=f"(d[117]),"=f"(d[118]),"=f"(d[119]),"=f"(d[120]),"=f"(d[121]),"=f"(d[122]),"=f"(d[123]),"=f"(d[124]),"=f"(d[125]),"=f"(d[126]),"=f"(d[127]) : "r"(a.x), "r"(a.y), "r"(a.z), "r"(a.w), "r"(db.lo), "r"(db.hi));
}
template<int N> __device__ __forceinline__ void wgmma_ra(float (&d)[N / 2], const uint4& a, Desc db, bool acc) {
  if (acc) wgmma_rs<N, 1>(d, a, db); else wgmma_rs<N, 0>(d, a, db);
}

__device__ __forceinline__ uint32_t smem_u32(const void* p) { return (uint32_t)__cvta_generic_to_shared(p); }
__device__ __forceinline__ void mbar_init(uint32_t bar, uint32_t cnt) { asm volatile("mbarrier.init.shared::cta.b64 [%0], %1;" ::"r"(bar), "r"(cnt)); }
__device__ __forceinline__ void mbar_expect_tx(uint32_t bar, uint32_t bytes) { asm volatile("mbarrier.arrive.expect_tx.shared::cta.b64 _, [%0], %1;" ::"r"(bar), "r"(bytes) : "memory"); }
__device__ __forceinline__ void mbar_arrive(uint32_t bar) { asm volatile("mbarrier.arrive.shared::cta.b64 _, [%0];" ::"r"(bar) : "memory"); }
__device__ __forceinline__ void mbar_arrive_remote(uint32_t rbar) { asm volatile("mbarrier.arrive.shared::cluster.b64 _, [%0];" ::"r"(rbar) : "memory"); }
__device__ __forceinline__ void mbar_wait(uint32_t bar, uint32_t parity) {
  asm volatile(
      "{\n.reg .pred p;\n.reg .u32 c;\nmov.u32 c, 0;\nLAB_WAIT:\nmbarrier.try_wait.parity.shared::cta.b64 p, [%0], %1;\n@p bra DONE;\n"
      "add.u32 c, c, 1;\nsetp.lt.u32 p, c, 1000000;\n@p bra LAB_WAIT;\ntrap;\nDONE:\n}\n" ::"r"(bar), "r"(parity) : "memory");
}
__device__ __forceinline__ void mbar_wait_c(uint32_t bar, uint32_t parity) {
  asm volatile("{\n.reg .pred p;\nLAB_WAIT:\nmbarrier.try_wait.parity.shared::cta.b64 p, [%0], %1;\n@!p bra LAB_WAIT;\n}\n" ::"r"(bar), "r"(parity) : "memory");
}
__device__ __forceinline__ uint32_t late(uint32_t bar, uint32_t v) {
  uint32_t r;
  asm volatile("{\n.reg .pred p;\nmbarrier.test_wait.parity.shared::cta.b64 p, [%1], 0;\nselp.b32 %0, %2, %1, p;\n}\n" : "=r"(r) : "r"(bar), "r"(v) : "memory");
  return r;
}
__device__ __forceinline__ void wtma2d(uint32_t dst, const CUtensorMap* m, int c0, int c1, uint32_t bar, uint64_t pol) {
  asm volatile("cp.async.bulk.tensor.2d.shared::cluster.global.mbarrier::complete_tx::bytes.multicast::cluster.L2::cache_hint [%0], [%1, {%3, %4}], [%2], %5, %6;"
               ::"r"(dst), "l"(m), "r"(bar), "r"(c0), "r"(c1), "h"((uint16_t)3), "l"(pol) : "memory");
}
__device__ __forceinline__ void wtma3d(uint32_t dst, const CUtensorMap* m, int c0, int c1, int c2, uint32_t bar, uint64_t pol) {
  asm volatile("cp.async.bulk.tensor.3d.shared::cluster.global.mbarrier::complete_tx::bytes.multicast::cluster.L2::cache_hint [%0], [%1, {%3, %4, %5}], [%2], %6, %7;"
               ::"r"(dst), "l"(m), "r"(bar), "r"(c0), "r"(c1), "r"(c2), "h"((uint16_t)3), "l"(pol) : "memory");
}
__device__ __forceinline__ void wbulk(uint32_t dst, const void* src, uint32_t bytes, uint32_t bar, uint64_t pol) {
  asm volatile("cp.async.bulk.shared::cluster.global.mbarrier::complete_tx::bytes.multicast::cluster.L2::cache_hint [%0], [%1], %2, [%3], %4, %5;"
               ::"r"(dst), "l"(src), "r"(bytes), "r"(bar), "h"((uint16_t)3), "l"(pol) : "memory");
}
__device__ __forceinline__ void tma3d(uint32_t dst, const CUtensorMap* m, int c0, int c1, int c2, uint32_t bar) {
  asm volatile("cp.async.bulk.tensor.3d.shared::cluster.global.mbarrier::complete_tx::bytes [%0], [%1, {%3, %4, %5}], [%2];"
               ::"r"(dst), "l"(m), "r"(bar), "r"(c0), "r"(c1), "r"(c2) : "memory");
}
__device__ __forceinline__ void prefetch_l2(const void* p, uint32_t bytes) { asm volatile("cp.async.bulk.prefetch.L2.global [%0], %1;" ::"l"(p), "r"(bytes) : "memory"); }
__device__ __forceinline__ uint64_t policy_evict_first() { uint64_t p; asm volatile("createpolicy.fractional.L2::evict_first.b64 %0, 1.0;" : "=l"(p)); return p; }
__device__ __forceinline__ uint64_t policy_evict_normal() { uint64_t p; asm volatile("createpolicy.fractional.L2::evict_normal.b64 %0, 1.0;" : "=l"(p)); return p; }
__device__ __forceinline__ void fence_async_smem() { asm volatile("fence.proxy.async.shared::cta;" ::: "memory"); }
__device__ __forceinline__ bool elect_one() {
  uint32_t p;
  asm volatile("{\n.reg .pred P;\nelect.sync _|P, 0xffffffff;\nselp.u32 %0, 1, 0, P;\n}\n" : "=r"(p));
  return p;
}
__device__ __forceinline__ void wg_fence() { asm volatile("wgmma.fence.sync.aligned;" ::: "memory"); }
__device__ __forceinline__ void wg_commit() { asm volatile("wgmma.commit_group.sync.aligned;" ::: "memory"); }
template <int n> __device__ __forceinline__ void wg_wait() { asm volatile("wgmma.wait_group.sync.aligned %0;" ::"n"(n) : "memory"); }
__device__ __forceinline__ void wg_bar(int w) { asm volatile("bar.sync %0, 128;" ::"r"(w + 1) : "memory"); }
__device__ __forceinline__ void fence_gpu() { asm volatile("fence.acq_rel.gpu;" ::: "memory"); }
__device__ __forceinline__ uint32_t ld_relaxed(const uint32_t* p) { uint32_t v; asm volatile("ld.relaxed.gpu.global.u32 %0, [%1];" : "=r"(v) : "l"(p) : "memory"); return v; }
__device__ __forceinline__ uint32_t ld_acquire(const uint32_t* p) { uint32_t v; asm volatile("ld.acquire.gpu.global.u32 %0, [%1];" : "=r"(v) : "l"(p) : "memory"); return v; }
__device__ __forceinline__ uint4 ld_relaxed4(const uint4* p) {
  uint4 v; asm volatile("ld.relaxed.gpu.global.v4.u32 {%0,%1,%2,%3}, [%4];" : "=r"(v.x), "=r"(v.y), "=r"(v.z), "=r"(v.w) : "l"(p) : "memory"); return v;
}
__device__ __forceinline__ uint2 ld_relaxed2(const uint2* p) {
  uint2 v; asm volatile("ld.relaxed.gpu.global.v2.u32 {%0,%1}, [%2];" : "=r"(v.x), "=r"(v.y) : "l"(p) : "memory"); return v;
}
__device__ __forceinline__ void st_relaxed(uint32_t* p, uint32_t a) { asm volatile("st.relaxed.gpu.global.u32 [%0], %1;" ::"l"(p), "r"(a) : "memory"); }
__device__ __forceinline__ void st_relaxed4(uint4* p, uint32_t a, uint32_t b, uint32_t c, uint32_t d) {
  asm volatile("st.relaxed.gpu.global.v4.u32 [%0], {%1,%2,%3,%4};" ::"l"(p), "r"(a), "r"(b), "r"(c), "r"(d) : "memory");
}
__device__ __forceinline__ void st_relaxed2(uint2* p, uint32_t a, uint32_t b) {
  asm volatile("st.relaxed.gpu.global.v2.u32 [%0], {%1,%2};" ::"l"(p), "r"(a), "r"(b) : "memory");
}
__device__ __forceinline__ void red4(uint4* p, uint32_t a, uint32_t b, uint32_t c, uint32_t d) {
  asm volatile("red.relaxed.gpu.global.add.noftz.v4.bf16x2 [%0], {%1,%2,%3,%4};" ::"l"(p), "r"(a), "r"(b), "r"(c), "r"(d) : "memory");
}
__device__ __forceinline__ void red2(uint2* p, uint32_t a, uint32_t b) {
  asm volatile("red.relaxed.gpu.global.add.noftz.v2.bf16x2 [%0], {%1,%2};" ::"l"(p), "r"(a), "r"(b) : "memory");
}
constexpr int SPIN_MAX = 1 << 21;
__device__ __forceinline__ uint32_t pack_bf16(float lo, float hi) { uint32_t r; asm("cvt.rn.bf16x2.f32 %0, %1, %2;" : "=r"(r) : "f"(hi), "f"(lo)); return r; }
__device__ __forceinline__ float bf_lo(uint32_t v) { return __uint_as_float(v << 16); }
__device__ __forceinline__ float bf_hi(uint32_t v) { return __uint_as_float(v & 0xffff0000u); }
__device__ __forceinline__ float2 lds64(uint32_t a) { float2 v; asm volatile("ld.shared.v2.f32 {%0,%1}, [%2];" : "=f"(v.x), "=f"(v.y) : "r"(a)); return v; }
__device__ __forceinline__ void sts64f(uint32_t a, float x, float y) { asm volatile("st.shared.v2.f32 [%0], {%1,%2};" ::"r"(a), "f"(x), "f"(y) : "memory"); }
__device__ __forceinline__ void sts32(uint32_t a, uint32_t x) { asm volatile("st.volatile.shared.b32 [%0], %1;" ::"r"(a), "r"(x) : "memory"); }
__device__ __forceinline__ void gate(uint32_t a, int need) {
#pragma unroll 1
  for (int it = 0; it < SPIN_MAX; it++) {
    int v; asm volatile("ld.volatile.shared.b32 %0, [%1];" : "=r"(v) : "r"(a) : "memory");
    if (v >= need) break;
    __nanosleep(200);
  }
}
__device__ __forceinline__ void sts128(uint32_t a, uint32_t x, uint32_t y, uint32_t z, uint32_t u) { asm volatile("st.shared.v4.b32 [%0], {%1,%2,%3,%4};" ::"r"(a), "r"(x), "r"(y), "r"(z), "r"(u) : "memory"); }
__device__ __forceinline__ uint4 lds128(uint32_t a) { uint4 v; asm volatile("ld.shared.v4.u32 {%0,%1,%2,%3}, [%4];" : "=r"(v.x), "=r"(v.y), "=r"(v.z), "=r"(v.w) : "r"(a) : "memory"); return v; }
__device__ __forceinline__ uint32_t hmul2(uint32_t a, uint32_t b) { uint32_t r; asm("mul.rn.bf16x2 %0, %1, %2;" : "=r"(r) : "r"(a), "r"(b)); return r; }
__device__ __forceinline__ uint32_t hadd2(uint32_t a, uint32_t b) { uint32_t r; asm("add.rn.bf16x2 %0, %1, %2;" : "=r"(r) : "r"(a), "r"(b)); return r; }
__device__ __forceinline__ void stsm4(uint32_t a, uint32_t r0, uint32_t r1, uint32_t r2, uint32_t r3) {
  asm volatile("stmatrix.sync.aligned.m8n8.x4.shared.b16 [%0], {%1,%2,%3,%4};" ::"r"(a), "r"(r0), "r"(r1), "r"(r2), "r"(r3) : "memory");
}
__device__ __forceinline__ void stsm2(uint32_t a, uint32_t r0, uint32_t r1) {
  asm volatile("stmatrix.sync.aligned.m8n8.x2.shared.b16 [%0], {%1,%2};" ::"r"(a), "r"(r0), "r"(r1) : "memory");
}
__device__ __forceinline__ uint4 ldsm4(uint32_t a) {
  uint4 r; asm volatile("ldmatrix.sync.aligned.m8n8.x4.shared.b16 {%0,%1,%2,%3}, [%4];" : "=r"(r.x), "=r"(r.y), "=r"(r.z), "=r"(r.w) : "r"(a) : "memory"); return r;
}
__device__ __forceinline__ uint32_t movm(uint32_t a) { uint32_t r; asm("movmatrix.sync.aligned.m8n8.trans.b16 %0, %1;" : "=r"(r) : "r"(a)); return r; }
__device__ __forceinline__ void mma16816z(float (&d)[4], uint32_t a0, uint32_t a1, uint32_t a2, uint32_t a3, uint32_t b0, uint32_t b1) {
  asm("mma.sync.aligned.m16n8k16.row.col.f32.bf16.bf16.f32 {%0,%1,%2,%3}, {%4,%5,%6,%7}, {%8,%9}, {%10,%10,%10,%10};"
      : "=f"(d[0]), "=f"(d[1]), "=f"(d[2]), "=f"(d[3]) : "r"(a0), "r"(a1), "r"(a2), "r"(a3), "r"(b0), "r"(b1), "f"(0.f));
}
__device__ __forceinline__ void mma16816(float (&d)[4], const uint4& a, uint32_t b0, uint32_t b1) {
  asm("mma.sync.aligned.m16n8k16.row.col.f32.bf16.bf16.f32 {%0,%1,%2,%3}, {%4,%5,%6,%7}, {%8,%9}, {%0,%1,%2,%3};"
      : "+f"(d[0]), "+f"(d[1]), "+f"(d[2]), "+f"(d[3]) : "r"(a.x), "r"(a.y), "r"(a.z), "r"(a.w), "r"(b0), "r"(b1));
}
__device__ __forceinline__ void mma1688(float (&d)[4], uint32_t a0, uint32_t a1, uint32_t b0) {
  asm("mma.sync.aligned.m16n8k8.row.col.f32.bf16.bf16.f32 {%0,%1,%2,%3}, {%4,%5}, {%6}, {%0,%1,%2,%3};"
      : "+f"(d[0]), "+f"(d[1]), "+f"(d[2]), "+f"(d[3]) : "r"(a0), "r"(a1), "r"(b0));
}
__device__ __forceinline__ float quad_sum(float v) { v += __shfl_xor_sync(0xffffffffu, v, 1); v += __shfl_xor_sync(0xffffffffu, v, 2); return v; }
__device__ __forceinline__ float rcp(float x) { float r; asm("rcp.approx.ftz.f32 %0, %1;" : "=f"(r) : "f"(x)); return r; }
__device__ __forceinline__ float rsq(float x) { float r; asm("rsqrt.approx.ftz.f32 %0, %1;" : "=f"(r) : "f"(x)); return r; }
__device__ __forceinline__ float ex2(float x) { float r; asm("ex2.approx.ftz.f32 %0, %1;" : "=f"(r) : "f"(x)); return r; }
__device__ __forceinline__ uint32_t chk(uint32_t acc, uint32_t v, uint32_t tag) { uint32_t r; asm("lop3.b32 %0, %1, %2, %3, 0xF6;" : "=r"(r) : "r"(acc), "r"(v), "r"(tag)); return r; }
__device__ __forceinline__ uint32_t chk2(uint32_t a, uint32_t b, uint32_t tag) { uint32_t r; asm("lop3.b32 %0, %1, %2, %3, 0x7E;" : "=r"(r) : "r"(a), "r"(b), "r"(tag)); return r; }
__device__ __forceinline__ uint32_t tagged(uint32_t v, uint32_t tag) { return (v & ~1u) | tag; }

__device__ __forceinline__ int group_k0(int g, int j) {
  const int h = g >= 9, r = g - 2 - 7 * h;
  return g < 2 ? 64 * j + 32 * g : g < 16 ? 64 * (r + (r >= j)) + 32 * h : 32 * g;
}
__device__ __forceinline__ uint32_t xin_off(int c, int w) { return SM_X + (2 * c + w) * 8192; }
__device__ __forceinline__ uint32_t xin_bar(int c) { return BAR_FULLX + 8 * (c < 8 ? c ^ 4 : c); }
__device__ __forceinline__ constexpr uint32_t qkv_xslot(int g) { return g < 5 || g > 11 ? 2 : (0x5140762u >> (4 * (g - 5))) & 15; }

template <int N> struct IC { static constexpr int v = N; };

struct Cons {
  uint32_t sb;
  uint32_t rem;
  uint32_t sB, mB;
  uint32_t mX;
  bool elect;
  __device__ __forceinline__ void release2(uint32_t bar) const { if (elect) { mbar_arrive(sb + bar); mbar_arrive_remote(rem + bar); } }
  __device__ __forceinline__ uint32_t nextB(uint32_t& prev) {
    mbar_wait_c(sb + BAR_FULLB + sB, mB);
    const uint32_t a = (((sb & 0x3FFFF) + SM_B) >> 4) + sB * (BSLOT / 128);
    prev = sB == 0 ? 32 : sB - 8;
    sB += 8;
    if (sB == 40) { sB = 0; mB ^= 1; }
    return a;
  }
  __device__ __forceinline__ void progress(uint32_t v) const { if (elect) sts32(sb + SM_PROG + (threadIdx.x >> 5), v); }
  __device__ __forceinline__ void releaseLastB() const { release2(BAR_EMPTYB + (sB == 0 ? 32 : sB - 8)); }
};

__device__ __forceinline__ float2 gather_sums(const uint2* a, uint32_t stag) {
  uint2 sa, sc;
  do { sa = ld_relaxed2(a); sc = ld_relaxed2(a + 8); } while (__any_sync(0xffffffffu, chk2(sa.x, sc.x, stag) & 3));
  return make_float2(quad_sum(__uint_as_float(sa.x) + __uint_as_float(sc.x)), quad_sum(__uint_as_float(sa.y) + __uint_as_float(sc.y)));
}

struct Norm {
  float m0, m1;
  uint32_t nm0, nm1;
  float d0, d1;
  uint2 u0, u1;
  __device__ __forceinline__ Norm(float2 sum) : m0(sum.x * (-1.f / 576)), m1(sum.y * (-1.f / 576)), nm0(pack_bf16(m0, m0)), nm1(pack_bf16(m1, m1)), d0(0.f), d1(0.f) {}
  __device__ __forceinline__ uint4 centre(const uint4& a) const { return make_uint4(hadd2(a.x, nm0), hadd2(a.y, nm1), hadd2(a.z, nm0), hadd2(a.w, nm1)); }
  __device__ __forceinline__ void sqr(uint32_t a, uint32_t b) {
    d0 = fmaf(bf_lo(a), bf_lo(a), fmaf(bf_hi(a), bf_hi(a), d0)); d1 = fmaf(bf_lo(b), bf_lo(b), fmaf(bf_hi(b), bf_hi(b), d1));
  }
  __device__ __forceinline__ void send(uint2* a, int t, uint32_t stag) {
    d0 = quad_sum(d0); d1 = quad_sum(d1);
    if ((t & 3) == 0) st_relaxed2(a, (__float_as_uint(d0) & ~3u) | stag, __float_as_uint(d1));
  }
  __device__ __forceinline__ void fetch(const uint2* a) { u0 = ld_relaxed2(a); u1 = ld_relaxed2(a + 8); }
  __device__ __forceinline__ float2 rstd(const uint2* a, uint32_t stag) {
    while (__any_sync(0xffffffffu, chk2(u0.x, u1.x, stag) & 3)) fetch(a);
    const float e0 = bf_lo(nm0) - m0, e1 = bf_lo(nm1) - m1;
    const float v0 = fmaf(quad_sum(__uint_as_float(u0.x) + __uint_as_float(u1.x)), 1.f / 576, -e0 * e0);
    const float v1 = fmaf(quad_sum(__uint_as_float(u0.y) + __uint_as_float(u1.y)), 1.f / 576, -e1 * e1);
    uint32_t u = pack_bf16(fmaxf(v0, 0.f), fmaxf(v1, 0.f));
    u = pack_bf16(bf_lo(u) + 1e-5f, bf_hi(u) + 1e-5f);
    u = pack_bf16(bf_lo(u) * rsq(bf_lo(u)), bf_hi(u) * rsq(bf_hi(u)));
    float2 r = make_float2(rcp(bf_lo(u)), rcp(bf_hi(u)));
    asm volatile("" : "+f"(r.x), "+f"(r.y));
    return r;
  }
};

template <class Pre, class Mma>
__device__ __forceinline__ float2 ln_gemm_in(Cons& c, Group* G, uint32_t (&p)[18], float2& sum, int w, int st0, int j, int t, Pre&& pre, Mma&& mma) {
  const uint32_t xa = c.sb + (t >> 5) * 2048 + (t & 15) * 128, sw = (((t >> 4) & 1) ^ (t & 7)) * 16;
  float ra[4] = {0.f, 0.f, 0.f, 0.f}, rb[4] = {0.f, 0.f, 0.f, 0.f};
#pragma unroll 1
  for (int cc = 0; cc < 9; cc++) {
    const uint32_t a = xa + xin_off(cc, w);
    mbar_wait_c(c.sb + xin_bar(cc), 0);
    const uint4 u0 = ldsm4(a + sw), u1 = ldsm4(a + (sw ^ 32)), u2 = ldsm4(a + (sw ^ 64)), u3 = ldsm4(a + (sw ^ 96));
    mma16816(ra, u0, 0x3f803f80u, 0x3f803f80u); mma16816(rb, u1, 0x3f803f80u, 0x3f803f80u);
    mma16816(ra, u2, 0x3f803f80u, 0x3f803f80u); mma16816(rb, u3, 0x3f803f80u, 0x3f803f80u);
  }
  sum = make_float2(ra[0] + rb[0], ra[2] + rb[2]);
  pre(0);
  Norm n(sum);
#pragma unroll
  for (int k = 0; k < 5; k++) {
    const uint4 u = ldsm4(xa + (k < 4 ? xin_off(j, w) + (sw ^ (32 * k)) : xin_off(8, w) + ((j ^ (t & 7)) << 4))), e = n.centre(u);
    p[4 * k] = u.x; p[4 * k + 1] = u.y;
    n.sqr(e.x, e.y);
    if (k < 4) { p[4 * k + 2] = u.z; p[4 * k + 3] = u.w; n.sqr(e.z, e.w); }
  }
  n.send(G->sq + st0 + 8 * j, t, 1);
  pre(1);
  float2 r;
  uint32_t xw[4] = {xa + xin_off(0, w) + sw, xa + xin_off(0, w) + (sw ^ 32), xa + xin_off(0, w) + (sw ^ 64), xa + xin_off(0, w) + (sw ^ 96)};
  asm volatile("" : "+r"(xw[0]), "+r"(xw[1]), "+r"(xw[2]), "+r"(xw[3]));
  auto frag = [&](int g, int i) { return n.centre(ldsm4(xw[2 * (g & 1) + i] + xin_off(g >> 1, 0))); };
  uint4 f0 = frag(0, 0), f1 = frag(0, 1);
#pragma unroll
  for (int g = 0; g < 18; g++) {
    mbar_wait_c(c.sb + BAR_FULLB + 8 * (g % 5), (g / 5) & 1);
    mma(g > 0, ((c.sb & 0x3FFFF) >> 4) + ((SM_B + (g % 5) * BSLOT) >> 4), f0, f1);
    wg_wait<1>();
    if (g > 0) c.release2(BAR_EMPTYB + 8 * ((g - 1) % 5));
    if (g < 17) { f0 = frag(g + 1, 0); f1 = frag(g + 1, 1); }
    if (g == 3) c.progress(3);
    if (g == 10) n.fetch(G->sq + st0 + 16 * (t & 3));
    if (g == 15) r = n.rstd(G->sq + st0 + 16 * (t & 3), late(c.sb + BAR_PAST, 1));
    if (g == 17 && w == 0) asm volatile("bar.arrive 6, 256;" ::: "memory");
    if (g >= 14) c.release2(BAR_EMPTYX + 32 + 8 * (g - 14));
  }
  c.mX = 0xff;
  if (w == 1) asm volatile("bar.sync 6, 256;" ::: "memory");
  wg_wait<0>();
  c.release2(BAR_EMPTYB + 8 * (17 % 5));
  c.release2(BAR_EMPTYX + 24);
  return r;
}

template <bool QKV, class Pre, class Mma>
__device__ __forceinline__ float2 ln_gemm(Cons& c, Group* G, const float (&v)[36], uint32_t (&p)[18], float2& sum, int st0, int j, int t,
                                          int layer, uint32_t tag, Pre&& pre, Mma&& mma) {
  const uint32_t stag = (2 * layer + (QKV ? 1 : 2)) & 3;
  uint4 x[6][2];
  uint4* src = G->xbox + t;
  asm volatile("" : "+l"(src));
  auto buf = [&](int g) -> uint4 (&)[2] { return x[g < 16 ? (g - 2) % 6 : g - 13]; };
  auto load = [&](int g0) {
#pragma unroll
    for (int g = g0; g < g0 + (g0 < 14 ? 3 : 2); g++) {
      const uint4* a = g < 16 ? src + ((g - 2) % 7 >= j ? 256 : 0) + (2 * ((g - 2) % 7) + 16 * (g >= 9)) * 128 : src + 2 * g * 128;
      buf(g)[0] = ld_relaxed4(a); buf(g)[1] = ld_relaxed4(a + 128);
    }
  };
  auto invalid = [&](int g, uint32_t tag) {
    uint32_t bad = chk(chk(chk2(buf(g)[0].x, buf(g)[1].x, tag), buf(g + 1)[0].x, tag), buf(g + 1)[1].x, tag);
    if (g < 14) bad = chk(chk(bad, buf(g + 2)[0].x, tag), buf(g + 2)[1].x, tag);
    if (g == 16) bad = chk(chk(chk(chk(bad, buf(g)[0].z, tag), buf(g)[1].z, tag), buf(g + 1)[0].z, tag), buf(g + 1)[1].z, tag);
    return __any_sync(0xffffffffu, bad & 1);
  };
  uint4* const d = src + 2 * j * 128;
  const int sq = st0 + 16 * (t & 3);
  if (QKV) {
    float s0 = v[0] + v[1], s1 = v[2] + v[3];
#pragma unroll
    for (int i = 1; i < 9; i++) { s0 += v[4 * i] + v[4 * i + 1]; s1 += v[4 * i + 2] + v[4 * i + 3]; }
    s0 = quad_sum(s0); s1 = quad_sum(s1);
    if ((t & 3) == 0) st_relaxed2(G->sum + st0 + 8 * j, (__float_as_uint(s0) & ~3u) | stag, __float_as_uint(s1));
  }
#pragma unroll
  for (int i = 0; i < 18; i++) p[i] = pack_bf16(v[2 * i], v[2 * i + 1]);
#pragma unroll
  for (int i = 0; i < 2; i++) st_relaxed4(d + i * 128, tagged(p[4 * i], tag), p[4 * i + 1], p[4 * i + 2], p[4 * i + 3]);
  pre(0);
  if (QKV) {
    sum = gather_sums(G->sum + sq, stag);
    load(2);
  }
  Norm n(sum);
  pre(1);
  const uint32_t* probe = &(G->xbox + (2 * (t & 3) + 1) * 128 + (t | 31))->x;
  uint32_t pv;
  float2 r;
  auto inx = [](int g) { return QKV && ((g >= 5 && g < 12) || g == 17); };
  auto use = [](int g) { return QKV ? (g < 5 ? 108 : 101) + g : 18 + g; };
#pragma unroll
  for (int g = 0; g < 18; g++) {
    if (g < 16 ? g % 3 == 2 : g == 16) {
      const uint32_t lt = late(c.sb + BAR_PAST, tag);
      while (invalid(g, lt)) load(g);
      if (g < 16) load(g < 14 ? g + 3 : 16);
    }
    const uint4 f0 = n.centre(g < 2 ? make_uint4(p[8 * g], p[8 * g + 1], p[8 * g + 2], p[8 * g + 3]) : buf(g)[0]);
    const uint4 f1 = n.centre(g < 2 ? make_uint4(p[8 * g + 4], p[8 * g + 5], p[8 * g + 6], p[8 * g + 7]) : buf(g)[1]);
    if (g == 11) n.fetch(G->sq + sq);
    if (g == 16) r = n.rstd(G->sq + sq, stag);
    if (inx(g)) mbar_wait_c(c.sb + BAR_FULLX + 8 * qkv_xslot(g), ((0x34 >> qkv_xslot(g)) & 1) ^ (g == 17));
    else mbar_wait_c(c.sb + BAR_FULLB + 8 * (use(g) % 5), (use(g) / 5) & 1);
    mma(g, ((c.sb & 0x3FFFF) >> 4) + ((inx(g) ? xslot(qkv_xslot(g)) : SM_B + (use(g) % 5) * BSLOT) >> 4), f0, f1);
    if (g == 1) { wg_wait<1>(); c.release2(BAR_EMPTYB + 8 * (use(0) % 5)); }
    if (g < 2) {
      if (!QKV) {
        if (g == 0) {
          pv = ld_relaxed(probe);
        } else {
          const uint32_t lt = late(c.sb + BAR_PAST, tag);
          while (__any_sync(0xffffffffu, (pv ^ lt) & 1)) pv = ld_relaxed(probe);
          load(2);
        }
      }
      if (g == (QKV ? 0 : 1)) {
#pragma unroll
        for (int i = 2; i < 4; i++) st_relaxed4(d + (14 + i) * 128, tagged(p[4 * i], tag), p[4 * i + 1], p[4 * i + 2], p[4 * i + 3]);
        st_relaxed2((uint2*)(src + (32 + (j >> 1)) * 128) + (j & 1), tagged(p[16], tag), p[17]);
      }
      n.sqr(f0.x, f0.y); n.sqr(f0.z, f0.w); n.sqr(f1.x, f1.y); n.sqr(f1.z, f1.w);
      if (g == 1) {
        n.sqr(hadd2(p[16], n.nm0), hadd2(p[17], n.nm1));
        n.send(G->sq + st0 + 8 * j, t, stag);
      }
    }
    if (g == 1 && !QKV) { wg_wait<0>(); c.release2(BAR_EMPTYB + 8 * (use(1) % 5)); }
    else wg_wait<1>();
    if (g > (QKV ? 1 : 2) && !inx(g - 1)) c.release2(BAR_EMPTYB + 8 * (use(g - 1) % 5));
    if (QKV && g < 13) c.progress(33 + g);
    if (QKV && g == 11) c.release2(BAR_EMPTYX + 8 * qkv_xslot(17));
    if (QKV && g >= 12 && g < 16) c.release2(BAR_EMPTYX + 32 + 8 * (g - 12));
  }
  if (QKV) c.mX = 0x34 ^ 0xf3;
  else { c.sB = 8 * (36 % 5); c.mB = (36 / 5) & 1; }
  wg_wait<0>();
  if (!QKV) c.release2(BAR_EMPTYB + 8 * (use(17) % 5));
  return r;
}

template <int NB, int OFF>
__device__ __forceinline__ void glu(const float (&a)[128], uint32_t (&h)[144]) {
#pragma unroll
  for (int b = 0; b < 2 * NB; b++) {
    if (OFF == 120) h[OFF + b] = pack_bf16(a[2 * b] * a[4 * NB + 2 * b], a[2 * b + 1] * a[4 * NB + 2 * b + 1]);
    else h[OFF + b] = hmul2(pack_bf16(a[2 * b], a[2 * b + 1]), pack_bf16(a[4 * NB + 2 * b], a[4 * NB + 2 * b + 1]));
  }
}

__global__ void __cluster_dims__(2, 1, 1) __launch_bounds__(384, 1)
fused_kernel(const __nv_bfloat16* __restrict__ x_in, Group* ws, const char* __restrict__ wqkv,
             const char* __restrict__ wo, char* __restrict__ out, uint32_t first, const __grid_constant__ Maps maps,
             const char* __restrict__ wg, const char* __restrict__ wu) {
  extern __shared__ __align__(1024) uint8_t smem_raw[];
  const uint32_t sb = smem_u32(smem_raw);
  const uint32_t bx = blockIdx.x - first;
  if (bx >= NCTA) {
    const int e = blockIdx.x & 3;
    const uint32_t par = ~ld_relaxed(ws->flag + 32) & 1;
    __nanosleep(1000);
    if (threadIdx.x < 16) prefetch_l2(wo + (144 * e + 9 * threadIdx.x) * 1152, 9 * 1152);
#pragma unroll 1
    for (int r = threadIdx.x >> 3; r < 144; r += 48) {
      const uint4* row = (const uint4*)(wo + (144 * e + r) * 1152) + (threadIdx.x & 7);
      float a = 0.f;
      uint4 u;
#pragma unroll
      for (int i = 0; i < 72; i += 8) {
        u = __ldg(row + i);
        a += ((bf_lo(u.x) + bf_hi(u.x)) + (bf_lo(u.y) + bf_hi(u.y))) + ((bf_lo(u.z) + bf_hi(u.z)) + (bf_lo(u.w) + bf_hi(u.w)));
      }
      const int h = r >= 72, k = r - 72 * h;
      ((Scratch*)ws)->woc[threadIdx.x & 7][k < 64 ? 64 + 8 * k + ((2 * e + h) ^ (k & 7)) : 576 * h + 8 * (k & 7) + (e ^ (k & 7))] = u;
      a = quad_sum(a);
      a += __shfl_xor_sync(0xffffffffu, a, 4);
      if ((threadIdx.x & 7) == 0) ((Scratch*)ws)->woc[2 * e + h][640 + k] = make_uint4(pack_bf16(a, a - bf_lo(pack_bf16(a, 0.f))), 0, 0, 0);
    }
    fence_gpu();
    __syncthreads();
    if (threadIdx.x == 0) st_relaxed(((Scratch*)ws)->done + e, par);
    const int cc = threadIdx.x % 54, r0 = threadIdx.x / 54, part = cc / 18, jj = 2 * e + (cc % 18) / 9, c9 = cc % 9;
    if (r0 < 6) {
#pragma unroll 4
      for (int k = r0; k < 576; k += 6) {
        const uint4 u = __ldg((const uint4*)(wqkv + k * 3456 + part * 1152 + 144 * jj) + c9);
        ((Scratch*)ws)->wq[jj][k >> 4][c9 < 8 ? part * 128 + (k & 15) * 8 + (c9 ^ (k & 7)) : 384 + part * 16 + (k & 15)] = u;
      }
    }
    fence_gpu();
    __syncthreads();
    if (threadIdx.x == 0) st_relaxed(((Scratch*)ws)->done + 32 + e, par);
    return;
  }
  if (threadIdx.x == 0) asm volatile("prefetch.tensormap [%0];" ::"l"(&maps.x) : "memory");
  const int warp = __shfl_sync(0xffffffffu, threadIdx.x >> 5, 0);
  const int lane = threadIdx.x & 31;
  const int rank = blockIdx.x & 1;
  if (warp == 3) {
#pragma unroll
    for (int i = 0; i < 5; i++)
      if (2 * i + (lane >> 4) < 9) asm volatile("prefetch.global.L2 [%0];" ::"l"((const char*)x_in + (bx * 16 + (lane & 15)) * 1152 + (2 * i + (lane >> 4)) * 128));
  }
  if (elect_one()) {
    if (warp >= 8) {
#pragma unroll
      for (int i = 0; i < 9; i++) mbar_init(sb + SM_BAR + 72 * (warp - 8) + 8 * i, warp < 10 ? 1 : 4);
      sts32(sb + SM_PROG + 4 * (warp - 8), 0);
      asm volatile("fence.mbarrier_init.release.cluster;" ::: "memory");
    } else if (warp == 1 || warp == 2) {
      asm volatile("prefetch.tensormap [%0];" ::"l"(&maps.x + warp) : "memory");
    }
  }
  __syncwarp();
  asm volatile("barrier.cluster.arrive.relaxed.aligned;" ::: "memory");
  if (warp == 8) PROFX(53);
  const int cl = bx >> 1, u = cl - 36;
  const int lb = (cl < 4 ? cl : cl < 36 ? 8 * ((cl - 4) & 7) + ((cl - 4) >> 3) + (((cl - 4) & 7) ? 0 : 4) : 8 * (1 + u % 7) + 4 + u / 7) * 2 + rank;
#define CTA_J(b) (((b) >> 1) & 7)
#define CTA_RB(b) ((((b) >> 4) << 1) | ((b) & 1))
  const int j = CTA_J(lb), rb = CTA_RB(lb);

  PROF(23);
  if (warp >= 8) {
    asm volatile("setmaxnreg.dec.sync.aligned.u32 40;");
    auto x_chunk = [&](int cc) {
      mbar_expect_tx(sb + xin_bar(cc), 16384);
      tma3d(sb + xin_off(cc, 0), &maps.x, 64 * cc, 0, 64 * rb, sb + xin_bar(cc));
      tma3d(sb + xin_off(cc, 1), &maps.x, 64 * cc, 1, 64 * rb, sb + xin_bar(cc));
    };
    if (warp == 9 && elect_one()) {
      fence_async_smem();
#pragma unroll 1
      for (int i = 0; i < 9; i++) x_chunk(i);
    }
    __syncwarp();
    if (warp == 9) PROFX(54);
    asm volatile("barrier.cluster.wait.aligned;" ::: "memory");
    if (warp == 8) PROFX(56);
    const uint64_t pol = policy_evict_first(), pola = policy_evict_normal();
    uint4 (* const wq)[432] = ((Scratch*)ws)->wq[j];
    const uint32_t par = ~ld_relaxed(ws[2 * rb].flag + 32 + 32 * j) & 1;
    auto qkv_group = [&](bool copy, int k, uint32_t dst, uint32_t bar) {
      if (copy) {
        wbulk(dst + rank * 8192, wq[(k >> 4) + rank], 6912, bar, pol);
      } else {
        wtma3d(dst + rank * 8192, &maps.qm, 72 * j, k + 16 * rank, 0, bar, pola);
        wtma3d(dst + rank * 8192 + 6144, &maps.qc, 72 * j + 64, k + 16 * rank, 0, bar, pola);
      }
    };
    auto chore = [&](int i) {
#pragma unroll 1
      for (int it = 0; __any_sync(0xffffffffu, ld_acquire(((Scratch*)ws)->done + i) != par); it++) if (it == SPIN_MAX) asm volatile("trap;");
      asm volatile("fence.proxy.async.global;" ::: "memory");
    };
    const int ktab = group_k0(lane, j);
    auto qkv_gate = [&](int g) { if (g >= 8) gate(sb + SM_PROG, 33 + ((g - 8) * 23 >> 4)); };
    if (warp == 8) {
      uint32_t s = 0, ph = 1;
      auto slot = [&](uint32_t bytes, auto&& issue) {
        const uint32_t bar = sb + BAR_FULLB + 8 * s;
        mbar_wait(sb + BAR_EMPTYB + 8 * s, ph);
        if (elect_one()) {
          mbar_expect_tx(bar, bytes);
          issue(sb + SM_B + s * BSLOT, bar);
        }
        if (++s == 5) { s = 0; ph ^= 1; }
      };
#pragma unroll 1
      for (int layer = 0; layer < NLAYERS; layer++) {
        if (layer) chore(32 + (j >> 1));
#pragma unroll 1
        for (int g = 0; g < 18 - layer; g += layer && g == 4 ? 8 : 1) {
          const int k = layer ? __shfl_sync(0xffffffffu, ktab, g) : 32 * g;
          if (layer) qkv_gate(g);
          else if (g == 0) mbar_wait(sb + xin_bar(3), 0);
          slot(2 * 6912, [&](uint32_t dst, uint32_t bar) { qkv_group(layer, k, dst, bar); });
        }
#pragma unroll 1
        for (int t = 0; t < 5; t++) {
          const CUtensorMap* m = &maps.g + (t < 3 ? rank : 2 + rank);
          asm volatile("" : "+l"(m));
          const int c2 = t < 3 ? 9 * j + 2 * t : 18 * j + 3 + 3 * t;
          const uint32_t half = t < 3 ? 8192 : 6144;
          const uint64_t pt = layer == 0 && (t == 0 || t > 2) ? pola : pol;
          auto tile = [&](int g) {
            const int k = __shfl_sync(0xffffffffu, ktab, g);
            slot(2 * half, [&](uint32_t dst, uint32_t bar) { wtma3d(dst + rank * half, m, 0, k, c2, bar, pt); });
          };
          int g = 0;
          if (t == 0) {
#pragma unroll 1
            for (; g < 5; g++) {
              mbar_wait(sb + BAR_FULLB + 8 * (s == 0 ? 4 : s - 1), s == 0 ? ph : ph ^ 1);
              if (g == 2) gate(sb + SM_PROG + 4, 32 * layer + 20);
              tile(g);
            }
          }
#pragma unroll 1
          for (; g < 18; g++) tile(g);
        }
      }
    } else if (warp == 9) {
      uint32_t mE = 0;
      auto acquire = [&](uint32_t s) { mbar_wait(sb + BAR_EMPTYX + 8 * s, (mE >> s) & 1); mE ^= 1u << s; };
      auto slot = [&](uint32_t s, const CUtensorMap* m, int col, int row, uint64_t pol) {
        acquire(s);
        if (elect_one()) {
          mbar_expect_tx(sb + BAR_FULLX + 8 * s, XSLOT);
          wtma2d(sb + xslot(s) + rank * 9216, m, col, row + 72 * rank, sb + BAR_FULLX + 8 * s, pol);
        }
      };
#pragma unroll 1
      for (int layer = 0; layer < NLAYERS; layer++) {
        if (layer) chore(32 + (j >> 1));
#pragma unroll 1
        for (int g = 5; g < 18 * layer; g += g == 11 ? 6 : 1) {
          const uint32_t s = qkv_xslot(g);
          const int k = __shfl_sync(0xffffffffu, ktab, g);
          if (g < 12) qkv_gate(g);
          acquire(s);
          if (elect_one()) {
            mbar_expect_tx(sb + BAR_FULLX + 8 * s, 2 * 6912);
            qkv_group(true, k, sb + xslot(s), sb + BAR_FULLX + 8 * s);
          }
          mbar_wait(sb + BAR_FULLX + 8 * s, (mE >> s) & 1);
        }
#pragma unroll 1
        for (int i = 0; i < 4; i++) slot(4 + i, &maps.o, 64 * j, 144 * i, pola);
        if (layer == 0) { chore(lane & 3); PROFX(57); }
        acquire(3);
        if (elect_one()) {
          mbar_expect_tx(sb + BAR_FULLX + 24, 10240 + 1280);
          wbulk(sb + SM_WOC + rank * 5120, ((Scratch*)ws)->woc[j] + rank * 320, 5120, sb + BAR_FULLX + 24, pola);
          wbulk(sb + SM_WSUM + rank * 640, ((Scratch*)ws)->woc[j] + 640 + rank * 40, 640, sb + BAR_FULLX + 24, pola);
        }
#pragma unroll 1
        for (int u = 0; u < 36; u++) slot(4 * (u & 1) + ((u >> 1) & 3), &maps.d, u < 4 ? 512 : 64 * ((j + (u >> 2)) & 7), 576 * j + 144 * (u & 3), pol);
      }
    } else {
      const int w = warp - 10, grp = 2 * rb + w;
      auto exchange = [&](uint32_t v, uint32_t bar) {
        fence_gpu();
        __syncwarp();
        if (w == 0 && v != 1) PROFX(64 + 58 - 2 * v);
        if (lane == 0) st_relaxed(ws[grp].flag + j, v);
#pragma unroll 1
        for (int it = 0;; it++) {
          const uint32_t f = ld_relaxed(ws[grp].flag + (lane & 7));
          if (__all_sync(0xffffffffu, v ? f >= v : f == 0)) break;
          if (it == SPIN_MAX) asm volatile("trap;");
        }
        if (lane == 0) mbar_arrive(sb + bar + 8 * w);
      };
      mbar_wait(sb + xin_bar(0), 0);
#pragma unroll 1
      for (int i = 0; i < 3; i++) {
        if (lane == 0) prefetch_l2(wqkv + (256 * i + 2 * bx + w) * 2592, 2592);
        __nanosleep(300);
      }
      gate(sb + SM_PROG, 3);
      if (w == 0 && lane < 6) asm volatile("prefetch.tensormap [%0];" ::"l"(&maps.o + lane) : "memory");
#pragma unroll 1
      for (int i = lane; i < 72; i += 32) {
        asm volatile("prefetch.global.L2 [%0];" ::"l"((w ? wu : wg) + (size_t)(36 * rb + (i >> 1)) * 9216 + 1152 * j + 128 * (i & 1)));
        __nanosleep(700);
      }
      gate(sb + SM_PROG, 22);
#pragma unroll 1
      for (int i = lane; i < 2 * INBOX; i += 64) {
        uint4* p = ws[grp].inbox[0] + 2 * j * INBOX + i;
        st_relaxed4(p, 0, 0, 0, 0); st_relaxed4(p + 32, 0, 0, 0, 0);
        __nanosleep(150);
      }
      exchange(1, BAR_CLR);
      if (w == 0) PROFX(59);
#pragma unroll 1
      for (int layer = 0; layer < NLAYERS; layer++) {
        mbar_wait(sb + BAR_REDDONE + 8 * w, layer);
        if (w == 0) PROFX(64 + 53 + 4 * layer);
        exchange(2 - 2 * layer, BAR_RREADY);
        if (w == 0) PROFX(64 + 56 + 4 * layer);
      }
      mbar_wait(sb + BAR_DONE + 8 * w, 0);
    }
  } else {
    asm volatile("setmaxnreg.inc.sync.aligned.u32 232;");
#define THREAD_IDS()                                                                   \
    int tid_ = threadIdx.x, bid_ = lb;                                                  \
    asm volatile("" : "+r"(tid_), "+r"(bid_));                                          \
    const int w = warp >> 2, wp = warp & 3;                                             \
    const int lane = tid_ & 31, t = tid_ & 127, g = lane >> 2, q = lane & 3;           \
    const int j = CTA_J(bid_), rb = CTA_RB(bid_), grp = 2 * rb + w;                    \
    const int st0 = wp * 64 + g;                         \
    Group* const G = ws + grp;                                                         \
    const uint32_t dsb = (sb & 0x3FFFF) >> 4;                                          \
    (void)t; (void)g; (void)q; (void)grp; (void)j; (void)st0; (void)dsb; (void)G
    Cons c;
    c.sb = sb; c.sB = 0; c.mB = 0; c.mX = 0; c.elect = (threadIdx.x & 127) == 0;
    asm volatile("mapa.shared::cluster.u32 %0, %1, %2;" : "=r"(c.rem) : "r"(sb), "r"(rank ^ 1));
    float v[36], a1[96], a2[12];
    float2 sum, rs;
    uint32_t res[18], xtag;
    auto qkv_mma = [&](bool acc, uint32_t bb, const uint4& f0, const uint4& f1) {
      wg_fence();
      wgmma_ra<192>(a1, f0, desc_hi(2048, 1024, 1) + bb, acc);
      wgmma_ra<24>(a2, f0, desc_hi(128, 256, 0) + (bb + 384), acc);
      wgmma_ra<192>(a1, f1, desc_hi(2048, 1024, 1) + (bb + 512), true);
      wgmma_ra<24>(a2, f1, desc_hi(128, 256, 0) + (bb + 896), true);
      wg_commit();
    };
    {
      THREAD_IDS();
      {
        if (q == 0) { st_relaxed2(G->sum + st0 + 8 * j, 0, 0); st_relaxed2(G->sq + st0 + 8 * j, 0, 0); }
        if (wp == 3) {
#pragma unroll
          for (int i = 0; i < 5; i++) st_relaxed4(G->halo + j * 160 + lane + i * 32, 0, 0, 0, 0);
        }
        if (lane >= 24) st_relaxed4(G->obox + (8 + j) * 128 + t, 0, 0, 0, 0);
      }
      xtag = __shfl_sync(0xffffffffu, ~ld_relaxed(G->flag + 32 + 32 * j) & 1, 0);
      if (lane >= 24) st_relaxed4(G->xbox + (2 * j + 1) * 128 + t, xtag ^ 1, 0, 0, 0);
      asm volatile("barrier.cluster.wait.aligned;" ::: "memory");
      PROF(0);
      PROF(1);
      rs = ln_gemm_in(c, G, res, sum, w, st0, j, t, [&](int i) { PROF(2 + i); if (i) PROF(4); }, qkv_mma);
    }
#pragma unroll 1
    for (int layer = 0;; layer++) {
      const uint32_t tag = layer ^ 1;
      uint4 own[5];
      {
        THREAD_IDS();
        PROF(pb + 4);
        uint32_t kv[3][18];
        auto cvt = [&](int b, float r) {
#pragma unroll
          for (int cc = 0; cc < 18; cc++) {
            const float* a = (cc == 8 ? a2 + 4 : cc == 17 ? a2 + 8 : cc < 8 ? a1 + 32 + 4 * cc : a1 + 28 + 4 * cc) + 2 * (b - 1);
            const uint32_t u = pack_bf16(a[0] * r, a[1] * r);
            kv[b][cc] = cc < 9 ? u : movm(u);
          }
        };
        cvt(2, rs.y);
#pragma unroll
        for (int i = 0; i < 18; i += 4) kv[2][i] = tagged(kv[2][i], tag);
        const uint32_t msg = sb + (w ? xslot(3) : xslot(0) + 24576) + wp * 2304 + lane * 16;
        if (wp == 3) {
          uint4* hp = G->halo + j * 160 + lane;
#pragma unroll
          for (int i = 0; i < 4; i++) st_relaxed4(hp + i * 32, kv[2][4 * i], kv[2][4 * i + 1], kv[2][4 * i + 2], kv[2][4 * i + 3]);
          st_relaxed2((uint2*)(hp + 128), kv[2][16], kv[2][17]);
        } else {
#pragma unroll
          for (int i = 0; i < 4; i++) sts128(msg + i * 512, kv[2][4 * i], kv[2][4 * i + 1], kv[2][4 * i + 2], kv[2][4 * i + 3]);
          sts64f(msg + 2048 - lane * 8, __uint_as_float(kv[2][16]), __uint_as_float(kv[2][17]));
        }
        cvt(1, rs.x);
        uint32_t Q[4][6];
#pragma unroll
        for (int h = 0; h < 4; h++)
#pragma unroll
          for (int i = 0; i < 6; i++) {
            const float* a = 4 * h + i < 16 ? a1 + 8 * h + 2 * i : a2 + 8 * h + 2 * i - 32;
            const uint32_t u = pack_bf16(a[0], a[1]);
            Q[h][i] = i < 2 ? (q >= h ? u : 0) : i < 4 ? u : (q <= h ? u : 0);
          }
        const bool lo0 = 2 * q > g, lo1 = 2 * q + 1 > g;
        const uint32_t M = (lo0 ? 0xffffu : 0u) | (lo1 ? 0xffff0000u : 0u);
        auto scores = [&](int h, int b, float (&s)[4]) {
          mma16816z(s, Q[h][0], Q[h][1], Q[h][2], Q[h][3], kv[b][2 * h], kv[b][2 * h + 1]);
          mma1688(s, Q[h][4], Q[h][5], kv[b][2 * h + 2]);
        };
        auto softmax = [&](float (&l)[4][2], float r, uint32_t (&P)[4]) {
          const float sl = r * (0.23570226039551584f * 1.4426950408889634f);
          float m[4];
#pragma unroll
          for (int h = 0; h < 4; h++) { m[h] = fmaxf(l[h][0], l[h][1]); m[h] = fmaxf(m[h], __shfl_xor_sync(0xffffffffu, m[h], 1)); }
#pragma unroll
          for (int h = 0; h < 4; h++) m[h] = fmaxf(m[h], __shfl_xor_sync(0xffffffffu, m[h], 2)) * sl;
#pragma unroll
          for (int h = 0; h < 4; h++) P[h] = pack_bf16(ex2(fmaf(l[h][0], sl, -m[h])), ex2(fmaf(l[h][1], sl, -m[h])));
        };
        const bool remote = wp == 0 && rb > 0;
        const uint4* hp = (G - 2)->halo + j * 160 + lane;
        auto halo = [&] {
#pragma unroll
          for (int i = 0; i < 4; i++) { const uint4 u = ld_relaxed4(hp + i * 32); kv[0][4 * i] = u.x; kv[0][4 * i + 1] = u.y; kv[0][4 * i + 2] = u.z; kv[0][4 * i + 3] = u.w; }
          const uint2 u = ld_relaxed2((const uint2*)(hp + 128));
          kv[0][16] = u.x; kv[0][17] = u.y;
        };
#pragma unroll
        for (int i = 0; i < 18; i++) kv[0][i] = 0;
        float l0[4][2], l1[4][2];
#pragma unroll
        for (int h = 0; h < 4; h++) {
          float s1[4], s2[4];
          scores(h, 1, s1); scores(h, 2, s2);
          l0[h][0] = s1[0]; l0[h][1] = s1[1];
          l1[h][0] = lo0 ? s1[2] : s2[2]; l1[h][1] = lo1 ? s1[3] : s2[3];
        }
        hp += __float_as_uint(l1[0][0]) & late(sb + BAR_PAST, 0);
        if (remote) halo();
        uint32_t P0[4], P1[4];
        softmax(l1, rs.y, P1);
        wg_bar(w);
        if (wp > 0) {
          const uint32_t from = msg - 2304;
#pragma unroll
          for (int i = 0; i < 4; i++) { const uint4 u = lds128(from + i * 512); kv[0][4 * i] = u.x; kv[0][4 * i + 1] = u.y; kv[0][4 * i + 2] = u.z; kv[0][4 * i + 3] = u.w; }
          const float2 u = lds64(from + 2048 - lane * 8);
          kv[0][16] = __float_as_uint(u.x); kv[0][17] = __float_as_uint(u.y);
        }
        if (remote) {
          while (__any_sync(0xffffffffu, chk(chk(chk(chk2(kv[0][0], kv[0][4], tag), kv[0][8], tag), kv[0][12], tag), kv[0][16], tag) & 1)) halo();
        }
        PROF(pb + 5);
        const bool first = (rb == 0 && wp == 0);
#pragma unroll
        for (int h = 0; h < 4; h++) {
          float s0[4];
          scores(h, 0, s0);
          if (first) s0[0] = s0[1] = -INFINITY;
          l0[h][0] = lo0 ? s0[0] : l0[h][0]; l0[h][1] = lo1 ? s0[1] : l0[h][1];
        }
        softmax(l0, rs.x, P0);
        uint4* ob = G->obox + t;
        uint32_t car0 = 0, car1 = 0;
#pragma unroll
        for (int h = 0; h < 4; h++) {
          float o[3][4], z[4] = {0.f, 0.f, 0.f, 0.f};
          mma1688(z, P0[h], P1[h], 0x3f803f80u);
#pragma unroll
          for (int i = 0; i < 3; i++) {
            mma16816z(o[i], P0[h] & ~M, P1[h] & M, 0u, P1[h] & ~M, kv[1][9 + 2 * h + i], kv[2][9 + 2 * h + i]);
            mma1688(o[i], P0[h] & M, 0u, kv[0][9 + 2 * h + i]);
          }
          const float i0 = rcp(z[0]), i1 = rcp(z[2]);
#pragma unroll
          for (int i = 0; i < 3; i++) { o[i][0] *= i0; o[i][1] *= i0; o[i][2] *= i1; o[i][3] *= i1; }
          const uint32_t o0 = q < h ? car0 : pack_bf16(o[0][0], o[0][1]), o1 = q < h ? car1 : pack_bf16(o[0][2], o[0][3]);
          own[h] = make_uint4(o0 | 1, o1, pack_bf16(o[1][0], o[1][1]), pack_bf16(o[1][2], o[1][3]));
          if (h < 3) st_relaxed4(ob + (8 * h + j) * 128, own[h].x, own[h].y, own[h].z, own[h].w);
          car0 = pack_bf16(o[2][0], o[2][1]); car1 = pack_bf16(o[2][2], o[2][3]);
          if (h == 1) { const uint32_t z = late(sb + BAR_PAST, 0); P0[2] ^= z; P0[3] ^= z; }
        }
        car0 = tagged(car0, tag);
        own[4] = make_uint4(car0, car1, 0, 0);
        PROF(pb + 6);
      }
      uint2 sa, sc;
      {
        THREAD_IDS();
        uint4* src = G->obox + t;
        asm volatile("" : "+l"(src));
        uint4 x[32];
        const uint4* from[7];
#pragma unroll
        for (int r = 0; r < 7; r++) { from[r] = src + (r >= j ? 128 : 0); asm volatile("" : "+l"(from[r])); }
        auto load = [&](int i) { x[i] = ld_relaxed4(i < 28 ? from[i % 7] + (8 * (i / 7) + i % 7) * 128 : src + (i + 4) * 128); };
        const uint32_t* probe = &(G->obox + (8 + (lane & 7)) * 128 + (t | 31))->x;
        uint32_t pv = ld_relaxed(probe);
#pragma unroll
        for (int i = 3; i < 8; i++) mbar_wait_c(sb + BAR_FULLX + 8 * i, (c.mX >> i) & 1);
        c.mX ^= 0xf8;
        while (__any_sync(0xffffffffu, ~pv & 1)) pv = ld_relaxed(probe);
        PROF(25 - layer);
        if (w == 1) asm volatile("bar.sync 7, 256;" ::: "memory");
#pragma unroll
        for (int i = 0; i < 10; i++) load(i);
        if (w == 0) asm volatile("bar.arrive 7, 256;" ::: "memory");
        st_relaxed4(src + (24 + j) * 128, own[3].x, own[3].y, own[3].z, own[3].w);
        st_relaxed2((uint2*)(src + (32 + (j >> 1)) * 128) + (j & 1), own[4].x, own[4].y);
        PROF(27 - layer);
        float a[36];
        float e[4];
        constexpr uint32_t NEXT = 576 - (575u << 16);
        auto step = [&](const uint4& f, uint32_t s, int i, uint32_t more, bool acc) {
          const uint32_t r = (xslot(4) >> 4) + (i < 4 ? 72 * s + 16 * i : 144 * s + 64) * 8, c = (SM_WOC >> 4) + (i < 4 ? 64 + 128 * i : 0) + s;
          wgmma_ra<72>(a, f, desc_hi(0, i < 4 ? 1024 : 9216, 1) + (dsb + more + (r + ((c - r) << 16))), acc);
        };
        wg_fence();
#pragma unroll
        for (int i = 0; i < 5; i++) wgmma_ra<8>(e, own[i], desc_hi(128, 0, 0) + (dsb + (SM_WSUM >> 4) + 16 * i), i > 0);
        wg_commit();
#pragma unroll
        for (int i = 0; i < 4; i++) step(own[i], 0, i, j * NEXT, i > 0);
        wg_commit();
        PROF(29 - layer);
        auto batch = [&](auto e0, auto e1, auto e2, int b) {
          constexpr int E0 = decltype(e0)::v, E1 = decltype(e1)::v, E2 = decltype(e2)::v;
          const uint32_t one = late(sb + BAR_PAST, 1);
          while (true) {
            uint32_t bad = 0;
#pragma unroll
            for (int i = E0; i < E1; i++) bad = i < 28 ? chk(bad, x[i].x, one) : chk(chk(bad, x[i].x, tag), x[i].z, tag);
            if (!__any_sync(0xffffffffu, bad & 1)) break;
#pragma unroll
            for (int i = E0; i < E1; i++) load(i);
          }
          if (b == 0) PROF(pb + 7);
          if (b == 1) { c.progress(32 * layer + 20); wg_wait<1>(); }
#pragma unroll
          for (int i = E1; i < E2; i++) load(i);
          if (b == 2) { sa = ld_relaxed2(G->sum + st0 + 16 * q); sc = ld_relaxed2(G->sum + st0 + 16 * q + 8); }
          wg_fence();
#pragma unroll
          for (int i = E0; i < E1; i++) step(x[i], i % 7, i / 7, i < 28 && i % 7 >= j ? NEXT : 0, true);
          wg_commit();
          if (b == 0) {
            wg_wait<2>();
            if (q == 0) st_relaxed2(G->sum + st0 + 8 * j, (__float_as_uint(e[0] + e[1]) & ~3u) | ((2 * layer + 2) & 3), __float_as_uint(e[2] + e[3]));
          }
        };
        batch(IC<0>(), IC<10>(), IC<21>(), 0);
        batch(IC<10>(), IC<21>(), IC<32>(), 1);
        batch(IC<21>(), IC<32>(), IC<32>(), 2);
        wg_wait<0>();
        if (w == 0) asm volatile("bar.arrive 3, 256;" ::: "memory");
        PROF(pb + 8);
#pragma unroll
        for (int i = 0; i < 18; i++) {
          v[2 * i] = bf_lo(res[i]) + a[2 * i];
          v[2 * i + 1] = bf_hi(res[i]) + a[2 * i + 1];
        }
      }
      uint32_t lsb;
      uint32_t h[144];
      {
        THREAD_IDS();
        float a[128];
        const uint32_t xd = sb + xslot(4 * w) + (lane >> 4) * 1024 + (16 * wp + (lane & 15)) * 16;
        const float2 rs = ln_gemm<false>(c, G, v, res, sum, st0, j, t, layer, xtag,
          [&](int i) {
            if (i == 0) {
              lsb = ((res[0] & 1) | (res[4] & 1) << 1 | (res[8] & 1) << 2 | (res[12] & 1) << 3 | (res[16] & 1) << 4) ^ (xtag * 31);
              const uint32_t st = late(sb + BAR_PAST, (2 * layer + 2) & 3);
              while (__any_sync(0xffffffffu, chk2(sa.x, sc.x, st) & 3)) { sa = ld_relaxed2(G->sum + st0 + 16 * q); sc = ld_relaxed2(G->sum + st0 + 16 * q + 8); }
              sum.x += quad_sum(__uint_as_float(sa.x) + __uint_as_float(sc.x)); sum.y += quad_sum(__uint_as_float(sa.y) + __uint_as_float(sc.y));
              if (w == 1) asm volatile("bar.sync 3, 256;" ::: "memory");
            }
            PROF(pb + 9 + i);
          },
          [&](int gi, uint32_t bb, const uint4& f0, const uint4& f1) {
            if (gi == 0) PROF(pb + 11);
            if (gi == 16 && w == 1) asm volatile("bar.sync 5, 256;" ::: "memory");
            wg_fence();
            wgmma_ra<256>(a, f0, desc_hi(4096, 1024, 1) + bb, gi > 0);
            wgmma_ra<256>(a, f1, desc_hi(4096, 1024, 1) + (bb + 128), true);
            wg_commit();
            if (gi == 17 && w == 0) asm volatile("bar.arrive 5, 256;" ::: "memory");
            stsm4(xd + gi * 4096, f0.x, f0.y, f0.z, f0.w);
            stsm4(xd + gi * 4096 + 2048, f1.x, f1.y, f1.z, f1.w);
            if (gi == 17) { fence_async_smem(); wg_bar(w); }
          });
        sts64f(sb + SM_KEEP + (tid_ >> 2) * 8, rs.x * rs.x, rs.y * rs.y);
        c.progress(32 * layer + 22);
        PROF(pb + 12);
        glu<16, 0>(a, h);
        const Desc da0 = desc_hi(1024, 128, 0) + (dsb + (xslot(4 * w) >> 4));
        auto tile = [&](auto wide, auto last) {
          const uint32_t xe = BAR_EMPTYX + 32 * (t & 1) + 4 * (t & 6);
          auto group = [&](int gi) {
            uint32_t prev;
            const uint32_t bb = c.nextB(prev);
            const Desc da = da0 + gi * 256;
            wg_fence();
            if (wide()) {
              wgmma_ss<256>(a, da, desc_hi(4096, 1024, 1) + bb, gi);
              wgmma_ss<256>(a, da + 128, desc_hi(4096, 1024, 1) + (bb + 128), 1);
            } else {
              wgmma_ss<192>(*(float(*)[96])a, da, desc_hi(2048, 512, 2) + bb, gi);
              wgmma_ss<192>(*(float(*)[96])a, da + 128, desc_hi(2048, 512, 2) + (bb + 64), 1);
            }
            wg_commit();
            if (gi == 17 && w == 0) asm volatile("bar.arrive 5, 256;" ::: "memory");
            wg_wait<1>();
            if (gi > 0 && !(last() && gi > 13)) c.release2(BAR_EMPTYB + prev);
            if (last() && gi >= 8 && !(gi & 1)) c.release2(BAR_EMPTYX + 16 * ((gi - 8) & 2) + 2 * ((gi - 8) & 12));
          };
          int gi = 0, end = w ? 16 : 18;
#pragma unroll 1
          while (true) {
#pragma unroll 1
            for (; gi < end; gi++) group(gi);
            if (end == 18) break;
            asm volatile("bar.sync 5, 256;" ::: "memory");
            end = 18;
          }
          wg_wait<0>();
          if (!last()) c.releaseLastB();
          if (last() && t >= 5 && t < 8) { mbar_arrive(sb + xe); mbar_arrive_remote(c.rem + xe); }
        };
        auto yes = [] { return true; };
        auto no = [] { return false; };
        tile(yes, no); PROF(pb + 13); glu<16, 32>(a, h);
        tile(yes, no); PROF(pb + 14); glu<16, 64>(a, h);
        tile(no, no); PROF(pb + 15); glu<12, 96>(a, h);
        const uint32_t hole = sb + SM_B + 12288 + tid_ * 16;
#pragma unroll
        for (int i = 0; i < 4; i++) sts128(hole + i * BSLOT, h[96 + 4 * i], h[97 + 4 * i], h[98 + 4 * i], h[99 + 4 * i]);
        if (w == 1) asm volatile("bar.arrive 8, 256;" ::: "memory");
        tile(no, yes); PROF(pb + 16); glu<12, 120>(a, h);
#pragma unroll
        for (int i = 0; i < 4; i++) { const uint4 u = lds128(hole + i * BSLOT); h[96 + 4 * i] = u.x; h[97 + 4 * i] = u.y; h[98 + 4 * i] = u.z; h[99 + 4 * i] = u.w; }
      }
      {
        THREAD_IDS();
        float d[32];
        uint4* gt = G->obox + t;
        asm volatile("" : "+l"(gt));
        uint4* const ib = gt + 2 * 4608 + layer * 8 * INBOX;
        auto pass = [&](uint32_t s0, bool last, auto&& hook) {
          const Desc db = desc_hi(0, 1024, 1) + (dsb + s0 * (XSLOT >> 4));
          auto full = [&](int i) { const int si = 4 * (i & 1) + (i >> 1); mbar_wait_c(sb + BAR_FULLX + 8 * (s0 + si), (c.mX >> (s0 + si)) & 1); };
          auto empty = [&](int i) { c.release2(BAR_EMPTYX + 8 * (s0 + 4 * (i & 1) + (i >> 1))); };
          full(0);
          hook();
          asm volatile("bar.sync %0, 256;" ::"r"(8 + w) : "memory");
#pragma unroll
          for (int i = 0; i < 4; i++) {
            const int si = 4 * (i & 1) + (i >> 1);
            if (i > 0) full(i);
            wg_fence();
#pragma unroll
            for (int k = 0; k < 9; k++) {
              const uint32_t* hk = h + 36 * i + 4 * k;
              wgmma_ra<64>(d, make_uint4(hk[0], hk[1], hk[2], hk[3]), db + ((xslot(si) >> 4) + k * 128), last || i + k > 0);
            }
            if (i == 3 && !(last && w == 1)) asm volatile("bar.arrive %0, 256;" ::"r"(9 - w) : "memory");
            if (i > 0) wg_commit();
            if (i > 1) { wg_wait<1>(); empty(i - 1); }
            if (i == 2) empty(0);
          }
          c.mX ^= 0x33u << s0;
        };
        PROF(pb + 17);
#pragma unroll 1
        for (int p = 0; p < 8; p++) {
          const uint32_t s0 = 2 * (p & 1);
          pass(s0, false, [] {});
          wg_wait<0>();
          c.release2(BAR_EMPTYX + 8 * (s0 + 5));
          if (p == 6 && layer == NLAYERS - 1) c.elect = false;
          uint32_t pk[16];
#pragma unroll
          for (int i = 0; i < 16; i++) pk[i] = pack_bf16(d[2 * i], d[2 * i + 1]);
          if (p >= 1 && p < 6 && layer < NLAYERS - 1) {
            const uint32_t o = c.sB + 8 * (p - 1);
            c.release2(BAR_EMPTYB + (o < 40 ? o : o - 40));
          }
          uint4* const dst = ib + ((j + p) & 7) * INBOX;
          if (p == 0) {
            mbar_wait_c(sb + BAR_CLR + 8 * w, 0);
#pragma unroll
            for (int k = 0; k < 8; k++) red2((uint2*)(ib + k * INBOX + 512) - t, pk[2 * k], pk[2 * k + 1]);
          } else if (p < 7) {
#pragma unroll
            for (int k = 0; k < 4; k++) red4(dst + k * 128, pk[4 * k], pk[4 * k + 1], pk[4 * k + 2], pk[4 * k + 3]);
            if (p == 6) { __syncwarp(); if (lane == 0) mbar_arrive(sb + BAR_REDDONE + 8 * w); }
          } else {
#pragma unroll
            for (int k = 0; k < 4; k++) st_relaxed4(gt + ((j + 7) & 7) * 128 + k * 1024, pk[4 * k] & ~1u, pk[4 * k + 1], pk[4 * k + 2], pk[4 * k + 3]);
          }
        }
        PROF(pb + 18);
        const uint4 *in = ib + j * INBOX, *pin = gt + j * 128;
        const uint2* in9 = (const uint2*)(in + 512) - t;
        asm volatile("" : "+l"(in), "+l"(pin), "+l"(in9));
        const float2 r2 = lds64(sb + SM_KEEP + (tid_ >> 2) * 8);
        uint2 X9;
        {
          uint4 X[4];
          const uint4* box = gt + 4608;
#pragma unroll
          for (int k = 0; k < 4; k++) X[k] = ld_relaxed4(box + 256 * j + ((k & 1) + 8 * (k & 2)) * 128);
          X9 = ld_relaxed2((const uint2*)(box + (32 + (j >> 1)) * 128) + (j & 1));
          const float i0 = rcp(r2.x), i1 = rcp(r2.y);
#pragma unroll
          for (int k = 0; k < 4; k++) {
            float* e = d + 8 * k;
            X[k].x ^= (lsb >> k) & 1;
            e[0] = bf_lo(X[k].x) * i0; e[1] = bf_hi(X[k].x) * i0; e[2] = bf_lo(X[k].y) * i1; e[3] = bf_hi(X[k].y) * i1;
            e[4] = bf_lo(X[k].z) * i0; e[5] = bf_hi(X[k].z) * i0; e[6] = bf_lo(X[k].w) * i1; e[7] = bf_hi(X[k].w) * i1;
          }
        }
        uint4 R[4], P[4];
        uint2 R9;
        PROF(pb + 19);
        pass(0, true, [&] {
          mbar_wait_c(sb + BAR_RREADY + 8 * w, layer);
#pragma unroll
          for (int k = 0; k < 4; k++) R[k] = ld_relaxed4(in + k * 128);
          R9 = ld_relaxed2(in9);
#pragma unroll
          for (int k = 0; k < 4; k++) P[k] = ld_relaxed4(pin + k * 1024);
        });
        const uint32_t zero = late(sb + BAR_PAST, 0);
        while (__any_sync(0xffffffffu, (chk2(P[0].x, P[1].x, zero) | chk2(P[2].x, P[3].x, zero)) & 1)) {
#pragma unroll
          for (int k = 0; k < 4; k++) P[k] = ld_relaxed4(pin + k * 1024);
        }
#pragma unroll
        for (int k = 0; k < 4; k++) {
          const uint32_t u[4] = {hadd2(R[k].x, P[k].x), hadd2(R[k].y, P[k].y), hadd2(R[k].z, P[k].z), hadd2(R[k].w, P[k].w)};
#pragma unroll
          for (int i = 0; i < 4; i++) { v[8 * k + 2 * i] = bf_lo(u[i]); v[8 * k + 2 * i + 1] = bf_hi(u[i]); }
        }
        X9.x = chk(zero, X9.x, lsb >> 4);
        v[32] = fmaf(bf_lo(R9.x), r2.x, bf_lo(X9.x)); v[33] = fmaf(bf_hi(R9.x), r2.x, bf_hi(X9.x));
        v[34] = fmaf(bf_lo(R9.y), r2.y, bf_lo(X9.y)); v[35] = fmaf(bf_hi(R9.y), r2.y, bf_hi(X9.y));
        PROF(pb + 20);
        wg_wait<0>();
        c.release2(BAR_EMPTYX + 40);
        PROF(pb + 21);
#pragma unroll
        for (int i = 0; i < 32; i++) v[i] = (v[i] + d[i]) * (i & 2 ? r2.y : r2.x);
      }
      if (layer == NLAYERS - 1) break;
      {
        THREAD_IDS();
        PROF(31);
        rs = ln_gemm<true>(c, G, v, res, sum, st0, j, t, 1, xtag ^ 1, [&](int i) { PROF(32 + i); if (i) PROF(34); }, qkv_mma);
      }
    }
    {
      THREAD_IDS();
      const uint32_t stg = sb + SM_B + warp * 4096;
      const uint32_t sd = stg + (lane & 15) * 128;
#pragma unroll
      for (int i = 0; i < 4; i++)
        stsm4(sd + (((2 * i + (lane >> 4)) ^ (lane & 7)) << 4), pack_bf16(v[8 * i], v[8 * i + 1]), pack_bf16(v[8 * i + 2], v[8 * i + 3]),
              pack_bf16(v[8 * i + 4], v[8 * i + 5]), pack_bf16(v[8 * i + 6], v[8 * i + 7]));
      stsm2(stg + 2048 + (lane & 15) * 16, pack_bf16(v[32], v[33]), pack_bf16(v[34], v[35]));
      __syncwarp();
      char* o = out + (128 * rb + 32 * wp + w) * 1152;
#pragma unroll
      for (int i = 0; i < 4; i++) {
        const int r = 4 * i + (lane >> 3);
        *(uint4*)(o + r * 2304 + 128 * j + 16 * (lane & 7)) = lds128(stg + r * 128 + (((lane ^ r) & 7) << 4));
      }
      if (lane < 16) *(uint4*)(o + lane * 2304 + 1024 + 16 * j) = lds128(stg + 2048 + lane * 16);
      if (lane == 0) {
        if (wp == 0) st_relaxed(G->flag + 32 + 32 * j, xtag);
        mbar_arrive(sb + BAR_DONE + 8 * w);
      }
      PROF(61);
    }
  }
}

typedef CUresult (*EncFn)(CUtensorMap*, CUtensorMapDataType, cuuint32_t, void*, const cuuint64_t*, const cuuint64_t*, const cuuint32_t*,
                          const cuuint32_t*, CUtensorMapInterleave, CUtensorMapSwizzle, CUtensorMapL2promotion, CUtensorMapFloatOOBfill);

void make_map(EncFn enc, CUtensorMap* m, const void* p, int rank, uint64_t d0, uint64_t d1, uint64_t d2, uint64_t s1, uint64_t s2, uint32_t b0,
              uint32_t b1, uint32_t b2, CUtensorMapSwizzle sw) {
  cuuint64_t gd[3] = {d0, d1, d2};
  cuuint64_t gs[2] = {s1, s2};
  cuuint32_t bd[3] = {b0, b1, b2};
  cuuint32_t es[3] = {1, 1, 1};
  enc(m, CU_TENSOR_MAP_DATA_TYPE_BFLOAT16, rank, const_cast<void*>(p), gd, gs, bd, es, CU_TENSOR_MAP_INTERLEAVE_NONE, sw,
      CU_TENSOR_MAP_L2_PROMOTION_L2_128B, CU_TENSOR_MAP_FLOAT_OOB_FILL_NONE);
}

}

extern "C" void kernel_launch(void* const* d_in, const int* in_sizes, int n_in, void* d_out, int out_size) {
  const __nv_bfloat16* x = (const __nv_bfloat16*)d_in[0];
  const char *wqkv = (const char*)d_in[1], *wo = (const char*)d_in[2], *wg = (const char*)d_in[4], *wu = (const char*)d_in[5], *wd = (const char*)d_in[6];
  static EncFn enc = nullptr;
  static uint32_t first = 0;
  static Group* ws = nullptr;
  if (!enc) {
    cudaDriverEntryPointQueryResult qr;
    cudaGetDriverEntryPoint("cuTensorMapEncodeTiled", (void**)&enc, cudaEnableDefault, &qr);
    cudaGetSymbolAddress((void**)&ws, g_ws);
    cudaFuncSetAttribute(fused_kernel, cudaFuncAttributeMaxDynamicSharedMemorySize, SMEM_BYTES);
    cudaLaunchConfig_t cfg = {};
    cfg.gridDim = NCTA + 4; cfg.blockDim = 384; cfg.dynamicSmemBytes = SMEM_BYTES;
    int clusters = 0;
    if (XFIRST || cudaOccupancyMaxActiveClusters(&clusters, fused_kernel, &cfg) != cudaSuccess || 2 * clusters < NCTA + 4) first = 4;
    cudaGetLastError();
  }
  const CUtensorMapSwizzle S0 = CU_TENSOR_MAP_SWIZZLE_NONE, S64 = CU_TENSOR_MAP_SWIZZLE_64B, S128 = CU_TENSOR_MAP_SWIZZLE_128B;
  Maps m;
  make_map(enc, &m.x, x, 3, 576, 2, 1024, 1152, 2304, 64, 1, 64, S128);
  make_map(enc, &m.qm, wqkv, 3, 576, 576, 3, 3456, 1152, 64, 16, 3, S128);
  make_map(enc, &m.qc, wqkv, 3, 576, 576, 3, 3456, 1152, 8, 16, 3, S0);
  make_map(enc, &m.o, wo, 2, 576, 576, 1, 1152, 0, 64, 72, 1, S128);
  make_map(enc, &m.g, wg, 3, 64, 576, 72, 9216, 128, 64, 32, 2, S128);
  make_map(enc, &m.u, wu, 3, 64, 576, 72, 9216, 128, 64, 32, 2, S128);
  make_map(enc, &m.g3, wg, 3, 32, 576, 144, 9216, 64, 32, 32, 3, S64);
  make_map(enc, &m.u3, wu, 3, 32, 576, 144, 9216, 64, 32, 32, 3, S64);
  make_map(enc, &m.d, wd, 2, 576, 4608, 1, 1152, 0, 64, 72, 1, S128);
  fused_kernel<<<NCTA + 4, 384, SMEM_BYTES>>>(x, ws, wqkv, wo, (char*)d_out, first, m, wg, wu);
}
```

```cpp
#include <cuda_runtime.h>
#include <cuda_bf16.h>
#include <cuda.h>
#include <stdint.h>
#include <stddef.h>

namespace {

constexpr int NCTA = 128;
#define NLAYERS 2
#define XFIRST 0
constexpr uint32_t SM_X = 0;
constexpr uint32_t XSLOT = 18432;
__host__ __device__ constexpr uint32_t xslot(uint32_t s) { return SM_X + (s ^ 4) * XSLOT; }
constexpr uint32_t SM_WOC = xslot(3) + 8192;
constexpr uint32_t SM_B = 147456;
constexpr uint32_t BSLOT = 16384;
constexpr uint32_t SM_KEEP = 229376;
constexpr uint32_t SM_WSUM = SM_KEEP + 512;
constexpr uint32_t SM_BAR = SM_KEEP + 2048;
constexpr uint32_t BAR_FULLB = SM_BAR;
constexpr uint32_t BAR_RREADY = SM_BAR + 40;
constexpr uint32_t BAR_CLR = SM_BAR + 56;
constexpr uint32_t BAR_FULLX = SM_BAR + 72;
constexpr uint32_t BAR_PAST = BAR_FULLX + 64;
constexpr uint32_t BAR_EMPTYB = SM_BAR + 144;
constexpr uint32_t BAR_EMPTYX = SM_BAR + 184;
constexpr uint32_t BAR_REDDONE = SM_BAR + 248;
constexpr uint32_t BAR_DONE = SM_BAR + 264;
constexpr uint32_t SM_PROG = SM_BAR + 288;
constexpr uint32_t SMEM_BYTES = SM_BAR + 1024;

struct Maps { CUtensorMap x, qm, qc, o, g, u, g3, u3, d; };

constexpr int INBOX = 576;
struct Group {
  uint2 sum[4 * 8 * 8];
  uint2 sq[4 * 8 * 8];
  uint32_t flag[1024];
  uint4 halo[8 * 160];
  uint4 obox[36 * 128];
  uint4 xbox[36 * 128];
  uint4 inbox[2][8 * INBOX];
};
struct Scratch { Group g[32]; uint4 wq[8][36][432]; uint4 woc[8][720]; uint32_t done[64]; };
__device__ __align__(1024) Scratch g_ws;
#define PROF(i)
#define PROFX(i)

struct Desc { uint32_t lo, hi; };
__device__ __forceinline__ constexpr Desc desc_hi(uint32_t lbo, uint32_t sbo, uint32_t sw) { return Desc{(lbo >> 4) << 16, (sbo >> 4) | sw << 30}; }
__device__ __forceinline__ constexpr Desc operator+(Desc d, uint32_t a) { return Desc{d.lo + a, d.hi}; }

template<int N> __device__ __forceinline__ void wgmma_ss(float (&d)[N / 2], Desc da, Desc db, int sc);
template<> __device__ __forceinline__ void wgmma_ss<192>(float (&d)[96], Desc da, Desc db, int sc) {
  asm volatile("{\n.reg .pred p;\n.reg .b64 a, b;\nsetp.ne.b32 p, %100, 0;\nmov.b64 a, {%96, %97};\nmov.b64 b, {%98, %99};\n"
    "wgmma.mma_async.sync.aligned.m64n192k16.f32.bf16.bf16 {%0,%1,%2,%3,%4,%5,%6,%7,%8,%9,%10,%11,%12,%13,%14,%15,%16,%17,%18,%19,%20,%21,%22,%23,%24,%25,%26,%27,%28,%29,%30,%31,%32,%33,%34,%35,%36,%37,%38,%39,%40,%41,%42,%43,%44,%45,%46,%47,%48,%49,%50,%51,%52,%53,%54,%55,%56,%57,%58,%59,%60,%61,%62,%63,%64,%65,%66,%67,%68,%69,%70,%71,%72,%73,%74,%75,%76,%77,%78,%79,%80,%81,%82,%83,%84,%85,%86,%87,%88,%89,%90,%91,%92,%93,%94,%95}, a, b, p, 1, 1, 0, 1;\n}\n"
    : "+f"(d[0]),"+f"(d[1]),"+f"(d[2]),"+f"(d[3]),"+f"(d[4]),"+f"(d[5]),"+f"(d[6]),"+f"(d[7]),"+f"(d[8]),"+f"(d[9]),"+f"(d[10]),"+f"(d[11]),"+f"(d[12]),"+f"(d[13]),"+f"(d[14]),"+f"(d[15]),"+f"(d[16]),"+f"(d[17]),"+f"(d[18]),"+f"(d[19]),"+f"(d[20]),"+f"(d[21]),"+f"(d[22]),"+f"(d[23]),"+f"(d[24]),"+f"(d[25]),"+f"(d[26]),"+f"(d[27]),"+f"(d[28]),"+f"(d[29]),"+f"(d[30]),"+f"(d[31]),"+f"(d[32]),"+f"(d[33]),"+f"(d[34]),"+f"(d[35]),"+f"(d[36]),"+f"(d[37]),"+f"(d[38]),"+f"(d[39]),"+f"(d[40]),"+f"(d[41]),"+f"(d[42]),"+f"(d[43]),"+f"(d[44]),"+f"(d[45]),"+f"(d[46]),"+f"(d[47]),"+f"(d[48]),"+f"(d[49]),"+f"(d[50]),"+f"(d[51]),"+f"(d[52]),"+f"(d[53]),"+f"(d[54]),"+f"(d[55]),"+f"(d[56]),"+f"(d[57]),"+f"(d[58]),"+f"(d[59]),"+f"(d[60]),"+f"(d[61]),"+f"(d[62]),"+f"(d[63]),"+f"(d[64]),"+f"(d[65]),"+f"(d[66]),"+f"(d[67]),"+f"(d[68]),"+f"(d[69]),"+f"(d[70]),"+f"(d[71]),"+f"(d[72]),"+f"(d[73]),"+f"(d[74]),"+f"(d[75]),"+f"(d[76]),"+f"(d[77]),"+f"(d[78]),"+f"(d[79]),"+f"(d[80]),"+f"(d[81]),"+f"(d[82]),"+f"(d[83]),"+f"(d[84]),"+f"(d[85]),"+f"(d[86]),"+f"(d[87]),"+f"(d[88]),"+f"(d[89]),"+f"(d[90]),"+f"(d[91]),"+f"(d[92]),"+f"(d[93]),"+f"(d[94]),"+f"(d[95]) : "r"(da.lo), "r"(da.hi), "r"(db.lo), "r"(db.hi), "r"(sc));
}
template<> __device__ __forceinline__ void wgmma_ss<256>(float (&d)[128], Desc da, Desc db, int sc) {
  asm volatile("{\n.reg .pred p;\n.reg .b64 a, b;\nsetp.ne.b32 p, %132, 0;\nmov.b64 a, {%128, %129};\nmov.b64 b, {%130, %131};\n"
    "wgmma.mma_async.sync.aligned.m64n256k16.f32.bf16.bf16 {%0,%1,%2,%3,%4,%5,%6,%7,%8,%9,%10,%11,%12,%13,%14,%15,%16,%17,%18,%19,%20,%21,%22,%23,%24,%25,%26,%27,%28,%29,%30,%31,%32,%33,%34,%35,%36,%37,%38,%39,%40,%41,%42,%43,%44,%45,%46,%47,%48,%49,%50,%51,%52,%53,%54,%55,%56,%57,%58,%59,%60,%61,%62,%63,%64,%65,%66,%67,%68,%69,%70,%71,%72,%73,%74,%75,%76,%77,%78,%79,%80,%81,%82,%83,%84,%85,%86,%87,%88,%89,%90,%91,%92,%93,%94,%95,%96,%97,%98,%99,%100,%101,%102,%103,%104,%105,%106,%107,%108,%109,%110,%111,%112,%113,%114,%115,%116,%117,%118,%119,%120,%121,%122,%123,%124,%125,%126,%127}, a, b, p, 1, 1, 0, 1;\n}\n"
    : "+f"(d[0]),"+f"(d[1]),"+f"(d[2]),"+f"(d[3]),"+f"(d[4]),"+f"(d[5]),"+f"(d[6]),"+f"(d[7]),"+f"(d[8]),"+f"(d[9]),"+f"(d[10]),"+f"(d[11]),"+f"(d[12]),"+f"(d[13]),"+f"(d[14]),"+f"(d[15]),"+f"(d[16]),"+f"(d[17]),"+f"(d[18]),"+f"(d[19]),"+f"(d[20]),"+f"(d[21]),"+f"(d[22]),"+f"(d[23]),"+f"(d[24]),"+f"(d[25]),"+f"(d[26]),"+f"(d[27]),"+f"(d[28]),"+f"(d[29]),"+f"(d[30]),"+f"(d[31]),"+f"(d[32]),"+f"(d[33]),"+f"(d[34]),"+f"(d[35]),"+f"(d[36]),"+f"(d[37]),"+f"(d[38]),"+f"(d[39]),"+f"(d[40]),"+f"(d[41]),"+f"(d[42]),"+f"(d[43]),"+f"(d[44]),"+f"(d[45]),"+f"(d[46]),"+f"(d[47]),"+f"(d[48]),"+f"(d[49]),"+f"(d[50]),"+f"(d[51]),"+f"(d[52]),"+f"(d[53]),"+f"(d[54]),"+f"(d[55]),"+f"(d[56]),"+f"(d[57]),"+f"(d[58]),"+f"(d[59]),"+f"(d[60]),"+f"(d[61]),"+f"(d[62]),"+f"(d[63]),"+f"(d[64]),"+f"(d[65]),"+f"(d[66]),"+f"(d[67]),"+f"(d[68]),"+f"(d[69]),"+f"(d[70]),"+f"(d[71]),"+f"(d[72]),"+f"(d[73]),"+f"(d[74]),"+f"(d[75]),"+f"(d[76]),"+f"(d[77]),"+f"(d[78]),"+f"(d[79]),"+f"(d[80]),"+f"(d[81]),"+f"(d[82]),"+f"(d[83]),"+f"(d[84]),"+f"(d[85]),"+f"(d[86]),"+f"(d[87]),"+f"(d[88]),"+f"(d[89]),"+f"(d[90]),"+f"(d[91]),"+f"(d[92]),"+f"(d[93]),"+f"(d[94]),"+f"(d[95]),"+f"(d[96]),"+f"(d[97]),"+f"(d[98]),"+f"(d[99]),"+f"(d[100]),"+f"(d[101]),"+f"(d[102]),"+f"(d[103]),"+f"(d[104]),"+f"(d[105]),"+f"(d[106]),"+f"(d[107]),"+f"(d[108]),"+f"(d[109]),"+f"(d[110]),"+f"(d[111]),"+f"(d[112]),"+f"(d[113]),"+f"(d[114]),"+f"(d[115]),"+f"(d[116]),"+f"(d[117]),"+f"(d[118]),"+f"(d[119]),"+f"(d[120]),"+f"(d[121]),"+f"(d[122]),"+f"(d[123]),"+f"(d[124]),"+f"(d[125]),"+f"(d[126]),"+f"(d[127]) : "r"(da.lo), "r"(da.hi), "r"(db.lo), "r"(db.hi), "r"(sc));
}
template<int N, int ACC> __device__ __forceinline__ void wgmma_rs(float (&d)[N / 2], const uint4& a, Desc db);
template<> __device__ __forceinline__ void wgmma_rs<8, 1>(float (&d)[4], const uint4& a, Desc db) {
  asm volatile("{\n.reg .pred p;\n.reg .b64 b;\nsetp.ne.b32 p, 1, 0;\nmov.b64 b, {%8, %9};\n"
    "wgmma.mma_async.sync.aligned.m64n8k16.f32.bf16.bf16 {%0,%1,%2,%3}, {%4,%5,%6,%7}, b, p, 1, 1, 1;\n}\n"
    : "+f"(d[0]),"+f"(d[1]),"+f"(d[2]),"+f"(d[3]) : "r"(a.x), "r"(a.y), "r"(a.z), "r"(a.w), "r"(db.lo), "r"(db.hi));
}
template<> __device__ __forceinline__ void wgmma_rs<8, 0>(float (&d)[4], const uint4& a, Desc db) {
  asm volatile("{\n.reg .pred p;\n.reg .b64 b;\nsetp.ne.b32 p, 0, 0;\nmov.b64 b, {%8, %9};\n"
    "wgmma.mma_async.sync.aligned.m64n8k16.f32.bf16.bf16 {%0,%1,%2,%3}, {%4,%5,%6,%7}, b, p, 1, 1, 1;\n}\n"
    : "=f"(d[0]),"=f"(d[1]),"=f"(d[2]),"=f"(d[3]) : "r"(a.x), "r"(a.y), "r"(a.z), "r"(a.w), "r"(db.lo), "r"(db.hi));
}
template<> __device__ __forceinline__ void wgmma_rs<24, 1>(float (&d)[12], const uint4& a, Desc db) {
  asm volatile("{\n.reg .pred p;\n.reg .b64 b;\nsetp.ne.b32 p, 1, 0;\nmov.b64 b, {%16, %17};\n"
    "wgmma.mma_async.sync.aligned.m64n24k16.f32.bf16.bf16 {%0,%1,%2,%3,%4,%5,%6,%7,%8,%9,%10,%11}, {%12,%13,%14,%15}, b, p, 1, 1, 1;\n}\n"
    : "+f"(d[0]),"+f"(d[1]),"+f"(d[2]),"+f"(d[3]),"+f"(d[4]),"+f"(d[5]),"+f"(d[6]),"+f"(d[7]),"+f"(d[8]),"+f"(d[9]),"+f"(d[10]),"+f"(d[11]) : "r"(a.x), "r"(a.y), "r"(a.z), "r"(a.w), "r"(db.lo), "r"(db.hi));
}
template<> __device__ __forceinline__ void wgmma_rs<24, 0>(float (&d)[12], const uint4& a, Desc db) {
  asm volatile("{\n.reg .pred p;\n.reg .b64 b;\nsetp.ne.b32 p, 0, 0;\nmov.b64 b, {%16, %17};\n"
    "wgmma.mma_async.sync.aligned.m64n24k16.f32.bf16.bf16 {%0,%1,%2,%3,%4,%5,%6,%7,%8,%9,%10,%11}, {%12,%13,%14,%15}, b, p, 1, 1, 1;\n}\n"
    : "=f"(d[0]),"=f"(d[1]),"=f"(d[2]),"=f"(d[3]),"=f"(d[4]),"=f"(d[5]),"=f"(d[6]),"=f"(d[7]),"=f"(d[8]),"=f"(d[9]),"=f"(d[10]),"=f"(d[11]) : "r"(a.x), "r"(a.y), "r"(a.z), "r"(a.w), "r"(db.lo), "r"(db.hi));
}
template<> __device__ __forceinline__ void wgmma_rs<64, 1>(float (&d)[32], const uint4& a, Desc db) {
  asm volatile("{\n.reg .pred p;\n.reg .b64 b;\nsetp.ne.b32 p, 1, 0;\nmov.b64 b, {%36, %37};\n"
    "wgmma.mma_async.sync.aligned.m64n64k16.f32.bf16.bf16 {%0,%1,%2,%3,%4,%5,%6,%7,%8,%9,%10,%11,%12,%13,%14,%15,%16,%17,%18,%19,%20,%21,%22,%23,%24,%25,%26,%27,%28,%29,%30,%31}, {%32,%33,%34,%35}, b, p, 1, 1, 1;\n}\n"
    : "+f"(d[0]),"+f"(d[1]),"+f"(d[2]),"+f"(d[3]),"+f"(d[4]),"+f"(d[5]),"+f"(d[6]),"+f"(d[7]),"+f"(d[8]),"+f"(d[9]),"+f"(d[10]),"+f"(d[11]),"+f"(d[12]),"+f"(d[13]),"+f"(d[14]),"+f"(d[15]),"+f"(d[16]),"+f"(d[17]),"+f"(d[18]),"+f"(d[19]),"+f"(d[20]),"+f"(d[21]),"+f"(d[22]),"+f"(d[23]),"+f"(d[24]),"+f"(d[25]),"+f"(d[26]),"+f"(d[27]),"+f"(d[28]),"+f"(d[29]),"+f"(d[30]),"+f"(d[31]) : "r"(a.x), "r"(a.y), "r"(a.z), "r"(a.w), "r"(db.lo), "r"(db.hi));
}
template<> __device__ __forceinline__ void wgmma_rs<64, 0>(float (&d)[32], const uint4& a, Desc db) {
  asm volatile("{\n.reg .pred p;\n.reg .b64 b;\nsetp.ne.b32 p, 0, 0;\nmov.b64 b, {%36, %37};\n"
    "wgmma.mma_async.sync.aligned.m64n64k16.f32.bf16.bf16 {%0,%1,%2,%3,%4,%5,%6,%7,%8,%9,%10,%11,%12,%13,%14,%15,%16,%17,%18,%19,%20,%21,%22,%23,%24,%25,%26,%27,%28,%29,%30,%31}, {%32,%33,%34,%35}, b, p, 1, 1, 1;\n}\n"
    : "=f"(d[0]),"=f"(d[1]),"=f"(d[2]),"=f"(d[3]),"=f"(d[4]),"=f"(d[5]),"=f"(d[6]),"=f"(d[7]),"=f"(d[8]),"=f"(d[9]),"=f"(d[10]),"=f"(d[11]),"=f"(d[12]),"=f"(d[13]),"=f"(d[14]),"=f"(d[15]),"=f"(d[16]),"=f"(d[17]),"=f"(d[18]),"=f"(d[19]),"=f"(d[20]),"=f"(d[21]),"=f"(d[22]),"=f"(d[23]),"=f"(d[24]),"=f"(d[25]),"=f"(d[26]),"=f"(d[27]),"=f"(d[28]),"=f"(d[29]),"=f"(d[30]),"=f"(d[31]) : "r"(a.x), "r"(a.y), "r"(a.z), "r"(a.w), "r"(db.lo), "r"(db.hi));
}
template<> __device__ __forceinline__ void wgmma_rs<72, 1>(float (&d)[36], const uint4& a, Desc db) {
  asm volatile("{\n.reg .pred p;\n.reg .b64 b;\nsetp.ne.b32 p, 1, 0;\nmov.b64 b, {%40, %41};\n"
    "wgmma.mma_async.sync.aligned.m64n72k16.f32.bf16.bf16 {%0,%1,%2,%3,%4,%5,%6,%7,%8,%9,%10,%11,%12,%13,%14,%15,%16,%17,%18,%19,%20,%21,%22,%23,%24,%25,%26,%27,%28,%29,%30,%31,%32,%33,%34,%35}, {%36,%37,%38,%39}, b, p, 1, 1, 1;\n}\n"
    : "+f"(d[0]),"+f"(d[1]),"+f"(d[2]),"+f"(d[3]),"+f"(d[4]),"+f"(d[5]),"+f"(d[6]),"+f"(d[7]),"+f"(d[8]),"+f"(d[9]),"+f"(d[10]),"+f"(d[11]),"+f"(d[12]),"+f"(d[13]),"+f"(d[14]),"+f"(d[15]),"+f"(d[16]),"+f"(d[17]),"+f"(d[18]),"+f"(d[19]),"+f"(d[20]),"+f"(d[21]),"+f"(d[22]),"+f"(d[23]),"+f"(d[24]),"+f"(d[25]),"+f"(d[26]),"+f"(d[27]),"+f"(d[28]),"+f"(d[29]),"+f"(d[30]),"+f"(d[31]),"+f"(d[32]),"+f"(d[33]),"+f"(d[34]),"+f"(d[35]) : "r"(a.x), "r"(a.y), "r"(a.z), "r"(a.w), "r"(db.lo), "r"(db.hi));
}
template<> __device__ __forceinline__ void wgmma_rs<72, 0>(float (&d)[36], const uint4& a, Desc db) {
  asm volatile("{\n.reg .pred p;\n.reg .b64 b;\nsetp.ne.b32 p, 0, 0;\nmov.b64 b, {%40, %41};\n"
    "wgmma.mma_async.sync.aligned.m64n72k16.f32.bf16.bf16 {%0,%1,%2,%3,%4,%5,%6,%7,%8,%9,%10,%11,%12,%13,%14,%15,%16,%17,%18,%19,%20,%21,%22,%23,%24,%25,%26,%27,%28,%29,%30,%31,%32,%33,%34,%35}, {%36,%37,%38,%39}, b, p, 1, 1, 1;\n}\n"
    : "=f"(d[0]),"=f"(d[1]),"=f"(d[2]),"=f"(d[3]),"=f"(d[4]),"=f"(d[5]),"=f"(d[6]),"=f"(d[7]),"=f"(d[8]),"=f"(d[9]),"=f"(d[10]),"=f"(d[11]),"=f"(d[12]),"=f"(d[13]),"=f"(d[14]),"=f"(d[15]),"=f"(d[16]),"=f"(d[17]),"=f"(d[18]),"=f"(d[19]),"=f"(d[20]),"=f"(d[21]),"=f"(d[22]),"=f"(d[23]),"=f"(d[24]),"=f"(d[25]),"=f"(d[26]),"=f"(d[27]),"=f"(d[28]),"=f"(d[29]),"=f"(d[30]),"=f"(d[31]),"=f"(d[32]),"=f"(d[33]),"=f"(d[34]),"=f"(d[35]) : "r"(a.x), "r"(a.y), "r"(a.z), "r"(a.w), "r"(db.lo), "r"(db.hi));
}
template<> __device__ __forceinline__ void wgmma_rs<192, 1>(float (&d)[96], const uint4& a, Desc db) {
  asm volatile("{\n.reg .pred p;\n.reg .b64 b;\nsetp.ne.b32 p, 1, 0;\nmov.b64 b, {%100, %101};\n"
    "wgmma.mma_async.sync.aligned.m64n192k16.f32.bf16.bf16 {%0,%1,%2,%3,%4,%5,%6,%7,%8,%9,%10,%11,%12,%13,%14,%15,%16,%17,%18,%19,%20,%21,%22,%23,%24,%25,%26,%27,%28,%29,%30,%31,%32,%33,%34,%35,%36,%37,%38,%39,%40,%41,%42,%43,%44,%45,%46,%47,%48,%49,%50,%51,%52,%53,%54,%55,%56,%57,%58,%59,%60,%61,%62,%63,%64,%65,%66,%67,%68,%69,%70,%71,%72,%73,%74,%75,%76,%77,%78,%79,%80,%81,%82,%83,%84,%85,%86,%87,%88,%89,%90,%91,%92,%93,%94,%95}, {%96,%97,%98,%99}, b, p, 1, 1, 1;\n}\n"
    : "+f"(d[0]),"+f"(d[1]),"+f"(d[2]),"+f"(d[3]),"+f"(d[4]),"+f"(d[5]),"+f"(d[6]),"+f"(d[7]),"+f"(d[8]),"+f"(d[9]),"+f"(d[10]),"+f"(d[11]),"+f"(d[12]),"+f"(d[13]),"+f"(d[14]),"+f"(d[15]),"+f"(d[16]),"+f"(d[17]),"+f"(d[18]),"+f"(d[19]),"+f"(d[20]),"+f"(d[21]),"+f"(d[22]),"+f"(d[23]),"+f"(d[24]),"+f"(d[25]),"+f"(d[26]),"+f"(d[27]),"+f"(d[28]),"+f"(d[29]),"+f"(d[30]),"+f"(d[31]),"+f"(d[32]),"+f"(d[33]),"+f"(d[34]),"+f"(d[35]),"+f"(d[36]),"+f"(d[37]),"+f"(d[38]),"+f"(d[39]),"+f"(d[40]),"+f"(d[41]),"+f"(d[42]),"+f"(d[43]),"+f"(d[44]),"+f"(d[45]),"+f"(d[46]),"+f"(d[47]),"+f"(d[48]),"+f"(d[49]),"+f"(d[50]),"+f"(d[51]),"+f"(d[52]),"+f"(d[53]),"+f"(d[54]),"+f"(d[55]),"+f"(d[56]),"+f"(d[57]),"+f"(d[58]),"+f"(d[59]),"+f"(d[60]),"+f"(d[61]),"+f"(d[62]),"+f"(d[63]),"+f"(d[64]),"+f"(d[65]),"+f"(d[66]),"+f"(d[67]),"+f"(d[68]),"+f"(d[69]),"+f"(d[70]),"+f"(d[71]),"+f"(d[72]),"+f"(d[73]),"+f"(d[74]),"+f"(d[75]),"+f"(d[76]),"+f"(d[77]),"+f"(d[78]),"+f"(d[79]),"+f"(d[80]),"+f"(d[81]),"+f"(d[82]),"+f"(d[83]),"+f"(d[84]),"+f"(d[85]),"+f"(d[86]),"+f"(d[87]),"+f"(d[88]),"+f"(d[89]),"+f"(d[90]),"+f"(d[91]),"+f"(d[92]),"+f"(d[93]),"+f"(d[94]),"+f"(d[95]) : "r"(a.x), "r"(a.y), "r"(a.z), "r"(a.w), "r"(db.lo), "r"(db.hi));
}
template<> __device__ __forceinline__ void wgmma_rs<192, 0>(float (&d)[96], const uint4& a, Desc db) {
  asm volatile("{\n.reg .pred p;\n.reg .b64 b;\nsetp.ne.b32 p, 0, 0;\nmov.b64 b, {%100, %101};\n"
    "wgmma.mma_async.sync.aligned.m64n192k16.f32.bf16.bf16 {%0,%1,%2,%3,%4,%5,%6,%7,%8,%9,%10,%11,%12,%13,%14,%15,%16,%17,%18,%19,%20,%21,%22,%23,%24,%25,%26,%27,%28,%29,%30,%31,%32,%33,%34,%35,%36,%37,%38,%39,%40,%41,%42,%43,%44,%45,%46,%47,%48,%49,%50,%51,%52,%53,%54,%55,%56,%57,%58,%59,%60,%61,%62,%63,%64,%65,%66,%67,%68,%69,%70,%71,%72,%73,%74,%75,%76,%77,%78,%79,%80,%81,%82,%83,%84,%85,%86,%87,%88,%89,%90,%91,%92,%93,%94,%95}, {%96,%97,%98,%99}, b, p, 1, 1, 1;\n}\n"
    : "=f"(d[0]),"=f"(d[1]),"=f"(d[2]),"=f"(d[3]),"=f"(d[4]),"=f"(d[5]),"=f"(d[6]),"=f"(d[7]),"=f"(d[8]),"=f"(d[9]),"=f"(d[10]),"=f"(d[11]),"=f"(d[12]),"=f"(d[13]),"=f"(d[14]),"=f"(d[15]),"=f"(d[16]),"=f"(d[17]),"=f"(d[18]),"=f"(d[19]),"=f"(d[20]),"=f"(d[21]),"=f"(d[22]),"=f"(d[23]),"=f"(d[24]),"=f"(d[25]),"=f"(d[26]),"=f"(d[27]),"=f"(d[28]),"=f"(d[29]),"=f"(d[30]),"=f"(d[31]),"=f"(d[32]),"=f"(d[33]),"=f"(d[34]),"=f"(d[35]),"=f"(d[36]),"=f"(d[37]),"=f"(d[38]),"=f"(d[39]),"=f"(d[40]),"=f"(d[41]),"=f"(d[42]),"=f"(d[43]),"=f"(d[44]),"=f"(d[45]),"=f"(d[46]),"=f"(d[47]),"=f"(d[48]),"=f"(d[49]),"=f"(d[50]),"=f"(d[51]),"=f"(d[52]),"=f"(d[53]),"=f"(d[54]),"=f"(d[55]),"=f"(d[56]),"=f"(d[57]),"=f"(d[58]),"=f"(d[59]),"=f"(d[60]),"=f"(d[61]),"=f"(d[62]),"=f"(d[63]),"=f"(d[64]),"=f"(d[65]),"=f"(d[66]),"=f"(d[67]),"=f"(d[68]),"=f"(d[69]),"=f"(d[70]),"=f"(d[71]),"=f"(d[72]),"=f"(d[73]),"=f"(d[74]),"=f"(d[75]),"=f"(d[76]),"=f"(d[77]),"=f"(d[78]),"=f"(d[79]),"=f"(d[80]),"=f"(d[81]),"=f"(d[82]),"=f"(d[83]),"=f"(d[84]),"=f"(d[85]),"=f"(d[86]),"=f"(d[87]),"=f"(d[88]),"=f"(d[89]),"=f"(d[90]),"=f"(d[91]),"=f"(d[92]),"=f"(d[93]),"=f"(d[94]),"=f"(d[95]) : "r"(a.x), "r"(a.y), "r"(a.z), "r"(a.w), "r"(db.lo), "r"(db.hi));
}
template<> __device__ __forceinline__ void wgmma_rs<256, 1>(float (&d)[128], const uint4& a, Desc db) {
  asm volatile("{\n.reg .pred p;\n.reg .b64 b;\nsetp.ne.b32 p, 1, 0;\nmov.b64 b, {%132, %133};\n"
    "wgmma.mma_async.sync.aligned.m64n256k16.f32.bf16.bf16 {%0,%1,%2,%3,%4,%5,%6,%7,%8,%9,%10,%11,%12,%13,%14,%15,%16,%17,%18,%19,%20,%21,%22,%23,%24,%25,%26,%27,%28,%29,%30,%31,%32,%33,%34,%35,%36,%37,%38,%39,%40,%41,%42,%43,%44,%45,%46,%47,%48,%49,%50,%51,%52,%53,%54,%55,%56,%57,%58,%59,%60,%61,%62,%63,%64,%65,%66,%67,%68,%69,%70,%71,%72,%73,%74,%75,%76,%77,%78,%79,%80,%81,%82,%83,%84,%85,%86,%87,%88,%89,%90,%91,%92,%93,%94,%95,%96,%97,%98,%99,%100,%101,%102,%103,%104,%105,%106,%107,%108,%109,%110,%111,%112,%113,%114,%115,%116,%117,%118,%119,%120,%121,%122,%123,%124,%125,%126,%127}, {%128,%129,%130,%131}, b, p, 1, 1, 1;\n}\n"
    : "+f"(d[0]),"+f"(d[1]),"+f"(d[2]),"+f"(d[3]),"+f"(d[4]),"+f"(d[5]),"+f"(d[6]),"+f"(d[7]),"+f"(d[8]),"+f"(d[9]),"+f"(d[10]),"+f"(d[11]),"+f"(d[12]),"+f"(d[13]),"+f"(d[14]),"+f"(d[15]),"+f"(d[16]),"+f"(d[17]),"+f"(d[18]),"+f"(d[19]),"+f"(d[20]),"+f"(d[21]),"+f"(d[22]),"+f"(d[23]),"+f"(d[24]),"+f"(d[25]),"+f"(d[26]),"+f"(d[27]),"+f"(d[28]),"+f"(d[29]),"+f"(d[30]),"+f"(d[31]),"+f"(d[32]),"+f"(d[33]),"+f"(d[34]),"+f"(d[35]),"+f"(d[36]),"+f"(d[37]),"+f"(d[38]),"+f"(d[39]),"+f"(d[40]),"+f"(d[41]),"+f"(d[42]),"+f"(d[43]),"+f"(d[44]),"+f"(d[45]),"+f"(d[46]),"+f"(d[47]),"+f"(d[48]),"+f"(d[49]),"+f"(d[50]),"+f"(d[51]),"+f"(d[52]),"+f"(d[53]),"+f"(d[54]),"+f"(d[55]),"+f"(d[56]),"+f"(d[57]),"+f"(d[58]),"+f"(d[59]),"+f"(d[60]),"+f"(d[61]),"+f"(d[62]),"+f"(d[63]),"+f"(d[64]),"+f"(d[65]),"+f"(d[66]),"+f"(d[67]),"+f"(d[68]),"+f"(d[69]),"+f"(d[70]),"+f"(d[71]),"+f"(d[72]),"+f"(d[73]),"+f"(d[74]),"+f"(d[75]),"+f"(d[76]),"+f"(d[77]),"+f"(d[78]),"+f"(d[79]),"+f"(d[80]),"+f"(d[81]),"+f"(d[82]),"+f"(d[83]),"+f"(d[84]),"+f"(d[85]),"+f"(d[86]),"+f"(d[87]),"+f"(d[88]),"+f"(d[89]),"+f"(d[90]),"+f"(d[91]),"+f"(d[92]),"+f"(d[93]),"+f"(d[94]),"+f"(d[95]),"+f"(d[96]),"+f"(d[97]),"+f"(d[98]),"+f"(d[99]),"+f"(d[100]),"+f"(d[101]),"+f"(d[102]),"+f"(d[103]),"+f"(d[104]),"+f"(d[105]),"+f"(d[106]),"+f"(d[107]),"+f"(d[108]),"+f"(d[109]),"+f"(d[110]),"+f"(d[111]),"+f"(d[112]),"+f"(d[113]),"+f"(d[114]),"+f"(d[115]),"+f"(d[116]),"+f"(d[117]),"+f"(d[118]),"+f"(d[119]),"+f"(d[120]),"+f"(d[121]),"+f"(d[122]),"+f"(d[123]),"+f"(d[124]),"+f"(d[125]),"+f"(d[126]),"+f"(d[127]) : "r"(a.x), "r"(a.y), "r"(a.z), "r"(a.w), "r"(db.lo), "r"(db.hi));
}
template<> __device__ __forceinline__ void wgmma_rs<256, 0>(float (&d)[128], const uint4& a, Desc db) {
  asm volatile("{\n.reg .pred p;\n.reg .b64 b;\nsetp.ne.b32 p, 0, 0;\nmov.b64 b, {%132, %133};\n"
    "wgmma.mma_async.sync.aligned.m64n256k16.f32.bf16.bf16 {%0,%1,%2,%3,%4,%5,%6,%7,%8,%9,%10,%11,%12,%13,%14,%15,%16,%17,%18,%19,%20,%21,%22,%23,%24,%25,%26,%27,%28,%29,%30,%31,%32,%33,%34,%35,%36,%37,%38,%39,%40,%41,%42,%43,%44,%45,%46,%47,%48,%49,%50,%51,%52,%53,%54,%55,%56,%57,%58,%59,%60,%61,%62,%63,%64,%65,%66,%67,%68,%69,%70,%71,%72,%73,%74,%75,%76,%77,%78,%79,%80,%81,%82,%83,%84,%85,%86,%87,%88,%89,%90,%91,%92,%93,%94,%95,%96,%97,%98,%99,%100,%101,%102,%103,%104,%105,%106,%107,%108,%109,%110,%111,%112,%113,%114,%115,%116,%117,%118,%119,%120,%121,%122,%123,%124,%125,%126,%127}, {%128,%129,%130,%131}, b, p, 1, 1, 1;\n}\n"
    : "=f"(d[0]),"=f"(d[1]),"=f"(d[2]),"=f"(d[3]),"=f"(d[4]),"=f"(d[5]),"=f"(d[6]),"=f"(d[7]),"=f"(d[8]),"=f"(d[9]),"=f"(d[10]),"=f"(d[11]),"=f"(d[12]),"=f"(d[13]),"=f"(d[14]),"=f"(d[15]),"=f"(d[16]),"=f"(d[17]),"=f"(d[18]),"=f"(d[19]),"=f"(d[20]),"=f"(d[21]),"=f"(d[22]),"=f"(d[23]),"=f"(d[24]),"=f"(d[25]),"=f"(d[26]),"=f"(d[27]),"=f"(d[28]),"=f"(d[29]),"=f"(d[30]),"=f"(d[31]),"=f"(d[32]),"=f"(d[33]),"=f"(d[34]),"=f"(d[35]),"=f"(d[36]),"=f"(d[37]),"=f"(d[38]),"=f"(d[39]),"=f"(d[40]),"=f"(d[41]),"=f"(d[42]),"=f"(d[43]),"=f"(d[44]),"=f"(d[45]),"=f"(d[46]),"=f"(d[47]),"=f"(d[48]),"=f"(d[49]),"=f"(d[50]),"=f"(d[51]),"=f"(d[52]),"=f"(d[53]),"=f"(d[54]),"=f"(d[55]),"=f"(d[56]),"=f"(d[57]),"=f"(d[58]),"=f"(d[59]),"=f"(d[60]),"=f"(d[61]),"=f"(d[62]),"=f"(d[63]),"=f"(d[64]),"=f"(d[65]),"=f"(d[66]),"=f"(d[67]),"=f"(d[68]),"=f"(d[69]),"=f"(d[70]),"=f"(d[71]),"=f"(d[72]),"=f"(d[73]),"=f"(d[74]),"=f"(d[75]),"=f"(d[76]),"=f"(d[77]),"=f"(d[78]),"=f"(d[79]),"=f"(d[80]),"=f"(d[81]),"=f"(d[82]),"=f"(d[83]),"=f"(d[84]),"=f"(d[85]),"=f"(d[86]),"=f"(d[87]),"=f"(d[88]),"=f"(d[89]),"=f"(d[90]),"=f"(d[91]),"=f"(d[92]),"=f"(d[93]),"=f"(d[94]),"=f"(d[95]),"=f"(d[96]),"=f"(d[97]),"=f"(d[98]),"=f"(d[99]),"=f"(d[100]),"=f"(d[101]),"=f"(d[102]),"=f"(d[103]),"=f"(d[104]),"=f"(d[105]),"=f"(d[106]),"=f"(d[107]),"=f"(d[108]),"=f"(d[109]),"=f"(d[110]),"=f"(d[111]),"=f"(d[112]),"=f"(d[113]),"=f"(d[114]),"=f"(d[115]),"=f"(d[116]),"=f"(d[117]),"=f"(d[118]),"=f"(d[119]),"=f"(d[120]),"=f"(d[121]),"=f"(d[122]),"=f"(d[123]),"=f"(d[124]),"=f"(d[125]),"=f"(d[126]),"=f"(d[127]) : "r"(a.x), "r"(a.y), "r"(a.z), "r"(a.w), "r"(db.lo), "r"(db.hi));
}
template<int N> __device__ __forceinline__ void wgmma_ra(float (&d)[N / 2], const uint4& a, Desc db, bool acc) {
  if (acc) wgmma_rs<N, 1>(d, a, db); else wgmma_rs<N, 0>(d, a, db);
}

__device__ __forceinline__ uint32_t smem_u32(const void* p) { return (uint32_t)__cvta_generic_to_shared(p); }
__device__ __forceinline__ void mbar_init(uint32_t bar, uint32_t cnt) { asm volatile("mbarrier.init.shared::cta.b64 [%0], %1;" ::"r"(bar), "r"(cnt)); }
__device__ __forceinline__ void mbar_expect_tx(uint32_t bar, uint32_t bytes) { asm volatile("mbarrier.arrive.expect_tx.shared::cta.b64 _, [%0], %1;" ::"r"(bar), "r"(bytes) : "memory"); }
__device__ __forceinline__ void mbar_arrive(uint32_t bar) { asm volatile("mbarrier.arrive.shared::cta.b64 _, [%0];" ::"r"(bar) : "memory"); }
__device__ __forceinline__ void mbar_arrive_remote(uint32_t rbar) { asm volatile("mbarrier.arrive.shared::cluster.b64 _, [%0];" ::"r"(rbar) : "memory"); }
__device__ __forceinline__ void mbar_wait(uint32_t bar, uint32_t parity) {
  asm volatile(
      "{\n.reg .pred p;\n.reg .u32 c;\nmov.u32 c, 0;\nLAB_WAIT:\nmbarrier.try_wait.parity.shared::cta.b64 p, [%0], %1;\n@p bra DONE;\n"
      "add.u32 c, c, 1;\nsetp.lt.u32 p, c, 1000000;\n@p bra LAB_WAIT;\ntrap;\nDONE:\n}\n" ::"r"(bar), "r"(parity) : "memory");
}
__device__ __forceinline__ void mbar_wait_c(uint32_t bar, uint32_t parity) {
  asm volatile("{\n.reg .pred p;\nLAB_WAIT:\nmbarrier.try_wait.parity.shared::cta.b64 p, [%0], %1;\n@!p bra LAB_WAIT;\n}\n" ::"r"(bar), "r"(parity) : "memory");
}
__device__ __forceinline__ uint32_t late(uint32_t bar, uint32_t v) {
  uint32_t r;
  asm volatile("{\n.reg .pred p;\nmbarrier.test_wait.parity.shared::cta.b64 p, [%1], 0;\nselp.b32 %0, %2, %1, p;\n}\n" : "=r"(r) : "r"(bar), "r"(v) : "memory");
  return r;
}
__device__ __forceinline__ void wtma2d(uint32_t dst, const CUtensorMap* m, int c0, int c1, uint32_t bar, uint64_t pol) {
  asm volatile("cp.async.bulk.tensor.2d.shared::cluster.global.mbarrier::complete_tx::bytes.multicast::cluster.L2::cache_hint [%0], [%1, {%3, %4}], [%2], %5, %6;"
               ::"r"(dst), "l"(m), "r"(bar), "r"(c0), "r"(c1), "h"((uint16_t)3), "l"(pol) : "memory");
}
__device__ __forceinline__ void wtma3d(uint32_t dst, const CUtensorMap* m, int c0, int c1, int c2, uint32_t bar, uint64_t pol) {
  asm volatile("cp.async.bulk.tensor.3d.shared::cluster.global.mbarrier::complete_tx::bytes.multicast::cluster.L2::cache_hint [%0], [%1, {%3, %4, %5}], [%2], %6, %7;"
               ::"r"(dst), "l"(m), "r"(bar), "r"(c0), "r"(c1), "r"(c2), "h"((uint16_t)3), "l"(pol) : "memory");
}
__device__ __forceinline__ void wbulk(uint32_t dst, const void* src, uint32_t bytes, uint32_t bar, uint64_t pol) {
  asm volatile("cp.async.bulk.shared::cluster.global.mbarrier::complete_tx::bytes.multicast::cluster.L2::cache_hint [%0], [%1], %2, [%3], %4, %5;"
               ::"r"(dst), "l"(src), "r"(bytes), "r"(bar), "h"((uint16_t)3), "l"(pol) : "memory");
}
__device__ __forceinline__ void tma3d(uint32_t dst, const CUtensorMap* m, int c0, int c1, int c2, uint32_t bar) {
  asm volatile("cp.async.bulk.tensor.3d.shared::cluster.global.mbarrier::complete_tx::bytes [%0], [%1, {%3, %4, %5}], [%2];"
               ::"r"(dst), "l"(m), "r"(bar), "r"(c0), "r"(c1), "r"(c2) : "memory");
}
__device__ __forceinline__ void prefetch_l2(const void* p, uint32_t bytes) { asm volatile("cp.async.bulk.prefetch.L2.global [%0], %1;" ::"l"(p), "r"(bytes) : "memory"); }
__device__ __forceinline__ uint64_t policy_evict_first() { uint64_t p; asm volatile("createpolicy.fractional.L2::evict_first.b64 %0, 1.0;" : "=l"(p)); return p; }
__device__ __forceinline__ uint64_t policy_evict_normal() { uint64_t p; asm volatile("createpolicy.fractional.L2::evict_normal.b64 %0, 1.0;" : "=l"(p)); return p; }
__device__ __forceinline__ void fence_async_smem() { asm volatile("fence.proxy.async.shared::cta;" ::: "memory"); }
__device__ __forceinline__ bool elect_one() {
  uint32_t p;
  asm volatile("{\n.reg .pred P;\nelect.sync _|P, 0xffffffff;\nselp.u32 %0, 1, 0, P;\n}\n" : "=r"(p));
  return p;
}
__device__ __forceinline__ void wg_fence() { asm volatile("wgmma.fence.sync.aligned;" ::: "memory"); }
__device__ __forceinline__ void wg_commit() { asm volatile("wgmma.commit_group.sync.aligned;" ::: "memory"); }
template <int n> __device__ __forceinline__ void wg_wait() { asm volatile("wgmma.wait_group.sync.aligned %0;" ::"n"(n) : "memory"); }
__device__ __forceinline__ void wg_bar(int w) { asm volatile("bar.sync %0, 128;" ::"r"(w + 1) : "memory"); }
__device__ __forceinline__ void fence_gpu() { asm volatile("fence.acq_rel.gpu;" ::: "memory"); }
__device__ __forceinline__ uint32_t ld_relaxed(const uint32_t* p) { uint32_t v; asm volatile("ld.relaxed.gpu.global.u32 %0, [%1];" : "=r"(v) : "l"(p) : "memory"); return v; }
__device__ __forceinline__ uint32_t ld_acquire(const uint32_t* p) { uint32_t v; asm volatile("ld.acquire.gpu.global.u32 %0, [%1];" : "=r"(v) : "l"(p) : "memory"); return v; }
__device__ __forceinline__ uint4 ld_relaxed4(const uint4* p) {
  uint4 v; asm volatile("ld.relaxed.gpu.global.v4.u32 {%0,%1,%2,%3}, [%4];" : "=r"(v.x), "=r"(v.y), "=r"(v.z), "=r"(v.w) : "l"(p) : "memory"); return v;
}
__device__ __forceinline__ uint2 ld_relaxed2(const uint2* p) {
  uint2 v; asm volatile("ld.relaxed.gpu.global.v2.u32 {%0,%1}, [%2];" : "=r"(v.x), "=r"(v.y) : "l"(p) : "memory"); return v;
}
__device__ __forceinline__ void st_relaxed(uint32_t* p, uint32_t a) { asm volatile("st.relaxed.gpu.global.u32 [%0], %1;" ::"l"(p), "r"(a) : "memory"); }
__device__ __forceinline__ void st_relaxed4(uint4* p, uint32_t a, uint32_t b, uint32_t c, uint32_t d) {
  asm volatile("st.relaxed.gpu.global.v4.u32 [%0], {%1,%2,%3,%4};" ::"l"(p), "r"(a), "r"(b), "r"(c), "r"(d) : "memory");
}
__device__ __forceinline__ void st_relaxed2(uint2* p, uint32_t a, uint32_t b) {
  asm volatile("st.relaxed.gpu.global.v2.u32 [%0], {%1,%2};" ::"l"(p), "r"(a), "r"(b) : "memory");
}
__device__ __forceinline__ void red4(uint4* p, uint32_t a, uint32_t b, uint32_t c, uint32_t d) {
  asm volatile("red.relaxed.gpu.global.add.noftz.v4.bf16x2 [%0], {%1,%2,%3,%4};" ::"l"(p), "r"(a), "r"(b), "r"(c), "r"(d) : "memory");
}
__device__ __forceinline__ void red2(uint2* p, uint32_t a, uint32_t b) {
  asm volatile("red.relaxed.gpu.global.add.noftz.v2.bf16x2 [%0], {%1,%2};" ::"l"(p), "r"(a), "r"(b) : "memory");
}
constexpr int SPIN_MAX = 1 << 21;
__device__ __forceinline__ uint32_t pack_bf16(float lo, float hi) { uint32_t r; asm("cvt.rn.bf16x2.f32 %0, %1, %2;" : "=r"(r) : "f"(hi), "f"(lo)); return r; }
__device__ __forceinline__ float bf_lo(uint32_t v) { return __uint_as_float(v << 16); }
__device__ __forceinline__ float bf_hi(uint32_t v) { return __uint_as_float(v & 0xffff0000u); }
__device__ __forceinline__ float2 lds64(uint32_t a) { float2 v; asm volatile("ld.shared.v2.f32 {%0,%1}, [%2];" : "=f"(v.x), "=f"(v.y) : "r"(a)); return v; }
__device__ __forceinline__ void sts64f(uint32_t a, float x, float y) { asm volatile("st.shared.v2.f32 [%0], {%1,%2};" ::"r"(a), "f"(x), "f"(y) : "memory"); }
__device__ __forceinline__ void sts32(uint32_t a, uint32_t x) { asm volatile("st.volatile.shared.b32 [%0], %1;" ::"r"(a), "r"(x) : "memory"); }
__device__ __forceinline__ void gate(uint32_t a, int need) {
#pragma unroll 1
  for (int it = 0; it < SPIN_MAX; it++) {
    int v; asm volatile("ld.volatile.shared.b32 %0, [%1];" : "=r"(v) : "r"(a) : "memory");
    if (v >= need) break;
    __nanosleep(200);
  }
}
__device__ __forceinline__ void sts128(uint32_t a, uint32_t x, uint32_t y, uint32_t z, uint32_t u) { asm volatile("st.shared.v4.b32 [%0], {%1,%2,%3,%4};" ::"r"(a), "r"(x), "r"(y), "r"(z), "r"(u) : "memory"); }
__device__ __forceinline__ uint4 lds128(uint32_t a) { uint4 v; asm volatile("ld.shared.v4.u32 {%0,%1,%2,%3}, [%4];" : "=r"(v.x), "=r"(v.y), "=r"(v.z), "=r"(v.w) : "r"(a) : "memory"); return v; }
__device__ __forceinline__ uint32_t hmul2(uint32_t a, uint32_t b) { uint32_t r; asm("mul.rn.bf16x2 %0, %1, %2;" : "=r"(r) : "r"(a), "r"(b)); return r; }
__device__ __forceinline__ uint32_t hadd2(uint32_t a, uint32_t b) { uint32_t r; asm("add.rn.bf16x2 %0, %1, %2;" : "=r"(r) : "r"(a), "r"(b)); return r; }
__device__ __forceinline__ void stsm4(uint32_t a, uint32_t r0, uint32_t r1, uint32_t r2, uint32_t r3) {
  asm volatile("stmatrix.sync.aligned.m8n8.x4.shared.b16 [%0], {%1,%2,%3,%4};" ::"r"(a), "r"(r0), "r"(r1), "r"(r2), "r"(r3) : "memory");
}
__device__ __forceinline__ void stsm2(uint32_t a, uint32_t r0, uint32_t r1) {
  asm volatile("stmatrix.sync.aligned.m8n8.x2.shared.b16 [%0], {%1,%2};" ::"r"(a), "r"(r0), "r"(r1) : "memory");
}
__device__ __forceinline__ uint4 ldsm4(uint32_t a) {
  uint4 r; asm volatile("ldmatrix.sync.aligned.m8n8.x4.shared.b16 {%0,%1,%2,%3}, [%4];" : "=r"(r.x), "=r"(r.y), "=r"(r.z), "=r"(r.w) : "r"(a) : "memory"); return r;
}
__device__ __forceinline__ uint32_t movm(uint32_t a) { uint32_t r; asm("movmatrix.sync.aligned.m8n8.trans.b16 %0, %1;" : "=r"(r) : "r"(a)); return r; }
__device__ __forceinline__ void mma16816z(float (&d)[4], uint32_t a0, uint32_t a1, uint32_t a2, uint32_t a3, uint32_t b0, uint32_t b1) {
  asm("mma.sync.aligned.m16n8k16.row.col.f32.bf16.bf16.f32 {%0,%1,%2,%3}, {%4,%5,%6,%7}, {%8,%9}, {%10,%10,%10,%10};"
      : "=f"(d[0]), "=f"(d[1]), "=f"(d[2]), "=f"(d[3]) : "r"(a0), "r"(a1), "r"(a2), "r"(a3), "r"(b0), "r"(b1), "f"(0.f));
}
__device__ __forceinline__ void mma16816(float (&d)[4], const uint4& a, uint32_t b0, uint32_t b1) {
  asm("mma.sync.aligned.m16n8k16.row.col.f32.bf16.bf16.f32 {%0,%1,%2,%3}, {%4,%5,%6,%7}, {%8,%9}, {%0,%1,%2,%3};"
      : "+f"(d[0]), "+f"(d[1]), "+f"(d[2]), "+f"(d[3]) : "r"(a.x), "r"(a.y), "r"(a.z), "r"(a.w), "r"(b0), "r"(b1));
}
__device__ __forceinline__ void mma1688(float (&d)[4], uint32_t a0, uint32_t a1, uint32_t b0) {
  asm("mma.sync.aligned.m16n8k8.row.col.f32.bf16.bf16.f32 {%0,%1,%2,%3}, {%4,%5}, {%6}, {%0,%1,%2,%3};"
      : "+f"(d[0]), "+f"(d[1]), "+f"(d[2]), "+f"(d[3]) : "r"(a0), "r"(a1), "r"(b0));
}
__device__ __forceinline__ float quad_sum(float v) { v += __shfl_xor_sync(0xffffffffu, v, 1); v += __shfl_xor_sync(0xffffffffu, v, 2); return v; }
__device__ __forceinline__ float rcp(float x) { float r; asm("rcp.approx.ftz.f32 %0, %1;" : "=f"(r) : "f"(x)); return r; }
__device__ __forceinline__ float rsq(float x) { float r; asm("rsqrt.approx.ftz.f32 %0, %1;" : "=f"(r) : "f"(x)); return r; }
__device__ __forceinline__ float ex2(float x) { float r; asm("ex2.approx.ftz.f32 %0, %1;" : "=f"(r) : "f"(x)); return r; }
__device__ __forceinline__ uint32_t chk(uint32_t acc, uint32_t v, uint32_t tag) { uint32_t r; asm("lop3.b32 %0, %1, %2, %3, 0xF6;" : "=r"(r) : "r"(acc), "r"(v), "r"(tag)); return r; }
__device__ __forceinline__ uint32_t chk2(uint32_t a, uint32_t b, uint32_t tag) { uint32_t r; asm("lop3.b32 %0, %1, %2, %3, 0x7E;" : "=r"(r) : "r"(a), "r"(b), "r"(tag)); return r; }
__device__ __forceinline__ uint32_t tagged(uint32_t v, uint32_t tag) { return (v & ~1u) | tag; }

__device__ __forceinline__ int group_k0(int g, int j) {
  const int h = g >= 9, r = g - 2 - 7 * h;
  return g < 2 ? 64 * j + 32 * g : g < 16 ? 64 * (r + (r >= j)) + 32 * h : 32 * g;
}
__device__ __forceinline__ uint32_t xin_off(int c, int w) { return SM_X + (2 * c + w) * 8192; }
__device__ __forceinline__ uint32_t xin_bar(int c) { return BAR_FULLX + 8 * (c < 8 ? c ^ 4 : c); }
__device__ __forceinline__ constexpr uint32_t qkv_xslot(int g) { return g < 5 || g > 11 ? 2 : (0x5140762u >> (4 * (g - 5))) & 15; }

template <int N> struct IC { static constexpr int v = N; };

struct Cons {
  uint32_t sb;
  uint32_t rem;
  uint32_t sB, mB;
  uint32_t mX;
  bool elect;
  __device__ __forceinline__ void release2(uint32_t bar) const { if (elect) { mbar_arrive(sb + bar); mbar_arrive_remote(rem + bar); } }
  __device__ __forceinline__ uint32_t nextB(uint32_t& prev) {
    mbar_wait_c(sb + BAR_FULLB + sB, mB);
    const uint32_t a = (((sb & 0x3FFFF) + SM_B) >> 4) + sB * (BSLOT / 128);
    prev = sB == 0 ? 32 : sB - 8;
    sB += 8;
    if (sB == 40) { sB = 0; mB ^= 1; }
    return a;
  }
  __device__ __forceinline__ void progress(uint32_t v) const { if (elect) sts32(sb + SM_PROG + (threadIdx.x >> 5), v); }
  __device__ __forceinline__ void releaseLastB() const { release2(BAR_EMPTYB + (sB == 0 ? 32 : sB - 8)); }
};

__device__ __forceinline__ float2 gather_sums(const uint2* a, uint32_t stag) {
  uint2 sa, sc;
  do { sa = ld_relaxed2(a); sc = ld_relaxed2(a + 8); } while (__any_sync(0xffffffffu, chk2(sa.x, sc.x, stag) & 3));
  return make_float2(quad_sum(__uint_as_float(sa.x) + __uint_as_float(sc.x)), quad_sum(__uint_as_float(sa.y) + __uint_as_float(sc.y)));
}

struct Norm {
  float m0, m1;
  uint32_t nm0, nm1;
  float d0, d1;
  uint2 u0, u1;
  __device__ __forceinline__ Norm(float2 sum) : m0(sum.x * (-1.f / 576)), m1(sum.y * (-1.f / 576)), nm0(pack_bf16(m0, m0)), nm1(pack_bf16(m1, m1)), d0(0.f), d1(0.f) {}
  __device__ __forceinline__ uint4 centre(const uint4& a) const { return make_uint4(hadd2(a.x, nm0), hadd2(a.y, nm1), hadd2(a.z, nm0), hadd2(a.w, nm1)); }
  __device__ __forceinline__ void sqr(uint32_t a, uint32_t b) {
    d0 = fmaf(bf_lo(a), bf_lo(a), fmaf(bf_hi(a), bf_hi(a), d0)); d1 = fmaf(bf_lo(b), bf_lo(b), fmaf(bf_hi(b), bf_hi(b), d1));
  }
  __device__ __forceinline__ void send(uint2* a, int t, uint32_t stag) {
    d0 = quad_sum(d0); d1 = quad_sum(d1);
    if ((t & 3) == 0) st_relaxed2(a, (__float_as_uint(d0) & ~3u) | stag, __float_as_uint(d1));
  }
  __device__ __forceinline__ void fetch(const uint2* a) { u0 = ld_relaxed2(a); u1 = ld_relaxed2(a + 8); }
  __device__ __forceinline__ float2 rstd(const uint2* a, uint32_t stag) {
    while (__any_sync(0xffffffffu, chk2(u0.x, u1.x, stag) & 3)) fetch(a);
    const float e0 = bf_lo(nm0) - m0, e1 = bf_lo(nm1) - m1;
    const float v0 = fmaf(quad_sum(__uint_as_float(u0.x) + __uint_as_float(u1.x)), 1.f / 576, -e0 * e0);
    const float v1 = fmaf(quad_sum(__uint_as_float(u0.y) + __uint_as_float(u1.y)), 1.f / 576, -e1 * e1);
    uint32_t u = pack_bf16(fmaxf(v0, 0.f), fmaxf(v1, 0.f));
    u = pack_bf16(bf_lo(u) + 1e-5f, bf_hi(u) + 1e-5f);
    u = pack_bf16(bf_lo(u) * rsq(bf_lo(u)), bf_hi(u) * rsq(bf_hi(u)));
    float2 r = make_float2(rcp(bf_lo(u)), rcp(bf_hi(u)));
    asm volatile("" : "+f"(r.x), "+f"(r.y));
    return r;
  }
};

template <class Pre, class Mma>
__device__ __forceinline__ float2 ln_gemm_in(Cons& c, Group* G, uint32_t (&p)[18], float2& sum, int w, int st0, int j, int t, Pre&& pre, Mma&& mma) {
  const uint32_t xa = c.sb + (t >> 5) * 2048 + (t & 15) * 128, sw = (((t >> 4) & 1) ^ (t & 7)) * 16;
  float ra[4] = {0.f, 0.f, 0.f, 0.f}, rb[4] = {0.f, 0.f, 0.f, 0.f};
#pragma unroll 1
  for (int cc = 0; cc < 9; cc++) {
    const uint32_t a = xa + xin_off(cc, w);
    mbar_wait_c(c.sb + xin_bar(cc), 0);
    const uint4 u0 = ldsm4(a + sw), u1 = ldsm4(a + (sw ^ 32)), u2 = ldsm4(a + (sw ^ 64)), u3 = ldsm4(a + (sw ^ 96));
    mma16816(ra, u0, 0x3f803f80u, 0x3f803f80u); mma16816(rb, u1, 0x3f803f80u, 0x3f803f80u);
    mma16816(ra, u2, 0x3f803f80u, 0x3f803f80u); mma16816(rb, u3, 0x3f803f80u, 0x3f803f80u);
  }
  sum = make_float2(ra[0] + rb[0], ra[2] + rb[2]);
  pre(0);
  Norm n(sum);
#pragma unroll
  for (int k = 0; k < 5; k++) {
    const uint4 u = ldsm4(xa + (k < 4 ? xin_off(j, w) + (sw ^ (32 * k)) : xin_off(8, w) + ((j ^ (t & 7)) << 4))), e = n.centre(u);
    p[4 * k] = u.x; p[4 * k + 1] = u.y;
    n.sqr(e.x, e.y);
    if (k < 4) { p[4 * k + 2] = u.z; p[4 * k + 3] = u.w; n.sqr(e.z, e.w); }
  }
  n.send(G->sq + st0 + 8 * j, t, 1);
  pre(1);
  float2 r;
  uint32_t xw[4] = {xa + xin_off(0, w) + sw, xa + xin_off(0, w) + (sw ^ 32), xa + xin_off(0, w) + (sw ^ 64), xa + xin_off(0, w) + (sw ^ 96)};
  asm volatile("" : "+r"(xw[0]), "+r"(xw[1]), "+r"(xw[2]), "+r"(xw[3]));
  auto frag = [&](int g, int i) { return n.centre(ldsm4(xw[2 * (g & 1) + i] + xin_off(g >> 1, 0))); };
  uint4 f0 = frag(0, 0), f1 = frag(0, 1);
#pragma unroll
  for (int g = 0; g < 18; g++) {
    mbar_wait_c(c.sb + BAR_FULLB + 8 * (g % 5), (g / 5) & 1);
    mma(g > 0, ((c.sb & 0x3FFFF) >> 4) + ((SM_B + (g % 5) * BSLOT) >> 4), f0, f1);
    wg_wait<1>();
    if (g > 0) c.release2(BAR_EMPTYB + 8 * ((g - 1) % 5));
    if (g < 17) { f0 = frag(g + 1, 0); f1 = frag(g + 1, 1); }
    if (g == 3) c.progress(3);
    if (g == 10) n.fetch(G->sq + st0 + 16 * (t & 3));
    if (g == 15) r = n.rstd(G->sq + st0 + 16 * (t & 3), late(c.sb + BAR_PAST, 1));
    if (g == 17 && w == 0) asm volatile("bar.arrive 6, 256;" ::: "memory");
    if (g >= 14) c.release2(BAR_EMPTYX + 32 + 8 * (g - 14));
  }
  c.mX = 0xff;
  if (w == 1) asm volatile("bar.sync 6, 256;" ::: "memory");
  wg_wait<0>();
  c.release2(BAR_EMPTYB + 8 * (17 % 5));
  c.release2(BAR_EMPTYX + 24);
  return r;
}

template <bool QKV, class Pre, class Mma>
__device__ __forceinline__ float2 ln_gemm(Cons& c, Group* G, const float (&v)[36], uint32_t (&p)[18], float2& sum, int st0, int j, int t,
                                          int layer, uint32_t tag, Pre&& pre, Mma&& mma) {
  const uint32_t stag = (2 * layer + (QKV ? 1 : 2)) & 3;
  uint4 x[6][2];
  uint4* src = G->xbox + t;
  asm volatile("" : "+l"(src));
  auto buf = [&](int g) -> uint4 (&)[2] { return x[g < 16 ? (g - 2) % 6 : g - 13]; };
  auto load = [&](int g0) {
#pragma unroll
    for (int g = g0; g < g0 + (g0 < 14 ? 3 : 2); g++) {
      const uint4* a = g < 16 ? src + ((g - 2) % 7 >= j ? 256 : 0) + (2 * ((g - 2) % 7) + 16 * (g >= 9)) * 128 : src + 2 * g * 128;
      buf(g)[0] = ld_relaxed4(a); buf(g)[1] = ld_relaxed4(a + 128);
    }
  };
  auto invalid = [&](int g, uint32_t tag) {
    uint32_t bad = chk(chk(chk2(buf(g)[0].x, buf(g)[1].x, tag), buf(g + 1)[0].x, tag), buf(g + 1)[1].x, tag);
    if (g < 14) bad = chk(chk(bad, buf(g + 2)[0].x, tag), buf(g + 2)[1].x, tag);
    if (g == 16) bad = chk(chk(chk(chk(bad, buf(g)[0].z, tag), buf(g)[1].z, tag), buf(g + 1)[0].z, tag), buf(g + 1)[1].z, tag);
    return __any_sync(0xffffffffu, bad & 1);
  };
  uint4* const d = src + 2 * j * 128;
  const int sq = st0 + 16 * (t & 3);
  if (QKV) {
    float s0 = v[0] + v[1], s1 = v[2] + v[3];
#pragma unroll
    for (int i = 1; i < 9; i++) { s0 += v[4 * i] + v[4 * i + 1]; s1 += v[4 * i + 2] + v[4 * i + 3]; }
    s0 = quad_sum(s0); s1 = quad_sum(s1);
    if ((t & 3) == 0) st_relaxed2(G->sum + st0 + 8 * j, (__float_as_uint(s0) & ~3u) | stag, __float_as_uint(s1));
  }
#pragma unroll
  for (int i = 0; i < 18; i++) p[i] = pack_bf16(v[2 * i], v[2 * i + 1]);
#pragma unroll
  for (int i = 0; i < 2; i++) st_relaxed4(d + i * 128, tagged(p[4 * i], tag), p[4 * i + 1], p[4 * i + 2], p[4 * i + 3]);
  pre(0);
  if (QKV) {
    sum = gather_sums(G->sum + sq, stag);
    load(2);
  }
  Norm n(sum);
  pre(1);
  const uint32_t* probe = &(G->xbox + (2 * (t & 3) + 1) * 128 + (t | 31))->x;
  uint32_t pv;
  float2 r;
  auto inx = [](int g) { return QKV && ((g >= 5 && g < 12) || g == 17); };
  auto use = [](int g) { return QKV ? (g < 5 ? 108 : 101) + g : 18 + g; };
#pragma unroll
  for (int g = 0; g < 18; g++) {
    if (g < 16 ? g % 3 == 2 : g == 16) {
      const uint32_t lt = late(c.sb + BAR_PAST, tag);
      while (invalid(g, lt)) load(g);
      if (g < 16) load(g < 14 ? g + 3 : 16);
    }
    const uint4 f0 = n.centre(g < 2 ? make_uint4(p[8 * g], p[8 * g + 1], p[8 * g + 2], p[8 * g + 3]) : buf(g)[0]);
    const uint4 f1 = n.centre(g < 2 ? make_uint4(p[8 * g + 4], p[8 * g + 5], p[8 * g + 6], p[8 * g + 7]) : buf(g)[1]);
    if (g == 11) n.fetch(G->sq + sq);
    if (g == 16) r = n.rstd(G->sq + sq, stag);
    if (inx(g)) mbar_wait_c(c.sb + BAR_FULLX + 8 * qkv_xslot(g), ((0x34 >> qkv_xslot(g)) & 1) ^ (g == 17));
    else mbar_wait_c(c.sb + BAR_FULLB + 8 * (use(g) % 5), (use(g) / 5) & 1);
    mma(g, ((c.sb & 0x3FFFF) >> 4) + ((inx(g) ? xslot(qkv_xslot(g)) : SM_B + (use(g) % 5) * BSLOT) >> 4), f0, f1);
    if (g == 1) { wg_wait<1>(); c.release2(BAR_EMPTYB + 8 * (use(0) % 5)); }
    if (g < 2) {
      if (!QKV) {
        if (g == 0) {
          pv = ld_relaxed(probe);
        } else {
          const uint32_t lt = late(c.sb + BAR_PAST, tag);
          while (__any_sync(0xffffffffu, (pv ^ lt) & 1)) pv = ld_relaxed(probe);
          load(2);
        }
      }
      if (g == (QKV ? 0 : 1)) {
#pragma unroll
        for (int i = 2; i < 4; i++) st_relaxed4(d + (14 + i) * 128, tagged(p[4 * i], tag), p[4 * i + 1], p[4 * i + 2], p[4 * i + 3]);
        st_relaxed2((uint2*)(src + (32 + (j >> 1)) * 128) + (j & 1), tagged(p[16], tag), p[17]);
      }
      n.sqr(f0.x, f0.y); n.sqr(f0.z, f0.w); n.sqr(f1.x, f1.y); n.sqr(f1.z, f1.w);
      if (g == 1) {
        n.sqr(hadd2(p[16], n.nm0), hadd2(p[17], n.nm1));
        n.send(G->sq + st0 + 8 * j, t, stag);
      }
    }
    if (g == 1 && !QKV) { wg_wait<0>(); c.release2(BAR_EMPTYB + 8 * (use(1) % 5)); }
    else wg_wait<1>();
    if (g > (QKV ? 1 : 2) && !inx(g - 1)) c.release2(BAR_EMPTYB + 8 * (use(g - 1) % 5));
    if (QKV && g < 13) c.progress(33 + g);
    if (QKV && g == 11) c.release2(BAR_EMPTYX + 8 * qkv_xslot(17));
    if (QKV && g >= 12 && g < 16) c.release2(BAR_EMPTYX + 32 + 8 * (g - 12));
  }
  if (QKV) c.mX = 0x34 ^ 0xf3;
  else { c.sB = 8 * (36 % 5); c.mB = (36 / 5) & 1; }
  wg_wait<0>();
  if (!QKV) c.release2(BAR_EMPTYB + 8 * (use(17) % 5));
  return r;
}

template <int NB, int OFF>
__device__ __forceinline__ void glu(const float (&a)[128], uint32_t (&h)[144]) {
#pragma unroll
  for (int b = 0; b < 2 * NB; b++) {
    if (OFF == 120) h[OFF + b] = pack_bf16(a[2 * b] * a[4 * NB + 2 * b], a[2 * b + 1] * a[4 * NB + 2 * b + 1]);
    else h[OFF + b] = hmul2(pack_bf16(a[2 * b], a[2 * b + 1]), pack_bf16(a[4 * NB + 2 * b], a[4 * NB + 2 * b + 1]));
  }
}

__global__ void __cluster_dims__(2, 1, 1) __launch_bounds__(384, 1)
fused_kernel(const __nv_bfloat16* __restrict__ x_in, Group* ws, const char* __restrict__ wqkv,
             const char* __restrict__ wo, char* __restrict__ out, uint32_t first, const __grid_constant__ Maps maps,
             const char* __restrict__ wg, const char* __restrict__ wu) {
  extern __shared__ __align__(1024) uint8_t smem_raw[];
  const uint32_t sb = smem_u32(smem_raw);
  const uint32_t bx = blockIdx.x - first;
  if (bx >= NCTA) {
    const int e = blockIdx.x & 3;
    const uint32_t par = ~ld_relaxed(ws->flag + 32) & 1;
    __nanosleep(1000);
    if (threadIdx.x < 16) prefetch_l2(wo + (144 * e + 9 * threadIdx.x) * 1152, 9 * 1152);
#pragma unroll 1
    for (int r = threadIdx.x >> 3; r < 144; r += 48) {
      const uint4* row = (const uint4*)(wo + (144 * e + r) * 1152) + (threadIdx.x & 7);
      float a = 0.f;
      uint4 u;
#pragma unroll
      for (int i = 0; i < 72; i += 8) {
        u = __ldg(row + i);
        a += ((bf_lo(u.x) + bf_hi(u.x)) + (bf_lo(u.y) + bf_hi(u.y))) + ((bf_lo(u.z) + bf_hi(u.z)) + (bf_lo(u.w) + bf_hi(u.w)));
      }
      const int h = r >= 72, k = r - 72 * h;
      ((Scratch*)ws)->woc[threadIdx.x & 7][k < 64 ? 64 + 8 * k + ((2 * e + h) ^ (k & 7)) : 576 * h + 8 * (k & 7) + (e ^ (k & 7))] = u;
      a = quad_sum(a);
      a += __shfl_xor_sync(0xffffffffu, a, 4);
      if ((threadIdx.x & 7) == 0) ((Scratch*)ws)->woc[2 * e + h][640 + k] = make_uint4(pack_bf16(a, a - bf_lo(pack_bf16(a, 0.f))), 0, 0, 0);
    }
    fence_gpu();
    __syncthreads();
    if (threadIdx.x == 0) st_relaxed(((Scratch*)ws)->done + e, par);
    const int cc = threadIdx.x % 54, r0 = threadIdx.x / 54, part = cc / 18, jj = 2 * e + (cc % 18) / 9, c9 = cc % 9;
    if (r0 < 6) {
#pragma unroll 4
      for (int k = r0; k < 576; k += 6) {
        const uint4 u = __ldg((const uint4*)(wqkv + k * 3456 + part * 1152 + 144 * jj) + c9);
        ((Scratch*)ws)->wq[jj][k >> 4][c9 < 8 ? part * 128 + (k & 15) * 8 + (c9 ^ (k & 7)) : 384 + part * 16 + (k & 15)] = u;
      }
    }
    fence_gpu();
    __syncthreads();
    if (threadIdx.x == 0) st_relaxed(((Scratch*)ws)->done + 32 + e, par);
#pragma unroll 1
    for (int r = threadIdx.x / 48; r < 144; r += 8) {
      const int i = threadIdx.x % 48;
      asm volatile("prefetch.global.L2 [%0];" ::"l"((i < 24 ? wg : wu) + (size_t)(4 * r + e) * 9216 + 1152 * ((i % 24) / 3) + 768 + 128 * (i % 3)));
      __nanosleep(100);
    }
    return;
  }
  if (threadIdx.x == 0) asm volatile("prefetch.tensormap [%0];" ::"l"(&maps.x) : "memory");
  const int warp = __shfl_sync(0xffffffffu, threadIdx.x >> 5, 0);
  const int lane = threadIdx.x & 31;
  const int rank = blockIdx.x & 1;
  if (warp == 3) {
#pragma unroll
    for (int i = 0; i < 5; i++)
      if (2 * i + (lane >> 4) < 9) asm volatile("prefetch.global.L2 [%0];" ::"l"((const char*)x_in + (bx * 16 + (lane & 15)) * 1152 + (2 * i + (lane >> 4)) * 128));
  }
  if (elect_one()) {
    if (warp >= 8) {
#pragma unroll
      for (int i = 0; i < 9; i++) mbar_init(sb + SM_BAR + 72 * (warp - 8) + 8 * i, warp < 10 ? 1 : 4);
      sts32(sb + SM_PROG + 4 * (warp - 8), 0);
      asm volatile("fence.mbarrier_init.release.cluster;" ::: "memory");
    } else if (warp == 1 || warp == 2) {
      asm volatile("prefetch.tensormap [%0];" ::"l"(&maps.x + warp) : "memory");
    }
  }
  __syncwarp();
  asm volatile("barrier.cluster.arrive.relaxed.aligned;" ::: "memory");
  if (warp == 8) PROFX(53);
  const int cl = bx >> 1, u = cl - 36;
  const int lb = (cl < 4 ? cl : cl < 36 ? 8 * ((cl - 4) & 7) + ((cl - 4) >> 3) + (((cl - 4) & 7) ? 0 : 4) : 8 * (1 + u % 7) + 4 + u / 7) * 2 + rank;
#define CTA_J(b) (((b) >> 1) & 7)
#define CTA_RB(b) ((((b) >> 4) << 1) | ((b) & 1))
  const int j = CTA_J(lb), rb = CTA_RB(lb);

  PROF(23);
  if (warp >= 8) {
    asm volatile("setmaxnreg.dec.sync.aligned.u32 40;");
    auto x_chunk = [&](int cc) {
      mbar_expect_tx(sb + xin_bar(cc), 16384);
      tma3d(sb + xin_off(cc, 0), &maps.x, 64 * cc, 0, 64 * rb, sb + xin_bar(cc));
      tma3d(sb + xin_off(cc, 1), &maps.x, 64 * cc, 1, 64 * rb, sb + xin_bar(cc));
    };
    if (warp == 9 && elect_one()) {
      fence_async_smem();
#pragma unroll 1
      for (int i = 0; i < 9; i++) x_chunk(i);
    }
    __syncwarp();
    if (warp == 9) PROFX(54);
    asm volatile("barrier.cluster.wait.aligned;" ::: "memory");
    if (warp == 8) PROFX(56);
    const uint64_t pol = policy_evict_first(), pola = policy_evict_normal();
    uint4 (* const wq)[432] = ((Scratch*)ws)->wq[j];
    const uint32_t par = ~ld_relaxed(ws[2 * rb].flag + 32 + 32 * j) & 1;
    auto qkv_group = [&](bool copy, int k, uint32_t dst, uint32_t bar) {
      if (copy) {
        wbulk(dst + rank * 8192, wq[(k >> 4) + rank], 6912, bar, pol);
      } else {
        wtma3d(dst + rank * 8192, &maps.qm, 72 * j, k + 16 * rank, 0, bar, pola);
        wtma3d(dst + rank * 8192 + 6144, &maps.qc, 72 * j + 64, k + 16 * rank, 0, bar, pola);
      }
    };
    auto chore = [&](int i) {
#pragma unroll 1
      for (int it = 0; __any_sync(0xffffffffu, ld_acquire(((Scratch*)ws)->done + i) != par); it++) if (it == SPIN_MAX) asm volatile("trap;");
      asm volatile("fence.proxy.async.global;" ::: "memory");
    };
    const int ktab = group_k0(lane, j);
    auto qkv_gate = [&](int g) { if (g >= 8) gate(sb + SM_PROG, 33 + ((g - 8) * 23 >> 4)); };
    if (warp == 8) {
      uint32_t s = 0, ph = 1;
      auto slot = [&](uint32_t bytes, auto&& issue) {
        const uint32_t bar = sb + BAR_FULLB + 8 * s;
        mbar_wait(sb + BAR_EMPTYB + 8 * s, ph);
        if (elect_one()) {
          mbar_expect_tx(bar, bytes);
          issue(sb + SM_B + s * BSLOT, bar);
        }
        if (++s == 5) { s = 0; ph ^= 1; }
      };
#pragma unroll 1
      for (int layer = 0; layer < NLAYERS; layer++) {
        if (layer) chore(32 + (j >> 1));
#pragma unroll 1
        for (int g = 0; g < 18 - layer; g += layer && g == 4 ? 8 : 1) {
          const int k = layer ? __shfl_sync(0xffffffffu, ktab, g) : 32 * g;
          if (layer) qkv_gate(g);
          else if (g == 0) mbar_wait(sb + xin_bar(3), 0);
          slot(2 * 6912, [&](uint32_t dst, uint32_t bar) { qkv_group(layer, k, dst, bar); });
        }
#pragma unroll 1
        for (int t = 0; t < 5; t++) {
          const CUtensorMap* m = &maps.g + (t < 3 ? rank : 2 + rank);
          asm volatile("" : "+l"(m));
          const int c2 = t < 3 ? 9 * j + 2 * t : 18 * j + 3 + 3 * t;
          const uint32_t half = t < 3 ? 8192 : 6144;
          const uint64_t pt = layer == 0 && (t == 0 || t > 2) ? pola : pol;
          auto tile = [&](int g) {
            const int k = __shfl_sync(0xffffffffu, ktab, g);
            slot(2 * half, [&](uint32_t dst, uint32_t bar) { wtma3d(dst + rank * half, m, 0, k, c2, bar, pt); });
          };
          int g = 0;
          if (t == 0) {
#pragma unroll 1
            for (; g < 5; g++) {
              mbar_wait(sb + BAR_FULLB + 8 * (s == 0 ? 4 : s - 1), s == 0 ? ph : ph ^ 1);
              if (g == 2) gate(sb + SM_PROG + 4, 32 * layer + 20);
              tile(g);
            }
          }
#pragma unroll 1
          for (; g < 18; g++) tile(g);
        }
      }
    } else if (warp == 9) {
      uint32_t mE = 0;
      auto acquire = [&](uint32_t s) { mbar_wait(sb + BAR_EMPTYX + 8 * s, (mE >> s) & 1); mE ^= 1u << s; };
      auto slot = [&](uint32_t s, const CUtensorMap* m, int col, int row, uint64_t pol) {
        acquire(s);
        if (elect_one()) {
          mbar_expect_tx(sb + BAR_FULLX + 8 * s, XSLOT);
          wtma2d(sb + xslot(s) + rank * 9216, m, col, row + 72 * rank, sb + BAR_FULLX + 8 * s, pol);
        }
      };
#pragma unroll 1
      for (int layer = 0; layer < NLAYERS; layer++) {
        if (layer) chore(32 + (j >> 1));
#pragma unroll 1
        for (int g = 5; g < 18 * layer; g += g == 11 ? 6 : 1) {
          const uint32_t s = qkv_xslot(g);
          const int k = __shfl_sync(0xffffffffu, ktab, g);
          if (g < 12) qkv_gate(g);
          acquire(s);
          if (elect_one()) {
            mbar_expect_tx(sb + BAR_FULLX + 8 * s, 2 * 6912);
            qkv_group(true, k, sb + xslot(s), sb + BAR_FULLX + 8 * s);
          }
          mbar_wait(sb + BAR_FULLX + 8 * s, (mE >> s) & 1);
        }
#pragma unroll 1
        for (int i = 0; i < 4; i++) slot(4 + i, &maps.o, 64 * j, 144 * i, pola);
        if (layer == 0) { chore(lane & 3); PROFX(57); }
        acquire(3);
        if (elect_one()) {
          mbar_expect_tx(sb + BAR_FULLX + 24, 10240 + 1280);
          wbulk(sb + SM_WOC + rank * 5120, ((Scratch*)ws)->woc[j] + rank * 320, 5120, sb + BAR_FULLX + 24, pola);
          wbulk(sb + SM_WSUM + rank * 640, ((Scratch*)ws)->woc[j] + 640 + rank * 40, 640, sb + BAR_FULLX + 24, pola);
        }
#pragma unroll 1
        for (int u = 0; u < 36; u++) slot(4 * (u & 1) + ((u >> 1) & 3), &maps.d, u < 4 ? 512 : 64 * ((j + (u >> 2)) & 7), 576 * j + 144 * (u & 3), pol);
      }
    } else {
      const int w = warp - 10, grp = 2 * rb + w;
      auto exchange = [&](uint32_t v, uint32_t bar) {
        fence_gpu();
        __syncwarp();
        if (w == 0 && v != 1) PROFX(64 + 58 - 2 * v);
        if (lane == 0) st_relaxed(ws[grp].flag + j, v);
#pragma unroll 1
        for (int it = 0;; it++) {
          const uint32_t f = ld_relaxed(ws[grp].flag + (lane & 7));
          if (__all_sync(0xffffffffu, v ? f >= v : f == 0)) break;
          if (it == SPIN_MAX) asm volatile("trap;");
        }
        if (lane == 0) mbar_arrive(sb + bar + 8 * w);
      };
      mbar_wait(sb + xin_bar(0), 0);
#pragma unroll 1
      for (int i = 0; i < 3; i++) {
        if (lane == 0) prefetch_l2(wqkv + (256 * i + 2 * bx + w) * 2592, 2592);
        __nanosleep(300);
      }
      gate(sb + SM_PROG, 3);
      if (w == 0 && lane < 6) asm volatile("prefetch.tensormap [%0];" ::"l"(&maps.o + lane) : "memory");
#pragma unroll 1
      for (int i = lane; i < 72; i += 32) {
        asm volatile("prefetch.global.L2 [%0];" ::"l"((w ? wu : wg) + (size_t)(36 * rb + (i >> 1)) * 9216 + 1152 * j + 128 * (i & 1)));
        __nanosleep(700);
      }
      gate(sb + SM_PROG, 22);
#pragma unroll 1
      for (int i = lane; i < 2 * INBOX; i += 64) {
        uint4* p = ws[grp].inbox[0] + 2 * j * INBOX + i;
        st_relaxed4(p, 0, 0, 0, 0); st_relaxed4(p + 32, 0, 0, 0, 0);
        __nanosleep(150);
      }
      exchange(1, BAR_CLR);
      if (w == 0) PROFX(59);
#pragma unroll 1
      for (int layer = 0; layer < NLAYERS; layer++) {
        mbar_wait(sb + BAR_REDDONE + 8 * w, layer);
        if (w == 0) PROFX(64 + 53 + 4 * layer);
        exchange(2 - 2 * layer, BAR_RREADY);
        if (w == 0) PROFX(64 + 56 + 4 * layer);
      }
      mbar_wait(sb + BAR_DONE + 8 * w, 0);
    }
  } else {
    asm volatile("setmaxnreg.inc.sync.aligned.u32 232;");
#define THREAD_IDS()                                                                   \
    int tid_ = threadIdx.x, bid_ = lb;                                                  \
    asm volatile("" : "+r"(tid_), "+r"(bid_));                                          \
    const int w = warp >> 2, wp = warp & 3;                                             \
    const int lane = tid_ & 31, t = tid_ & 127, g = lane >> 2, q = lane & 3;           \
    const int j = CTA_J(bid_), rb = CTA_RB(bid_), grp = 2 * rb + w;                    \
    const int st0 = wp * 64 + g;                         \
    Group* const G = ws + grp;                                                         \
    const uint32_t dsb = (sb & 0x3FFFF) >> 4;                                          \
    (void)t; (void)g; (void)q; (void)grp; (void)j; (void)st0; (void)dsb; (void)G
    Cons c;
    c.sb = sb; c.sB = 0; c.mB = 0; c.mX = 0; c.elect = (threadIdx.x & 127) == 0;
    asm volatile("mapa.shared::cluster.u32 %0, %1, %2;" : "=r"(c.rem) : "r"(sb), "r"(rank ^ 1));
    float v[36], a1[96], a2[12];
    float2 sum, rs;
    uint32_t res[18], xtag;
    auto qkv_mma = [&](bool acc, uint32_t bb, const uint4& f0, const uint4& f1) {
      wg_fence();
      wgmma_ra<192>(a1, f0, desc_hi(2048, 1024, 1) + bb, acc);
      wgmma_ra<24>(a2, f0, desc_hi(128, 256, 0) + (bb + 384), acc);
      wgmma_ra<192>(a1, f1, desc_hi(2048, 1024, 1) + (bb + 512), true);
      wgmma_ra<24>(a2, f1, desc_hi(128, 256, 0) + (bb + 896), true);
      wg_commit();
    };
    {
      THREAD_IDS();
      {
        if (q == 0) { st_relaxed2(G->sum + st0 + 8 * j, 0, 0); st_relaxed2(G->sq + st0 + 8 * j, 0, 0); }
        if (wp == 3) {
#pragma unroll
          for (int i = 0; i < 5; i++) st_relaxed4(G->halo + j * 160 + lane + i * 32, 0, 0, 0, 0);
        }
        if (lane >= 24) st_relaxed4(G->obox + (8 + j) * 128 + t, 0, 0, 0, 0);
      }
      xtag = __shfl_sync(0xffffffffu, ~ld_relaxed(G->flag + 32 + 32 * j) & 1, 0);
      if (lane >= 24) st_relaxed4(G->xbox + (2 * j + 1) * 128 + t, xtag ^ 1, 0, 0, 0);
      asm volatile("barrier.cluster.wait.aligned;" ::: "memory");
      PROF(0);
      PROF(1);
      rs = ln_gemm_in(c, G, res, sum, w, st0, j, t, [&](int i) { PROF(2 + i); if (i) PROF(4); }, qkv_mma);
    }
#pragma unroll 1
    for (int layer = 0;; layer++) {
      const uint32_t tag = layer ^ 1;
      uint4 own[5];
      {
        THREAD_IDS();
        PROF(pb + 4);
        uint32_t kv[3][18];
        auto cvt = [&](int b, float r) {
#pragma unroll
          for (int cc = 0; cc < 18; cc++) {
            const float* a = (cc == 8 ? a2 + 4 : cc == 17 ? a2 + 8 : cc < 8 ? a1 + 32 + 4 * cc : a1 + 28 + 4 * cc) + 2 * (b - 1);
            const uint32_t u = pack_bf16(a[0] * r, a[1] * r);
            kv[b][cc] = cc < 9 ? u : movm(u);
          }
        };
        cvt(2, rs.y);
#pragma unroll
        for (int i = 0; i < 18; i += 4) kv[2][i] = tagged(kv[2][i], tag);
        const uint32_t msg = sb + (w ? xslot(3) : xslot(0) + 24576) + wp * 2304 + lane * 16;
        if (wp == 3) {
          uint4* hp = G->halo + j * 160 + lane;
#pragma unroll
          for (int i = 0; i < 4; i++) st_relaxed4(hp + i * 32, kv[2][4 * i], kv[2][4 * i + 1], kv[2][4 * i + 2], kv[2][4 * i + 3]);
          st_relaxed2((uint2*)(hp + 128), kv[2][16], kv[2][17]);
        } else {
#pragma unroll
          for (int i = 0; i < 4; i++) sts128(msg + i * 512, kv[2][4 * i], kv[2][4 * i + 1], kv[2][4 * i + 2], kv[2][4 * i + 3]);
          sts64f(msg + 2048 - lane * 8, __uint_as_float(kv[2][16]), __uint_as_float(kv[2][17]));
        }
        cvt(1, rs.x);
        uint32_t Q[4][6];
#pragma unroll
        for (int h = 0; h < 4; h++)
#pragma unroll
          for (int i = 0; i < 6; i++) {
            const float* a = 4 * h + i < 16 ? a1 + 8 * h + 2 * i : a2 + 8 * h + 2 * i - 32;
            const uint32_t u = pack_bf16(a[0], a[1]);
            Q[h][i] = i < 2 ? (q >= h ? u : 0) : i < 4 ? u : (q <= h ? u : 0);
          }
        const bool lo0 = 2 * q > g, lo1 = 2 * q + 1 > g;
        const uint32_t M = (lo0 ? 0xffffu : 0u) | (lo1 ? 0xffff0000u : 0u);
        auto scores = [&](int h, int b, float (&s)[4]) {
          mma16816z(s, Q[h][0], Q[h][1], Q[h][2], Q[h][3], kv[b][2 * h], kv[b][2 * h + 1]);
          mma1688(s, Q[h][4], Q[h][5], kv[b][2 * h + 2]);
        };
        auto softmax = [&](float (&l)[4][2], float r, uint32_t (&P)[4]) {
          const float sl = r * (0.23570226039551584f * 1.4426950408889634f);
          float m[4];
#pragma unroll
          for (int h = 0; h < 4; h++) { m[h] = fmaxf(l[h][0], l[h][1]); m[h] = fmaxf(m[h], __shfl_xor_sync(0xffffffffu, m[h], 1)); }
#pragma unroll
          for (int h = 0; h < 4; h++) m[h] = fmaxf(m[h], __shfl_xor_sync(0xffffffffu, m[h], 2)) * sl;
#pragma unroll
          for (int h = 0; h < 4; h++) P[h] = pack_bf16(ex2(fmaf(l[h][0], sl, -m[h])), ex2(fmaf(l[h][1], sl, -m[h])));
        };
        const bool remote = wp == 0 && rb > 0;
        const uint4* hp = (G - 2)->halo + j * 160 + lane;
        auto halo = [&] {
#pragma unroll
          for (int i = 0; i < 4; i++) { const uint4 u = ld_relaxed4(hp + i * 32); kv[0][4 * i] = u.x; kv[0][4 * i + 1] = u.y; kv[0][4 * i + 2] = u.z; kv[0][4 * i + 3] = u.w; }
          const uint2 u = ld_relaxed2((const uint2*)(hp + 128));
          kv[0][16] = u.x; kv[0][17] = u.y;
        };
#pragma unroll
        for (int i = 0; i < 18; i++) kv[0][i] = 0;
        float l0[4][2], l1[4][2];
#pragma unroll
        for (int h = 0; h < 4; h++) {
          float s1[4], s2[4];
          scores(h, 1, s1); scores(h, 2, s2);
          l0[h][0] = s1[0]; l0[h][1] = s1[1];
          l1[h][0] = lo0 ? s1[2] : s2[2]; l1[h][1] = lo1 ? s1[3] : s2[3];
        }
        hp += __float_as_uint(l1[0][0]) & late(sb + BAR_PAST, 0);
        if (remote) halo();
        uint32_t P0[4], P1[4];
        softmax(l1, rs.y, P1);
        wg_bar(w);
        if (wp > 0) {
          const uint32_t from = msg - 2304;
#pragma unroll
          for (int i = 0; i < 4; i++) { const uint4 u = lds128(from + i * 512); kv[0][4 * i] = u.x; kv[0][4 * i + 1] = u.y; kv[0][4 * i + 2] = u.z; kv[0][4 * i + 3] = u.w; }
          const float2 u = lds64(from + 2048 - lane * 8);
          kv[0][16] = __float_as_uint(u.x); kv[0][17] = __float_as_uint(u.y);
        }
        if (remote) {
          while (__any_sync(0xffffffffu, chk(chk(chk(chk2(kv[0][0], kv[0][4], tag), kv[0][8], tag), kv[0][12], tag), kv[0][16], tag) & 1)) halo();
        }
        PROF(pb + 5);
        const bool first = (rb == 0 && wp == 0);
#pragma unroll
        for (int h = 0; h < 4; h++) {
          float s0[4];
          scores(h, 0, s0);
          if (first) s0[0] = s0[1] = -INFINITY;
          l0[h][0] = lo0 ? s0[0] : l0[h][0]; l0[h][1] = lo1 ? s0[1] : l0[h][1];
        }
        softmax(l0, rs.x, P0);
        uint4* ob = G->obox + t;
        uint32_t car0 = 0, car1 = 0;
#pragma unroll
        for (int h = 0; h < 4; h++) {
          float o[3][4], z[4] = {0.f, 0.f, 0.f, 0.f};
          mma1688(z, P0[h], P1[h], 0x3f803f80u);
#pragma unroll
          for (int i = 0; i < 3; i++) {
            mma16816z(o[i], P0[h] & ~M, P1[h] & M, 0u, P1[h] & ~M, kv[1][9 + 2 * h + i], kv[2][9 + 2 * h + i]);
            mma1688(o[i], P0[h] & M, 0u, kv[0][9 + 2 * h + i]);
          }
          const float i0 = rcp(z[0]), i1 = rcp(z[2]);
#pragma unroll
          for (int i = 0; i < 3; i++) { o[i][0] *= i0; o[i][1] *= i0; o[i][2] *= i1; o[i][3] *= i1; }
          const uint32_t o0 = q < h ? car0 : pack_bf16(o[0][0], o[0][1]), o1 = q < h ? car1 : pack_bf16(o[0][2], o[0][3]);
          own[h] = make_uint4(o0 | 1, o1, pack_bf16(o[1][0], o[1][1]), pack_bf16(o[1][2], o[1][3]));
          if (h < 3) st_relaxed4(ob + (8 * h + j) * 128, own[h].x, own[h].y, own[h].z, own[h].w);
          car0 = pack_bf16(o[2][0], o[2][1]); car1 = pack_bf16(o[2][2], o[2][3]);
          if (h == 1) { const uint32_t z = late(sb + BAR_PAST, 0); P0[2] ^= z; P0[3] ^= z; }
        }
        car0 = tagged(car0, tag);
        own[4] = make_uint4(car0, car1, 0, 0);
        PROF(pb + 6);
      }
      uint2 sa, sc;
      {
        THREAD_IDS();
        uint4* src = G->obox + t;
        asm volatile("" : "+l"(src));
        uint4 x[32];
        const uint4* from[7];
#pragma unroll
        for (int r = 0; r < 7; r++) { from[r] = src + (r >= j ? 128 : 0); asm volatile("" : "+l"(from[r])); }
        auto load = [&](int i) { x[i] = ld_relaxed4(i < 28 ? from[i % 7] + (8 * (i / 7) + i % 7) * 128 : src + (i + 4) * 128); };
        const uint32_t* probe = &(G->obox + (8 + (lane & 7)) * 128 + (t | 31))->x;
        uint32_t pv = ld_relaxed(probe);
#pragma unroll
        for (int i = 3; i < 8; i++) mbar_wait_c(sb + BAR_FULLX + 8 * i, (c.mX >> i) & 1);
        c.mX ^= 0xf8;
        while (__any_sync(0xffffffffu, ~pv & 1)) pv = ld_relaxed(probe);
        PROF(25 - layer);
        if (w == 1) asm volatile("bar.sync 7, 256;" ::: "memory");
#pragma unroll
        for (int i = 0; i < 10; i++) load(i);
        if (w == 0) asm volatile("bar.arrive 7, 256;" ::: "memory");
        st_relaxed4(src + (24 + j) * 128, own[3].x, own[3].y, own[3].z, own[3].w);
        st_relaxed2((uint2*)(src + (32 + (j >> 1)) * 128) + (j & 1), own[4].x, own[4].y);
        PROF(27 - layer);
        float a[36];
        float e[4];
        constexpr uint32_t NEXT = 576 - (575u << 16);
        auto step = [&](const uint4& f, uint32_t s, int i, uint32_t more, bool acc) {
          const uint32_t r = (xslot(4) >> 4) + (i < 4 ? 72 * s + 16 * i : 144 * s + 64) * 8, c = (SM_WOC >> 4) + (i < 4 ? 64 + 128 * i : 0) + s;
          wgmma_ra<72>(a, f, desc_hi(0, i < 4 ? 1024 : 9216, 1) + (dsb + more + (r + ((c - r) << 16))), acc);
        };
        wg_fence();
#pragma unroll
        for (int i = 0; i < 5; i++) wgmma_ra<8>(e, own[i], desc_hi(128, 0, 0) + (dsb + (SM_WSUM >> 4) + 16 * i), i > 0);
        wg_commit();
#pragma unroll
        for (int i = 0; i < 4; i++) step(own[i], 0, i, j * NEXT, i > 0);
        wg_commit();
        PROF(29 - layer);
        auto batch = [&](auto e0, auto e1, auto e2, int b) {
          constexpr int E0 = decltype(e0)::v, E1 = decltype(e1)::v, E2 = decltype(e2)::v;
          const uint32_t one = late(sb + BAR_PAST, 1);
          while (true) {
            uint32_t bad = 0;
#pragma unroll
            for (int i = E0; i < E1; i++) bad = i < 28 ? chk(bad, x[i].x, one) : chk(chk(bad, x[i].x, tag), x[i].z, tag);
            if (!__any_sync(0xffffffffu, bad & 1)) break;
#pragma unroll
            for (int i = E0; i < E1; i++) load(i);
          }
          if (b == 0) PROF(pb + 7);
          if (b == 1) { c.progress(32 * layer + 20); wg_wait<1>(); }
#pragma unroll
          for (int i = E1; i < E2; i++) load(i);
          if (b == 2) { sa = ld_relaxed2(G->sum + st0 + 16 * q); sc = ld_relaxed2(G->sum + st0 + 16 * q + 8); }
          wg_fence();
#pragma unroll
          for (int i = E0; i < E1; i++) step(x[i], i % 7, i / 7, i < 28 && i % 7 >= j ? NEXT : 0, true);
          wg_commit();
          if (b == 0) {
            wg_wait<2>();
            if (q == 0) st_relaxed2(G->sum + st0 + 8 * j, (__float_as_uint(e[0] + e[1]) & ~3u) | ((2 * layer + 2) & 3), __float_as_uint(e[2] + e[3]));
          }
        };
        batch(IC<0>(), IC<10>(), IC<21>(), 0);
        batch(IC<10>(), IC<21>(), IC<32>(), 1);
        batch(IC<21>(), IC<32>(), IC<32>(), 2);
        wg_wait<0>();
        if (w == 0) asm volatile("bar.arrive 3, 256;" ::: "memory");
        PROF(pb + 8);
#pragma unroll
        for (int i = 0; i < 18; i++) {
          v[2 * i] = bf_lo(res[i]) + a[2 * i];
          v[2 * i + 1] = bf_hi(res[i]) + a[2 * i + 1];
        }
      }
      uint32_t lsb;
      uint32_t h[144];
      {
        THREAD_IDS();
        float a[128];
        const uint32_t xd = sb + xslot(4 * w) + (lane >> 4) * 1024 + (16 * wp + (lane & 15)) * 16;
        const float2 rs = ln_gemm<false>(c, G, v, res, sum, st0, j, t, layer, xtag,
          [&](int i) {
            if (i == 0) {
              lsb = ((res[0] & 1) | (res[4] & 1) << 1 | (res[8] & 1) << 2 | (res[12] & 1) << 3 | (res[16] & 1) << 4) ^ (xtag * 31);
              const uint32_t st = late(sb + BAR_PAST, (2 * layer + 2) & 3);
              while (__any_sync(0xffffffffu, chk2(sa.x, sc.x, st) & 3)) { sa = ld_relaxed2(G->sum + st0 + 16 * q); sc = ld_relaxed2(G->sum + st0 + 16 * q + 8); }
              sum.x += quad_sum(__uint_as_float(sa.x) + __uint_as_float(sc.x)); sum.y += quad_sum(__uint_as_float(sa.y) + __uint_as_float(sc.y));
              if (w == 1) asm volatile("bar.sync 3, 256;" ::: "memory");
            }
            PROF(pb + 9 + i);
          },
          [&](int gi, uint32_t bb, const uint4& f0, const uint4& f1) {
            if (gi == 0) PROF(pb + 11);
            if (gi == 16 && w == 1) asm volatile("bar.sync 5, 256;" ::: "memory");
            wg_fence();
            wgmma_ra<256>(a, f0, desc_hi(4096, 1024, 1) + bb, gi > 0);
            wgmma_ra<256>(a, f1, desc_hi(4096, 1024, 1) + (bb + 128), true);
            wg_commit();
            if (gi == 17 && w == 0) asm volatile("bar.arrive 5, 256;" ::: "memory");
            stsm4(xd + gi * 4096, f0.x, f0.y, f0.z, f0.w);
            stsm4(xd + gi * 4096 + 2048, f1.x, f1.y, f1.z, f1.w);
            if (gi == 17) { fence_async_smem(); wg_bar(w); }
          });
        sts64f(sb + SM_KEEP + (tid_ >> 2) * 8, rs.x * rs.x, rs.y * rs.y);
        c.progress(32 * layer + 22);
        PROF(pb + 12);
        glu<16, 0>(a, h);
        const Desc da0 = desc_hi(1024, 128, 0) + (dsb + (xslot(4 * w) >> 4));
        auto tile = [&](auto wide, auto last) {
          const uint32_t xe = BAR_EMPTYX + 32 * (t & 1) + 4 * (t & 6);
          auto group = [&](int gi) {
            uint32_t prev;
            const uint32_t bb = c.nextB(prev);
            const Desc da = da0 + gi * 256;
            wg_fence();
            if (wide()) {
              wgmma_ss<256>(a, da, desc_hi(4096, 1024, 1) + bb, gi);
              wgmma_ss<256>(a, da + 128, desc_hi(4096, 1024, 1) + (bb + 128), 1);
            } else {
              wgmma_ss<192>(*(float(*)[96])a, da, desc_hi(2048, 512, 2) + bb, gi);
              wgmma_ss<192>(*(float(*)[96])a, da + 128, desc_hi(2048, 512, 2) + (bb + 64), 1);
            }
            wg_commit();
            if (gi == 17 && w == 0) asm volatile("bar.arrive 5, 256;" ::: "memory");
            wg_wait<1>();
            if (gi > 0 && !(last() && gi > 13)) c.release2(BAR_EMPTYB + prev);
            if (last() && gi >= 8 && !(gi & 1)) c.release2(BAR_EMPTYX + 16 * ((gi - 8) & 2) + 2 * ((gi - 8) & 12));
          };
          int gi = 0, end = w ? 16 : 18;
#pragma unroll 1
          while (true) {
#pragma unroll 1
            for (; gi < end; gi++) group(gi);
            if (end == 18) break;
            asm volatile("bar.sync 5, 256;" ::: "memory");
            end = 18;
          }
          wg_wait<0>();
          if (!last()) c.releaseLastB();
          if (last() && t >= 5 && t < 8) { mbar_arrive(sb + xe); mbar_arrive_remote(c.rem + xe); }
        };
        auto yes = [] { return true; };
        auto no = [] { return false; };
        tile(yes, no); PROF(pb + 13); glu<16, 32>(a, h);
        tile(yes, no); PROF(pb + 14); glu<16, 64>(a, h);
        tile(no, no); PROF(pb + 15); glu<12, 96>(a, h);
        const uint32_t hole = sb + SM_B + 12288 + tid_ * 16;
#pragma unroll
        for (int i = 0; i < 4; i++) sts128(hole + i * BSLOT, h[96 + 4 * i], h[97 + 4 * i], h[98 + 4 * i], h[99 + 4 * i]);
        if (w == 1) asm volatile("bar.arrive 8, 256;" ::: "memory");
        tile(no, yes); PROF(pb + 16); glu<12, 120>(a, h);
#pragma unroll
        for (int i = 0; i < 4; i++) { const uint4 u = lds128(hole + i * BSLOT); h[96 + 4 * i] = u.x; h[97 + 4 * i] = u.y; h[98 + 4 * i] = u.z; h[99 + 4 * i] = u.w; }
      }
      {
        THREAD_IDS();
        float d[32];
        uint4* gt = G->obox + t;
        asm volatile("" : "+l"(gt));
        uint4* const ib = gt + 2 * 4608 + layer * 8 * INBOX;
        auto pass = [&](uint32_t s0, bool last, auto&& hook) {
          const Desc db = desc_hi(0, 1024, 1) + (dsb + s0 * (XSLOT >> 4));
          auto full = [&](int i) { const int si = 4 * (i & 1) + (i >> 1); mbar_wait_c(sb + BAR_FULLX + 8 * (s0 + si), (c.mX >> (s0 + si)) & 1); };
          auto empty = [&](int i) { c.release2(BAR_EMPTYX + 8 * (s0 + 4 * (i & 1) + (i >> 1))); };
          full(0);
          hook();
          asm volatile("bar.sync %0, 256;" ::"r"(8 + w) : "memory");
#pragma unroll
          for (int i = 0; i < 4; i++) {
            const int si = 4 * (i & 1) + (i >> 1);
            if (i > 0) full(i);
            wg_fence();
#pragma unroll
            for (int k = 0; k < 9; k++) {
              const uint32_t* hk = h + 36 * i + 4 * k;
              wgmma_ra<64>(d, make_uint4(hk[0], hk[1], hk[2], hk[3]), db + ((xslot(si) >> 4) + k * 128), last || i + k > 0);
            }
            if (i == 3 && !(last && w == 1)) asm volatile("bar.arrive %0, 256;" ::"r"(9 - w) : "memory");
            if (i > 0) wg_commit();
            if (i > 1) { wg_wait<1>(); empty(i - 1); }
            if (i == 2) empty(0);
          }
          c.mX ^= 0x33u << s0;
        };
        PROF(pb + 17);
#pragma unroll 1
        for (int p = 0; p < 8; p++) {
          const uint32_t s0 = 2 * (p & 1);
          pass(s0, false, [] {});
          wg_wait<0>();
          c.release2(BAR_EMPTYX + 8 * (s0 + 5));
          if (p == 6 && layer == NLAYERS - 1) c.elect = false;
          uint32_t pk[16];
#pragma unroll
          for (int i = 0; i < 16; i++) pk[i] = pack_bf16(d[2 * i], d[2 * i + 1]);
          if (p >= 1 && p < 6 && layer < NLAYERS - 1) {
            const uint32_t o = c.sB + 8 * (p - 1);
            c.release2(BAR_EMPTYB + (o < 40 ? o : o - 40));
          }
          uint4* const dst = ib + ((j + p) & 7) * INBOX;
          if (p == 0) {
            mbar_wait_c(sb + BAR_CLR + 8 * w, 0);
#pragma unroll
            for (int k = 0; k < 8; k++) red2((uint2*)(ib + k * INBOX + 512) - t, pk[2 * k], pk[2 * k + 1]);
          } else if (p < 7) {
#pragma unroll
            for (int k = 0; k < 4; k++) red4(dst + k * 128, pk[4 * k], pk[4 * k + 1], pk[4 * k + 2], pk[4 * k + 3]);
            if (p == 6) { __syncwarp(); if (lane == 0) mbar_arrive(sb + BAR_REDDONE + 8 * w); }
          } else {
#pragma unroll
            for (int k = 0; k < 4; k++) st_relaxed4(gt + ((j + 7) & 7) * 128 + k * 1024, pk[4 * k] & ~1u, pk[4 * k + 1], pk[4 * k + 2], pk[4 * k + 3]);
          }
        }
        PROF(pb + 18);
        const uint4 *in = ib + j * INBOX, *pin = gt + j * 128;
        const uint2* in9 = (const uint2*)(in + 512) - t;
        asm volatile("" : "+l"(in), "+l"(pin), "+l"(in9));
        const float2 r2 = lds64(sb + SM_KEEP + (tid_ >> 2) * 8);
        uint2 X9;
        {
          uint4 X[4];
          const uint4* box = gt + 4608;
#pragma unroll
          for (int k = 0; k < 4; k++) X[k] = ld_relaxed4(box + 256 * j + ((k & 1) + 8 * (k & 2)) * 128);
          X9 = ld_relaxed2((const uint2*)(box + (32 + (j >> 1)) * 128) + (j & 1));
          const float i0 = rcp(r2.x), i1 = rcp(r2.y);
#pragma unroll
          for (int k = 0; k < 4; k++) {
            float* e = d + 8 * k;
            X[k].x ^= (lsb >> k) & 1;
            e[0] = bf_lo(X[k].x) * i0; e[1] = bf_hi(X[k].x) * i0; e[2] = bf_lo(X[k].y) * i1; e[3] = bf_hi(X[k].y) * i1;
            e[4] = bf_lo(X[k].z) * i0; e[5] = bf_hi(X[k].z) * i0; e[6] = bf_lo(X[k].w) * i1; e[7] = bf_hi(X[k].w) * i1;
          }
        }
        uint4 R[4], P[4];
        uint2 R9;
        PROF(pb + 19);
        pass(0, true, [&] {
          mbar_wait_c(sb + BAR_RREADY + 8 * w, layer);
#pragma unroll
          for (int k = 0; k < 4; k++) R[k] = ld_relaxed4(in + k * 128);
          R9 = ld_relaxed2(in9);
#pragma unroll
          for (int k = 0; k < 4; k++) P[k] = ld_relaxed4(pin + k * 1024);
        });
        const uint32_t zero = late(sb + BAR_PAST, 0);
        while (__any_sync(0xffffffffu, (chk2(P[0].x, P[1].x, zero) | chk2(P[2].x, P[3].x, zero)) & 1)) {
#pragma unroll
          for (int k = 0; k < 4; k++) P[k] = ld_relaxed4(pin + k * 1024);
        }
#pragma unroll
        for (int k = 0; k < 4; k++) {
          const uint32_t u[4] = {hadd2(R[k].x, P[k].x), hadd2(R[k].y, P[k].y), hadd2(R[k].z, P[k].z), hadd2(R[k].w, P[k].w)};
#pragma unroll
          for (int i = 0; i < 4; i++) { v[8 * k + 2 * i] = bf_lo(u[i]); v[8 * k + 2 * i + 1] = bf_hi(u[i]); }
        }
        X9.x = chk(zero, X9.x, lsb >> 4);
        v[32] = fmaf(bf_lo(R9.x), r2.x, bf_lo(X9.x)); v[33] = fmaf(bf_hi(R9.x), r2.x, bf_hi(X9.x));
        v[34] = fmaf(bf_lo(R9.y), r2.y, bf_lo(X9.y)); v[35] = fmaf(bf_hi(R9.y), r2.y, bf_hi(X9.y));
        PROF(pb + 20);
        wg_wait<0>();
        c.release2(BAR_EMPTYX + 40);
        PROF(pb + 21);
#pragma unroll
        for (int i = 0; i < 32; i++) v[i] = (v[i] + d[i]) * (i & 2 ? r2.y : r2.x);
      }
      if (layer == NLAYERS - 1) break;
      {
        THREAD_IDS();
        PROF(31);
        rs = ln_gemm<true>(c, G, v, res, sum, st0, j, t, 1, xtag ^ 1, [&](int i) { PROF(32 + i); if (i) PROF(34); }, qkv_mma);
      }
    }
    {
      THREAD_IDS();
      const uint32_t stg = sb + SM_B + warp * 4096;
      const uint32_t sd = stg + (lane & 15) * 128;
#pragma unroll
      for (int i = 0; i < 4; i++)
        stsm4(sd + (((2 * i + (lane >> 4)) ^ (lane & 7)) << 4), pack_bf16(v[8 * i], v[8 * i + 1]), pack_bf16(v[8 * i + 2], v[8 * i + 3]),
              pack_bf16(v[8 * i + 4], v[8 * i + 5]), pack_bf16(v[8 * i + 6], v[8 * i + 7]));
      stsm2(stg + 2048 + (lane & 15) * 16, pack_bf16(v[32], v[33]), pack_bf16(v[34], v[35]));
      __syncwarp();
      char* o = out + (128 * rb + 32 * wp + w) * 1152;
#pragma unroll
      for (int i = 0; i < 4; i++) {
        const int r = 4 * i + (lane >> 3);
        *(uint4*)(o + r * 2304 + 128 * j + 16 * (lane & 7)) = lds128(stg + r * 128 + (((lane ^ r) & 7) << 4));
      }
      if (lane < 16) *(uint4*)(o + lane * 2304 + 1024 + 16 * j) = lds128(stg + 2048 + lane * 16);
      if (lane == 0) {
        if (wp == 0) st_relaxed(G->flag + 32 + 32 * j, xtag);
        mbar_arrive(sb + BAR_DONE + 8 * w);
      }
      PROF(61);
    }
  }
}

typedef CUresult (*EncFn)(CUtensorMap*, CUtensorMapDataType, cuuint32_t, void*, const cuuint64_t*, const cuuint64_t*, const cuuint32_t*,
                          const cuuint32_t*, CUtensorMapInterleave, CUtensorMapSwizzle, CUtensorMapL2promotion, CUtensorMapFloatOOBfill);

void make_map(EncFn enc, CUtensorMap* m, const void* p, int rank, uint64_t d0, uint64_t d1, uint64_t d2, uint64_t s1, uint64_t s2, uint32_t b0,
              uint32_t b1, uint32_t b2, CUtensorMapSwizzle sw) {
  cuuint64_t gd[3] = {d0, d1, d2};
  cuuint64_t gs[2] = {s1, s2};
  cuuint32_t bd[3] = {b0, b1, b2};
  cuuint32_t es[3] = {1, 1, 1};
  enc(m, CU_TENSOR_MAP_DATA_TYPE_BFLOAT16, rank, const_cast<void*>(p), gd, gs, bd, es, CU_TENSOR_MAP_INTERLEAVE_NONE, sw,
      CU_TENSOR_MAP_L2_PROMOTION_L2_128B, CU_TENSOR_MAP_FLOAT_OOB_FILL_NONE);
}

}

extern "C" void kernel_launch(void* const* d_in, const int* in_sizes, int n_in, void* d_out, int out_size) {
  const __nv_bfloat16* x = (const __nv_bfloat16*)d_in[0];
  const char *wqkv = (const char*)d_in[1], *wo = (const char*)d_in[2], *wg = (const char*)d_in[4], *wu = (const char*)d_in[5], *wd = (const char*)d_in[6];
  static EncFn enc = nullptr;
  static uint32_t first = 0;
  static Group* ws = nullptr;
  if (!enc) {
    cudaDriverEntryPointQueryResult qr;
    cudaGetDriverEntryPoint("cuTensorMapEncodeTiled", (void**)&enc, cudaEnableDefault, &qr);
    cudaGetSymbolAddress((void**)&ws, g_ws);
    cudaFuncSetAttribute(fused_kernel, cudaFuncAttributeMaxDynamicSharedMemorySize, SMEM_BYTES);
    cudaLaunchConfig_t cfg = {};
    cfg.gridDim = NCTA + 4; cfg.blockDim = 384; cfg.dynamicSmemBytes = SMEM_BYTES;
    int clusters = 0;
    if (XFIRST || cudaOccupancyMaxActiveClusters(&clusters, fused_kernel, &cfg) != cudaSuccess || 2 * clusters < NCTA + 4) first = 4;
    cudaGetLastError();
  }
  const CUtensorMapSwizzle S0 = CU_TENSOR_MAP_SWIZZLE_NONE, S64 = CU_TENSOR_MAP_SWIZZLE_64B, S128 = CU_TENSOR_MAP_SWIZZLE_128B;
  Maps m;
  make_map(enc, &m.x, x, 3, 576, 2, 1024, 1152, 2304, 64, 1, 64, S128);
  make_map(enc, &m.qm, wqkv, 3, 576, 576, 3, 3456, 1152, 64, 16, 3, S128);
  make_map(enc, &m.qc, wqkv, 3, 576, 576, 3, 3456, 1152, 8, 16, 3, S0);
  make_map(enc, &m.o, wo, 2, 576, 576, 1, 1152, 0, 64, 72, 1, S128);
  make_map(enc, &m.g, wg, 3, 64, 576, 72, 9216, 128, 64, 32, 2, S128);
  make_map(enc, &m.u, wu, 3, 64, 576, 72, 9216, 128, 64, 32, 2, S128);
  make_map(enc, &m.g3, wg, 3, 32, 576, 144, 9216, 64, 32, 32, 3, S64);
  make_map(enc, &m.u3, wu, 3, 32, 576, 144, 9216, 64, 32, 32, 3, S64);
  make_map(enc, &m.d, wd, 2, 576, 4608, 1, 1152, 0, 64, 72, 1, S128);
  fused_kernel<<<NCTA + 4, 384, SMEM_BYTES>>>(x, ws, wqkv, wo, (char*)d_out, first, m, wg, wu);
}
```
